```python
import torch

def _softmax(x, axis=-1):
    return torch.softmax(x, dim=axis)
def _gelu(x):
    return torch.nn.functional.gelu(x, approximate="tanh")
def _silu(x):
    return torch.nn.functional.silu(x)
def _sigmoid(x):
    return torch.sigmoid(x)
def _layernorm(x, axis=-1, eps=1e-5):
    m = x.mean(dim=axis, keepdim=True)
    v = x.var(dim=axis, keepdim=True, unbiased=False)
    return (x - m) / torch.sqrt(v + eps)
def _scatter_add(tgt, idx, src, axis=0):
    return tgt.clone().index_add_(axis, idx, src)
def _segment_sum(src, seg, n):
    out = torch.zeros((n,) + src.shape[1:], dtype=src.dtype)
    return out.index_add_(0, seg, src)
def _pad(x, pw):
    flat = tuple(v for pair in reversed(pw) for v in pair)
    return torch.nn.functional.pad(x, flat)

kernel_name = 'sequential_preLN__linear_attn_block__moe_arch_mod__prompt'

def setup_inputs():

    _w = (lambda a: (lambda t: t.to(torch.bfloat16) if t.is_floating_point() else t)(torch.as_tensor(a)))
    def _A_setup():
        B, S, D = 1, 2048, 1024
        return {
            "x": _w((lambda *s: torch.randn(*s, dtype=torch.bfloat16) * 0.05)(B, S, D)),
            "wqkv": _w((lambda *s: torch.randn(*s, dtype=torch.bfloat16) * 0.05)(D, 3 * D)),
            "wo": _w((lambda *s: torch.randn(*s, dtype=torch.bfloat16) * 0.05)(D, D)),
        }
    _A_in = _A_setup()

    def _B_setup():
        B, S, D, F, C = 1, 2048, 1024, 3584, 2
        return {
            "x": _w((lambda *s: torch.randn(*s, dtype=torch.bfloat16) * 0.05)(B, S, D)),
            "w_r": _w((lambda *s: torch.randn(*s, dtype=torch.bfloat16) * 0.05)(D)),
            "w_gate": _w((lambda *s: torch.randn(*s, dtype=torch.bfloat16) * 0.05)(D, F)),
            "w_up": _w((lambda *s: torch.randn(*s, dtype=torch.bfloat16) * 0.05)(D, F)),
            "w_down": _w((lambda *s: torch.randn(*s, dtype=torch.bfloat16) * 0.05)(F, D)),
        }
    _B_in = _B_setup()

    return {
        "A_x": _A_in["x"],
        "A_wqkv": _A_in["wqkv"],
        "A_wo": _A_in["wo"],
        "B_x": _B_in["x"],
        "B_w_r": _B_in["w_r"],
        "B_w_gate": _B_in["w_gate"],
        "B_w_up": _B_in["w_up"],
        "B_w_down": _B_in["w_down"],
    }

def reference(A_x, A_wqkv, A_wo, B_x, B_w_r, B_w_gate, B_w_up, B_w_down):
    def _A_ref(x, wqkv, wo):
        B, S, D = x.shape
        H = 32; Dh = D // H
        qkv = (lambda x, *d: x.permute(*d))((x @ wqkv).reshape(B, S, 3, H, Dh), 2, 0, 3, 1, 4)
        q, k, v = qkv[0], qkv[1], qkv[2]
        phi = lambda t: torch.where(t > 0, t + 1, torch.exp(t)) + 1e-6
        pq, pk = phi(q), phi(k)
        kv = torch.einsum("bhsd,bhse->bhde", pk, v)
        z = torch.einsum("bhsd->bhd", pk)
        num = torch.einsum("bhqd,bhde->bhqe", pq, kv)
        den = torch.einsum("bhqd,bhd->bhq", pq, z)[..., None] + 1e-6
        o = num / den
        return (lambda x, *d: x.permute(*d))(o, 0, 2, 1, 3).reshape(B, S, D) @ wo

    def _B_ref(x, w_r, w_gate, w_up, w_down):
        B, S, D = x.shape
        C = 2
        r = x @ w_r
        idx = torch.argsort(-r, axis=-1)[:, :C]
        idx_e = (lambda x, n, axis: torch.repeat_interleave(x, n, dim=axis))(idx.reshape(B, C, 1), D, axis=2)
        x_sel = (lambda x, i, axis: torch.take_along_dim(x, i, dim=axis))(x, idx_e, axis=1)
        g = _silu(x_sel @ w_gate)
        u = x_sel @ w_up
        y = (g * u) @ w_down
        r_sel = _sigmoid((lambda x, i, axis: torch.take_along_dim(x, i, dim=axis))(r, idx, axis=1))
        y = y * r_sel.reshape(B, C, 1)
        b_off = (torch.arange(B) * S).reshape(B, 1)
        flat_idx = (idx + b_off).reshape(B * C)
        zero = (x * 0.0).reshape(B * S, D)
        upd = _scatter_add(zero, flat_idx, y.reshape(B * C, D), axis=0)
        return x + upd.reshape(B, S, D)

    x = A_x
    h = x + _A_ref(_layernorm(x, axis=-1), A_wqkv, A_wo)
    h2 = h + _B_ref(_layernorm(h, axis=-1), B_w_r, B_w_gate, B_w_up, B_w_down)
    return h2
```

```cpp
#include <cuda_runtime.h>
#include <cuda.h>
#include <cuda_bf16.h>
#include <stdint.h>
#include <type_traits>

namespace {

constexpr int S_ = 2048, D_ = 1024, F_ = 3584;
constexpr int NCTA = 128, NFFN = 112;
constexpr uint32_t SENT = 0xFFFFFFFFu;
constexpr int SPIN_LIMIT = 1 << 20;

#define ADELAY 700
#define PFA 1
#define QHOLD 1
#define NPULL 12
#define CDELAY 0
#define NOUTW 3
#define YDELAY 500
#define EFX 0
#define EFW 1
#define EFF 1
#define KLEAD 13
#define GPACE 12
#define NDIR 4
#define PULL0 5
#define DMASK 0x2490
#define PFST 1
#define W0OFF 2
#define MAPM 2
#define XWPF 0
constexpr uint32_t STAGE_B = 57344;
__host__ __device__ constexpr uint32_t xoff(int s) { return s < 2 ? s * 57344 : 98304 + s * 32768; }
__host__ __device__ constexpr uint32_t woff(int s) { return s < 1 ? 32768 : 65536 + s * 24576; }
constexpr uint32_t OFF_STATS = 229376;
constexpr uint32_t OFF_COLSUM = 231424;
constexpr uint32_t OFF_BARS = 232192;
constexpr uint32_t SMEM_BYTES = 232448;
constexpr uint32_t B_FULL = 0, B_EMPTY = 32, B_AUX = 64, B_EV0 = 72, B_EV1 = 80, B_FULL3 = 88, B_SW = 216, B_OUT = 224, B_LATE = 232, B_SEL = B_FULL + 8, B_FFN = 240;
constexpr uint32_t OFF_EBAR = OFF_STATS + 912;
constexpr uint32_t SLOT_B = 16384;
constexpr uint32_t sb = 1024;
constexpr uint32_t bars = sb + OFF_BARS;
constexpr uint32_t GU_SLOTS = 0xB1A09876u;
constexpr uint32_t OFF_LNP = OFF_STATS + 1024;
constexpr uint32_t OFF_KVB = 13 * SLOT_B + 8192;

__device__ unsigned g_epoch;
__device__ uint4 g_st1[S_ / 2];
__device__ uint4 g_csp[16 * 8 * 48];
__device__ uint4 g_kvp[16 * 8 * 272];
__device__ uint4 g_obuf[32 * 64 * 128];
__device__ uint4 g_st2[S_];
__device__ uint4 g_hsel[32 * 256];
__device__ uint32_t g_cand[8 * 32];
__device__ uint4 g_ybuf[NCTA * NFFN * 4];
#define TS_DECL
#define TS(i)
#define TSG(i)
#define TSV(i, v)
#define TS_DUMP(slot)
#define PTS(i)

__device__ __forceinline__ uint32_t smem_u32(const void* p) { return (uint32_t)__cvta_generic_to_shared(p); }
__device__ __forceinline__ void mbar_init(uint32_t bar, uint32_t cnt) { asm volatile("mbarrier.init.shared::cta.b64 [%0], %1;" :: "r"(bar), "r"(cnt) : "memory"); }
__device__ __forceinline__ void mbar_expect_tx(uint32_t bar, uint32_t bytes) { asm volatile("mbarrier.arrive.expect_tx.shared::cta.b64 _, [%0], %1;" :: "r"(bar), "r"(bytes) : "memory"); }
__device__ __forceinline__ void mbar_arrive(uint32_t bar) { asm volatile("mbarrier.arrive.shared::cta.b64 _, [%0];" :: "r"(bar) : "memory"); }
#define SPINCHK(it, code) if ((it) > SPIN_LIMIT) break
__device__ __forceinline__ void mbar_wait(uint32_t bar, uint32_t parity) {
  asm volatile("{\n.reg .pred p;\n.reg .u32 c;\nmov.u32 c, 0;\n"
               "WL:\nmbarrier.try_wait.parity.shared::cta.b64 p, [%0], %1;\n@p bra WD;\n"
               "add.u32 c, c, 1;\nsetp.lt.u32 p, c, 1048576;\n@p bra WL;\nWD:\n}" :: "r"(bar), "r"(parity) : "memory");
}
__device__ __forceinline__ uint64_t l2_stream() { uint64_t p; asm("createpolicy.fractional.L2::evict_first.b64 %0, 1.0;" : "=l"(p)); return p; }
__device__ __forceinline__ void tma_2d(uint32_t dst, const CUtensorMap* tm, int c0, int c1, uint32_t bar, bool stream) {
  if (stream) asm volatile("cp.async.bulk.tensor.2d.shared::cluster.global.mbarrier::complete_tx::bytes.L2::cache_hint [%0], [%1, {%3, %4}], [%2], %5;"
                           :: "r"(dst), "l"(tm), "r"(bar), "r"(c0), "r"(c1), "l"(l2_stream()) : "memory");
  else asm volatile("cp.async.bulk.tensor.2d.shared::cluster.global.mbarrier::complete_tx::bytes [%0], [%1, {%3, %4}], [%2];"
                    :: "r"(dst), "l"(tm), "r"(bar), "r"(c0), "r"(c1) : "memory");
}
__device__ __forceinline__ void tma_3d(uint32_t dst, const CUtensorMap* tm, int c0, int c1, int c2, uint32_t bar, bool stream) {
  if (stream) asm volatile("cp.async.bulk.tensor.3d.shared::cluster.global.mbarrier::complete_tx::bytes.L2::cache_hint [%0], [%1, {%3, %4, %5}], [%2], %6;"
                           :: "r"(dst), "l"(tm), "r"(bar), "r"(c0), "r"(c1), "r"(c2), "l"(l2_stream()) : "memory");
  else asm volatile("cp.async.bulk.tensor.3d.shared::cluster.global.mbarrier::complete_tx::bytes [%0], [%1, {%3, %4, %5}], [%2];"
                    :: "r"(dst), "l"(tm), "r"(bar), "r"(c0), "r"(c1), "r"(c2) : "memory");
}
__device__ __forceinline__ void tma_2d_mc(uint32_t dst, const CUtensorMap* tm, int c0, int c1, uint32_t bar, bool stream) {
  if (stream) asm volatile("cp.async.bulk.tensor.2d.shared::cluster.global.mbarrier::complete_tx::bytes.multicast::cluster.L2::cache_hint [%0], [%1, {%3, %4}], [%2], %5, %6;"
                           :: "r"(dst), "l"(tm), "r"(bar), "r"(c0), "r"(c1), "h"((uint16_t)3), "l"(l2_stream()) : "memory");
  else asm volatile("cp.async.bulk.tensor.2d.shared::cluster.global.mbarrier::complete_tx::bytes.multicast::cluster [%0], [%1, {%3, %4}], [%2], %5;"
                    :: "r"(dst), "l"(tm), "r"(bar), "r"(c0), "r"(c1), "h"((uint16_t)3) : "memory");
}
__device__ __forceinline__ bool elect_one() {
  uint32_t p;
  asm volatile("{\n.reg .pred q;\nelect.sync _|q, 0xFFFFFFFF;\nselp.u32 %0, 1, 0, q;\n}" : "=r"(p));
  return p;
}
__device__ __forceinline__ void bulk_load_mc(uint32_t dst, const void* src, uint32_t bytes, uint32_t bar) {
  asm volatile("{\n.reg .pred q;\nelect.sync _|q, 0xFFFFFFFF;\n"
               "@q cp.async.bulk.shared::cluster.global.mbarrier::complete_tx::bytes.multicast::cluster [%0], [%1], %2, [%3], %4;\n}"
               :: "r"(dst), "l"(src), "r"(bytes), "r"(bar), "h"((uint16_t)3) : "memory");
}
__device__ __forceinline__ void bulk_store(void* dst, uint32_t src, uint32_t bytes) {
  asm volatile("cp.async.bulk.global.shared::cta.bulk_group [%0], [%1], %2;" :: "l"(dst), "r"(src), "r"(bytes) : "memory");
}
__device__ __forceinline__ void mbar_arrive_rem(uint32_t bar) { asm volatile("mbarrier.arrive.shared::cluster.b64 _, [%0];" :: "r"(bar) : "memory"); }
__device__ __forceinline__ void st_async4(uint32_t addr, const uint4& v, uint32_t bar) {
  asm volatile("st.async.shared::cluster.mbarrier::complete_tx::bytes.v4.b32 [%0], {%1,%2,%3,%4}, [%5];" :: "r"(addr), "r"(v.x), "r"(v.y), "r"(v.z), "r"(v.w), "r"(bar) : "memory");
}
template <uint32_t O> __device__ __forceinline__ void ldsm4_o(uint32_t addr, uint32_t& a, uint32_t& b, uint32_t& c, uint32_t& d) {
  asm volatile("ldmatrix.sync.aligned.m8n8.x4.shared.b16 {%0,%1,%2,%3}, [%4+%5];" : "=r"(a), "=r"(b), "=r"(c), "=r"(d) : "r"(addr), "n"(O) : "memory");
}
template <uint32_t O> __device__ __forceinline__ void ldsm4t_o(uint32_t addr, uint32_t (&r)[4]) {
  asm volatile("ldmatrix.sync.aligned.m8n8.x4.trans.shared.b16 {%0,%1,%2,%3}, [%4+%5];" : "=r"(r[0]), "=r"(r[1]), "=r"(r[2]), "=r"(r[3]) : "r"(addr), "n"(O) : "memory");
}
__device__ __forceinline__ void mma16816(float (&c)[4], const uint32_t (&a)[4], uint32_t b0, uint32_t b1) {
  asm("mma.sync.aligned.m16n8k16.row.col.f32.bf16.bf16.f32 {%0,%1,%2,%3}, {%4,%5,%6,%7}, {%8,%9}, {%0,%1,%2,%3};"
      : "+f"(c[0]), "+f"(c[1]), "+f"(c[2]), "+f"(c[3]) : "r"(a[0]), "r"(a[1]), "r"(a[2]), "r"(a[3]), "r"(b0), "r"(b1));
}
__device__ __forceinline__ void l2_prefetch(const void* p) { asm volatile("prefetch.global.L2 [%0];" :: "l"(p) : "memory"); }
__device__ __forceinline__ uint32_t ld_line(const void* p) { uint32_t v; asm volatile("ld.global.cg.L2::128B.u32 %0, [%1];" : "=r"(v) : "l"(p) : "memory"); return v; }
__device__ __forceinline__ void tmap_prefetch(const CUtensorMap* tm) { asm volatile("prefetch.tensormap [%0];" :: "l"(tm) : "memory"); }
__device__ __forceinline__ void wg_fence() { asm volatile("wgmma.fence.sync.aligned;" ::: "memory"); }
__device__ __forceinline__ void wg_commit() { asm volatile("wgmma.commit_group.sync.aligned;" ::: "memory"); }
template <int N> __device__ __forceinline__ void wg_wait() { asm volatile("wgmma.wait_group.sync.aligned %0;" :: "n"(N) : "memory"); }
template <int N> __device__ __forceinline__ void pin(float (&d)[N]) {
#pragma unroll
  for (int i = 0; i < N; i++) asm volatile("" : "+f"(d[i]) :: "memory");
}
__device__ __forceinline__ void pin4(uint4& v) { asm volatile("" : "+r"(v.x), "+r"(v.y), "+r"(v.z), "+r"(v.w) :: "memory"); }
template <uint32_t SBO, uint32_t SWZ> __device__ __forceinline__ uint64_t dsc(uint32_t lo) { return ((uint64_t)((SBO >> 4) | (SWZ << 30)) << 32) | lo; }
__host__ __device__ constexpr uint32_t dlo(uint32_t addr, uint32_t lbo) { return (addr >> 4) | ((lbo >> 4) << 16); }
__device__ __forceinline__ void bar_sync(int id, int n) { asm volatile("bar.sync %0, %1;" :: "r"(id), "r"(n) : "memory"); }
__device__ __forceinline__ void bar_arrive(int id, int n) { asm volatile("bar.arrive %0, %1;" :: "r"(id), "r"(n) : "memory"); }
__device__ __forceinline__ void fence_async_smem() { asm volatile("fence.proxy.async.shared::cta;" ::: "memory"); }
__device__ __forceinline__ void fence_gpu() { asm volatile("fence.acq_rel.gpu;" ::: "memory"); }
__device__ __forceinline__ uint4 ld_cg4(const void* p) { uint4 v; asm volatile("ld.global.cg.v4.u32 {%0,%1,%2,%3}, [%4];" : "=r"(v.x), "=r"(v.y), "=r"(v.z), "=r"(v.w) : "l"(p) : "memory"); return v; }
__device__ __forceinline__ uint4 ld_rlx4(const void* p) { uint4 v; asm volatile("ld.relaxed.gpu.global.v4.u32 {%0,%1,%2,%3}, [%4];" : "=r"(v.x), "=r"(v.y), "=r"(v.z), "=r"(v.w) : "l"(p) : "memory"); return v; }
__device__ __forceinline__ uint32_t ld_rlx(const void* p) { uint32_t v; asm volatile("ld.relaxed.gpu.global.u32 %0, [%1];" : "=r"(v) : "l"(p) : "memory"); return v; }
__device__ __forceinline__ void st_rlx4(void* p, uint4 v) { asm volatile("st.relaxed.gpu.global.v4.u32 [%0], {%1,%2,%3,%4};" :: "l"(p), "r"(v.x), "r"(v.y), "r"(v.z), "r"(v.w) : "memory"); }
__device__ __forceinline__ void st_rlx2(void* p, uint32_t a, uint32_t b) { asm volatile("st.relaxed.gpu.global.v2.u32 [%0], {%1,%2};" :: "l"(p), "r"(a), "r"(b) : "memory"); }
__device__ __forceinline__ void st_rlx(void* p, uint32_t a) { asm volatile("st.relaxed.gpu.global.u32 [%0], %1;" :: "l"(p), "r"(a) : "memory"); }
__device__ __forceinline__ void red4(void* p, float a, float b, float c, float d) { asm volatile("red.relaxed.gpu.global.add.v4.f32 [%0], {%1,%2,%3,%4};" :: "l"(p), "f"(a), "f"(b), "f"(c), "f"(d) : "memory"); }
__device__ __forceinline__ uint32_t pack2(float lo, float hi) { uint32_t r; asm("cvt.rn.bf16x2.f32 %0, %1, %2;" : "=r"(r) : "f"(hi), "f"(lo)); return r; }
__device__ __forceinline__ float bf_lo(uint32_t v) { return __uint_as_float(v << 16); }
__device__ __forceinline__ float bf_hi(uint32_t v) { return __uint_as_float(v & 0xFFFF0000u); }
__device__ __forceinline__ void stsm4(uint32_t addr, uint32_t a, uint32_t b, uint32_t c, uint32_t d) {
  asm volatile("stmatrix.sync.aligned.m8n8.x4.shared.b16 [%0], {%1,%2,%3,%4};" :: "r"(addr), "r"(a), "r"(b), "r"(c), "r"(d) : "memory");
}
template <uint32_t O> __device__ __forceinline__ void stsm4_o(uint32_t addr, uint32_t a, uint32_t b, uint32_t c, uint32_t d) {
  asm volatile("stmatrix.sync.aligned.m8n8.x4.shared.b16 [%0+%5], {%1,%2,%3,%4};" :: "r"(addr), "r"(a), "r"(b), "r"(c), "r"(d), "n"(O) : "memory");
}
__device__ __forceinline__ void sts4(uint32_t addr, uint32_t a, uint32_t b, uint32_t c, uint32_t d) { asm volatile("st.shared.v4.u32 [%0], {%1,%2,%3,%4};" :: "r"(addr), "r"(a), "r"(b), "r"(c), "r"(d) : "memory"); }
__device__ __forceinline__ void sts2f(uint32_t addr, float a, float b) { asm volatile("st.shared.v2.f32 [%0], {%1,%2};" :: "r"(addr), "f"(a), "f"(b) : "memory"); }
__device__ __forceinline__ void sts1(uint32_t addr, uint32_t a) { asm volatile("st.shared.u32 [%0], %1;" :: "r"(addr), "r"(a) : "memory"); }
__device__ __forceinline__ float2 lds2f(uint32_t addr) { float2 v; asm volatile("ld.shared.v2.f32 {%0,%1}, [%2];" : "=f"(v.x), "=f"(v.y) : "r"(addr) : "memory"); return v; }
template <uint32_t O> __device__ __forceinline__ float2 lds2f_o(uint32_t addr) { float2 v; asm volatile("ld.shared.v2.f32 {%0,%1}, [%2+%3];" : "=f"(v.x), "=f"(v.y) : "r"(addr), "n"(O) : "memory"); return v; }
template <int I, int N, class F> __device__ __forceinline__ void static_for(F&& f) { if constexpr (I < N) { f(std::integral_constant<int, I>{}); static_for<I + 1, N>(f); } }
__device__ __forceinline__ uint4 lds4(uint32_t addr) { uint4 v; asm volatile("ld.shared.v4.u32 {%0,%1,%2,%3}, [%4];" : "=r"(v.x), "=r"(v.y), "=r"(v.z), "=r"(v.w) : "r"(addr) : "memory"); return v; }
__device__ __forceinline__ uint32_t lds1(uint32_t addr) { uint32_t v; asm volatile("ld.shared.u32 %0, [%1];" : "=r"(v) : "r"(addr) : "memory"); return v; }
__device__ __forceinline__ float ex2(float x) { float y; asm("ex2.approx.ftz.f32 %0, %1;" : "=f"(y) : "f"(x)); return y; }
__device__ __forceinline__ uint32_t max4(uint32_t m, const uint4& v) { return __vimax3_u32(__vimax3_u32(m, v.x, v.y), v.z, v.w); }
__device__ __forceinline__ float rsq(float x) { float y; asm("rsqrt.approx.ftz.f32 %0, %1;" : "=f"(y) : "f"(x)); return y; }
__device__ __forceinline__ float rcp(float x) { float y; asm("rcp.approx.ftz.f32 %0, %1;" : "=f"(y) : "f"(x)); return y; }
__device__ __forceinline__ uint2 ld_rlx2(const void* p) { uint2 v; asm volatile("ld.relaxed.gpu.global.v2.u32 {%0,%1}, [%2];" : "=r"(v.x), "=r"(v.y) : "l"(p) : "memory"); return v; }
template <uint32_t O> __device__ __forceinline__ uint4 lds4_o(uint32_t addr) { uint4 v; asm volatile("ld.shared.v4.u32 {%0,%1,%2,%3}, [%4+%5];" : "=r"(v.x), "=r"(v.y), "=r"(v.z), "=r"(v.w) : "r"(addr), "n"(O) : "memory"); return v; }
__device__ __forceinline__ float phi(float u, float rstd, float rl) { return fmaf(fmaxf(u, 0.f), rstd, __saturatef(ex2(u * rl) + 1e-6f)); }

template<int TA, int TB, int OFF, int SZ> __device__ __forceinline__ void wgmma_n192_ss(float (&d)[SZ], uint64_t da, uint64_t db, int scale_d) {
  asm volatile("{\n.reg .pred p;\nsetp.ne.b32 p, %98, 0;\n"
    "wgmma.mma_async.sync.aligned.m64n192k16.f32.bf16.bf16 {%0,%1,%2,%3,%4,%5,%6,%7,%8,%9,%10,%11,%12,%13,%14,%15,%16,%17,%18,%19,%20,%21,%22,%23,%24,%25,%26,%27,%28,%29,%30,%31,%32,%33,%34,%35,%36,%37,%38,%39,%40,%41,%42,%43,%44,%45,%46,%47,%48,%49,%50,%51,%52,%53,%54,%55,%56,%57,%58,%59,%60,%61,%62,%63,%64,%65,%66,%67,%68,%69,%70,%71,%72,%73,%74,%75,%76,%77,%78,%79,%80,%81,%82,%83,%84,%85,%86,%87,%88,%89,%90,%91,%92,%93,%94,%95}, %96, %97, p, 1, 1, %99, %100;\n}\n"
    : "+f"(d[OFF+0]), "+f"(d[OFF+1]), "+f"(d[OFF+2]), "+f"(d[OFF+3]), "+f"(d[OFF+4]), "+f"(d[OFF+5]), "+f"(d[OFF+6]), "+f"(d[OFF+7]),
      "+f"(d[OFF+8]), "+f"(d[OFF+9]), "+f"(d[OFF+10]), "+f"(d[OFF+11]), "+f"(d[OFF+12]), "+f"(d[OFF+13]), "+f"(d[OFF+14]), "+f"(d[OFF+15]),
      "+f"(d[OFF+16]), "+f"(d[OFF+17]), "+f"(d[OFF+18]), "+f"(d[OFF+19]), "+f"(d[OFF+20]), "+f"(d[OFF+21]), "+f"(d[OFF+22]), "+f"(d[OFF+23]),
      "+f"(d[OFF+24]), "+f"(d[OFF+25]), "+f"(d[OFF+26]), "+f"(d[OFF+27]), "+f"(d[OFF+28]), "+f"(d[OFF+29]), "+f"(d[OFF+30]), "+f"(d[OFF+31]),
      "+f"(d[OFF+32]), "+f"(d[OFF+33]), "+f"(d[OFF+34]), "+f"(d[OFF+35]), "+f"(d[OFF+36]), "+f"(d[OFF+37]), "+f"(d[OFF+38]), "+f"(d[OFF+39]),
      "+f"(d[OFF+40]), "+f"(d[OFF+41]), "+f"(d[OFF+42]), "+f"(d[OFF+43]), "+f"(d[OFF+44]), "+f"(d[OFF+45]), "+f"(d[OFF+46]), "+f"(d[OFF+47]),
      "+f"(d[OFF+48]), "+f"(d[OFF+49]), "+f"(d[OFF+50]), "+f"(d[OFF+51]), "+f"(d[OFF+52]), "+f"(d[OFF+53]), "+f"(d[OFF+54]), "+f"(d[OFF+55]),
      "+f"(d[OFF+56]), "+f"(d[OFF+57]), "+f"(d[OFF+58]), "+f"(d[OFF+59]), "+f"(d[OFF+60]), "+f"(d[OFF+61]), "+f"(d[OFF+62]), "+f"(d[OFF+63]),
      "+f"(d[OFF+64]), "+f"(d[OFF+65]), "+f"(d[OFF+66]), "+f"(d[OFF+67]), "+f"(d[OFF+68]), "+f"(d[OFF+69]), "+f"(d[OFF+70]), "+f"(d[OFF+71]),
      "+f"(d[OFF+72]), "+f"(d[OFF+73]), "+f"(d[OFF+74]), "+f"(d[OFF+75]), "+f"(d[OFF+76]), "+f"(d[OFF+77]), "+f"(d[OFF+78]), "+f"(d[OFF+79]),
      "+f"(d[OFF+80]), "+f"(d[OFF+81]), "+f"(d[OFF+82]), "+f"(d[OFF+83]), "+f"(d[OFF+84]), "+f"(d[OFF+85]), "+f"(d[OFF+86]), "+f"(d[OFF+87]),
      "+f"(d[OFF+88]), "+f"(d[OFF+89]), "+f"(d[OFF+90]), "+f"(d[OFF+91]), "+f"(d[OFF+92]), "+f"(d[OFF+93]), "+f"(d[OFF+94]), "+f"(d[OFF+95])
    : "l"(da), "l"(db), "r"(scale_d), "n"(TA), "n"(TB));
}
template<int TA, int TB, int OFF, int SZ> __device__ __forceinline__ void wgmma_n72_ss(float (&d)[SZ], uint64_t da, uint64_t db, int scale_d) {
  asm volatile("{\n.reg .pred p;\nsetp.ne.b32 p, %38, 0;\n"
    "wgmma.mma_async.sync.aligned.m64n72k16.f32.bf16.bf16 {%0,%1,%2,%3,%4,%5,%6,%7,%8,%9,%10,%11,%12,%13,%14,%15,%16,%17,%18,%19,%20,%21,%22,%23,%24,%25,%26,%27,%28,%29,%30,%31,%32,%33,%34,%35}, %36, %37, p, 1, 1, %39, %40;\n}\n"
    : "+f"(d[OFF+0]), "+f"(d[OFF+1]), "+f"(d[OFF+2]), "+f"(d[OFF+3]), "+f"(d[OFF+4]), "+f"(d[OFF+5]), "+f"(d[OFF+6]), "+f"(d[OFF+7]),
      "+f"(d[OFF+8]), "+f"(d[OFF+9]), "+f"(d[OFF+10]), "+f"(d[OFF+11]), "+f"(d[OFF+12]), "+f"(d[OFF+13]), "+f"(d[OFF+14]), "+f"(d[OFF+15]),
      "+f"(d[OFF+16]), "+f"(d[OFF+17]), "+f"(d[OFF+18]), "+f"(d[OFF+19]), "+f"(d[OFF+20]), "+f"(d[OFF+21]), "+f"(d[OFF+22]), "+f"(d[OFF+23]),
      "+f"(d[OFF+24]), "+f"(d[OFF+25]), "+f"(d[OFF+26]), "+f"(d[OFF+27]), "+f"(d[OFF+28]), "+f"(d[OFF+29]), "+f"(d[OFF+30]), "+f"(d[OFF+31]),
      "+f"(d[OFF+32]), "+f"(d[OFF+33]), "+f"(d[OFF+34]), "+f"(d[OFF+35])
    : "l"(da), "l"(db), "r"(scale_d), "n"(TA), "n"(TB));
}
template<int TB, int OFF, int SZ> __device__ __forceinline__ void wgmma_n40_rs(float (&d)[SZ], uint32_t a0, uint32_t a1, uint32_t a2, uint32_t a3, uint64_t db, int scale_d) {
  asm volatile("{\n.reg .pred p;\nsetp.ne.b32 p, %25, 0;\n"
    "wgmma.mma_async.sync.aligned.m64n40k16.f32.bf16.bf16 {%0,%1,%2,%3,%4,%5,%6,%7,%8,%9,%10,%11,%12,%13,%14,%15,%16,%17,%18,%19}, {%20,%21,%22,%23}, %24, p, 1, 1, %26;\n}\n"
    : "+f"(d[OFF+0]), "+f"(d[OFF+1]), "+f"(d[OFF+2]), "+f"(d[OFF+3]), "+f"(d[OFF+4]), "+f"(d[OFF+5]), "+f"(d[OFF+6]), "+f"(d[OFF+7]),
      "+f"(d[OFF+8]), "+f"(d[OFF+9]), "+f"(d[OFF+10]), "+f"(d[OFF+11]), "+f"(d[OFF+12]), "+f"(d[OFF+13]), "+f"(d[OFF+14]), "+f"(d[OFF+15]),
      "+f"(d[OFF+16]), "+f"(d[OFF+17]), "+f"(d[OFF+18]), "+f"(d[OFF+19])
    : "r"(a0), "r"(a1), "r"(a2), "r"(a3), "l"(db), "r"(scale_d), "n"(TB));
}
template<int TB, int OFF, int SZ> __device__ __forceinline__ void wgmma_n128_rs(float (&d)[SZ], uint32_t a0, uint32_t a1, uint32_t a2, uint32_t a3, uint64_t db, int scale_d) {
  asm volatile("{\n.reg .pred p;\nsetp.ne.b32 p, %69, 0;\n"
    "wgmma.mma_async.sync.aligned.m64n128k16.f32.bf16.bf16 {%0,%1,%2,%3,%4,%5,%6,%7,%8,%9,%10,%11,%12,%13,%14,%15,%16,%17,%18,%19,%20,%21,%22,%23,%24,%25,%26,%27,%28,%29,%30,%31,%32,%33,%34,%35,%36,%37,%38,%39,%40,%41,%42,%43,%44,%45,%46,%47,%48,%49,%50,%51,%52,%53,%54,%55,%56,%57,%58,%59,%60,%61,%62,%63}, {%64,%65,%66,%67}, %68, p, 1, 1, %70;\n}\n"
    : "+f"(d[OFF+0]), "+f"(d[OFF+1]), "+f"(d[OFF+2]), "+f"(d[OFF+3]), "+f"(d[OFF+4]), "+f"(d[OFF+5]), "+f"(d[OFF+6]), "+f"(d[OFF+7]),
      "+f"(d[OFF+8]), "+f"(d[OFF+9]), "+f"(d[OFF+10]), "+f"(d[OFF+11]), "+f"(d[OFF+12]), "+f"(d[OFF+13]), "+f"(d[OFF+14]), "+f"(d[OFF+15]),
      "+f"(d[OFF+16]), "+f"(d[OFF+17]), "+f"(d[OFF+18]), "+f"(d[OFF+19]), "+f"(d[OFF+20]), "+f"(d[OFF+21]), "+f"(d[OFF+22]), "+f"(d[OFF+23]),
      "+f"(d[OFF+24]), "+f"(d[OFF+25]), "+f"(d[OFF+26]), "+f"(d[OFF+27]), "+f"(d[OFF+28]), "+f"(d[OFF+29]), "+f"(d[OFF+30]), "+f"(d[OFF+31]),
      "+f"(d[OFF+32]), "+f"(d[OFF+33]), "+f"(d[OFF+34]), "+f"(d[OFF+35]), "+f"(d[OFF+36]), "+f"(d[OFF+37]), "+f"(d[OFF+38]), "+f"(d[OFF+39]),
      "+f"(d[OFF+40]), "+f"(d[OFF+41]), "+f"(d[OFF+42]), "+f"(d[OFF+43]), "+f"(d[OFF+44]), "+f"(d[OFF+45]), "+f"(d[OFF+46]), "+f"(d[OFF+47]),
      "+f"(d[OFF+48]), "+f"(d[OFF+49]), "+f"(d[OFF+50]), "+f"(d[OFF+51]), "+f"(d[OFF+52]), "+f"(d[OFF+53]), "+f"(d[OFF+54]), "+f"(d[OFF+55]),
      "+f"(d[OFF+56]), "+f"(d[OFF+57]), "+f"(d[OFF+58]), "+f"(d[OFF+59]), "+f"(d[OFF+60]), "+f"(d[OFF+61]), "+f"(d[OFF+62]), "+f"(d[OFF+63])
    : "r"(a0), "r"(a1), "r"(a2), "r"(a3), "l"(db), "r"(scale_d), "n"(TB));
}

struct Ptrs { const __nv_bfloat16 *x, *wqkv, *wo, *wr, *wg, *wu, *wd; __nv_bfloat16* out; };

__global__ void __cluster_dims__(2, 1, 1) __launch_bounds__(384, 1) fused_kernel(const __grid_constant__ CUtensorMap tmX, const __grid_constant__ CUtensorMap tmW,
                                                       const __grid_constant__ CUtensorMap tmO, const __grid_constant__ CUtensorMap tmG,
                                                       const __grid_constant__ CUtensorMap tmU, const __grid_constant__ CUtensorMap tmD,
                                                       const __grid_constant__ CUtensorMap tmR,
                                                       const Ptrs P) {
  extern __shared__ __align__(1024) uint8_t smem_raw[];
  const int tid = threadIdx.x, wid = __shfl_sync(~0u, tid >> 5, 0), wg = wid >> 2, lane = tid & 31;
  int b;
  { const int j = blockIdx.x >> 1, t = j - 4;
    const int grp = j < 4 ? 0 : t < 32 ? t & 7 : 1 + (t - 32) % 7, mem = j < 4 ? 4 + j : t < 32 ? t >> 3 : 4 + (t - 32) / 7;
    const int r = MAPM == 1 ? grp : MAPM == 2 ? mem : MAPM == 3 ? (grp >> 2) * 4 + (mem & 3) : (grp >> 1) * 2 + (mem & 1);
    const int q = MAPM == 1 ? mem : MAPM == 2 ? grp : MAPM == 3 ? (grp & 3) * 2 + (mem >> 2) : (grp & 1) * 4 + (mem >> 1);
    b = r * 16 + q * 2 + (blockIdx.x & 1); }
  const int rb = b >> 4, cg = b & 15, hf = cg >> 3, c3 = cg & 7;
  const int jp = cg >> 1;
  const int fidx = jp == rb ? -1 : b - 2 * rb - (jp > rb ? 2 : 0);
  const uint32_t rank = b & 1, own = rank << 24, peer = own ^ (1u << 24);
  const uint32_t sm = own + sb, mb = own + bars;
  auto chunk_of = [&](int p) { const int q = p >> 1; return q == 0 ? cg ^ p : ((q < 5 ? ((jp & 4) ^ 4) + q - 1 : jp ^ (q - 4)) << 1) + (p & 1); };
  TS_DECL; TS(0); TSG(30);
  if (wid == 8) {
    if (elect_one()) {
      if (smem_u32(smem_raw) != sm) asm volatile("trap;");
#pragma unroll
      for (int s = 0; s < 4; s++) mbar_init(mb + B_FULL + 8 * s, 1);
      asm volatile("fence.mbarrier_init.release.cluster;" ::: "memory");
      fence_async_smem();
      mbar_expect_tx(mb + B_FULL, STAGE_B);
      tma_3d(sm + woff(0), &tmW, cg * 64, 0, 0, mb + B_FULL, EFW);
      tma_2d(sm, &tmX, 0, rb * 256, mb + B_FULL, EFX);
      tma_2d(sm + 16384, &tmX, 0, rb * 256 + 128, mb + B_FULL, EFX);
#pragma unroll
      for (int kb = 1; kb < 4; kb++) {
        mbar_expect_tx(mb + B_FULL + 8 * kb, STAGE_B);
        tma_3d(sm + woff(kb), &tmW, cg * 64, kb * 64, 0, mb + B_FULL + 8 * kb, EFW);
      }
    }
  } else if (wid == 9) {
    if (elect_one()) {
#pragma unroll
      for (int i = 4; i < 32; i++)
        if (i != 27) mbar_init(mb + 8 * i, i < 8 ? 8 : i == 8 ? 64 : i == 9 ? 4 : i == 10 ? 16 : i == 26 ? 2 : 1);
      asm volatile("fence.mbarrier_init.release.cluster;" ::: "memory");
      fence_async_smem();
    }
  } else if (wid == 11) {
#pragma unroll
    for (int i = 0; i < 4; i++) sts4(sm + OFF_STATS + i * 512 + lane * 16, SENT, SENT, SENT, SENT);
    fence_async_smem();
  }
  __syncthreads();
  asm volatile("barrier.cluster.arrive.relaxed.aligned;\nbarrier.cluster.wait.aligned;" ::: "memory");

  if (wg == 2) {
    asm volatile("setmaxnreg.dec.sync.aligned.u32 56;");
    auto wait_e = [&](int p) { mbar_wait(sm + OFF_EBAR + (p >> 3) * 1024 + (p & 7) * 8, 0); };
    auto load_b = [&](int p, int slot) {
      mbar_expect_tx(mb + B_FULL3 + 8 * p, (p & ~2) ? 2 * SLOT_B : SLOT_B);
      tma_3d(sm + slot * SLOT_B, &tmO, 0, chunk_of(p) * 64, c3 * 2, mb + B_FULL3 + 8 * p, false);
    };
    auto load_f = [&](int f, int slot) {
      if (f < 8) {
        tma_2d(sm + slot * SLOT_B, &tmG, fidx * 32, f * 128, mb + B_FFN, EFF);
        tma_2d(sm + slot * SLOT_B + 8192, &tmU, fidx * 32, f * 128, mb + B_FFN, EFF);
      } else tma_3d(sm + slot * SLOT_B, &tmD, 0, fidx * 32, (f - 8) * 4, mb + B_FFN + 8, EFF);
    };
    if (wid == 8) {
      if (elect_one()) {
#pragma unroll
        for (int kb = 1; kb < 4; kb++) tma_2d_mc(sm + xoff(kb) + rank * 16384, &tmX, kb * 64, rb * 256 + rank * 128, mb + B_FULL + 8 * kb, EFX);
#pragma unroll 1
        for (int kb = 4; kb < 16; kb++) {
          const uint32_t fb = mb + B_FULL + 8 * (kb & 3);
          mbar_wait(fb + B_EMPTY, ((kb >> 2) & 1) ^ 1);
          mbar_expect_tx(fb, STAGE_B);
          tma_2d_mc(sm + xoff(kb & 3) + rank * 16384, &tmX, kb * 64, rb * 256 + rank * 128, fb, EFX);
          tma_3d(sm + woff(kb & 3), &tmW, cg * 64, kb * 64, 0, fb, EFW);
          if (kb >= 16 - NDIR) asm volatile("mbarrier.arrive.shared::cta.b64 _, [%0], 4;" :: "r"(fb + B_EMPTY) : "memory");
        }
        if (fidx >= 0) { mbar_expect_tx(mb + B_FFN, 131072); mbar_expect_tx(mb + B_FFN + 8, 65536); }
#pragma unroll 1
        for (int p = 0; p < 10; p++) {
          if (p == 0 || p == 3 || p == 7 || p == 8) mbar_wait(mb + B_EMPTY + 8 * ((p + 1) / 3), 1);
          load_b(p, p);
        }
        mbar_wait(mb + B_EV0, 0);
#pragma unroll
        for (int p = 0; p < 16; p++) mbar_init(sm + OFF_EBAR + (p >> 3) * 1024 + (p & 7) * 8, (p == 3 || p == 6) ? 17 : 16);
        asm volatile("fence.mbarrier_init.release.cluster;" ::: "memory");
        mbar_arrive(mb + B_FULL + 16);
        mbar_expect_tx(mb + B_FULL, 32768);
        tma_3d(sm + 10 * SLOT_B, &tmR, 0, (rb * 4 + hf) * 64, c3 * 2, mb + B_FULL, true);
        tma_3d(sm + 12 * SLOT_B, &tmR, 0, (rb * 4 + 2 + hf) * 64, c3 * 2, mb + B_FULL, true);
      }
      __syncwarp();
      const uint4* src = &g_obuf[(rb * 4 + rank * 2 + hf) * 64 * 128];
      mbar_wait(mb + B_EV1, 0);
      { const long long t0 = clock64(); while (clock64() - t0 < ADELAY) {} }
      {
        const uint32_t* probe = &src[chunk_of(3 + ((lane >> 2) & 3)) * 512 + 384 + (lane & 3) * 32 + 31].w;
        uint32_t v = ld_rlx(probe);
#pragma unroll
        for (int p = 3; p < 7; p++) {
          if (p == 4) wait_e(0);
          for (int it = 0; __ballot_sync(~0u, v == SENT) & (15 << (4 * (p - 3))); it++) { v = ld_rlx(probe); SPINCHK(it, 10); }
          bulk_load_mc(sm + (10 + (p & 3)) * SLOT_B + rank * 8192, src + chunk_of(p) * 512, 8192, mb + B_FULL3 + 8 * p);
        }
      }
      PTS(6);
#pragma unroll 1
      for (int p = 7; p < 16; p++) {
        const uint4* q = src + chunk_of(p) * 512;
        wait_e(p - 4);
        bulk_load_mc(sm + (10 + (p & 3)) * SLOT_B + rank * 8192, q, 8192, mb + B_FULL3 + 8 * p);
      }
      PTS(15);
      if (fidx >= 0 && elect_one()) {
#pragma unroll 1
        for (int i = 0; i < 4; i++) { wait_e(12 + i); load_f(5 + 2 * i, 10 + i); }
      }
    } else {
      const int r4 = lane >> 3, c8 = lane & 7;
      const uint32_t eb = (lane << 24) + bars + B_EMPTY;
      auto tagged = [](float v, uint32_t tag) { return ((__float_as_uint(v) + 128) & ~255u) | tag; };
      auto gather = [&](uint32_t tag) {
        const int L = tid - 288, q = (L >> 5) * 24 + min(lane, 23);
        const uint4* cp = &g_csp[cg * 8 * 48 + q];
        const uint4* sp = &g_st1[rb * 128 + L];
        uint4 v[10];
        mbar_wait(mb + B_FULL + 8 * (GPACE & 3), (GPACE >> 2) & 1);
#pragma unroll 1
        for (int it = 0;; it++) {
#pragma unroll
          for (int i = 0; i < 8; i++) v[i] = ld_rlx4(cp + i * 48);
          v[8] = ld_rlx4(sp); v[9] = ld_rlx4(sp + 64);
          uint32_t x = 0;
#pragma unroll
          for (int i = 0; i < 10; i++) { v[i].x ^= tag; v[i].y ^= tag; v[i].z ^= tag; v[i].w ^= tag; x |= v[i].x | v[i].y | v[i].z | v[i].w; }
          if (!__any_sync(~0u, (x & 255) != 0)) break;
          SPINCHK(it, 3);
        }
        sts4(sm + OFF_STATS + L * 16, v[8].x, v[8].y, v[8].z, v[8].w);
        sts4(sm + OFF_STATS + 1024 + L * 16, v[9].x, v[9].y, v[9].z, v[9].w);
        float c[4] = {0.f, 0.f, 0.f, 0.f};
#pragma unroll
        for (int i = 0; i < 8; i++) { c[0] += __uint_as_float(v[i].x); c[1] += __uint_as_float(v[i].y); c[2] += __uint_as_float(v[i].z); c[3] += __uint_as_float(v[i].w); }
        sts4(sm + OFF_COLSUM + q * 16, __float_as_uint(c[0]), __float_as_uint(c[1]), __float_as_uint(c[2]), __float_as_uint(c[3]));
        mbar_arrive(mb + B_AUX);
      };
      if (wid == 9) {
        float a[12];
#pragma unroll
        for (int i = 0; i < 12; i++) a[i] = 0.f;
        const int r2 = lane >> 4, c16 = lane & 15;
        const uint32_t a0 = sm + rb * 1024 + r2 * 128 + (((c16 >> 1) ^ r2) << 4) + (c16 & 1) * 8;
        const uint2* gw = (const uint2*)(P.wqkv + ((16 - NDIR) * 64 + rb * 8 + r2) * 3072 + cg * 64) + c16;
#pragma unroll 1
        for (int it = 0; it < 16; it++) {
          uint2 w[12];
          const int kb = it - __popc(DMASK & ((1 << it) - 1));
          const bool direct = (DMASK >> it) & 1;
          if (it == 1) {
#pragma unroll
            for (int i = 0; i < NDIR; i++) if (lane < 24) l2_prefetch(P.wqkv + ((16 - NDIR + i) * 64 + rb * 8 + (lane & 7)) * 3072 + (lane >> 3) * 1024 + cg * 64);
          }
          if (direct) {
#pragma unroll
            for (int i = 0; i < 12; i++) w[i] = ld_rlx2(gw + (i >> 2) * 256 + (i & 3) * 1536);
            gw += 64 * 768;
          } else {
            const uint32_t so = a0 + woff(kb & 3);
            mbar_wait(mb + B_FULL + 8 * (kb & 3), (kb >> 2) & 1);
            static_for<0, 12>([&](auto ic) { constexpr int i = decltype(ic)::value;
              const float2 v = lds2f_o<(i >> 2) * 8192 + (i & 3) * 256>(so ^ ((i & 3) << 5)); w[i] = make_uint2(__float_as_uint(v.x), __float_as_uint(v.y)); });
          }
#pragma unroll
          for (int i = 0; i < 12; i++) {
            float* q = a + (i >> 2) * 4;
            q[0] += bf_lo(w[i].x); q[1] += bf_hi(w[i].x); q[2] += bf_lo(w[i].y); q[3] += bf_hi(w[i].y);
          }
          __syncwarp();
          if (lane < 2 && !direct) mbar_arrive_rem(eb + 8 * (kb & 3));
        }
        float c[6];
#pragma unroll
        for (int i = 0; i < 6; i++) {
          const int o = (i >> 1) * 4 + (i & 1);
          c[i] = (r2 ? a[o + 2] : a[o]) + __shfl_xor_sync(~0u, r2 ? a[o] : a[o + 2], 16);
        }
        bar_sync(5, 96);
        TS(6);
        const uint32_t tag = lds1(mb + B_SW + 4) & 255;
#pragma unroll
        for (int sg = 0; sg < 3; sg++) st_rlx2((uint2*)&g_csp[(cg * 8 + rb) * 48] + sg * 32 + c16 * 2 + r2, tagged(c[sg * 2], tag), tagged(c[sg * 2 + 1], tag));
        gather(tag);
        TS(2);
        {
          const uint4 sv = make_uint4(SENT, SENT, SENT, SENT);
          uint4* y = &g_ybuf[b * NFFN * 4 + lane];
#pragma unroll
          for (int i = 0; i < 14; i++) y[i * 32] = sv;
          if (lane < 16) g_st2[b * 16 + lane] = make_uint4(0, 0, 0, 0);
          g_hsel[b * 64 + lane] = sv; g_hsel[b * 64 + 32 + lane] = sv;
          if (b < 8) g_cand[b * 32 + lane] = SENT;
          fence_gpu();
          __syncwarp();
          if (lane == 0) mbar_arrive(mb + B_LATE);
        }
        TS(3);
        TS_DUMP(2);
        if (elect_one()) {
#pragma unroll 1
          for (int p = 1; p < 15; p++) {
            if (p == 1) mbar_wait(mb + B_EV1, 0);
            wait_e(p + 1);
            PTS(16 + p);
            if (p < 7) load_b(p + 9, p - 1);
            else if (fidx >= 0) load_f(p < 11 ? p - 7 : 2 * p - 18, p < 11 ? p - 1 : p - 11);
          }
        }
      } else if (wid == 10) {
        float sx[4], qx[4], piv[4];
        const uint32_t xa = sm + (cg * 16 + r4) * 128;
        mbar_wait(mb + B_FULL, 0);
#pragma unroll
        for (int i = 0; i < 4; i++) { sx[i] = 0.f; qx[i] = 0.f; piv[i] = bf_lo(lds1(xa + i * 512)); }
        const uint4* gx = (const uint4*)(P.x + (b * 16 + r4) * D_ + (16 - NDIR) * 64) + c8;
#pragma unroll 1
        for (int it = 0; it < 16; it++) {
          uint4 xv[4];
          const int kb = it - __popc(DMASK & ((1 << it) - 1));
          const bool direct = (DMASK >> it) & 1;
          if (it == 1) {
#pragma unroll
            for (int i = 0; i < NDIR; i++) if (lane < 16) l2_prefetch(P.x + (b * 16 + lane) * D_ + (16 - NDIR + i) * 64);
          }
          if (direct) {
#pragma unroll
            for (int i = 0; i < 4; i++) xv[i] = ld_cg4(gx + i * 512);
            gx += 8;
          } else {
            const uint32_t so = xa + c8 * 16 + xoff(kb & 3);
            mbar_wait(mb + B_FULL + 8 * (kb & 3), (kb >> 2) & 1);
            xv[0] = lds4_o<0>(so); xv[1] = lds4_o<512>(so); xv[2] = lds4_o<1024>(so); xv[3] = lds4_o<1536>(so);
          }
#pragma unroll
          for (int i = 0; i < 4; i++) {
            const uint32_t e[4] = {xv[i].x, xv[i].y, xv[i].z, xv[i].w};
#pragma unroll
            for (int j = 0; j < 4; j++) {
              const float d0 = bf_lo(e[j]) - piv[i], d1 = bf_hi(e[j]) - piv[i];
              sx[i] += d0 + d1; qx[i] = fmaf(d0, d0, fmaf(d1, d1, qx[i]));
            }
          }
          __syncwarp();
          if (lane < 2 && !direct) mbar_arrive_rem(eb + 8 * (kb & 3));
        }
#pragma unroll
        for (int o = 1; o < 8; o <<= 1)
#pragma unroll
          for (int i = 0; i < 4; i++) { sx[i] += __shfl_xor_sync(~0u, sx[i], o); qx[i] += __shfl_xor_sync(~0u, qx[i], o); }
        const float m = (c8 == 0 ? sx[0] : c8 == 1 ? sx[1] : c8 == 2 ? sx[2] : sx[3]) * (1.f / D_);
        const float var = fmaxf(fmaf(-m, m, (c8 == 0 ? qx[0] : c8 == 1 ? qx[1] : c8 == 2 ? qx[2] : qx[3]) * (1.f / D_)), 0.f);
        const float mean = m + (c8 == 0 ? piv[0] : c8 == 1 ? piv[1] : c8 == 2 ? piv[2] : piv[3]);
        bar_sync(5, 96);
        const uint32_t tag = lds1(mb + B_SW + 4) & 255;
        if (c8 < 4) st_rlx2((uint2*)g_st1 + b * 16 + r4 + 4 * c8, tagged(-mean, tag), tagged(rsqrtf(var + 1e-5f), tag));
        gather(tag);
        uint32_t sink = 0;
#pragma unroll 1
        for (int i = 0; i < 4; i++) {
          const __nv_bfloat16* q = P.x + ((rb * 4 + hf) * 64 + i * 16 + (lane >> 1)) * D_ + c3 * 128 + (lane & 1) * 64;
          sink ^= ld_line(q) ^ ld_line(q + 128 * D_);
        }
        const uint2 w = ld_rlx2((const uint2*)(P.wr + c3 * 128) + lane);
        if (sink == 0x9E3779B9u && tag == 256) sts1(mb + B_SW + 4, sink);
        mbar_wait(mb + B_EV1, 0);
        sts4(sm + OFF_COLSUM + lane * 16, w.x << 16, w.x & 0xFFFF0000u, w.y << 16, w.y & 0xFFFF0000u);
        __syncwarp();
        if (lane == 0) mbar_arrive(mb + B_FULL3 + 8 * 15);
#pragma unroll 1
        for (int h = 0; h < 2; h++) {
          const uint32_t* probe = &g_obuf[(rb * 4 + rank * 2 + hf) * 64 * 128 + chunk_of(min(7 + 3 * h + (lane >> 2), 9 + 6 * h)) * 512 + 384 + (lane & 3) * 32 + 31].w;
          wait_e(2 + 2 * h);
          for (int it = 0; __any_sync(~0u, ld_rlx(probe) == SENT); it++) SPINCHK(it, 11);
          if (lane == 0) mbar_arrive(sm + OFF_EBAR + 24 + 24 * h);
        }
      } else {
        mbar_wait(mb + B_FULL + 8 * PFST, 0);
        if (elect_one()) {
#pragma unroll 1
          for (int i = 0; i < 16; i++) bulk_store(&g_obuf[((rb * 4 + (i >> 2)) * 64 + cg * 4 + (i & 3)) * 128], sm + OFF_STATS, 2048);
          bulk_store(&g_kvp[(cg * 8 + rb) * 272], sm + OFF_STATS, 2048); bulk_store(&g_kvp[(cg * 8 + rb) * 272 + 128], sm + OFF_STATS, 2048);
          bulk_store(&g_kvp[(cg * 8 + rb) * 272 + 256], sm + OFF_STATS, 256);
          asm volatile("cp.async.bulk.commit_group;" ::: "memory");
          tmap_prefetch(&tmO); tmap_prefetch(&tmG); tmap_prefetch(&tmU); tmap_prefetch(&tmD); tmap_prefetch(&tmR);
        }
        __syncwarp();
        const char* pg = (const char*)P.wg + (size_t)(rank * 32 + lane) * (F_ * 2) + (fidx >> 1) * 128;
        const char* pu = (const char*)P.wu + (size_t)(rank * 32 + lane) * (F_ * 2) + (fidx >> 1) * 128;
        const char* pd = (const char*)P.wd + (size_t)fidx * 65536 + lane * 128;
        uint32_t sink = 0;
        auto line = [&](int r, int h) { return r < 8 ? ((h & 1) ? pu : pg) + (size_t)(2 * r + (h >> 1)) * (64 * F_ * 2) : pd + (4 * r + h - 32) * 4096; };
#pragma unroll 1
        for (int r = -PFA; r < 12; r++) {
          uint32_t v[4] = {0, 0, 0, 0};
          if (r == 0) mbar_wait(mb + B_FULL + 8 * (PULL0 & 3), (PULL0 >> 2) & 1);
          if (fidx >= 0) {
            if (r >= 0 && r < NPULL) {
#pragma unroll
              for (int h = 0; h < 4; h++) v[h] = ld_line(line(r, h));
            }
            if (PFA && r + PFA < 12) {
#pragma unroll
              for (int h = 0; h < 4; h++) l2_prefetch(line(r + PFA, h));
            }
          }
          if (r == -1) {
            const uint32_t ep = ld_rlx(&g_epoch);
            float s = 0.f;
#pragma unroll
            for (int i = 0; i < 4; i++) {
              const uint4 v = ld_cg4((const uint4*)P.wr + lane + i * 32);
              s += (bf_lo(v.x) + bf_hi(v.x)) + (bf_lo(v.y) + bf_hi(v.y)) + (bf_lo(v.z) + bf_hi(v.z)) + (bf_lo(v.w) + bf_hi(v.w));
            }
#pragma unroll
            for (int o = 16; o; o >>= 1) s += __shfl_xor_sync(~0u, s, o);
            if (lane == 0) sts2f(mb + B_SW, s, __uint_as_float(ep + 1));
            asm volatile("cp.async.bulk.wait_group 0;\nfence.proxy.async;" ::: "memory");
            fence_gpu(); bar_arrive(5, 96); PTS(0);
          }
          if (r >= 3 && r < 7) l2_prefetch((const char*)P.wo + (size_t)b * 16384 + (r - 3) * 4096 + lane * 128);
          sink ^= v[0] ^ v[1] ^ v[2] ^ v[3];
          asm volatile("" : "+r"(sink));
        }
        PTS(1);
        if (sink == 0x9E3779B9u && P.out == nullptr) sts1(mb + B_SW + 4, sink);
      }
    }
    __syncwarp();
    mbar_wait(mb + B_OUT, 0);
    const float2 cf = lds2f(sm + OFF_STATS + 64);
    const int cand0 = 2047 - (__float_as_int(cf.x) & 2047), cand1 = 2047 - (__float_as_int(cf.y) & 2047), rr = lane >> 4;
    auto store_rows = [&](int tr, bool on) {
      const uint4 v = lds4(sm + 4 * SLOT_B + tr * 256 + (((lane & 15) ^ (tr & 7)) << 4));
      const float2 pr = lds2f(sm + OFF_LNP + (tr + (tr & 64)) * 8);
      const float f = 1.f + pr.x, n = pr.y;
      if (on) *(uint4*)(P.out + (size_t)(rb * 256 + hf * 64 + tr + (tr & 64)) * D_ + c3 * 128 + (lane & 15) * 8) =
          make_uint4(pack2(fmaf(bf_lo(v.x), f, n), fmaf(bf_hi(v.x), f, n)), pack2(fmaf(bf_lo(v.y), f, n), fmaf(bf_hi(v.y), f, n)),
                     pack2(fmaf(bf_lo(v.z), f, n), fmaf(bf_hi(v.z), f, n)), pack2(fmaf(bf_lo(v.w), f, n), fmaf(bf_hi(v.w), f, n)));
    };
    if (wid == 8) {
      { const long long t0 = clock64(); while (clock64() - t0 < CDELAY) {} }
      uint32_t k;
      for (int it = 0;; it++) { k = ld_rlx(&g_cand[c3 * 32 + lane]); if (!__any_sync(~0u, k == SENT)) break; SPINCHK(it, 12); }
      const uint32_t m1 = __reduce_max_sync(~0u, k), m2 = __reduce_max_sync(~0u, k == m1 ? 0 : k);
      if (k == m1 || k == m2) sts2f(sm + OFF_STATS + 80 + (k == m2) * 8, __uint_as_float(k), __int_as_float(lane));
      __syncwarp();
      if (lane == 0) { mbar_arrive(mb + B_SEL); PTS(16); }
      const uint32_t kc = __float_as_uint(rr ? cf.y : cf.x);
      const int c = rr ? cand1 : cand0;
      store_rows(((c >> 1) & 64) + (c & 63), kc != m1 && kc != m2);
    } else if (wid < 9 + NOUTW) {
#pragma unroll 2
      for (int tr = (wid - 9) * 2 + rr; tr < 128; tr += 2 * NOUTW) {
        const int row = rb * 256 + hf * 64 + tr + (tr & 64);
        store_rows(tr, row != cand0 && row != cand1);
      }
      if (wid == 9 && lane == 0) PTS(31);
    }
  } else {
    asm volatile("setmaxnreg.inc.sync.aligned.u32 224;");
    const int t128 = tid & 127, warp = wid & 3, g = lane >> 2, t = lane & 3;
    const int mb3 = rb * 4 + wg * 2 + hf;
    const int row0 = mb3 * 64 + warp * 16 + g;
    uint32_t pq[2][16];
    {
      float acc0[96], acc1[96];
#pragma unroll
      for (int i = 0; i < 96; i++) { acc0[i] = 0.f; acc1[i] = 0.f; }
      const uint32_t xo0 = dlo(sb, 16) + (wg * 2 + hf) * 512, xo1 = dlo(sb, 16) + (wg * 2 + (hf ^ 1)) * 512;
      const int nwait = wg ? 16 : KLEAD;
      const uint32_t eb0 = (t128 << 24) + bars + B_EMPTY;
#pragma unroll 1
      for (int kb = 0; kb < 16; kb++) {
        const int s = kb & 3;
        if (kb < nwait) mbar_wait(mb + B_FULL + 8 * s, (kb >> 2) & 1);
        if (kb == 0) TS(1);
        const uint32_t xs = xoff(s) >> 4, ws = dlo(sb, 8192) + (woff(s) >> 4);
        pin(acc0); pin(acc1);
        wg_fence();
#pragma unroll
        for (int k = 0; k < 4; k++) {
          const uint64_t db = dsc<1024, 1>(ws + k * 128);
          wgmma_n192_ss<0, 1, 0>(acc0, dsc<1024, 1>(xs + xo0 + k * 2), db, 1);
          wgmma_n192_ss<0, 1, 0>(acc1, dsc<1024, 1>(xs + xo1 + k * 2), db, 1);
        }
        wg_commit();
        wg_wait<1>();
        pin(acc0); pin(acc1);
        if (kb > 0 && t128 < 2 && kb != nwait) mbar_arrive_rem(eb0 + 8 * ((kb - 1) & 3));
        if (kb == nwait - 1) {
          if (wg) bar_arrive(6, 256);
          else {
            wg_wait<0>();
            pin(acc0); pin(acc1);
            if (t128 < 2) mbar_arrive_rem(eb0 + 8 * s);
#pragma unroll
            for (int k2 = KLEAD; k2 < 16; k2++) mbar_wait(mb + B_FULL + 8 * (k2 & 3), 1);
            bar_sync(6, 256);
          }
        }
      }
      mbar_wait(mb + B_AUX, 0);
      float rs[2][2], nm[2][2];
#pragma unroll
      for (int m = 0; m < 2; m++)
#pragma unroll
        for (int h = 0; h < 2; h++) { const float2 v = lds2f(sm + OFF_STATS + ((wg * 2 + (m ^ hf)) * 64 + warp * 16 + h * 8 + g) * 8); nm[m][h] = v.x; rs[m][h] = v.y; }
      if (!wg) bar_arrive(7, 256);
      wg_wait<0>();
      pin(acc0); pin(acc1);
      if (t128 < 2) mbar_arrive_rem((t128 << 24) + bars + B_EMPTY + 24);
      TS(2);
      auto center = [&](auto jc) {
        constexpr int j = decltype(jc)::value;
        const float2 cs = lds2f_o<sb + OFF_COLSUM + j * 32>(own + t * 8);
        acc0[j * 4] = fmaf(nm[0][0], cs.x, acc0[j * 4]); acc0[j * 4 + 1] = fmaf(nm[0][0], cs.y, acc0[j * 4 + 1]);
        acc0[j * 4 + 2] = fmaf(nm[0][1], cs.x, acc0[j * 4 + 2]); acc0[j * 4 + 3] = fmaf(nm[0][1], cs.y, acc0[j * 4 + 3]);
        acc1[j * 4] = fmaf(nm[1][0], cs.x, acc1[j * 4]); acc1[j * 4 + 1] = fmaf(nm[1][0], cs.y, acc1[j * 4 + 1]);
        acc1[j * 4 + 2] = fmaf(nm[1][1], cs.x, acc1[j * 4 + 2]); acc1[j * 4 + 3] = fmaf(nm[1][1], cs.y, acc1[j * 4 + 3]);
      };
      static_for<16, 20>(center);
      bar_sync(2 + wg, 128);
      const uint32_t srow = sm + (10 + wg) * SLOT_B + (warp * 16 + (lane & 15)) * 128;
      const float L2E = 1.4426950408889634f;
      uint32_t sad[4];
#pragma unroll
      for (int j = 0; j < 4; j++) sad[j] = srow + (((2 * j + (lane >> 4)) ^ (lane & 7)) << 4);
#pragma unroll
      for (int j = 0; j < 4; j++) {
        const int v = 64 + j * 8;
        if (j == 2) { static_for<20, 24>(center); static_for<8, 16>(center); }
        stsm4_o<8192>(sad[j], pack2(acc0[v] * rs[0][0], acc0[v + 1] * rs[0][0]), pack2(acc0[v + 2] * rs[0][1], acc0[v + 3] * rs[0][1]),
                              pack2(acc0[v + 4] * rs[0][0], acc0[v + 5] * rs[0][0]), pack2(acc0[v + 6] * rs[0][1], acc0[v + 7] * rs[0][1]));
        stsm4_o<2 * SLOT_B + 8192>(sad[j], pack2(acc1[v] * rs[1][0], acc1[v + 1] * rs[1][0]), pack2(acc1[v + 2] * rs[1][1], acc1[v + 3] * rs[1][1]),
                                       pack2(acc1[v + 4] * rs[1][0], acc1[v + 5] * rs[1][0]), pack2(acc1[v + 6] * rs[1][1], acc1[v + 7] * rs[1][1]));
      }
      {
        const float rl00 = rs[0][0] * L2E, rl01 = rs[0][1] * L2E, rl10 = rs[1][0] * L2E, rl11 = rs[1][1] * L2E;
#pragma unroll
        for (int j = 0; j < 4; j++) {
          const int o = 32 + j * 8;
          stsm4_o<0>(sad[j], pack2(phi(acc0[o], rs[0][0], rl00), phi(acc0[o + 1], rs[0][0], rl00)), pack2(phi(acc0[o + 2], rs[0][1], rl01), phi(acc0[o + 3], rs[0][1], rl01)),
                             pack2(phi(acc0[o + 4], rs[0][0], rl00), phi(acc0[o + 5], rs[0][0], rl00)), pack2(phi(acc0[o + 6], rs[0][1], rl01), phi(acc0[o + 7], rs[0][1], rl01)));
          stsm4_o<2 * SLOT_B>(sad[j], pack2(phi(acc1[o], rs[1][0], rl10), phi(acc1[o + 1], rs[1][0], rl10)), pack2(phi(acc1[o + 2], rs[1][1], rl11), phi(acc1[o + 3], rs[1][1], rl11)),
                                  pack2(phi(acc1[o + 4], rs[1][0], rl10), phi(acc1[o + 5], rs[1][0], rl10)), pack2(phi(acc1[o + 6], rs[1][1], rl11), phi(acc1[o + 7], rs[1][1], rl11)));
        }
      }
      if (wg) {
        bar_sync(7, 256);
        if (t128 < 16) sts4(sm + OFF_STATS + t128 * 128 + ((t128 & 7) << 4), 0x3F803F80u, 0x3F803F80u, 0x3F803F80u, 0x3F803F80u);
      }
      fence_async_smem();
      if (wg) bar_sync(3, 128); else bar_sync(4, 256);
      TS(3);
      float ka[36];
#pragma unroll
      for (int i = 0; i < 36; i++) ka[i] = 0.f;
      pin(ka);
      wg_fence();
#pragma unroll
      for (int i = 0; i < 8; i++) {
        const uint32_t o = sb + 10 * SLOT_B + (i >> 2) * 2 * SLOT_B + (i & 3) * 2048;
        wgmma_n72_ss<1, 1, 0>(ka, dsc<1024, 1>(dlo(o, 8192) + wg * 1024), dsc<1024, 1>(dlo(o + 8192, sb + OFF_STATS - o - 8192) + wg * (1024u - (1024u << 16))), 1);
      }
      wg_commit();
      wg_wait<0>();
      pin(ka);
      if (t128 < 2) mbar_arrive_rem((t128 << 24) + bars + B_EV0);
      TS(4);
      float kvv[16];
#pragma unroll
      for (int i = 0; i < 16; i++) kvv[i] = (warp >> 1) ? ka[16 + i] : ka[i];
      const uint32_t xch = sm + 13 * SLOT_B + t128 * 16;
      const int d0 = warp * 16 + g, d1 = d0 + 8;
      const uint32_t za0 = sm + OFF_STATS + (d0 >> 2) * 128 + ((((d0 >> 2) + 1) & 7) << 4) + (d0 & 3) * 4;
      const uint32_t za1 = sm + OFF_STATS + (d1 >> 2) * 128 + ((((d1 >> 2) + 1) & 7) << 4) + (d1 & 3) * 4;
      if (wg == 1) {
#pragma unroll
        for (int q = 0; q < 4; q++) sts4(xch + q * 2048, __float_as_uint(kvv[q * 4]), __float_as_uint(kvv[q * 4 + 1]), __float_as_uint(kvv[q * 4 + 2]), __float_as_uint(kvv[q * 4 + 3]));
        if (t == 0) { sts1(za0, __float_as_uint(ka[32])); sts1(za1, __float_as_uint(ka[34])); }
        bar_arrive(4, 256);
      } else {
        mbar_wait(mb + B_LATE, 0);
#pragma unroll
        for (int q = 0; q < 4; q++) {
          const uint4 v = lds4(xch + q * 2048);
          kvv[q * 4] += __uint_as_float(v.x); kvv[q * 4 + 1] += __uint_as_float(v.y); kvv[q * 4 + 2] += __uint_as_float(v.z); kvv[q * 4 + 3] += __uint_as_float(v.w);
        }
        uint4* dst = &g_kvp[(cg * 8 + rb) * 272];
        st_rlx4(dst + warp * 64 + lane, make_uint4(pack2(kvv[0], kvv[1]), pack2(kvv[4], kvv[5]), pack2(kvv[8], kvv[9]), pack2(kvv[12], kvv[13])));
        st_rlx4(dst + warp * 64 + 32 + lane, make_uint4(pack2(kvv[2], kvv[3]), pack2(kvv[6], kvv[7]), pack2(kvv[10], kvv[11]), pack2(kvv[14], kvv[15])));
        if (t == 0) {
          st_rlx((uint32_t*)(dst + 256) + d0, __float_as_uint(ka[32] + __uint_as_float(lds1(za0))));
          st_rlx((uint32_t*)(dst + 256) + d1, __float_as_uint(ka[34] + __uint_as_float(lds1(za1))));
        }
      }
      if (QHOLD) { if (wg) bar_sync(8, 256); else bar_arrive(8, 256); }
      TS(5);
      auto q_epi = [&](float (&a)[96], const float r0, const float r1, uint32_t (&o)[16]) {
        const float rl0 = r0 * L2E, rl1 = r1 * L2E;
#pragma unroll
        for (int j = 0; j < 8; j++) {
          const int c = j * 4;
          o[j * 2] = pack2(phi(a[c], r0, rl0), phi(a[c + 1], r0, rl0));
          o[j * 2 + 1] = pack2(phi(a[c + 2], r1, rl1), phi(a[c + 3], r1, rl1));
        }
      };
      static_for<0, 8>(center);
      q_epi(acc0, rs[0][0], rs[0][1], pq[0]);
      q_epi(acc1, rs[1][0], rs[1][1], pq[1]);
#pragma unroll
      for (int i = 0; i < 16; i++) asm volatile("" : "+r"(pq[0][i]), "+r"(pq[1][i]) :: "memory");
    }
    TS(6);
    {
      uint4 v[8]; uint2 z;
      uint32_t dep = 0;
#pragma unroll
      for (int i = 0; i < 16; i++) dep = __vimax3_u32(dep, pq[0][i], pq[1][i]);
      asm volatile("bar.sync 1, %0;" :: "r"(dep == SENT ? 0 : 256) : "memory");
      const uint4* src = &g_kvp[cg * 8 * 272];
#pragma unroll
      for (int s = 0; s < 8; s++) v[s] = ld_rlx4(src + s * 272 + tid);
      z = ld_rlx2((const uint2*)(src + g * 272 + 256) + wid * 4 + t);
#pragma unroll 1
      for (int it = 0;; it++) {
        uint32_t m[8], mm = max(z.x, z.y);
#pragma unroll
        for (int s = 0; s < 8; s++) m[s] = max4(0, v[s]);
#pragma unroll
        for (int s = 0; s < 8; s += 2) mm = __vimax3_u32(mm, m[s], m[s + 1]);
        TSV(20, it + 1);
        if (!__any_sync(~0u, mm == SENT)) break;
        SPINCHK(it, 4);
#pragma unroll
        for (int s = 0; s < 8; s++) if (m[s] == SENT) v[s] = ld_rlx4(src + s * 272 + tid);
        z = ld_rlx2((const uint2*)(src + g * 272 + 256) + wid * 4 + t);
      }
      TS(23);
      float a[8], z0 = __uint_as_float(z.x), z1 = __uint_as_float(z.y);
#pragma unroll
      for (int o = 4; o < 32; o <<= 1) { z0 += __shfl_xor_sync(~0u, z0, o); z1 += __shfl_xor_sync(~0u, z1, o); }
#pragma unroll
      for (int i = 0; i < 8; i++) a[i] = 0.f;
#pragma unroll
      for (int s = 0; s < 8; s++) {
        a[0] += bf_lo(v[s].x); a[1] += bf_hi(v[s].x); a[2] += bf_lo(v[s].y); a[3] += bf_hi(v[s].y);
        a[4] += bf_lo(v[s].z); a[5] += bf_hi(v[s].z); a[6] += bf_lo(v[s].w); a[7] += bf_hi(v[s].w);
      }
      const uint32_t kb0 = sm + OFF_KVB + wid * 1024;
      stsm4(kb0 + (lane & 7) * 128 + (((lane >> 3) ^ (lane & 7)) << 4), pack2(a[0], a[1]), pack2(a[2], a[3]), pack2(a[4], a[5]), pack2(a[6], a[7]));
      if (lane < 8) {
        const int r = t * 2 + g;
        const float zs = g ? z1 : z0;
        const uint32_t zz = pack2(zs, zs);
        sts4(kb0 + r * 128 + ((4 ^ r) << 4), zz, zz, zz, zz);
      }
      fence_async_smem();
      bar_sync(1, 256);
    }
    TS(7);
    uint4 abuf[2][4], ost[2][4];
    uint4* const od0 = &g_obuf[(mb3 * 64 + cg * 4) * 128 + t128];
    uint4* const od1 = &g_obuf[((mb3 ^ 1) * 64 + cg * 4) * 128 + t128];
    {
      float oa[4][20];
#pragma unroll
      for (int i = 0; i < 4; i++)
#pragma unroll
        for (int j = 0; j < 20; j++) oa[i][j] = 0.f;
#pragma unroll
      for (int i = 0; i < 4; i++) pin(oa[i]);
      wg_fence();
#pragma unroll
      for (int m = 1; m >= 0; m--) {
#pragma unroll
        for (int ks = 0; ks < 4; ks++)
          wgmma_n40_rs<1, 0>(oa[m * 2 + (ks >> 1)], pq[m][ks * 4], pq[m][ks * 4 + 1], pq[m][ks * 4 + 2], pq[m][ks * 4 + 3], dsc<1024, 1>(dlo(sb + OFF_KVB + ks * 2048, 8192)), 1);
      }
      wg_commit();
      wg_wait<0>();
#pragma unroll
      for (int i = 0; i < 4; i++) pin(oa[i]);
      if (lane < 2) mbar_arrive_rem((lane << 24) + bars + B_EV1);
      mbar_wait(mb + B_FULL + 16, 0);
#pragma unroll
      for (int m = 1; m >= 0; m--) {
#pragma unroll
        for (int h = 0; h < 2; h++) {
          const float (&d)[20] = oa[m * 2 + h];
          const float i0 = rcp(d[16] + 1e-6f), i1 = rcp(d[18] + 1e-6f);
#pragma unroll
          for (int k2 = 0; k2 < 2; k2++) {
            const uint4 v = make_uint4(pack2(d[k2 * 8] * i0, d[k2 * 8 + 1] * i0), pack2(d[k2 * 8 + 2] * i1, d[k2 * 8 + 3] * i1),
                                       pack2(d[k2 * 8 + 4] * i0, d[k2 * 8 + 5] * i0), pack2(d[k2 * 8 + 6] * i1, d[k2 * 8 + 7] * i1));
            ost[m][h * 2 + k2] = v;
            if (m == 1) { if (!(jp & 2)) st_rlx4(od1 + (h * 2 + k2) * 128, v); }
            else {
              abuf[0][h * 2 + k2] = v; abuf[1][h * 2 + k2] = v;
              st_async4(peer + sb + 11 * SLOT_B + wg * 8192 + (h * 2 + k2) * 2048 + t128 * 16, v, peer + bars + B_FULL3 + 8);
            }
          }
        }
      }
    }
    TS(8);
    float acc[64];
#pragma unroll
    for (int i = 0; i < 64; i++) acc[i] = 0.f;
    {
      const uint32_t la = own + wg * 8192 + t128 * 16, eb = (lane << 24) + sb + OFF_EBAR;
      auto fetch = [&](int p, uint4 (&a)[4]) {
        const uint32_t ra = la + (p & 3) * SLOT_B;
        a[0] = lds4_o<sb + 10 * SLOT_B>(ra); a[1] = lds4_o<sb + 10 * SLOT_B + 2048>(ra);
        a[2] = lds4_o<sb + 10 * SLOT_B + 4096>(ra); a[3] = lds4_o<sb + 10 * SLOT_B + 6144>(ra);
      };
      mbar_wait(mb + B_FULL3, 0);
#pragma unroll 1
      for (int pp = 0; pp < 16; pp += 2) {
#pragma unroll
        for (int j = 0; j < 2; j++) {
          const int p = pp + j;
          uint4 (&a)[4] = abuf[j];
          if (__any_sync(~0u, max(max4(max4(0, a[0]), a[1]), max4(max4(0, a[2]), a[3])) == SENT)) {
            int pl = p; asm volatile("" : "+r"(pl));
            const uint4* q = &g_obuf[(mb3 * 64 + chunk_of(pl) * 4) * 128 + t128];
#pragma unroll 1
            for (int it = 0;; it++) {
#pragma unroll
              for (int i = 0; i < 4; i++) a[i] = ld_rlx4(q + i * 128);
              TSV(21, _ts + 1);
              if (!__any_sync(~0u, max(max4(max4(0, a[0]), a[1]), max4(max4(0, a[2]), a[3])) == SENT)) break;
              SPINCHK(it, 5);
            }
          }
          if (lane < 2 && (j == 1 || p > 0)) mbar_arrive_rem(eb + (p >> 3) * 1024 + (p & 7) * 8);
          const bool early = j == 0 ? pp > 2 : (pp > 0 && pp < 14);
          if (early) mbar_wait(mb + B_FULL3 + 8 * (p + 1), 0);
          wg_wait<0>();
          pin(acc);
#pragma unroll
          for (int i = 0; i < 4; i++) pin4(abuf[j ^ 1][i]);
          if (early) fetch(p + 1, abuf[j ^ 1]);
          if (p == 2) TS(9);
          const uint32_t bs = dlo(sb, 8192) + (p < 10 ? p : p - 10) * (SLOT_B >> 4);
          wg_fence();
#pragma unroll
          for (int k = 0; k < 4; k++) wgmma_n128_rs<1, 0>(acc, a[k].x, a[k].y, a[k].z, a[k].w, dsc<1024, 1>(bs + k * 128), 1);
          wg_commit();
          if (pp < 6) {
            if (j == 0 && p == 0 && (jp & 2)) {
#pragma unroll
              for (int k = 0; k < 4; k++) st_rlx4(od1 + k * 128, ost[1][k]);
            }
            if (p == ((jp >> 1) & 1) + W0OFF) {
#pragma unroll
              for (int k = 0; k < 4; k++) st_rlx4(od0 + k * 128, ost[0][k]);
            }
            if (!early) {
              mbar_wait(mb + B_FULL3 + 8 * (p + 1), 0);
              if (j == 0) fetch(p + 1, abuf[j ^ 1]);
              else {
                abuf[0][0].x = SENT;
                mbar_wait(mb + B_FULL, 0);
                const uint32_t xa = sm + (10 + wg * 2) * SLOT_B + (warp * 16 + (lane & 15)) * 128;
                uint32_t r[8][4];
#pragma unroll
                for (int q = 0; q < 4; q++) {
                  const uint32_t ad = xa + (((2 * q + (lane >> 4)) ^ (lane & 7)) << 4);
                  ldsm4_o<0>(ad, r[q][0], r[q][1], r[q][2], r[q][3]); ldsm4_o<8192>(ad, r[4 + q][0], r[4 + q][1], r[4 + q][2], r[4 + q][3]);
                }
                wg_wait<0>();
                pin(acc);
                if (lane < 2) mbar_arrive_rem(eb);
#pragma unroll
                for (int q = 0; q < 32; q++) { acc[q * 2] += bf_lo(r[q >> 2][q & 3]); acc[q * 2 + 1] += bf_hi(r[q >> 2][q & 3]); }
                TS(28);
              }
            }
          }
        }
      }
    }
    float wf[32];
    static_for<0, 16>([&](auto jc) { constexpr int j = decltype(jc)::value; const float2 v = lds2f_o<sb + OFF_COLSUM + j * 32>(own + t * 8); wf[j * 2] = v.x; wf[j * 2 + 1] = v.y; });
    pin(wf);
    wg_wait<0>();
    pin(acc);
#pragma unroll
    for (int i = 0; i < 4; i++) pin4(abuf[1][i]);
    TS(10);
    {
      float s0 = 0.f, q0 = 0.f, e0 = 0.f, s1 = 0.f, q1 = 0.f, e1 = 0.f;
#pragma unroll
      for (int j = 0; j < 16; j++) {
        const float a = acc[j * 4], c = acc[j * 4 + 1], d = acc[j * 4 + 2], e = acc[j * 4 + 3];
        s0 += a + c; q0 = fmaf(a, a, fmaf(c, c, q0)); e0 = fmaf(a, wf[j * 2], fmaf(c, wf[j * 2 + 1], e0));
        s1 += d + e; q1 = fmaf(d, d, fmaf(e, e, q1)); e1 = fmaf(d, wf[j * 2], fmaf(e, wf[j * 2 + 1], e1));
      }
      const bool od = t & 1;
      float s = (od ? s1 : s0) + __shfl_xor_sync(~0u, od ? s0 : s1, 1);
      float q = (od ? q1 : q0) + __shfl_xor_sync(~0u, od ? q0 : q1, 1);
      float e = (od ? e1 : e0) + __shfl_xor_sync(~0u, od ? e0 : e1, 1);
      s += __shfl_xor_sync(~0u, s, 2); q += __shfl_xor_sync(~0u, q, 2); e += __shfl_xor_sync(~0u, e, 2);
      if (t < 2) red4(&g_st2[row0 + t * 8], s, q, e, 1.f);
    }
    TS(11);
    const uint32_t msc = sm + OFF_STATS;
    const uint32_t hst = sm + 4 * SLOT_B + wid * 4096, myslot = sm + ((GU_SLOTS >> (4 * wid)) & 15) * SLOT_B;
    bar_sync(1, 256);
#pragma unroll
    for (int j = 0; j < 8; j++)
      stsm4(hst + (lane & 15) * 256 + (((2 * j + (lane >> 4)) ^ (lane & 7)) << 4), pack2(acc[j * 8], acc[j * 8 + 1]), pack2(acc[j * 8 + 2], acc[j * 8 + 3]),
            pack2(acc[j * 8 + 4], acc[j * 8 + 5]), pack2(acc[j * 8 + 6], acc[j * 8 + 7]));
    uint32_t wa[8][4][4], wd[8][2][4];
    const uint32_t a0 = myslot + ((lane >> 4) * 8 + (lane & 7)) * 64 + ((((lane >> 3) & 1) ^ ((lane >> 1) & 3)) << 4);
    auto load_gu = [&](auto ic) { constexpr int i = decltype(ic)::value; ldsm4t_o<(i >> 2) * 1024 + ((i >> 1) & 1) * 8192>(a0 ^ ((i & 1) << 5), wa[i >> 2][i & 3]); };
    {
      const int row = mb3 * 64 + warp * 16 + (lane & 15);
      uint4 v;
#pragma unroll 1
      for (int it = 0;; it++) {
        v = ld_rlx4(&g_st2[row]);
        TSV(22, it + 1);
        if (!__any_sync(~0u, v.w != 0x41000000u)) break;
        SPINCHK(it, 6);
      }
      TS(12);
      const float sw = __uint_as_float(lds1(mb + B_SW));
      const float mean = __uint_as_float(v.x) * (1.f / D_);
      const float rstd = rsq(fmaxf(fmaf(-mean, mean, __uint_as_float(v.y) * (1.f / D_)), 0.f) + 1e-5f);
      const uint32_t u = __float_as_uint(rstd * fmaf(-mean, sw, __uint_as_float(v.z)));
      uint32_t k = min(((u ^ ((uint32_t)((int)u >> 31) | 0x80000000u)) & ~2047u), 0xFFFFF000u) | (2047 - row);
      uint32_t m1 = __reduce_max_sync(~0u, k), m2 = __reduce_max_sync(~0u, k == m1 ? 0 : k);
      if (lane < 16) sts2f(sm + OFF_LNP + (wg * 128 + warp * 16 + lane) * 8, rstd, -mean * rstd);
      if (lane == 0) sts2f(msc + wid * 8, __uint_as_float(m1), __uint_as_float(m2));
      bar_sync(1, 256);
      k = lds1(msc + (lane & 15) * 4);
      m1 = __reduce_max_sync(~0u, k); m2 = __reduce_max_sync(~0u, k == m1 ? 0 : k);
      const int grp = rb * 2 + hf, c0 = 2047 - (m1 & 2047), c1 = 2047 - (m2 & 2047);
      if (tid == 0) {
        st_rlx2(&g_cand[c3 * 32 + grp * 2], m1, m2);
        sts2f(msc + 64, __uint_as_float(m1), __uint_as_float(m2));
        mbar_arrive(mb + B_OUT);
      }
      if ((c0 >> 4) == mb3 * 4 + warp || (c1 >> 4) == mb3 * 4 + warp) {
        const int ra = (lane & 4) ? c1 : c0, rd = (lane & 16) ? c1 : c0;
        uint32_t h0, h1, h2, h3;
        ldsm4_o<0>(hst + (ra & 15) * 256 + ((((lane & 3) * 4 + (lane >> 3)) ^ (ra & 7)) << 4), h0, h1, h2, h3);
        const float2 pr = lds2f(sm + OFF_LNP + (wg * 128 + warp * 16 + (rd & 15)) * 8);
        if ((rd >> 4) == mb3 * 4 + warp) {
          uint4* d = &g_hsel[(grp * 2 + (lane >> 4)) * 256 + c3 * 32 + t * 4 + (g & 3)];
          st_rlx4(d, make_uint4(pack2(fmaf(bf_lo(h0), pr.x, pr.y), fmaf(bf_hi(h0), pr.x, pr.y)), pack2(fmaf(bf_lo(h1), pr.x, pr.y), fmaf(bf_hi(h1), pr.x, pr.y)),
                                pack2(fmaf(bf_lo(h2), pr.x, pr.y), fmaf(bf_hi(h2), pr.x, pr.y)), pack2(fmaf(bf_lo(h3), pr.x, pr.y), fmaf(bf_hi(h3), pr.x, pr.y))));
          st_rlx4(d + 16, make_uint4(h0, h1, h2, h3));
        }
      }
    }
    TS(13);
    if (fidx >= 0) mbar_wait(mb + B_FFN, 0);
    static_for<0, 32>(load_gu);
    const uint32_t da = sm + (2 + (wid >> 2) + (wid & 2) * 5) * SLOT_B + (wid & 1) * 8192 + ((lane >> 4) * 8 + (lane & 7)) * 128 + ((((lane >> 3) & 1) ^ (lane & 7)) << 4);
    TS(15);
    mbar_wait(mb + B_SEL, 0);
    const uint4 sel = lds4(msc + 80);
    TS(26);
    float gu[2][4][4];
    uint32_t fh = 0, fn = 0;
    const uint32_t* fq = (const uint32_t*)g_hsel + ((tid & 1) ? sel.w : sel.y) * 1024 + (b >> 4) * 128 + ((tid >> 2) & 3) * 16 + (b & 15);
    {
      uint4 xb[4];
      const uint4* xp = &g_hsel[((lane & 16) ? sel.w : sel.y) * 256 + wid * 32 + (lane & 15)];
      uint4 xv = ld_rlx4(xp);
      if (tid < 16) { fn = ld_rlx(fq); fh = ld_rlx(fq + 64); }
      if (fidx >= 0) mbar_wait(mb + B_FFN + 8, 0);
      static_for<0, 8>([&](auto ic) { constexpr int i = decltype(ic)::value; ldsm4t_o<(i & 1) * 2048>(da ^ ((i >> 1) << 5), wd[i >> 1][i & 1]); });
#pragma unroll 1
      for (int it = 0; __any_sync(~0u, max4(0, xv) == SENT); it++) { xv = ld_rlx4(xp); TSV(24, it + 1); SPINCHK(it, 7); }
      sts4(myslot + 2048 + ((lane & 3) * 8 + (lane >> 2)) * 16, xv.x, xv.y, xv.z, xv.w);
      __syncwarp();
#pragma unroll
      for (int i = 0; i < 4; i++) xb[i] = lds4(myslot + 2048 + (i * 8 + (lane & 7)) * 16);
      TS(14);
#pragma unroll
      for (int i = 0; i < 32; i++) gu[i >> 4][(i >> 2) & 3][i & 3] = 0.f;
#pragma unroll
      for (int ks = 0; ks < 8; ks++) {
#pragma unroll
        for (int i = 0; i < 4; i++) mma16816(gu[ks & 1][i], wa[ks][i], (ks & 1) ? xb[ks >> 1].z : xb[ks >> 1].x, (ks & 1) ? xb[ks >> 1].w : xb[ks >> 1].y);
        if (ks == 3) {
          uint32_t dd = da; asm volatile("" : "+r"(dd) : "f"(gu[0][0][0]));
          static_for<0, 8>([&](auto ic) { constexpr int i = decltype(ic)::value; ldsm4t_o<4096 + (i & 1) * 2048>(dd ^ ((i >> 1) << 5), wd[4 + (i >> 1)][i & 1]); });
        }
      }
    }
    {
      float o[4];
#pragma unroll
      for (int j = 0; j < 4; j++) {
        const float s0 = gu[0][0][j] + gu[1][0][j], s1 = gu[0][1][j] + gu[1][1][j], s2 = gu[0][2][j] + gu[1][2][j], s3 = gu[0][3][j] + gu[1][3][j];
        o[j] = t == 0 ? s0 : t == 1 ? s1 : t == 2 ? s2 : s3;
      }
      sts2f(myslot + 1024 + (t * 16 + g) * 8, o[0], o[1]);
      sts2f(myslot + 1024 + (t * 16 + g + 8) * 8, o[2], o[3]);
    }
    TS(25);
    bar_sync(1, 256);
    {
      float g0 = 0.f, g1 = 0.f, u0 = 0.f, u1 = 0.f;
      static_for<0, 8>([&](auto wc) { constexpr int w = decltype(wc)::value;
        const float2 a = lds2f_o<sb + ((GU_SLOTS >> (4 * w)) & 15) * SLOT_B + 1024>(own + lane * 8), c = lds2f_o<sb + ((GU_SLOTS >> (4 * w)) & 15) * SLOT_B + 1280>(own + lane * 8);
        g0 += a.x; g1 += a.y; u0 += c.x; u1 += c.y; });
      const uint32_t act = pack2(g0 * rcp(1.f + ex2(-1.4426950408889634f * g0)) * u0, g1 * rcp(1.f + ex2(-1.4426950408889634f * g1)) * u1);
      uint32_t bq[4];
#pragma unroll
      for (int i = 0; i < 4; i++) {
        const uint32_t lo = __shfl_sync(~0u, act, i * 8 + 2 * t), hi = __shfl_sync(~0u, act, i * 8 + 2 * t + 1);
        bq[i] = __byte_perm(lo, hi, (g & 1) ? 0x7632 : 0x5410);
      }
      TS(16);
      float ya[8][4];
#pragma unroll
      for (int i = 0; i < 8; i++) { ya[i][0] = 0.f; ya[i][1] = 0.f; ya[i][2] = 0.f; ya[i][3] = 0.f; }
#pragma unroll
      for (int ks = 0; ks < 2; ks++)
#pragma unroll
        for (int i = 0; i < 8; i++) mma16816(ya[i], wd[i][ks], bq[ks * 2], bq[ks * 2 + 1]);
      if (fidx >= 0) {
        uint2* yp = (uint2*)&g_ybuf[((wid * 16 + t * 2) * NFFN + fidx) * 4] + g;
#pragma unroll
        for (int h = 0; h < 2; h++) {
          float o[4];
#pragma unroll
          for (int j = 0; j < 4; j++) o[j] = t == 0 ? ya[h * 4][j] : t == 1 ? ya[h * 4 + 1][j] : t == 2 ? ya[h * 4 + 2][j] : ya[h * 4 + 3][j];
          st_rlx2(yp + h * (8 * NFFN * 8), __float_as_uint(o[0]), __float_as_uint(o[1]));
          st_rlx2(yp + h * (8 * NFFN * 8) + NFFN * 8, __float_as_uint(o[2]), __float_as_uint(o[3]));
        }
      }
    }
    TS(17);
    const long long ty = clock64();
    {
      while (clock64() - ty < YDELAY) {}
      uint4 v0, v1 = make_uint4(0, 0, 0, 0);
#pragma unroll 1
      for (int it = 0;; it++) {
        v0 = ld_rlx4(&g_ybuf[b * NFFN * 4 + tid]);
        if (tid < 192) v1 = ld_rlx4(&g_ybuf[b * NFFN * 4 + 256 + tid]);
        TSV(27, it + 1);
        if (!__any_sync(~0u, max(max4(0, v0), max4(0, v1)) == SENT)) break;
        SPINCHK(it, 8);
      }
      TS(18);
      float y0 = __uint_as_float(v0.x) + __uint_as_float(v1.x), y1 = __uint_as_float(v0.y) + __uint_as_float(v1.y);
      float y2 = __uint_as_float(v0.z) + __uint_as_float(v1.z), y3 = __uint_as_float(v0.w) + __uint_as_float(v1.w);
      float z0 = ((lane & 16) ? y2 : y0) + __shfl_xor_sync(~0u, (lane & 16) ? y0 : y2, 16), z1 = ((lane & 16) ? y3 : y1) + __shfl_xor_sync(~0u, (lane & 16) ? y1 : y3, 16);
      z0 = ((lane & 8) ? z1 : z0) + __shfl_xor_sync(~0u, (lane & 8) ? z0 : z1, 8);
      z0 += __shfl_xor_sync(~0u, z0, 4);
      const uint32_t yx = msc + 128;
      if (!(lane & 4)) sts1(yx + wid * 64 + (t * 4 + (lane >> 3)) * 4, __float_as_uint(z0));
      bar_sync(1, 256);
      if (tid < 16) {
        float y = 0.f;
#pragma unroll
        for (int w = 0; w < 8; w++) y += __uint_as_float(lds1(yx + w * 64 + tid * 4));
        for (int it = 0; max(fn, fh) == SENT; it++) { fn = ld_rlx(fq); fh = ld_rlx(fq + 64); SPINCHK(it, 9); }
        const uint32_t key = (tid & 1) ? sel.z : sel.x;
        const float r = __uint_as_float(key ^ (~(uint32_t)((int)key >> 31) | 0x80000000u));
        const float base = (tid & 2) ? bf_hi(fh) + bf_hi(fn) : bf_lo(fh) + bf_lo(fn);
        P.out[(size_t)(2047 - (key & 2047)) * D_ + b * 8 + (tid >> 1)] = __float2bfloat16(fmaf(y, rcp(1.f + ex2(-1.4426950408889634f * r)), base));
      }
      if (b == 0 && tid == 32) g_epoch = lds1(mb + B_SW + 4);
    }
    TS(19); TSG(31);
    if (warp == 0) TS_DUMP(wg);
  }
}

typedef CUresult (*EncodeFn)(CUtensorMap*, CUtensorMapDataType, cuuint32_t, void*, const cuuint64_t*, const cuuint64_t*, const cuuint32_t*,
                             const cuuint32_t*, CUtensorMapInterleave, CUtensorMapSwizzle, CUtensorMapL2promotion, CUtensorMapFloatOOBfill);
void make_map(EncodeFn enc, CUtensorMap* m, const void* p, uint64_t cols, uint64_t rows, uint64_t d0, uint32_t b0, uint32_t b1, uint32_t b2, CUtensorMapSwizzle sw) {
  cuuint64_t dims[3] = {d0, rows, cols / d0}, str[2] = {cols * 2, d0 * 2};
  cuuint32_t box[3] = {b0, b1, b2}, es[3] = {1, 1, 1};
  enc(m, CU_TENSOR_MAP_DATA_TYPE_BFLOAT16, b2 ? 3 : 2, const_cast<void*>(p), dims, str, box, es, CU_TENSOR_MAP_INTERLEAVE_NONE, sw,
      CU_TENSOR_MAP_L2_PROMOTION_L2_128B, CU_TENSOR_MAP_FLOAT_OOB_FILL_NONE);
}

}

extern "C" void kernel_launch(void* const* d_in, const int* in_sizes, int n_in, void* d_out, int out_size) {
  (void)in_sizes; (void)n_in; (void)out_size;
  Ptrs P;
  P.x = (const __nv_bfloat16*)d_in[0]; P.wqkv = (const __nv_bfloat16*)d_in[1]; P.wo = (const __nv_bfloat16*)d_in[2];
  P.wr = (const __nv_bfloat16*)d_in[4]; P.wg = (const __nv_bfloat16*)d_in[5]; P.wu = (const __nv_bfloat16*)d_in[6];
  P.wd = (const __nv_bfloat16*)d_in[7]; P.out = (__nv_bfloat16*)d_out;
  void* fn = nullptr;
  cudaDriverEntryPointQueryResult q;
  cudaGetDriverEntryPoint("cuTensorMapEncodeTiled", &fn, cudaEnableDefault, &q);
  EncodeFn enc = (EncodeFn)fn;
  CUtensorMap tmX, tmW, tmO, tmG, tmU, tmD, tmR;
  make_map(enc, &tmX, P.x, D_, S_, D_, 64, 128, 0, CU_TENSOR_MAP_SWIZZLE_128B);
  make_map(enc, &tmW, P.wqkv, 3 * D_, D_, D_, 64, 64, 3, CU_TENSOR_MAP_SWIZZLE_128B);
  make_map(enc, &tmO, P.wo, D_, D_, 64, 64, 64, 2, CU_TENSOR_MAP_SWIZZLE_128B);
  make_map(enc, &tmG, P.wg, F_, D_, F_, 32, 128, 0, CU_TENSOR_MAP_SWIZZLE_64B);
  make_map(enc, &tmU, P.wu, F_, D_, F_, 32, 128, 0, CU_TENSOR_MAP_SWIZZLE_64B);
  make_map(enc, &tmD, P.wd, D_, F_, 64, 64, 32, 4, CU_TENSOR_MAP_SWIZZLE_128B);
  make_map(enc, &tmR, P.x, D_, S_, 64, 64, 64, 2, CU_TENSOR_MAP_SWIZZLE_128B);
  cudaFuncSetAttribute(fused_kernel, cudaFuncAttributeMaxDynamicSharedMemorySize, SMEM_BYTES);
  fused_kernel<<<NCTA, 384, SMEM_BYTES>>>(tmX, tmW, tmO, tmG, tmU, tmD, tmR, P);
}
```

```cpp
#include <cuda_runtime.h>
#include <cuda.h>
#include <cuda_bf16.h>
#include <stdint.h>
#include <type_traits>
#include <initializer_list>

namespace {

constexpr int S_ = 2048, D_ = 1024, F_ = 3584;
constexpr int NCTA = 128, NFFN = 112;
constexpr uint32_t SENT = 0xFFFFFFFFu;
constexpr int SPIN_LIMIT = 1 << 20;

#define ADELAY 0
#define ADELAY2 100
#define PFA 6
#define PF0 8
#define WPF0 8
#define DPER 1200
#define PDEPTH 2
#define PSTART 4000
#define PPER 1700
#define PEARLY 5
#define PLEAD 0
#define RST 1
#define PSUB 2
#define HOLDP 1
#define QHOLD 1
#define NPULL 12
#define CDELAY 0
#define NOUTW 3
#define YDELAY 500
#define EFX 0
#define EFW 1
#define EFF 1
#define KLEAD 13
#define GDELAY 1000
#define NDIR 6
#define PULL0 5
#define FD0 400
#define FD1 800
#define SPF 1
#define MPF 1
#define TLBW 2
#define GORD 0
#define GSPLIT 2
#define EFW0 0
#define EFX0 0
#define EFWK 8
#define PSLEEP 20
#define P3PULL 1
#define RST2 4
#define KDELAY 450
#define AEARLY 1
#define BHOLD 2
#define SDELAY 150
#define FSTAG 150
#define OFL 0
#define PSTOP 3
#define DMASK 0x5550
#define PFST 1
#define W0OFF 2
#define MAPM 2
#define XWPF 0
constexpr uint32_t STAGE_B = 57344;
constexpr uint32_t OFF_STATS = 229376;
constexpr uint32_t OFF_COLSUM = 231424;
constexpr uint32_t OFF_BARS = 232192;
constexpr uint32_t SMEM_BYTES = 232448;
constexpr uint32_t B_FULL = 0, B_EMPTY = 32, B_E = 64, B_AUX = 128, B_EVA = 136, B_EVB = 144, B_BF = 152, B_LATE = 232, B_FFN = 240, B_SW = 248;
constexpr uint32_t B_OUT = B_FULL, B_SEL = B_FULL + 8, B_WR = B_FULL + 16, B_FFD = B_FULL + 24, B_E16 = B_EMPTY + 16, B_KVB = B_EMPTY + 8, B_DUMMY = B_SW + 4,
                   B_KVP = B_BF + 64, B_F15 = B_BF + 72;
#define B_HOLD B_F15
#define HOLDPAR 0
constexpr uint32_t UNIT = 8192;
constexpr uint32_t sb = 1024;
constexpr uint32_t bars = sb + OFF_BARS;
constexpr uint64_t tab5(int a, int b, int c, int d, int e, int f, int g, int h, int i = 0, int j = 0) {
  return (uint64_t)a | (uint64_t)b << 5 | (uint64_t)c << 10 | (uint64_t)d << 15 | (uint64_t)e << 20 | (uint64_t)f << 25 | (uint64_t)g << 30 | (uint64_t)h << 35 |
         (uint64_t)i << 40 | (uint64_t)j << 45;
}
constexpr uint64_t BT0 = tab5(4, 11, 18, 25, 2, 7, 9, 16, 21, 23), BT1 = tab5(4, 11, 18, 25, 16, 21, 23, 2, 7, 9);
constexpr uint64_t GT0 = tab5(9, 16, 21, 23, 0, 4, 14, 11), GT1 = tab5(23, 2, 7, 9, 0, 4, 14, 11), DT = tab5(6, 13, 18, 19, 20, 27, 25, 26);
__device__ __forceinline__ uint32_t unit_of(uint64_t tab, int i) { return ((uint32_t)(tab >> (5 * i)) & 31) * UNIT; }
__device__ __forceinline__ uint32_t ring_of(int p, int w) { return (p & 1) * (2 * STAGE_B) + ((p & 2) ? 49152 + w * STAGE_B : w * UNIT); }
constexpr uint32_t OFF_LNP = OFF_STATS + 1024;

struct Scratch {
  uint4 obuf[32 * 64 * 128];
  uint4 kvp[16 * 8 * 256];
  uint4 zp[16 * 8 * 16];
  uint4 ybuf[NCTA * NFFN * 4];
  uint4 st1[S_];
  uint4 csp[16 * 8 * 48];
  uint4 st2[S_];
  uint4 hsel[32 * 256];
  uint32_t cand[8 * 32];
  uint32_t ocnt[16 * 32];
  unsigned epoch;
};
__device__ __align__(1024) Scratch g_scratch;
#define TS_DECL
#define TS(i)
#define TSG(i)
#define TSV(i, v)
#define TSD(i)
#define RTS_DECL
#define RTS(i)
#define RTS_DUMP
#define TS_DUMP(slot)
#define PTS(i)
#define g_dbgv(i, v)

__device__ __forceinline__ uint32_t smem_u32(const void* p) { return (uint32_t)__cvta_generic_to_shared(p); }
__device__ __forceinline__ void mbar_init(uint32_t bar, uint32_t cnt) { asm volatile("mbarrier.init.shared::cta.b64 [%0], %1;" :: "r"(bar), "r"(cnt) : "memory"); }
__device__ __forceinline__ void mbar_expect_tx(uint32_t bar, uint32_t bytes) { asm volatile("mbarrier.arrive.expect_tx.shared::cta.b64 _, [%0], %1;" :: "r"(bar), "r"(bytes) : "memory"); }
__device__ __forceinline__ void mbar_arrive(uint32_t bar) { asm volatile("mbarrier.arrive.shared::cta.b64 _, [%0];" :: "r"(bar) : "memory"); }
#define SPINCHK(it, code) if ((it) > SPIN_LIMIT) break
__device__ __forceinline__ void mbar_wait(uint32_t bar, uint32_t parity) {
  asm volatile("{\n.reg .pred p;\n.reg .u32 c;\nmov.u32 c, 0;\n"
               "WL:\nmbarrier.try_wait.parity.shared::cta.b64 p, [%0], %1;\n@p bra WD;\n"
               "add.u32 c, c, 1;\nsetp.lt.u32 p, c, 1048576;\n@p bra WL;\nWD:\n}" :: "r"(bar), "r"(parity) : "memory");
}
__device__ __forceinline__ bool mbar_test(uint32_t bar, uint32_t parity) {
  uint32_t ok;
  asm volatile("{\n.reg .pred p;\nmbarrier.test_wait.parity.shared::cta.b64 p, [%1], %2;\nselp.u32 %0, 1, 0, p;\n}" : "=r"(ok) : "r"(bar), "r"(parity) : "memory");
  return ok;
}
__device__ __forceinline__ uint64_t l2_stream() { uint64_t p; asm("createpolicy.fractional.L2::evict_first.b64 %0, 1.0;" : "=l"(p)); return p; }
__device__ __forceinline__ void tma_2d(uint32_t dst, const CUtensorMap* tm, int c0, int c1, uint32_t bar, bool stream) {
  if (stream) asm volatile("cp.async.bulk.tensor.2d.shared::cluster.global.mbarrier::complete_tx::bytes.L2::cache_hint [%0], [%1, {%3, %4}], [%2], %5;"
                           :: "r"(dst), "l"(tm), "r"(bar), "r"(c0), "r"(c1), "l"(l2_stream()) : "memory");
  else asm volatile("cp.async.bulk.tensor.2d.shared::cluster.global.mbarrier::complete_tx::bytes [%0], [%1, {%3, %4}], [%2];"
                    :: "r"(dst), "l"(tm), "r"(bar), "r"(c0), "r"(c1) : "memory");
}
__device__ __forceinline__ void tma_3d(uint32_t dst, const CUtensorMap* tm, int c0, int c1, int c2, uint32_t bar, bool stream) {
  if (stream) asm volatile("cp.async.bulk.tensor.3d.shared::cluster.global.mbarrier::complete_tx::bytes.L2::cache_hint [%0], [%1, {%3, %4, %5}], [%2], %6;"
                           :: "r"(dst), "l"(tm), "r"(bar), "r"(c0), "r"(c1), "r"(c2), "l"(l2_stream()) : "memory");
  else asm volatile("cp.async.bulk.tensor.3d.shared::cluster.global.mbarrier::complete_tx::bytes [%0], [%1, {%3, %4, %5}], [%2];"
                    :: "r"(dst), "l"(tm), "r"(bar), "r"(c0), "r"(c1), "r"(c2) : "memory");
}
__device__ __forceinline__ void tma_pf_3d(const CUtensorMap* tm, int c0, int c1, int c2) {
  asm volatile("cp.async.bulk.prefetch.tensor.3d.L2.global [%0, {%1, %2, %3}];" :: "l"(tm), "r"(c0), "r"(c1), "r"(c2) : "memory");
}
__device__ __forceinline__ void tma_4d(uint32_t dst, const CUtensorMap* tm, int c0, int c1, int c2, int c3, uint32_t bar) {
  asm volatile("cp.async.bulk.tensor.4d.shared::cluster.global.mbarrier::complete_tx::bytes [%0], [%1, {%3, %4, %5, %6}], [%2];"
               :: "r"(dst), "l"(tm), "r"(bar), "r"(c0), "r"(c1), "r"(c2), "r"(c3) : "memory");
}
__device__ __forceinline__ void tma_2d_mc(uint32_t dst, const CUtensorMap* tm, int c0, int c1, uint32_t bar, bool stream) {
  if (stream) asm volatile("cp.async.bulk.tensor.2d.shared::cluster.global.mbarrier::complete_tx::bytes.multicast::cluster.L2::cache_hint [%0], [%1, {%3, %4}], [%2], %5, %6;"
                           :: "r"(dst), "l"(tm), "r"(bar), "r"(c0), "r"(c1), "h"((uint16_t)3), "l"(l2_stream()) : "memory");
  else asm volatile("cp.async.bulk.tensor.2d.shared::cluster.global.mbarrier::complete_tx::bytes.multicast::cluster [%0], [%1, {%3, %4}], [%2], %5;"
                    :: "r"(dst), "l"(tm), "r"(bar), "r"(c0), "r"(c1), "h"((uint16_t)3) : "memory");
}
__device__ __forceinline__ bool elect_one() {
  uint32_t p;
  asm volatile("{\n.reg .pred q;\nelect.sync _|q, 0xFFFFFFFF;\nselp.u32 %0, 1, 0, q;\n}" : "=r"(p));
  return p;
}
__device__ __forceinline__ void bulk_load_mc(uint32_t dst, const void* src, uint32_t bytes, uint32_t bar) {
  asm volatile("cp.async.bulk.shared::cluster.global.mbarrier::complete_tx::bytes.multicast::cluster [%0], [%1], %2, [%3], %4;"
               :: "r"(dst), "l"(src), "r"(bytes), "r"(bar), "h"((uint16_t)3) : "memory");
}
__device__ __forceinline__ void bulk_load(uint32_t dst, const void* src, uint32_t bytes, uint32_t bar) {
  asm volatile("cp.async.bulk.shared::cluster.global.mbarrier::complete_tx::bytes [%0], [%1], %2, [%3];" :: "r"(dst), "l"(src), "r"(bytes), "r"(bar) : "memory");
}
__device__ __forceinline__ void bulk_store(void* dst, uint32_t src, uint32_t bytes) {
  asm volatile("cp.async.bulk.global.shared::cta.bulk_group [%0], [%1], %2;" :: "l"(dst), "r"(src), "r"(bytes) : "memory");
}
__device__ __forceinline__ void mbar_arrive_rem(uint32_t bar) { asm volatile("mbarrier.arrive.shared::cluster.b64 _, [%0];" :: "r"(bar) : "memory"); }
__device__ __forceinline__ void st_async4(uint32_t addr, const uint4& v, uint32_t bar) {
  asm volatile("st.async.shared::cluster.mbarrier::complete_tx::bytes.v4.b32 [%0], {%1,%2,%3,%4}, [%5];" :: "r"(addr), "r"(v.x), "r"(v.y), "r"(v.z), "r"(v.w), "r"(bar) : "memory");
}
template <uint32_t O> __device__ __forceinline__ void ldsm4_o(uint32_t addr, uint32_t& a, uint32_t& b, uint32_t& c, uint32_t& d) {
  asm volatile("ldmatrix.sync.aligned.m8n8.x4.shared.b16 {%0,%1,%2,%3}, [%4+%5];" : "=r"(a), "=r"(b), "=r"(c), "=r"(d) : "r"(addr), "n"(O) : "memory");
}
template <uint32_t O> __device__ __forceinline__ void ldsm4t_o(uint32_t addr, uint32_t (&r)[4]) {
  asm volatile("ldmatrix.sync.aligned.m8n8.x4.trans.shared.b16 {%0,%1,%2,%3}, [%4+%5];" : "=r"(r[0]), "=r"(r[1]), "=r"(r[2]), "=r"(r[3]) : "r"(addr), "n"(O) : "memory");
}
__device__ __forceinline__ void mma16816(float (&c)[4], const uint32_t (&a)[4], uint32_t b0, uint32_t b1) {
  asm("mma.sync.aligned.m16n8k16.row.col.f32.bf16.bf16.f32 {%0,%1,%2,%3}, {%4,%5,%6,%7}, {%8,%9}, {%0,%1,%2,%3};"
      : "+f"(c[0]), "+f"(c[1]), "+f"(c[2]), "+f"(c[3]) : "r"(a[0]), "r"(a[1]), "r"(a[2]), "r"(a[3]), "r"(b0), "r"(b1));
}
__device__ __forceinline__ void l2_prefetch(const void* p) { asm volatile("prefetch.global.L2 [%0];" :: "l"(p) : "memory"); }
__device__ __forceinline__ uint32_t ld_line(const void* p) { uint32_t v; asm volatile("ld.global.cg.L2::128B.u32 %0, [%1];" : "=r"(v) : "l"(p) : "memory"); return v; }
__device__ __forceinline__ void tmap_prefetch(const CUtensorMap* tm) { asm volatile("prefetch.tensormap [%0];" :: "l"(tm) : "memory"); }
__device__ __forceinline__ void wg_fence() { asm volatile("wgmma.fence.sync.aligned;" ::: "memory"); }
__device__ __forceinline__ void wg_commit() { asm volatile("wgmma.commit_group.sync.aligned;" ::: "memory"); }
template <int N> __device__ __forceinline__ void wg_wait() { asm volatile("wgmma.wait_group.sync.aligned %0;" :: "n"(N) : "memory"); }
template <int N> __device__ __forceinline__ void pin(float (&d)[N]) {
#pragma unroll
  for (int i = 0; i < N; i++) asm volatile("" : "+f"(d[i]) :: "memory");
}
__device__ __forceinline__ void pin4(uint4& v) { asm volatile("" : "+r"(v.x), "+r"(v.y), "+r"(v.z), "+r"(v.w) :: "memory"); }
template <uint32_t SBO, uint32_t SWZ> __device__ __forceinline__ uint64_t dsc(uint32_t lo) { return ((uint64_t)((SBO >> 4) | (SWZ << 30)) << 32) | lo; }
__host__ __device__ constexpr uint32_t dlo(uint32_t addr, uint32_t lbo) { return (addr >> 4) | ((lbo >> 4) << 16); }
__device__ __forceinline__ void bar_sync(int id, int n) { asm volatile("bar.sync %0, %1;" :: "r"(id), "r"(n) : "memory"); }
__device__ __forceinline__ void bar_arrive(int id, int n) { asm volatile("bar.arrive %0, %1;" :: "r"(id), "r"(n) : "memory"); }
__device__ __forceinline__ void fence_async_smem() { asm volatile("fence.proxy.async.shared::cta;" ::: "memory"); }
__device__ __forceinline__ void fence_gpu() { asm volatile("fence.acq_rel.gpu;" ::: "memory"); }
__device__ __forceinline__ uint4 ld_cg4(const void* p) { uint4 v; asm volatile("ld.global.cg.v4.u32 {%0,%1,%2,%3}, [%4];" : "=r"(v.x), "=r"(v.y), "=r"(v.z), "=r"(v.w) : "l"(p) : "memory"); return v; }
__device__ __forceinline__ uint4 ld_rlx4(const void* p) { uint4 v; asm volatile("ld.relaxed.gpu.global.v4.u32 {%0,%1,%2,%3}, [%4];" : "=r"(v.x), "=r"(v.y), "=r"(v.z), "=r"(v.w) : "l"(p) : "memory"); return v; }
__device__ __forceinline__ uint32_t ld_rlx(const void* p) { uint32_t v; asm volatile("ld.relaxed.gpu.global.u32 %0, [%1];" : "=r"(v) : "l"(p) : "memory"); return v; }
__device__ __forceinline__ void st_rlx4(void* p, uint4 v) { asm volatile("st.relaxed.gpu.global.v4.u32 [%0], {%1,%2,%3,%4};" :: "l"(p), "r"(v.x), "r"(v.y), "r"(v.z), "r"(v.w) : "memory"); }
__device__ __forceinline__ void st_rlx2(void* p, uint32_t a, uint32_t b) { asm volatile("st.relaxed.gpu.global.v2.u32 [%0], {%1,%2};" :: "l"(p), "r"(a), "r"(b) : "memory"); }
__device__ __forceinline__ void st_rlx(void* p, uint32_t a) { asm volatile("st.relaxed.gpu.global.u32 [%0], %1;" :: "l"(p), "r"(a) : "memory"); }
__device__ __forceinline__ void red4(void* p, float a, float b, float c, float d) { asm volatile("red.relaxed.gpu.global.add.v4.f32 [%0], {%1,%2,%3,%4};" :: "l"(p), "f"(a), "f"(b), "f"(c), "f"(d) : "memory"); }
__device__ __forceinline__ uint32_t pack2(float lo, float hi) { uint32_t r; asm("cvt.rn.bf16x2.f32 %0, %1, %2;" : "=r"(r) : "f"(hi), "f"(lo)); return r; }
__device__ __forceinline__ float bf_lo(uint32_t v) { return __uint_as_float(v << 16); }
__device__ __forceinline__ float bf_hi(uint32_t v) { return __uint_as_float(v & 0xFFFF0000u); }
__device__ __forceinline__ void stsm4(uint32_t addr, uint32_t a, uint32_t b, uint32_t c, uint32_t d) {
  asm volatile("stmatrix.sync.aligned.m8n8.x4.shared.b16 [%0], {%1,%2,%3,%4};" :: "r"(addr), "r"(a), "r"(b), "r"(c), "r"(d) : "memory");
}
template <uint32_t O> __device__ __forceinline__ void stsm4_o(uint32_t addr, uint32_t a, uint32_t b, uint32_t c, uint32_t d) {
  asm volatile("stmatrix.sync.aligned.m8n8.x4.shared.b16 [%0+%5], {%1,%2,%3,%4};" :: "r"(addr), "r"(a), "r"(b), "r"(c), "r"(d), "n"(O) : "memory");
}
__device__ __forceinline__ void sts4(uint32_t addr, uint32_t a, uint32_t b, uint32_t c, uint32_t d) { asm volatile("st.shared.v4.u32 [%0], {%1,%2,%3,%4};" :: "r"(addr), "r"(a), "r"(b), "r"(c), "r"(d) : "memory"); }
__device__ __forceinline__ void sts2f(uint32_t addr, float a, float b) { asm volatile("st.shared.v2.f32 [%0], {%1,%2};" :: "r"(addr), "f"(a), "f"(b) : "memory"); }
__device__ __forceinline__ void sts1(uint32_t addr, uint32_t a) { asm volatile("st.shared.u32 [%0], %1;" :: "r"(addr), "r"(a) : "memory"); }
__device__ __forceinline__ float2 lds2f(uint32_t addr) { float2 v; asm volatile("ld.shared.v2.f32 {%0,%1}, [%2];" : "=f"(v.x), "=f"(v.y) : "r"(addr) : "memory"); return v; }
template <uint32_t O> __device__ __forceinline__ float2 lds2f_o(uint32_t addr) { float2 v; asm volatile("ld.shared.v2.f32 {%0,%1}, [%2+%3];" : "=f"(v.x), "=f"(v.y) : "r"(addr), "n"(O) : "memory"); return v; }
template <int I, int N, class F> __device__ __forceinline__ void static_for(F&& f) { if constexpr (I < N) { f(std::integral_constant<int, I>{}); static_for<I + 1, N>(f); } }
__device__ __forceinline__ uint4 lds4(uint32_t addr) { uint4 v; asm volatile("ld.shared.v4.u32 {%0,%1,%2,%3}, [%4];" : "=r"(v.x), "=r"(v.y), "=r"(v.z), "=r"(v.w) : "r"(addr) : "memory"); return v; }
__device__ __forceinline__ uint32_t lds1(uint32_t addr) { uint32_t v; asm volatile("ld.shared.u32 %0, [%1];" : "=r"(v) : "r"(addr) : "memory"); return v; }
__device__ __forceinline__ float ex2(float x) { float y; asm("ex2.approx.ftz.f32 %0, %1;" : "=f"(y) : "f"(x)); return y; }
__device__ __forceinline__ uint32_t max4(uint32_t m, const uint4& v) { return __vimax3_u32(__vimax3_u32(m, v.x, v.y), v.z, v.w); }
__device__ __forceinline__ float rsq(float x) { float y; asm("rsqrt.approx.ftz.f32 %0, %1;" : "=f"(y) : "f"(x)); return y; }
__device__ __forceinline__ float rcp(float x) { float y; asm("rcp.approx.ftz.f32 %0, %1;" : "=f"(y) : "f"(x)); return y; }
__device__ __forceinline__ uint2 ld_rlx2(const void* p) { uint2 v; asm volatile("ld.relaxed.gpu.global.v2.u32 {%0,%1}, [%2];" : "=r"(v.x), "=r"(v.y) : "l"(p) : "memory"); return v; }
template <uint32_t O> __device__ __forceinline__ uint4 lds4_o(uint32_t addr) { uint4 v; asm volatile("ld.shared.v4.u32 {%0,%1,%2,%3}, [%4+%5];" : "=r"(v.x), "=r"(v.y), "=r"(v.z), "=r"(v.w) : "r"(addr), "n"(O) : "memory"); return v; }
__device__ __forceinline__ uint32_t phi2(float u0, float u1, float rl, uint32_t r2) {
  uint32_t pu, r;
  asm("cvt.rn.relu.bf16x2.f32 %0, %1, %2;" : "=r"(pu) : "f"(u1), "f"(u0));
  asm("fma.rn.bf16x2 %0, %1, %2, %3;" : "=r"(r) : "r"(pu), "r"(r2), "r"(pack2(__saturatef(ex2(u0 * rl) + 1e-6f), __saturatef(ex2(u1 * rl) + 1e-6f))));
  return r;
}
__device__ __forceinline__ uint32_t dup2(float r) { uint32_t v; asm("cvt.rn.relu.bf16x2.f32 %0, %1, %1;" : "=r"(v) : "f"(r)); return v; }
__device__ __forceinline__ uint32_t zero_after(const uint32_t (&v)[16]) {
  uint32_t z = 0;
#pragma unroll
  for (int i = 0; i < 16; i++) z |= v[i];
  return z & 0x80008000u;
}
__device__ __forceinline__ uint32_t hadd2(uint32_t a, uint32_t b) { uint32_t v; asm("add.rn.bf16x2 %0, %1, %2;" : "=r"(v) : "r"(a), "r"(b)); return v; }
__device__ __forceinline__ void sched_fence() { asm volatile("{\n.reg .pred p;\n.reg .u64 c;\nSF:\nmov.u64 c, %clock64;\nsetp.eq.u64 p, c, 0;\n@p bra SF;\n}" ::: "memory"); }
__device__ __forceinline__ uint4 ld_gen4(const void* p) { uint4 v; asm volatile("ld.relaxed.gpu.v4.u32 {%0,%1,%2,%3}, [%4];" : "=r"(v.x), "=r"(v.y), "=r"(v.z), "=r"(v.w) : "l"(p) : "memory"); return v; }
__device__ __forceinline__ uint2 ld_gen2(const void* p) { uint2 v; asm volatile("ld.relaxed.gpu.v2.u32 {%0,%1}, [%2];" : "=r"(v.x), "=r"(v.y) : "l"(p) : "memory"); return v; }
__device__ __forceinline__ uint32_t lane_id() { uint32_t v; asm volatile("mov.u32 %0, %%laneid;" : "=r"(v)); return v; }
template <int A, int B, int N> __device__ __forceinline__ void pinr(float (&d)[N]) {
#pragma unroll
  for (int i = A; i < B; i++) asm volatile("" : "+f"(d[i]) :: "memory");
}
template <int N> __device__ __forceinline__ void pinu(uint32_t (&d)[N]) {
#pragma unroll
  for (int i = 0; i < N; i++) asm volatile("" : "+r"(d[i]) :: "memory");
}

template<int TA, int TB, int OFF, int SZ> __device__ __forceinline__ void wgmma_n192_ss(float (&d)[SZ], uint64_t da, uint64_t db, int scale_d) {
  asm volatile("{\n.reg .pred p;\nsetp.ne.b32 p, %98, 0;\n"
    "wgmma.mma_async.sync.aligned.m64n192k16.f32.bf16.bf16 {%0,%1,%2,%3,%4,%5,%6,%7,%8,%9,%10,%11,%12,%13,%14,%15,%16,%17,%18,%19,%20,%21,%22,%23,%24,%25,%26,%27,%28,%29,%30,%31,%32,%33,%34,%35,%36,%37,%38,%39,%40,%41,%42,%43,%44,%45,%46,%47,%48,%49,%50,%51,%52,%53,%54,%55,%56,%57,%58,%59,%60,%61,%62,%63,%64,%65,%66,%67,%68,%69,%70,%71,%72,%73,%74,%75,%76,%77,%78,%79,%80,%81,%82,%83,%84,%85,%86,%87,%88,%89,%90,%91,%92,%93,%94,%95}, %96, %97, p, 1, 1, %99, %100;\n}\n"
    : "+f"(d[OFF+0]), "+f"(d[OFF+1]), "+f"(d[OFF+2]), "+f"(d[OFF+3]), "+f"(d[OFF+4]), "+f"(d[OFF+5]), "+f"(d[OFF+6]), "+f"(d[OFF+7]),
      "+f"(d[OFF+8]), "+f"(d[OFF+9]), "+f"(d[OFF+10]), "+f"(d[OFF+11]), "+f"(d[OFF+12]), "+f"(d[OFF+13]), "+f"(d[OFF+14]), "+f"(d[OFF+15]),
      "+f"(d[OFF+16]), "+f"(d[OFF+17]), "+f"(d[OFF+18]), "+f"(d[OFF+19]), "+f"(d[OFF+20]), "+f"(d[OFF+21]), "+f"(d[OFF+22]), "+f"(d[OFF+23]),
      "+f"(d[OFF+24]), "+f"(d[OFF+25]), "+f"(d[OFF+26]), "+f"(d[OFF+27]), "+f"(d[OFF+28]), "+f"(d[OFF+29]), "+f"(d[OFF+30]), "+f"(d[OFF+31]),
      "+f"(d[OFF+32]), "+f"(d[OFF+33]), "+f"(d[OFF+34]), "+f"(d[OFF+35]), "+f"(d[OFF+36]), "+f"(d[OFF+37]), "+f"(d[OFF+38]), "+f"(d[OFF+39]),
      "+f"(d[OFF+40]), "+f"(d[OFF+41]), "+f"(d[OFF+42]), "+f"(d[OFF+43]), "+f"(d[OFF+44]), "+f"(d[OFF+45]), "+f"(d[OFF+46]), "+f"(d[OFF+47]),
      "+f"(d[OFF+48]), "+f"(d[OFF+49]), "+f"(d[OFF+50]), "+f"(d[OFF+51]), "+f"(d[OFF+52]), "+f"(d[OFF+53]), "+f"(d[OFF+54]), "+f"(d[OFF+55]),
      "+f"(d[OFF+56]), "+f"(d[OFF+57]), "+f"(d[OFF+58]), "+f"(d[OFF+59]), "+f"(d[OFF+60]), "+f"(d[OFF+61]), "+f"(d[OFF+62]), "+f"(d[OFF+63]),
      "+f"(d[OFF+64]), "+f"(d[OFF+65]), "+f"(d[OFF+66]), "+f"(d[OFF+67]), "+f"(d[OFF+68]), "+f"(d[OFF+69]), "+f"(d[OFF+70]), "+f"(d[OFF+71]),
      "+f"(d[OFF+72]), "+f"(d[OFF+73]), "+f"(d[OFF+74]), "+f"(d[OFF+75]), "+f"(d[OFF+76]), "+f"(d[OFF+77]), "+f"(d[OFF+78]), "+f"(d[OFF+79]),
      "+f"(d[OFF+80]), "+f"(d[OFF+81]), "+f"(d[OFF+82]), "+f"(d[OFF+83]), "+f"(d[OFF+84]), "+f"(d[OFF+85]), "+f"(d[OFF+86]), "+f"(d[OFF+87]),
      "+f"(d[OFF+88]), "+f"(d[OFF+89]), "+f"(d[OFF+90]), "+f"(d[OFF+91]), "+f"(d[OFF+92]), "+f"(d[OFF+93]), "+f"(d[OFF+94]), "+f"(d[OFF+95])
    : "l"(da), "l"(db), "r"(scale_d), "n"(TA), "n"(TB));
}
template<int TA, int TB, int OFF, int SZ> __device__ __forceinline__ void wgmma_n128_ss(float (&d)[SZ], uint64_t da, uint64_t db, int scale_d) {
  asm volatile("{\n.reg .pred p;\nsetp.ne.b32 p, %66, 0;\n"
    "wgmma.mma_async.sync.aligned.m64n128k16.f32.bf16.bf16 {%0,%1,%2,%3,%4,%5,%6,%7,%8,%9,%10,%11,%12,%13,%14,%15,%16,%17,%18,%19,%20,%21,%22,%23,%24,%25,%26,%27,%28,%29,%30,%31,%32,%33,%34,%35,%36,%37,%38,%39,%40,%41,%42,%43,%44,%45,%46,%47,%48,%49,%50,%51,%52,%53,%54,%55,%56,%57,%58,%59,%60,%61,%62,%63}, %64, %65, p, 1, 1, %67, %68;\n}\n"
    : "+f"(d[OFF+0]), "+f"(d[OFF+1]), "+f"(d[OFF+2]), "+f"(d[OFF+3]), "+f"(d[OFF+4]), "+f"(d[OFF+5]), "+f"(d[OFF+6]), "+f"(d[OFF+7]),
      "+f"(d[OFF+8]), "+f"(d[OFF+9]), "+f"(d[OFF+10]), "+f"(d[OFF+11]), "+f"(d[OFF+12]), "+f"(d[OFF+13]), "+f"(d[OFF+14]), "+f"(d[OFF+15]),
      "+f"(d[OFF+16]), "+f"(d[OFF+17]), "+f"(d[OFF+18]), "+f"(d[OFF+19]), "+f"(d[OFF+20]), "+f"(d[OFF+21]), "+f"(d[OFF+22]), "+f"(d[OFF+23]),
      "+f"(d[OFF+24]), "+f"(d[OFF+25]), "+f"(d[OFF+26]), "+f"(d[OFF+27]), "+f"(d[OFF+28]), "+f"(d[OFF+29]), "+f"(d[OFF+30]), "+f"(d[OFF+31]),
      "+f"(d[OFF+32]), "+f"(d[OFF+33]), "+f"(d[OFF+34]), "+f"(d[OFF+35]), "+f"(d[OFF+36]), "+f"(d[OFF+37]), "+f"(d[OFF+38]), "+f"(d[OFF+39]),
      "+f"(d[OFF+40]), "+f"(d[OFF+41]), "+f"(d[OFF+42]), "+f"(d[OFF+43]), "+f"(d[OFF+44]), "+f"(d[OFF+45]), "+f"(d[OFF+46]), "+f"(d[OFF+47]),
      "+f"(d[OFF+48]), "+f"(d[OFF+49]), "+f"(d[OFF+50]), "+f"(d[OFF+51]), "+f"(d[OFF+52]), "+f"(d[OFF+53]), "+f"(d[OFF+54]), "+f"(d[OFF+55]),
      "+f"(d[OFF+56]), "+f"(d[OFF+57]), "+f"(d[OFF+58]), "+f"(d[OFF+59]), "+f"(d[OFF+60]), "+f"(d[OFF+61]), "+f"(d[OFF+62]), "+f"(d[OFF+63])
    : "l"(da), "l"(db), "r"(scale_d), "n"(TA), "n"(TB));
}
template<int TA, int TB, int OFF, int SZ> __device__ __forceinline__ void wgmma_n64_ss(float (&d)[SZ], uint64_t da, uint64_t db, int scale_d) {
  asm volatile("{\n.reg .pred p;\nsetp.ne.b32 p, %34, 0;\n"
    "wgmma.mma_async.sync.aligned.m64n64k16.f32.bf16.bf16 {%0,%1,%2,%3,%4,%5,%6,%7,%8,%9,%10,%11,%12,%13,%14,%15,%16,%17,%18,%19,%20,%21,%22,%23,%24,%25,%26,%27,%28,%29,%30,%31}, %32, %33, p, 1, 1, %35, %36;\n}\n"
    : "+f"(d[OFF+0]), "+f"(d[OFF+1]), "+f"(d[OFF+2]), "+f"(d[OFF+3]), "+f"(d[OFF+4]), "+f"(d[OFF+5]), "+f"(d[OFF+6]), "+f"(d[OFF+7]),
      "+f"(d[OFF+8]), "+f"(d[OFF+9]), "+f"(d[OFF+10]), "+f"(d[OFF+11]), "+f"(d[OFF+12]), "+f"(d[OFF+13]), "+f"(d[OFF+14]), "+f"(d[OFF+15]),
      "+f"(d[OFF+16]), "+f"(d[OFF+17]), "+f"(d[OFF+18]), "+f"(d[OFF+19]), "+f"(d[OFF+20]), "+f"(d[OFF+21]), "+f"(d[OFF+22]), "+f"(d[OFF+23]),
      "+f"(d[OFF+24]), "+f"(d[OFF+25]), "+f"(d[OFF+26]), "+f"(d[OFF+27]), "+f"(d[OFF+28]), "+f"(d[OFF+29]), "+f"(d[OFF+30]), "+f"(d[OFF+31])
    : "l"(da), "l"(db), "r"(scale_d), "n"(TA), "n"(TB));
}
template<int TA, int TB, int OFF, int SZ> __device__ __forceinline__ void wgmma_n72_ss(float (&d)[SZ], uint64_t da, uint64_t db, int scale_d) {
  asm volatile("{\n.reg .pred p;\nsetp.ne.b32 p, %38, 0;\n"
    "wgmma.mma_async.sync.aligned.m64n72k16.f32.bf16.bf16 {%0,%1,%2,%3,%4,%5,%6,%7,%8,%9,%10,%11,%12,%13,%14,%15,%16,%17,%18,%19,%20,%21,%22,%23,%24,%25,%26,%27,%28,%29,%30,%31,%32,%33,%34,%35}, %36, %37, p, 1, 1, %39, %40;\n}\n"
    : "+f"(d[OFF+0]), "+f"(d[OFF+1]), "+f"(d[OFF+2]), "+f"(d[OFF+3]), "+f"(d[OFF+4]), "+f"(d[OFF+5]), "+f"(d[OFF+6]), "+f"(d[OFF+7]),
      "+f"(d[OFF+8]), "+f"(d[OFF+9]), "+f"(d[OFF+10]), "+f"(d[OFF+11]), "+f"(d[OFF+12]), "+f"(d[OFF+13]), "+f"(d[OFF+14]), "+f"(d[OFF+15]),
      "+f"(d[OFF+16]), "+f"(d[OFF+17]), "+f"(d[OFF+18]), "+f"(d[OFF+19]), "+f"(d[OFF+20]), "+f"(d[OFF+21]), "+f"(d[OFF+22]), "+f"(d[OFF+23]),
      "+f"(d[OFF+24]), "+f"(d[OFF+25]), "+f"(d[OFF+26]), "+f"(d[OFF+27]), "+f"(d[OFF+28]), "+f"(d[OFF+29]), "+f"(d[OFF+30]), "+f"(d[OFF+31]),
      "+f"(d[OFF+32]), "+f"(d[OFF+33]), "+f"(d[OFF+34]), "+f"(d[OFF+35])
    : "l"(da), "l"(db), "r"(scale_d), "n"(TA), "n"(TB));
}
template<int TB, int OFF, int SZ> __device__ __forceinline__ void wgmma_n64_rs(float (&d)[SZ], uint32_t a0, uint32_t a1, uint32_t a2, uint32_t a3, uint64_t db, int scale_d) {
  asm volatile("{\n.reg .pred p;\nsetp.ne.b32 p, %37, 0;\n"
    "wgmma.mma_async.sync.aligned.m64n64k16.f32.bf16.bf16 {%0,%1,%2,%3,%4,%5,%6,%7,%8,%9,%10,%11,%12,%13,%14,%15,%16,%17,%18,%19,%20,%21,%22,%23,%24,%25,%26,%27,%28,%29,%30,%31}, {%32,%33,%34,%35}, %36, p, 1, 1, %38;\n}\n"
    : "+f"(d[OFF+0]), "+f"(d[OFF+1]), "+f"(d[OFF+2]), "+f"(d[OFF+3]), "+f"(d[OFF+4]), "+f"(d[OFF+5]), "+f"(d[OFF+6]), "+f"(d[OFF+7]),
      "+f"(d[OFF+8]), "+f"(d[OFF+9]), "+f"(d[OFF+10]), "+f"(d[OFF+11]), "+f"(d[OFF+12]), "+f"(d[OFF+13]), "+f"(d[OFF+14]), "+f"(d[OFF+15]),
      "+f"(d[OFF+16]), "+f"(d[OFF+17]), "+f"(d[OFF+18]), "+f"(d[OFF+19]), "+f"(d[OFF+20]), "+f"(d[OFF+21]), "+f"(d[OFF+22]), "+f"(d[OFF+23]),
      "+f"(d[OFF+24]), "+f"(d[OFF+25]), "+f"(d[OFF+26]), "+f"(d[OFF+27]), "+f"(d[OFF+28]), "+f"(d[OFF+29]), "+f"(d[OFF+30]), "+f"(d[OFF+31])
    : "r"(a0), "r"(a1), "r"(a2), "r"(a3), "l"(db), "r"(scale_d), "n"(TB));
}
template<int TB, int OFF, int SZ> __device__ __forceinline__ void wgmma_n40_rs(float (&d)[SZ], uint32_t a0, uint32_t a1, uint32_t a2, uint32_t a3, uint64_t db, int scale_d) {
  asm volatile("{\n.reg .pred p;\nsetp.ne.b32 p, %25, 0;\n"
    "wgmma.mma_async.sync.aligned.m64n40k16.f32.bf16.bf16 {%0,%1,%2,%3,%4,%5,%6,%7,%8,%9,%10,%11,%12,%13,%14,%15,%16,%17,%18,%19}, {%20,%21,%22,%23}, %24, p, 1, 1, %26;\n}\n"
    : "+f"(d[OFF+0]), "+f"(d[OFF+1]), "+f"(d[OFF+2]), "+f"(d[OFF+3]), "+f"(d[OFF+4]), "+f"(d[OFF+5]), "+f"(d[OFF+6]), "+f"(d[OFF+7]),
      "+f"(d[OFF+8]), "+f"(d[OFF+9]), "+f"(d[OFF+10]), "+f"(d[OFF+11]), "+f"(d[OFF+12]), "+f"(d[OFF+13]), "+f"(d[OFF+14]), "+f"(d[OFF+15]),
      "+f"(d[OFF+16]), "+f"(d[OFF+17]), "+f"(d[OFF+18]), "+f"(d[OFF+19])
    : "r"(a0), "r"(a1), "r"(a2), "r"(a3), "l"(db), "r"(scale_d), "n"(TB));
}
template<int TB, int OFF, int SZ> __device__ __forceinline__ void wgmma_n128_rs(float (&d)[SZ], uint32_t a0, uint32_t a1, uint32_t a2, uint32_t a3, uint64_t db, int scale_d) {
  asm volatile("{\n.reg .pred p;\nsetp.ne.b32 p, %69, 0;\n"
    "wgmma.mma_async.sync.aligned.m64n128k16.f32.bf16.bf16 {%0,%1,%2,%3,%4,%5,%6,%7,%8,%9,%10,%11,%12,%13,%14,%15,%16,%17,%18,%19,%20,%21,%22,%23,%24,%25,%26,%27,%28,%29,%30,%31,%32,%33,%34,%35,%36,%37,%38,%39,%40,%41,%42,%43,%44,%45,%46,%47,%48,%49,%50,%51,%52,%53,%54,%55,%56,%57,%58,%59,%60,%61,%62,%63}, {%64,%65,%66,%67}, %68, p, 1, 1, %70;\n}\n"
    : "+f"(d[OFF+0]), "+f"(d[OFF+1]), "+f"(d[OFF+2]), "+f"(d[OFF+3]), "+f"(d[OFF+4]), "+f"(d[OFF+5]), "+f"(d[OFF+6]), "+f"(d[OFF+7]),
      "+f"(d[OFF+8]), "+f"(d[OFF+9]), "+f"(d[OFF+10]), "+f"(d[OFF+11]), "+f"(d[OFF+12]), "+f"(d[OFF+13]), "+f"(d[OFF+14]), "+f"(d[OFF+15]),
      "+f"(d[OFF+16]), "+f"(d[OFF+17]), "+f"(d[OFF+18]), "+f"(d[OFF+19]), "+f"(d[OFF+20]), "+f"(d[OFF+21]), "+f"(d[OFF+22]), "+f"(d[OFF+23]),
      "+f"(d[OFF+24]), "+f"(d[OFF+25]), "+f"(d[OFF+26]), "+f"(d[OFF+27]), "+f"(d[OFF+28]), "+f"(d[OFF+29]), "+f"(d[OFF+30]), "+f"(d[OFF+31]),
      "+f"(d[OFF+32]), "+f"(d[OFF+33]), "+f"(d[OFF+34]), "+f"(d[OFF+35]), "+f"(d[OFF+36]), "+f"(d[OFF+37]), "+f"(d[OFF+38]), "+f"(d[OFF+39]),
      "+f"(d[OFF+40]), "+f"(d[OFF+41]), "+f"(d[OFF+42]), "+f"(d[OFF+43]), "+f"(d[OFF+44]), "+f"(d[OFF+45]), "+f"(d[OFF+46]), "+f"(d[OFF+47]),
      "+f"(d[OFF+48]), "+f"(d[OFF+49]), "+f"(d[OFF+50]), "+f"(d[OFF+51]), "+f"(d[OFF+52]), "+f"(d[OFF+53]), "+f"(d[OFF+54]), "+f"(d[OFF+55]),
      "+f"(d[OFF+56]), "+f"(d[OFF+57]), "+f"(d[OFF+58]), "+f"(d[OFF+59]), "+f"(d[OFF+60]), "+f"(d[OFF+61]), "+f"(d[OFF+62]), "+f"(d[OFF+63])
    : "r"(a0), "r"(a1), "r"(a2), "r"(a3), "l"(db), "r"(scale_d), "n"(TB));
}

struct Ptrs { const __nv_bfloat16 *x, *wqkv, *wo, *wr, *wg, *wu, *wd; __nv_bfloat16* out; Scratch* s; };

enum { M_X, M_W, M_Q, M_O, M_S, M_G, M_U, M_D, M_N };
struct Maps { CUtensorMap m[M_N]; };

__global__ void __cluster_dims__(2, 1, 1) __launch_bounds__(384, 1) fused_kernel(const Ptrs P, const __grid_constant__ Maps T) {
  extern __shared__ __align__(1024) uint8_t smem_raw[];
  TS_DECL; TS(0); TSG(30);
  if (MPF == 1 && threadIdx.x == 0) { tmap_prefetch(&T.m[M_W]); tmap_prefetch(&T.m[M_Q]); tmap_prefetch(&T.m[M_X]); }
  if (MPF == 2 && threadIdx.x < 3) l2_prefetch(&T.m[threadIdx.x]);
  if (MPF == 3 && (threadIdx.x & 31) == 0 && threadIdx.x < 96) tmap_prefetch(&T.m[threadIdx.x >> 5]);
  const int tid = threadIdx.x, wid = __shfl_sync(~0u, tid >> 5, 0), wg = wid >> 2, lane = lane_id();
  int b;
  { const int j = blockIdx.x >> 1, t = j - 4;
    const int grp = j < 4 ? 0 : t < 32 ? t & 7 : 1 + (t - 32) % 7, mem = j < 4 ? 4 + j : t < 32 ? t >> 3 : 4 + (t - 32) / 7;
    const int r = MAPM == 1 ? grp : MAPM == 2 ? mem : MAPM == 3 ? (grp >> 2) * 4 + (mem & 3) : (grp >> 1) * 2 + (mem & 1);
    const int q = MAPM == 1 ? mem : MAPM == 2 ? grp : MAPM == 3 ? (grp & 3) * 2 + (mem >> 2) : (grp & 1) * 4 + (mem >> 1);
    b = r * 16 + q * 2 + (blockIdx.x & 1); }
  const int rb = b >> 4, cg = b & 15, hf = cg >> 3, s3 = cg & 7, c3 = s3 ^ ((rb & 1) << 2);
  const int jp = cg >> 1;
  const int fidx = jp == rb ? -1 : b - 2 * rb - (jp > rb ? 2 : 0);
  const uint32_t rank = b & 1, own = rank << 24, peer = own ^ (1u << 24);
  const uint32_t sm = own + sb, mb = own + bars;
  const int km = (~c3 & 6) << 1;
  auto kcol = [&](int kb) { return (kb ^ (kb < 8 ? km & 8 : km)) * 64; };
  auto src_of = [&](int p) { return p == 0 ? s3 : p == 15 ? s3 ^ 1 : (((jp & 3) ^ ((p - 7) >> 1)) << 1) + ((p - 1) & 1); };
  auto frag_of = [&](int p) { return p < 9 ? (p - 1) * 512 : 4096 + src_of(p) * 512; };
  const uint64_t btab = rank ? BT1 : BT0;
  auto load_w = [&](uint32_t st, int kc, uint32_t bar, bool last) { tma_3d(st + 32768, &T.m[M_W], cg * 64, kc, 1, bar, last); tma_2d(st + 49152, &T.m[M_Q], cg * 64, kc, bar, last); };
  const uint32_t tk = clock64();
  if (SPF && tid < 80) {
    const int i = tid - 32;
    l2_prefetch(tid < 32 ? P.x + (rb * 256 + (hf * 4 + (cg & 3)) * 32 + tid) * D_ + kcol(0) : P.wqkv + (kcol(0) + (rb >> 1) * 16 + (i & 15)) * 3072 + (i >> 4) * 1024 + cg * 64);
  }
  RTS_DECL;
  if (wid == 8) {
    if (elect_one()) {
      if (smem_u32(smem_raw) != sm) asm volatile("trap;");
#pragma unroll
      for (int s = 0; s < 4; s++) mbar_init(mb + B_FULL + 8 * s, 1);
      asm volatile("fence.mbarrier_init.release.cluster;" ::: "memory");
      fence_async_smem();
      mbar_expect_tx(mb + B_FULL, STAGE_B);
      load_w(sm, kcol(0), mb + B_FULL, EFW0);
      tma_2d(sm, &T.m[M_X], kcol(0), rb * 256, mb + B_FULL, EFX0);
      tma_2d(sm + 16384, &T.m[M_X], kcol(0), rb * 256 + 128, mb + B_FULL, EFX0);
      RTS(0);
    }
  } else if (wid == 9) {
    if (elect_one()) {
#pragma unroll
      for (int i = 4; i < 31; i++) mbar_init(mb + 8 * i, i < 8 ? 8 : i < 16 ? 16 : i == 16 ? 64 : i == 17 ? 8 : i == 18 ? 4 : 1);
      asm volatile("fence.mbarrier_init.release.cluster;" ::: "memory");
      fence_async_smem();
    }
  } else if (wid == 11) {
#pragma unroll
    for (int i = 0; i < 4; i++) sts4(sm + OFF_STATS + i * 512 + lane * 16, SENT, SENT, SENT, SENT);
    fence_async_smem();
  }
  __syncthreads();
  asm volatile("barrier.cluster.arrive.relaxed.aligned;\nbarrier.cluster.wait.aligned;" ::: "memory");

  if (wg == 2) {
    asm volatile("setmaxnreg.dec.sync.aligned.u32 56;");
    if (wid == 8) {
      if (elect_one()) {
#pragma unroll 1
        for (int kb = 1; kb < 15; kb++) {
          const uint32_t fb = mb + B_FULL + 8 * (kb & 3), st = sm + (kb & 3) * STAGE_B;
          const int kc = kcol(kb);
          if (kb < 4) while ((uint32_t)clock64() - tk < FD0 + kb * FD1) {}
          else mbar_wait(fb + B_EMPTY, ((kb >> 2) & 1) ^ 1);
          mbar_expect_tx(fb, STAGE_B);
          tma_2d_mc(st + rank * 16384, &T.m[M_X], kc, rb * 256 + rank * 128, fb, EFX);
          load_w(st, kc, fb, EFW && kb >= EFWK);
          if (kb >= 8 && kb < 11) asm volatile("mbarrier.arrive.shared::cta.b64 _, [%0], %1;" :: "r"(fb + B_EMPTY), "r"(4) : "memory");
        }
        {
          const uint32_t st = sm + 3 * STAGE_B, fa = mb + B_FULL + 24, fb = mb + B_F15;
          const int kc = kcol(15);
          mbar_wait(fa, 0);
          mbar_expect_tx(fa, 32768); mbar_expect_tx(fb, 24576);
          if (rank) { mbar_wait(mb + B_EMPTY + 24, 0); tma_2d_mc(st + 16384, &T.m[M_X], kc, rb * 256 + 128, fa, EFX); }
          mbar_wait(mb + B_EMPTY, 1);
          tma_3d(st + 32768, &T.m[M_W], cg * 64, kc, 1, fa, EFW);
          if (!rank) { mbar_wait(mb + B_EMPTY + 24, 0); tma_2d_mc(st, &T.m[M_X], kc, rb * 256, fb, EFX); }
          tma_2d(st + 49152, &T.m[M_Q], cg * 64, kc, fb, EFW);
        }
        const uint4* kp = &P.s->kvp[cg * 8 * 256], *zq = &P.s->zp[cg * 8 * 16], *src = &P.s->obuf[(rb * 4 + rank * 2 + hf) * 64 * 128];
        const uint32_t* cnt = &P.s->ocnt[(rb * 2 + (hf ^ 1)) * 32];
        mbar_expect_tx(mb + B_KVP, 32768 + 2048);
        asm volatile("" : "+l"(kp), "+l"(zq), "+l"(src), "+l"(cnt));
        mbar_wait(mb + B_EVB, 0);
        { const uint32_t t1 = clock64(); while ((uint32_t)clock64() - t1 < KDELAY) {} }
        bulk_load(sm + rank * (2 * STAGE_B) + STAGE_B, kp, 32768, mb + B_KVP);
        bulk_load(sm + rank * (2 * STAGE_B) + UNIT, zq, 2048, mb + B_KVP);
        mbar_wait(mb + B_E, 0);
        RTS(3);
        for (int it = 0; ld_rlx(cnt) != 7; it++) SPINCHK(it, 10);
        const uint32_t t0 = clock64();
        while ((uint32_t)clock64() - t0 < ADELAY) {}
        RTS(4);
#pragma unroll
        for (int p = 1; p < 5; p++) {
          if (p == 3) while ((uint32_t)clock64() - t0 < ADELAY2) {}
          bulk_load_mc(sm + ring_of(p, rank), src + (p - 1) * 512, UNIT, mb + B_BF + 8 * p);
        }
#pragma unroll 1
        for (int p = 5; p < 15; p++) {
          uint32_t dst = sm + ring_of(p, rank), bar = mb + B_BF + 8 * (p < 10 ? p : p - 10);
          const uint4* q = src + frag_of(p);
          asm volatile("" : "+r"(dst), "+r"(bar), "+l"(q));
          mbar_wait(mb + B_E + 8 * ((p - 4) & 7), p >= 12);
          bulk_load_mc(dst, q, UNIT, bar);
        }
        const uint4* s15 = &P.s->obuf[(rb * 4 + hf) * 64 * 128 + frag_of(15)];
        RTS_DUMP;
        mbar_wait(mb + B_E + 24, 1);
        bulk_load(sm + ring_of(15, 0), s15, UNIT, mb + B_BF + 40); bulk_load(sm + ring_of(15, 1), s15 + 2 * 64 * 128, UNIT, mb + B_BF + 40);
      }
    } else if (wid == 11) {
      mbar_wait(mb + B_FULL + 24, 0);
      mbar_wait(mb + B_FULL + 8 * (PULL0 & 3), PULL0 >> 2);
      int pr = fidx >= 0 ? 0 : 24, back = 0;
#pragma unroll 1
      for (int ph = 0; ph < 3; ph++) {
        const uint32_t stop = mb + (ph ? B_E16 : B_HOLD);
#pragma unroll 1
        while (pr < 24) {
          const bool gu = pr < 16;
          const uint32_t d = gu ? 64 * F_ * 2 : 8192;
          const uint32_t o = (gu ? (rank * 32 + lane) * (F_ * 2) + (fidx >> 1) * 128 : (fidx - 2) * 65536 + lane * 256) + pr * d;
          const char* q0 = (const char*)(gu ? P.wg : P.wd) + o, *q1 = gu ? (const char*)P.wu + o : q0 + 128;
#pragma unroll 1
          do {
            if (ph == 1) { l2_prefetch(q0); __nanosleep(PSLEEP); l2_prefetch(q1); __nanosleep(PSLEEP); }
            else {
              if (mbar_test(stop, ph >> 1)) goto next;
              asm volatile("cp.async.ca.shared.global.L2::128B [%0], [%1], 4;\ncp.async.commit_group;\ncp.async.wait_group %3;\n"
                           "cp.async.ca.shared.global.L2::128B [%0], [%2], 4;\ncp.async.commit_group;\ncp.async.wait_group %3;" :: "r"(mb + B_DUMMY), "l"(q0), "l"(q1), "n"(PDEPTH) : "memory");
            }
            q0 += d; q1 += d;
          } while (++pr & 7);
        }
      next:
        if (lane == 0) { PTS(ph == 2 ? 4 : 1 + ph); g_dbgv(3 + 2 * ph, pr); }
        if (ph == 0) back = pr;
        if (ph == 1) { pr = P3PULL ? back : 24; mbar_wait(mb + B_EVA, 0); mbar_wait(mb + B_KVB, 1); }
      }
      asm volatile("cp.async.wait_all;" ::: "memory");
    } else {
      const uint32_t eb = (lane << 24) + bars + B_EMPTY;
      float c[6];
      if (wid == 10) {
        float sx[4] = {0.f, 0.f, 0.f, 0.f}, qx[4] = {0.f, 0.f, 0.f, 0.f};
        const uint32_t xa = sm + ((hf * 4 + (cg & 3)) * 32 + lane) * 128 + ((lane & 7) << 4);
#pragma unroll 1
        for (int kb = 0; kb < 8; kb++) {
          uint4 xv[8];
          const uint32_t so = xa + (kb & 3) * STAGE_B;
          mbar_wait(mb + B_FULL + 8 * (kb & 3), kb >> 2);
#pragma unroll
          for (int i = 0; i < 8; i++) xv[i] = lds4(so ^ (i << 4));
#pragma unroll
          for (int i = 0; i < 8; i++) {
            const uint32_t e[4] = {xv[i].x, xv[i].y, xv[i].z, xv[i].w};
#pragma unroll
            for (int j = 0; j < 4; j++) {
              const float d0 = bf_lo(e[j]), d1 = bf_hi(e[j]);
              sx[j] += d0 + d1; qx[j] = fmaf(d0, d0, fmaf(d1, d1, qx[j]));
            }
          }
          __syncwarp();
          if (lane < 2) mbar_arrive_rem(eb + 8 * (kb & 3));
          if (kb == RST2) {
        {
          const uint32_t ep = ld_rlx(&P.s->epoch);
          float s = 0.f;
#pragma unroll
          for (int i = 0; i < 4; i++) {
            const uint4 v = ld_cg4((const uint4*)P.wr + lane + i * 32);
            s += (bf_lo(v.x) + bf_hi(v.x)) + (bf_lo(v.y) + bf_hi(v.y)) + (bf_lo(v.z) + bf_hi(v.z)) + (bf_lo(v.w) + bf_hi(v.w));
          }
#pragma unroll
          for (int o = 16; o; o >>= 1) s += __shfl_xor_sync(~0u, s, o);
          if (lane == 0) sts1(mb + B_SW, (__float_as_uint(s) & ~255u) | ((ep + 1) & 255));
        }
        asm volatile("cp.async.bulk.wait_group 0;\nfence.proxy.async.global;" ::: "memory");
        fence_gpu();
        if (lane == 0) PTS(0);
          }
          if (kb == RST) {
        if (elect_one()) {
#pragma unroll 1
          for (int i = 0; i < 16; i++) bulk_store(&P.s->obuf[((rb * 4 + (i >> 2)) * 64 + (((i >> 2) & 1) == hf ? 32 + s3 * 4 + (i & 3) : (i & 3) * 8 + s3)) * 128], sm + OFF_STATS, 2048);
          bulk_store(&P.s->kvp[(cg * 8 + rb) * 256], sm + OFF_STATS, 2048); bulk_store(&P.s->kvp[(cg * 8 + rb) * 256 + 128], sm + OFF_STATS, 2048);
          bulk_store(&P.s->zp[(cg * 8 + rb) * 16], sm + OFF_STATS, 256);
          if (s3 == 0) bulk_store(&P.s->ocnt[(rb * 2 + hf) * 32], sm + OFF_STATS, 128);
          asm volatile("cp.async.bulk.commit_group;" ::: "memory");
          #pragma unroll
          for (int i = M_O; i < M_N; i++) tmap_prefetch(&T.m[i]);
        }
        __syncwarp();
          }
        }
        c[0] = ((sx[0] + sx[1]) + (sx[2] + sx[3])) * (2.f / D_);
        c[1] = fmaxf(fmaf(-c[0], c[0], ((qx[0] + qx[1]) + (qx[2] + qx[3])) * (2.f / D_)), 0.f);
      } else {
        float a[12];
#pragma unroll
        for (int i = 0; i < 12; i++) a[i] = 0.f;
        const int r2 = lane >> 4, c16 = lane & 15;
        const uint32_t a0 = sm + 32768 + (rb >> 1) * 2048 + r2 * 128 + (((c16 >> 1) ^ r2) << 4) + (c16 & 1) * 8;
#pragma unroll 1
        for (int it = 0; it < 16; it++) {
          uint2 w[12];
          const int s = (it >> 1) & 3;
          const uint32_t so = a0 + s * STAGE_B + (it & 1) * 1024;
          if (!(it & 1)) { mbar_wait(mb + B_FULL + 8 * s, it >> 3); TSD(8 + (it >> 1)); }
          static_for<0, 12>([&](auto ic) { constexpr int i = decltype(ic)::value;
            const float2 v = lds2f_o<(i >> 2) * 8192 + (i & 3) * 256>(so ^ ((i & 3) << 5)); w[i] = make_uint2(__float_as_uint(v.x), __float_as_uint(v.y)); });
#pragma unroll
          for (int i = 0; i < 12; i++) { float* q = a + (i >> 2) * 4; q[0] += bf_lo(w[i].x); q[1] += bf_hi(w[i].x); q[2] += bf_lo(w[i].y); q[3] += bf_hi(w[i].y); }
          __syncwarp();
          if (lane < 2 && (it & 1)) mbar_arrive_rem(eb + 8 * s);
        }
#pragma unroll
        for (int i = 0; i < 6; i++) {
          const int o = (i >> 1) * 4 + (i & 1);
          c[i] = (r2 ? a[o + 2] : a[o]) + __shfl_xor_sync(~0u, r2 ? a[o] : a[o + 2], 16);
        }
      }
      TS(5);
      bar_sync(10, 64);
      TS(6);
      {
        const uint32_t tag = lds1(mb + B_SW) & 255;
        auto tagged = [&](float v) { return ((__float_as_uint(v) + 128) & ~255u) | tag; };
        if (wid == 9) {
#pragma unroll
          for (int sg = 0; sg < 3; sg++) {
            st_rlx2((uint2*)&P.s->csp[(cg * 8 + rb) * 48] + sg * 32 + (lane & 15) * 2 + (lane >> 4), tagged(c[sg * 2]), tagged(c[sg * 2 + 1]));
          }
        } else st_rlx2((uint2*)&P.s->st1[rb * 256 + (hf * 4 + (cg & 3)) * 32 + lane] + ((cg >> 2) & 1), tagged(c[0]), tagged(c[1]));
        { const uint32_t t0 = clock64(); while ((uint32_t)clock64() - t0 < GDELAY) {} }
#pragma unroll 1
        for (int h = wid - 9; h < 2; h++) {
          const int q = h * 24 + min(lane, 23), sd = wid == 10 ? 32 : 48;
          const uint4* gp = wid == 10 ? &P.s->st1[rb * 256 + lane] : &P.s->csp[cg * 8 * 48 + q];
          uint4 v[8];
#pragma unroll 1
          for (int it = 0;; it++) {
            uint32_t x = 0;
#pragma unroll
            for (int i = 0; i < 8; i++) v[i] = ld_rlx4(gp + i * sd);
#pragma unroll
            for (int i = 0; i < 8; i++) { v[i].x ^= tag; v[i].y ^= tag; v[i].z ^= tag; v[i].w ^= tag; x |= v[i].x | v[i].y | v[i].z | v[i].w; }
            if (!__any_sync(~0u, (x & 255) != 0)) break;
            SPINCHK(it, 3);
          }
          if (wid == 10) {
#pragma unroll
            for (int i = 0; i < 8; i++) {
              const float m0 = __uint_as_float(v[i].x), m1 = __uint_as_float(v[i].z), dm = 0.5f * (m0 - m1);
              sts2f(sm + OFF_STATS + (i * 32 + lane) * 8, -0.5f * (m0 + m1), rsq(fmaf(dm, dm, 0.5f * (__uint_as_float(v[i].y) + __uint_as_float(v[i].w))) + 1e-5f));
            }
          } else {
            float s4[4] = {0.f, 0.f, 0.f, 0.f};
#pragma unroll
            for (int i = 0; i < 8; i++) { s4[0] += __uint_as_float(v[i].x); s4[1] += __uint_as_float(v[i].y); s4[2] += __uint_as_float(v[i].z); s4[3] += __uint_as_float(v[i].w); }
            sts4(sm + OFF_COLSUM + q * 16, __float_as_uint(s4[0]), __float_as_uint(s4[1]), __float_as_uint(s4[2]), __float_as_uint(s4[3]));
          }
        }
        mbar_arrive(mb + B_AUX);
      }
      TS(2);
      if (wid == 9) {
        {
          const uint4 sv = make_uint4(SENT, SENT, SENT, SENT);
          uint4* y = &P.s->ybuf[b * NFFN * 4 + lane];
#pragma unroll
          for (int i = 0; i < 14; i++) y[i * 32] = sv;
          if (lane < 16) P.s->st2[b * 16 + lane] = make_uint4(0, 0, 0, 0);
          P.s->hsel[b * 64 + lane] = sv; P.s->hsel[b * 64 + 32 + lane] = sv;
          if (b < 8) P.s->cand[b * 32 + lane] = SENT;
          fence_gpu();
          __syncwarp();
          if (lane == 0) mbar_arrive(mb + B_LATE);
        }
        TS(3);
        TS_DUMP(2);
        if (elect_one()) {
#pragma unroll 1
          for (int p = 0; p < 16; p++) {
            const int sl = p < 10 ? p : p - 10;
            const bool sliced = p > 0 && p < 9;
            uint32_t bar = mb + B_BF + 8 * sl, dst = sm + unit_of(btab, sl);
            int c1 = sliced ? ((p - 1) >> 1) * 16 : 0, c2 = sliced ? (hf ^ 1) * 8 + ((p - 1) & 1) * 4 : hf * 8 + src_of(p);
            asm volatile("" : "+r"(dst), "+r"(bar), "+r"(c1), "+r"(c2));
            if (p == 0 || p == BHOLD || p > 4) mbar_wait(mb + (p == 0 ? B_EVA : p < 5 ? B_KVP : B_E + 8 * (max(p - 6, 1) & 7)), p >= 14);
            if (p > 6) PTS(9 + p);
            mbar_expect_tx(bar, p ? 4 * UNIT : 2 * UNIT);
            tma_4d(dst, &T.m[M_O + sliced], 0, c1, c2, c3 * 2, bar);
          }
          if (fidx >= 0) {
            mbar_expect_tx(mb + B_FFN, 131072); mbar_expect_tx(mb + B_FFD, 65536);
#pragma unroll 1
            for (int f = 0; f < 12; f++) {
              const bool dn = f >= 8;
              const int q = f < 3 ? f + 9 : (f + 21) >> 1;
              uint32_t d0 = sm + (dn ? unit_of(DT, 2 * f - 16) : unit_of(rank ? GT1 : GT0, f)), d1 = dn ? sm + unit_of(DT, 2 * f - 15) : d0 + UNIT;
              asm volatile("" : "+r"(d0), "+r"(d1));
              mbar_wait(mb + (q < 16 ? B_E + 8 * (q - 8) : B_E16), 1);
              PTS(15 + q);
              tma_3d(d0, &T.m[dn ? M_D : M_G], dn ? 0 : fidx * 32, dn ? fidx * 32 : f * 128, dn ? 4 * f - 32 : 0, mb + (dn ? B_FFD : B_FFN), EFF);
              tma_3d(d1, &T.m[dn ? M_D : M_U], dn ? 0 : fidx * 32, dn ? fidx * 32 : f * 128, dn ? 4 * f - 30 : 0, mb + (dn ? B_FFD : B_FFN), EFF);
            }
          }
        }
      } else {
        const uint2 w = ld_rlx2((const uint2*)(P.wr + c3 * 128) + lane);
#pragma unroll 1
        for (int i = 0; i < 4; i++) { l2_prefetch((const char*)P.wo + b * 16384 + i * 4096 + lane * 128); __nanosleep(300); }
        mbar_wait(mb + B_EVA, 0);
        sts4(sm + OFF_COLSUM + lane * 16, w.x << 16, w.x & 0xFFFF0000u, w.y << 16, w.y & 0xFFFF0000u);
        __syncwarp();
        if (lane == 0) mbar_arrive(mb + B_WR);
      }
    }
    __syncwarp();
    mbar_wait(mb + B_EVA, 0);
    mbar_wait(mb + B_OUT, 0);
    const float2 cf = lds2f(sm + OFF_STATS + 64);
    const int cand0 = 2047 - (__float_as_int(cf.x) & 2047), cand1 = 2047 - (__float_as_int(cf.y) & 2047), rr = lane >> 4;
    auto store_rows = [&](int tr, bool on) {
      const uint4 v = lds4(sm + unit_of(btab, 4 + (tr >> 6)) + (tr & 63) * 256 + (((lane & 15) ^ (tr & 7)) << 4));
      const float2 pr = lds2f(sm + OFF_LNP + tr * 8);
      const float f = 1.f + pr.x, n = pr.y;
      if (on) *(uint4*)(P.out + (size_t)(rb * 256 + hf * 64 + tr + (tr & 64)) * D_ + c3 * 128 + (lane & 15) * 8) =
          make_uint4(pack2(fmaf(bf_lo(v.x), f, n), fmaf(bf_hi(v.x), f, n)), pack2(fmaf(bf_lo(v.y), f, n), fmaf(bf_hi(v.y), f, n)),
                     pack2(fmaf(bf_lo(v.z), f, n), fmaf(bf_hi(v.z), f, n)), pack2(fmaf(bf_lo(v.w), f, n), fmaf(bf_hi(v.w), f, n)));
    };
    if (wid == 8) {
      { const long long t0 = clock64(); while (clock64() - t0 < CDELAY) {} }
      uint32_t k;
      for (int it = 0;; it++) { k = ld_rlx(&P.s->cand[c3 * 32 + lane]); if (!__any_sync(~0u, k == SENT)) break; SPINCHK(it, 12); }
      const uint32_t m1 = __reduce_max_sync(~0u, k), m2 = __reduce_max_sync(~0u, k == m1 ? 0 : k);
      if (k == m1 || k == m2) sts2f(sm + OFF_STATS + 80 + (k == m2) * 8, __uint_as_float(k), __int_as_float(lane));
      __syncwarp();
      if (lane == 0) { mbar_arrive(mb + B_SEL); PTS(13); }
      const uint32_t kc = __float_as_uint(rr ? cf.y : cf.x);
      const int c = rr ? cand1 : cand0;
      store_rows(((c >> 1) & 64) + (c & 63), kc != m1 && kc != m2);
    } else if (wid < 9 + NOUTW) {
#pragma unroll 2
      for (int tr = (wid - 9) * 2 + rr; tr < 128; tr += 2 * NOUTW) {
        const int row = rb * 256 + hf * 64 + tr + (tr & 64);
        store_rows(tr, row != cand0 && row != cand1);
      }
      if (wid == 9 && lane == 0) PTS(14);
    }
  } else {
    asm volatile("setmaxnreg.inc.sync.aligned.u32 224;");
    const int t128 = tid & 127, warp = wid & 3, g = lane >> 2, t = lane & 3;
    const int mb3 = rb * 4 + wg * 2 + hf;
    const int row0 = mb3 * 64 + warp * 16 + g;
    const uint32_t sk = rank * (2 * STAGE_B);
    uint4 ost[2][4];
    uint4* od1 = &P.s->obuf[((mb3 ^ 1) * 64 + s3) * 128 + t128];
    const uint32_t eb = (lane << 24) + bars + B_E;
    float acc[64], wf[32];
    {
      float acc1[96], acc0[96];
#pragma unroll
      for (int i = 0; i < 96; i++) { acc0[i] = 0.f; acc1[i] = 0.f; }
      const uint32_t xo0 = dlo(sb, 16) + (wg * 2 + hf) * 512, xo1 = dlo(sb, 16) + (wg * 2 + (hf ^ 1)) * 512;
      constexpr uint32_t ST = STAGE_B >> 4, WD = dlo(sb + 49152, 8192), WV = dlo(sb + 32768, 8192);
      const uint32_t eb0 = (t128 << 24) + bars + B_EMPTY;
#pragma unroll 1
      for (int kb = 0; kb < 12; kb++) {
        const int s = kb & 3;
        mbar_wait(mb + B_FULL + 8 * s, (kb >> 2) & 1);
        if (kb == 0) TS(1);
        if (kb == 0 && !wg) bar_sync(2, 256);
        pin(acc0); pin(acc1);
        wg_fence();
#pragma unroll
        for (int k = 0; k < 4; k++) {
          const uint64_t db = dsc<1024, 1>(WV + s * ST + k * 128);
          wgmma_n192_ss<0, 1, 0>(acc0, dsc<1024, 1>(s * ST + xo0 + k * 2), db, 1);
          wgmma_n192_ss<0, 1, 0>(acc1, dsc<1024, 1>(s * ST + xo1 + k * 2), db, 1);
        }
        wg_commit();
        if (kb == 0 && wg) bar_arrive(2, 256);
        wg_wait<0>();
        pin(acc0); pin(acc1);
        if (t128 < 2 && kb < 11) mbar_arrive_rem(eb0 + 8 * s);
      }
      mbar_wait(mb + B_FULL, 1);
      if (t128 < 8) mbar_arrive_rem(t128 < 4 ? (wg << 24) + bars + B_EMPTY + 24 : mb + B_EMPTY);
      TS(2);
      mbar_wait(mb + B_AUX, 0);
      float rs[2][2], nm[2][2];
#pragma unroll
      for (int m = 0; m < 2; m++)
#pragma unroll
        for (int h = 0; h < 2; h++) { const float2 v = lds2f(sm + OFF_STATS + ((wg * 2 + (m ^ hf)) * 64 + warp * 16 + h * 8 + g) * 8); nm[m][h] = v.x; rs[m][h] = v.y; }
      auto center = [&](auto jc) {
        constexpr int j = decltype(jc)::value;
        const float2 cs = lds2f_o<sb + OFF_COLSUM + j * 32>(own + t * 8);
        acc1[j * 4] = fmaf(nm[1][0], cs.x, acc1[j * 4]); acc1[j * 4 + 1] = fmaf(nm[1][0], cs.y, acc1[j * 4 + 1]);
        acc1[j * 4 + 2] = fmaf(nm[1][1], cs.x, acc1[j * 4 + 2]); acc1[j * 4 + 3] = fmaf(nm[1][1], cs.y, acc1[j * 4 + 3]);
        acc0[j * 4] = fmaf(nm[0][0], cs.x, acc0[j * 4]); acc0[j * 4 + 1] = fmaf(nm[0][0], cs.y, acc0[j * 4 + 1]);
        acc0[j * 4 + 2] = fmaf(nm[0][1], cs.x, acc0[j * 4 + 2]); acc0[j * 4 + 3] = fmaf(nm[0][1], cs.y, acc0[j * 4 + 3]);
      };
      static_for<0, 16>(center);
      const float L2E = 1.4426950408889634f;
      uint32_t fa = sm + sk + (warp * 16 + (lane & 15)) * 128 + (((lane >> 4) ^ (lane & 7)) << 4);
      asm volatile("" : "+r"(fa));
      uint32_t xf0[32], xf1[32];
      auto pack_kv = [&](float (&a)[96], int i, float r0, float r1, uint32_t* o, uint32_t z = 0) {
        const float* p = a + i * 8;
        if (i < 4) {
          const float rl0 = __uint_as_float(__float_as_uint(r0 * L2E) | z), rl1 = __uint_as_float(__float_as_uint(r1 * L2E) | z);
          const uint32_t q0 = pack2(r0, r0), q1 = pack2(r1, r1);
          o[0] = phi2(p[0], p[1], rl0, q0); o[1] = phi2(p[2], p[3], rl1, q1); o[2] = phi2(p[4], p[5], rl0, q0); o[3] = phi2(p[6], p[7], rl1, q1);
        } else {
          r0 = __uint_as_float(__float_as_uint(r0) | z); r1 = __uint_as_float(__float_as_uint(r1) | z);
          o[0] = pack2(p[0] * r0, p[1] * r0); o[1] = pack2(p[2] * r1, p[3] * r1); o[2] = pack2(p[4] * r0, p[5] * r0); o[3] = pack2(p[6] * r1, p[7] * r1); }
      };
      auto swap_kv = [&](uint32_t (&xf)[32], uint32_t tile, int i, const uint32_t* o, uint32_t z = 0) {
        const uint32_t ad = (fa + tile * UNIT) ^ ((i & 3) << 5);
        if (i < 4) { ldsm4_o<0>(ad, xf[i * 4], xf[i * 4 + 1], xf[i * 4 + 2], xf[i * 4 + 3]); stsm4_o<0>(ad, o[0], o[1], o[2], o[3]); }
        else { ldsm4_o<STAGE_B>(ad | z, xf[i * 4], xf[i * 4 + 1], xf[i * 4 + 2], xf[i * 4 + 3]); stsm4_o<STAGE_B>(ad, o[0], o[1], o[2], o[3]); }
      };
      auto mma_q = [&](float (&a)[96], uint32_t (&xf)[32], uint32_t xo, bool ss) {
        const uint32_t r = __shfl_sync(~0u, sk >> 4, 0), o = 2 * ST - r;
#pragma unroll
        for (int j = 0; j < 8; j++) {
          if (ss) wgmma_n64_ss<0, 1, 64>(a, dsc<1024, 1>(o + (j >> 2) * ST + xo + (j & 3) * 2), dsc<1024, 1>(WD + o + (j >> 2) * ST + (j & 3) * 128), 1);
          else wgmma_n64_rs<1, 64>(a, xf[j * 4], xf[j * 4 + 1], xf[j * 4 + 2], xf[j * 4 + 3], dsc<1024, 1>(WD + r + (j >> 2) * ST + (j & 3) * 128), 1);
        }
      };
      auto epi_q = [&](float (&a)[96], float r0, float r1, uint32_t (&o)[16]) {
        const float rl0 = r0 * 1.44269511f, rl1 = r1 * 1.44269511f;
        const uint32_t q0 = dup2(r0), q1 = dup2(r1);
#pragma unroll
        for (int j = 0; j < 8; j++) { o[j * 2] = phi2(a[64 + j * 4], a[65 + j * 4], rl0, q0); o[j * 2 + 1] = phi2(a[66 + j * 4], a[67 + j * 4], rl1, q1); }
        pinu(o);
      };
      auto mma_kv1 = [&](float (&a)[96], uint32_t xo, int s) {
#pragma unroll
        for (int k = 0; k < 4; k++) wgmma_n128_ss<0, 1, 0>(a, dsc<1024, 1>(s * ST + xo + k * 2), dsc<1024, 1>(WV + s * ST + k * 128), 1);
      };
      auto epi_kv = [&](float (&a)[96], uint32_t (&xf)[32], uint32_t tile, float r0, float r1) {
        uint32_t o[8][4];
#pragma unroll
        for (int j = 3; j >= 0; j--) {
          const uint32_t z = j < 3 ? (xf[(j + 5) * 4] | (j < 2 ? o[j + 2][0] | o[j + 6][0] : 0)) & blockIdx.y : 0;
          pack_kv(a, j + 4, r0, r1, o[j + 4], z);
          swap_kv(xf, tile, j + 4, o[j + 4], (o[j + 4][2] | o[j + 4][3]) & blockIdx.y);
          pack_kv(a, j, r0, r1, o[j], z);
          swap_kv(xf, tile, j, o[j]);
        }
      };
      mbar_wait(mb + B_FULL + 8, 1);
      if (!wg) bar_sync(3, 256);
      pinr<0, 64>(acc0); pinr<0, 64>(acc1);
      wg_fence();
      mma_kv1(acc1, xo1, 0); mma_kv1(acc0, xo0, 0); mma_kv1(acc1, xo1, 1);
      if (GSPLIT == 2) mma_kv1(acc0, xo0, 1);
      mbar_wait(mb + B_FULL + 16, 1);
      wg_fence();
      mma_kv1(acc1, xo1, 2);
      mbar_wait(mb + (wg ? B_FULL + 24 : B_F15), wg);
      wg_fence();
      mma_kv1(acc1, xo1, 3);
      wg_commit();
      bar_arrive(4 - wg, 256);
      static_for<16, 24>(center);
      pinr<64, 96>(acc0); pinr<64, 96>(acc1);
      mbar_wait(mb + B_AUX, 0);
      wg_wait<0>();
      pinr<0, 64>(acc0); pinr<0, 64>(acc1);
      TS(4);
      epi_kv(acc1, xf1, wg * 2 + (hf ^ 1), rs[1][0], rs[1][1]);
      pinu(xf1);
      bar_sync(5 - wg, 256);
      wg_fence();
      if (GSPLIT == 1) mma_kv1(acc0, xo0, 1);
      mma_kv1(acc0, xo0, 2); mma_kv1(acc0, xo0, 3);
      wg_commit();
      mma_q(acc1, xf1, xo1, false);
      wg_commit();
      if (wg) bar_arrive(5, 256);
      else { fence_async_smem(); bar_arrive(6, 256); }
      if (tid >= 240) sts4(sm + OFF_STATS + (tid & 15) * 128 + ((tid & 7) << 4), 0x3F803F80u, 0x3F803F80u, 0x3F803F80u, 0x3F803F80u);
      wg_wait<1>();
      pinr<0, 64>(acc0);
      if (lane == 0) mbar_arrive(mb + B_EVA);
      TS(6);
      epi_kv(acc0, xf0, wg * 2 + hf, rs[0][0], rs[0][1]);
      fence_async_smem();
      TS(7);
      pinu(xf0);
      if (wg) {
        float ka[36];
        auto mma_kv = [&](uint32_t tile, int i, int acc) {
          const uint32_t o = (sk >> 4) + tile * 512 + i * 128;
          wgmma_n72_ss<1, 1, 0>(ka, dsc<1024, 1>(dlo(sb, 8192) + o), dsc<1024, 1>(dlo(sb + STAGE_B, OFF_STATS - STAGE_B) + o * (1u - (1u << 16))), acc);
        };
#pragma unroll
        for (int i = 0; i < 36; i++) ka[i] = 0.f;
        bar_sync(6, 256);
        wg_fence();
#pragma unroll
        for (int i = 0; i < 4; i++) {
          mma_kv(2, i, i); mma_kv(3, i, 1); mma_kv(hf ^ 1, i, 1);
#pragma unroll
          for (int j = 2 * i; j < 2 * i + 2; j++)
            wgmma_n64_rs<1, 64>(acc0, xf0[j * 4], xf0[j * 4 + 1], xf0[j * 4 + 2], xf0[j * 4 + 3], dsc<1024, 1>(WD + (sk >> 4) + (j >> 2) * ST + (j & 3) * 128), 1);
        }
        uint4* dst = &P.s->kvp[(cg * 8 + rb) * 256 + warp * 64 + lane];
        uint32_t* dz = (uint32_t*)&P.s->zp[(cg * 8 + rb) * 16] + warp * 16 + g + t * 8;
        asm volatile("" : "+l"(dst), "+l"(dz));
        mbar_wait(mb + B_LATE, 0);
        bar_sync(7, 256);
        wg_fence();
#pragma unroll
        for (int i = 0; i < 4; i++) mma_kv(hf, i, 1);
        wg_commit();
        bar_arrive(8, 256);
        wg_wait<0>();
        pin(ka); pinr<64, 96>(acc0);
        uint32_t kw[8];
#pragma unroll
        for (int i = 0; i < 8; i++) {
          const int j = (i & 3) * 4 + (i >> 2) * 2;
          asm("{\n.reg .pred p;\nsetp.ne.u32 p, %5, 0;\n@p cvt.rn.bf16x2.f32 %0, %4, %3;\n@!p cvt.rn.bf16x2.f32 %0, %2, %1;\n}"
              : "=r"(kw[i]) : "f"(ka[j]), "f"(ka[j + 1]), "f"(ka[16 + j]), "f"(ka[17 + j]), "r"(warp & 2));
        }
        st_rlx4(dst, make_uint4(kw[0], kw[1], kw[2], kw[3]));
        st_rlx4(dst + 32, make_uint4(kw[4], kw[5], kw[6], kw[7]));
        if (t < 2) st_rlx(dz, __float_as_uint(t ? ka[34] : ka[32]));
        if (lane == 0) mbar_arrive(mb + B_EVB);
        TS(8);
      } else {
        bar_arrive(7, 256);
        bar_sync(8, 256);
        wg_fence();
        mma_q(acc0, xf0, xo0, false);
      }
      const uint32_t t1 = clock64(), kvb = 2 * STAGE_B + (2 + (hf ^ 1)) * UNIT - sk;
      uint32_t* of = &P.s->ocnt[(rb * 2 + hf) * 32];
      uint32_t ka0 = sm + kvb + wid * 1024 + (lane & 7) * 128 + (((lane >> 3) ^ (lane & 7)) << 4), ka1 = sm + kvb + wid * 1024 + (t * 2 + g) * 128 + ((4 ^ (t * 2 + g)) << 4);
      const uint8_t* g0 = smem_raw + sk + STAGE_B + tid * 16, *g1 = smem_raw + sk + UNIT + g * 256 + wid * 32 + t * 8;
      const uint8_t* h0 = (const uint8_t*)&P.s->kvp[cg * 8 * 256 + tid], *h1 = (const uint8_t*)&P.s->zp[(cg * 8 + g) * 16] + wid * 32 + t * 8;
      asm volatile("" : "+r"(ka0), "+r"(ka1), "+l"(g0), "+l"(g1), "+l"(h0), "+l"(h1), "+l"(of), "+l"(od1));
      while ((uint32_t)clock64() - t1 < SDELAY) {}
      if (!wg) bar_sync(9, 256);
      wg_fence();
      mma_q(acc1, xf1, xo1, true);
      wg_commit();
      if (wg) bar_arrive(9, 256);
      wg_wait<0>();
      pinr<64, 96>(acc1); pinr<64, 96>(acc0);
      TS(9);
      uint32_t pq[16];
      epi_q(acc1, rs[1][0], rs[1][1], pq);
      bar_sync(11 + wg + zero_after(pq), 128);
      wg_fence();
      mma_q(acc0, xf0, xo0, true);
      wg_commit();
      TS(5);
      {
        uint4 gv[8]; uint2 gz;
        uint32_t m[8], a[4];
        float z0, z1;
#pragma unroll
        for (int s = 0; s < 8; s++) { m[s] = ~blockIdx.y; asm volatile("" : "=r"(gv[s].x), "=r"(gv[s].y), "=r"(gv[s].z), "=r"(gv[s].w), "+r"(m[s])); }
        mbar_wait(mb + B_KVP, 0);
        TS(28);
        wg_wait<0>();
        pinr<64, 96>(acc0);
#pragma unroll 1
        for (int it = 0; it < SPIN_LIMIT; it++) {
          gz = ld_gen2(g1);
#pragma unroll
          for (int s = 0; s < 8; s++) if (m[s] == SENT) gv[s] = ld_gen4(g0 + s * 4096);
          g0 = h0; g1 = h1;
          uint32_t mm = max(gz.x, gz.y);
          z0 = __uint_as_float(gz.x); z1 = __uint_as_float(gz.y);
#pragma unroll
          for (int o = 4; o < 32; o <<= 1) { z0 += __shfl_xor_sync(~0u, z0, o); z1 += __shfl_xor_sync(~0u, z1, o); }
#pragma unroll
          for (int s = 0; s < 8; s++) m[s] = max4(0, gv[s]);
#pragma unroll
          for (int s = 0; s < 8; s += 2) mm = __vimax3_u32(mm, m[s], m[s + 1]);
          a[0] = hadd2(hadd2(hadd2(gv[0].x, gv[1].x), hadd2(gv[2].x, gv[3].x)), hadd2(hadd2(gv[4].x, gv[5].x), hadd2(gv[6].x, gv[7].x)));
          a[1] = hadd2(hadd2(hadd2(gv[0].y, gv[1].y), hadd2(gv[2].y, gv[3].y)), hadd2(hadd2(gv[4].y, gv[5].y), hadd2(gv[6].y, gv[7].y)));
          a[2] = hadd2(hadd2(hadd2(gv[0].z, gv[1].z), hadd2(gv[2].z, gv[3].z)), hadd2(hadd2(gv[4].z, gv[5].z), hadd2(gv[6].z, gv[7].z)));
          a[3] = hadd2(hadd2(hadd2(gv[0].w, gv[1].w), hadd2(gv[2].w, gv[3].w)), hadd2(hadd2(gv[4].w, gv[5].w), hadd2(gv[6].w, gv[7].w)));
          pinu(a);
          if (!__any_sync(~0u, mm == SENT)) break;
          TSV(20, 1);
        }
        TS(23);
        stsm4(ka0, a[0], a[1], a[2], a[3]);
        const uint32_t zz = pack2(g ? z1 : z0, g ? z1 : z0);
        if (lane < 8) sts4(ka1, zz, zz, zz, zz);
        fence_async_smem();
        bar_sync(1, 256);
        if (tid == 0) asm volatile("red.relaxed.gpu.global.add.u32 [%0], 1;" :: "l"(of) : "memory");
      }
      TS(21);
      auto make_o = [&](uint4 (&o)[4], auto first) {
        float oa[2][20];
        wg_fence();
#pragma unroll
        for (int ks = 0; ks < 4; ks++)
          wgmma_n40_rs<1, 0>(oa[ks >> 1], pq[ks * 4], pq[ks * 4 + 1], pq[ks * 4 + 2], pq[ks * 4 + 3], dsc<1024, 1>(dlo(sb, 8192) + (kvb >> 4) + ks * 128), ks & 1);
        wg_commit();
        if constexpr (!decltype(first)::value) {
          pinu(xf0);
#pragma unroll
          for (int q = 0; q < 32; q++) { acc[q * 2] = bf_lo(xf0[q]); acc[q * 2 + 1] = bf_hi(xf0[q]); }
          pin(acc);
          mbar_wait(mb + B_BF, 0);
        }
        wg_wait<0>();
        pin(oa[0]); pin(oa[1]);
        if (decltype(first)::value && lane < 2) mbar_arrive_rem(eb);
#pragma unroll
        for (int h = 0; h < 2; h++) {
          const float (&d)[20] = oa[h];
          const float i0 = rcp(d[16] + 1e-6f), i1 = rcp(d[18] + 1e-6f);
#pragma unroll
          for (int k2 = 0; k2 < 2; k2++) {
            o[h * 2 + k2] = make_uint4(pack2(d[k2 * 8] * i0, d[k2 * 8 + 1] * i0), pack2(d[k2 * 8 + 2] * i1, d[k2 * 8 + 3] * i1),
                                       pack2(d[k2 * 8 + 4] * i0, d[k2 * 8 + 5] * i0), pack2(d[k2 * 8 + 6] * i1, d[k2 * 8 + 7] * i1));
            if (decltype(first)::value && !h) st_rlx4(od1 + k2 * 1024, o[k2]);
          }
          if (decltype(first)::value && !h) { sched_fence(); TS(24); }
        }
      };
      make_o(ost[1], std::true_type{});
      epi_q(acc0, rs[0][0], rs[0][1], pq);
      if (AEARLY) { st_rlx4(od1 + 2048, ost[1][2]); st_rlx4(od1 + 3072, ost[1][3]); }
      make_o(ost[0], std::false_type{});
    }
    {
      uint4 abuf[3][4] = {};
      const uint4* const ain = &P.s->obuf[mb3 * 64 * 128 + t128];
      uint4* const od0 = &P.s->obuf[(mb3 * 64 + 32 + s3 * 4) * 128 + t128];
#pragma unroll
      for (int i = 0; i < 4; i++) pin4(ost[0][i]);
      wg_fence();
#pragma unroll
      for (int k = 0; k < 4; k++) wgmma_n128_rs<1, 0>(acc, ost[0][k].x, ost[0][k].y, ost[0][k].z, ost[0][k].w, dsc<1024, 1>(dlo(sb + 4 * UNIT, 8192) + k * 128), 1);
      wg_commit();
      TS(29);
      if (!AEARLY) { st_rlx4(od1 + 2048, ost[1][2]); st_rlx4(od1 + 3072, ost[1][3]); }
      auto fetch = [&](int p, uint4 (&a)[4]) {
        const uint32_t ra = sm + ring_of(p, wg) + t128 * 16;
        a[0] = lds4_o<0>(ra); a[1] = lds4_o<2048>(ra); a[2] = lds4_o<4096>(ra); a[3] = lds4_o<6144>(ra);
      };
      auto check = [&](int p, uint4 (&a)[4]) {
        if (__builtin_expect(__any_sync(~0u, max(max4(max4(0, a[0]), a[1]), max4(max4(0, a[2]), a[3])) == SENT), 0)) {
          int pl = p; asm volatile("" : "+r"(pl));
          const uint4* q = ain + frag_of(pl);
#pragma unroll 1
          for (int it = 0;; it++) {
            uint32_t mm = 0;
#pragma unroll
            for (int i = 0; i < 4; i++) { const uint32_t m = max4(0, a[i]); mm = max(mm, m); if (m == SENT) a[i] = ld_rlx4(q + i * 128); }
            if (!__any_sync(~0u, mm == SENT)) break;
            TSV(27, p < 3 ? 1 : p < 5 ? 100 : 10000);
            SPINCHK(it, 5);
          }
        }
        if (lane < 2) mbar_arrive_rem(eb + 8 * (p & 7));
      };
      auto step = [&](int p, uint4 (&a)[4], uint4 (&nx)[4], auto jc) {
        constexpr int j = decltype(jc)::value;
        const uint32_t bs = dlo(sb, 8192) + (unit_of(btab, p < 10 ? p : p - 10) >> 4);
        wg_wait<1>();
#pragma unroll
        for (int i = 0; i < 4; i++) { pin4(a[i]); pin4(nx[i]); }
        if (j == 0 ? p > 1 : j == 1 || p < 15) fetch(p + 1, nx);
        wg_fence();
#pragma unroll
        for (int k = 0; k < 4; k++) wgmma_n128_rs<1, 0>(acc, a[k].x, a[k].y, a[k].z, a[k].w, dsc<1024, 1>(bs + k * 128), 1);
        wg_commit();
        if (p < 4) {
          if (j == 0) { TS(25); mbar_wait(mb + B_BF + 16, 0); fetch(2, nx); st_rlx4(od0, ost[0][0]); }
          if (j == 2) TS(26);
          if (j == HOLDP && lane == 0) mbar_arrive(mb + B_KVB);
          st_rlx4(od0 + (j + 1) * 128, ost[0][j + 1]);
        }
        if (j == 0 || p < 14) mbar_wait(mb + B_BF + 8 * (p < 8 ? p + 2 : p - 8), p >= 6);
        if (j < 2 || p < 15) check(p + 1, nx);
      };
      mbar_wait(mb + B_BF + 8, 0);
      TS(3);
      fetch(1, abuf[0]);
      check(1, abuf[0]);
#pragma unroll 1
      for (int p = 1; p < 16; p += 3) {
        step(p, abuf[0], abuf[1], std::integral_constant<int, 0>{});
        step(p + 1, abuf[1], abuf[2], std::integral_constant<int, 1>{});
        step(p + 2, abuf[2], abuf[0], std::integral_constant<int, 2>{});
      }
      if (lane == 0) mbar_arrive(mb + B_E16);
      mbar_wait(mb + B_WR, 0);
      static_for<0, 16>([&](auto jc) { constexpr int j = decltype(jc)::value; const float2 v = lds2f_o<sb + OFF_COLSUM + j * 32>(own + t * 8); wf[j * 2] = v.x; wf[j * 2 + 1] = v.y; });
      pin(wf);
      wg_wait<0>();
      pin(acc);
#pragma unroll
      for (int i = 0; i < 4; i++) { pin4(abuf[0][i]); pin4(abuf[1][i]); pin4(abuf[2][i]); }
    }
    TS(10);
    {
      float s0 = 0.f, q0 = 0.f, e0 = 0.f, s1 = 0.f, q1 = 0.f, e1 = 0.f;
#pragma unroll
      for (int j = 0; j < 16; j++) {
        const float a = acc[j * 4], c = acc[j * 4 + 1], d = acc[j * 4 + 2], e = acc[j * 4 + 3];
        s0 += a + c; q0 = fmaf(a, a, fmaf(c, c, q0)); e0 = fmaf(a, wf[j * 2], fmaf(c, wf[j * 2 + 1], e0));
        s1 += d + e; q1 = fmaf(d, d, fmaf(e, e, q1)); e1 = fmaf(d, wf[j * 2], fmaf(e, wf[j * 2 + 1], e1));
      }
      const bool od = t & 1;
      float s = (od ? s1 : s0) + __shfl_xor_sync(~0u, od ? s0 : s1, 1);
      float q = (od ? q1 : q0) + __shfl_xor_sync(~0u, od ? q0 : q1, 1);
      float e = (od ? e1 : e0) + __shfl_xor_sync(~0u, od ? e0 : e1, 1);
      s += __shfl_xor_sync(~0u, s, 2); q += __shfl_xor_sync(~0u, q, 2); e += __shfl_xor_sync(~0u, e, 2);
      if (t < 2) red4(&P.s->st2[row0 + t * 8], s, q, e, 1.f);
    }
    TS(11);
    const uint32_t msc = sm + OFF_STATS;
    const uint32_t hst = sm + unit_of(btab, 4 + wg) + warp * 4096, myslot = sm + unit_of(DT, wid);
    bar_sync(1, 256);
#pragma unroll
    for (int j = 0; j < 8; j++)
      stsm4(hst + (lane & 15) * 256 + (((2 * j + (lane >> 4)) ^ (lane & 7)) << 4), pack2(acc[j * 8], acc[j * 8 + 1]), pack2(acc[j * 8 + 2], acc[j * 8 + 3]),
            pack2(acc[j * 8 + 4], acc[j * 8 + 5]), pack2(acc[j * 8 + 6], acc[j * 8 + 7]));
    uint32_t wa[8][4][4], wd[8][2][4];
    const uint32_t a0 = sm + unit_of(rank ? GT1 : GT0, wid) + ((lane >> 4) * 8 + (lane & 7)) * 64 + ((((lane >> 3) & 1) ^ ((lane >> 1) & 3)) << 4);
    auto load_gu = [&](auto ic) { constexpr int i = decltype(ic)::value; ldsm4t_o<(i >> 2) * 1024 + ((i >> 1) & 1) * 8192>(a0 ^ ((i & 1) << 5), wa[i >> 2][i & 3]); };
    {
      const int row = mb3 * 64 + warp * 16 + (lane & 15);
      uint4 v;
#pragma unroll 1
      for (int it = 0;; it++) {
        v = ld_rlx4(&P.s->st2[row]);
        TSV(22, 1);
        if (!__any_sync(~0u, v.w != 0x41000000u)) break;
        SPINCHK(it, 6);
      }
      TS(12);
      const float sw = __uint_as_float((lds1(mb + B_SW) & ~255u) | 128);
      const float mean = __uint_as_float(v.x) * (1.f / D_);
      const float rstd = rsq(fmaxf(fmaf(-mean, mean, __uint_as_float(v.y) * (1.f / D_)), 0.f) + 1e-5f);
      const uint32_t u = __float_as_uint(rstd * fmaf(-mean, sw, __uint_as_float(v.z)));
      uint32_t k = min(((u ^ ((uint32_t)((int)u >> 31) | 0x80000000u)) & ~2047u), 0xFFFFF000u) | (2047 - row);
      uint32_t m1 = __reduce_max_sync(~0u, k), m2 = __reduce_max_sync(~0u, k == m1 ? 0 : k);
      if (lane < 16) sts2f(sm + OFF_LNP + (wid * 16 + lane) * 8, rstd, -mean * rstd);
      if (lane == 0) sts2f(msc + wid * 8, __uint_as_float(m1), __uint_as_float(m2));
      bar_sync(1, 256);
      k = lds1(msc + (lane & 15) * 4);
      m1 = __reduce_max_sync(~0u, k); m2 = __reduce_max_sync(~0u, k == m1 ? 0 : k);
      const int grp = rb * 2 + hf, c0 = 2047 - (m1 & 2047), c1 = 2047 - (m2 & 2047);
      if (tid == 0) {
        st_rlx2(&P.s->cand[c3 * 32 + grp * 2], m1, m2);
        sts2f(msc + 64, __uint_as_float(m1), __uint_as_float(m2));
        mbar_arrive(mb + B_OUT);
      }
      if ((c0 >> 4) == mb3 * 4 + warp || (c1 >> 4) == mb3 * 4 + warp) {
        const int ra = (lane & 4) ? c1 : c0, rd = (lane & 16) ? c1 : c0;
        uint32_t h0, h1, h2, h3;
        ldsm4_o<0>(hst + (ra & 15) * 256 + ((((lane & 3) * 4 + (lane >> 3)) ^ (ra & 7)) << 4), h0, h1, h2, h3);
        const float2 pr = lds2f(sm + OFF_LNP + (wid * 16 + (rd & 15)) * 8);
        if ((rd >> 4) == mb3 * 4 + warp) {
          uint4* d = &P.s->hsel[(grp * 2 + (lane >> 4)) * 256 + c3 * 32 + t * 4 + (g & 3)];
          st_rlx4(d, make_uint4(pack2(fmaf(bf_lo(h0), pr.x, pr.y), fmaf(bf_hi(h0), pr.x, pr.y)), pack2(fmaf(bf_lo(h1), pr.x, pr.y), fmaf(bf_hi(h1), pr.x, pr.y)),
                                pack2(fmaf(bf_lo(h2), pr.x, pr.y), fmaf(bf_hi(h2), pr.x, pr.y)), pack2(fmaf(bf_lo(h3), pr.x, pr.y), fmaf(bf_hi(h3), pr.x, pr.y))));
          st_rlx4(d + 16, make_uint4(h0, h1, h2, h3));
        }
      }
    }
    TS(13);
    if (fidx >= 0) mbar_wait(mb + B_FFN, 0);
    static_for<0, 32>(load_gu);
    const uint32_t da = myslot + ((lane >> 4) * 8 + (lane & 7)) * 128 + ((((lane >> 3) & 1) ^ (lane & 7)) << 4);
    mbar_wait(mb + B_SEL, 0);
    const uint4 sel = lds4(msc + 80);
    float gu[2][4][4];
    uint32_t fh = 0, fn = 0;
    const uint32_t* fq = (const uint32_t*)P.s->hsel + ((tid & 1) ? sel.w : sel.y) * 1024 + (b >> 4) * 128 + ((tid >> 2) & 3) * 16 + (b & 15);
    {
      uint4 xb[4];
      const uint4* xp = &P.s->hsel[((lane & 16) ? sel.w : sel.y) * 256 + wid * 32 + (lane & 15)];
      uint4 xv = ld_rlx4(xp);
      if (tid < 16) { fn = ld_rlx(fq); fh = ld_rlx(fq + 64); }
      if (fidx >= 0) mbar_wait(mb + B_FFD, 0);
      static_for<0, 8>([&](auto ic) { constexpr int i = decltype(ic)::value; ldsm4t_o<(i & 1) * 2048>(da ^ ((i >> 1) << 5), wd[i >> 1][i & 1]); });
#pragma unroll 1
      for (int it = 0; __any_sync(~0u, max4(0, xv) == SENT); it++) { xv = ld_rlx4(xp); SPINCHK(it, 7); }
      sts4(myslot + 2048 + ((lane & 3) * 8 + (lane >> 2)) * 16, xv.x, xv.y, xv.z, xv.w);
      __syncwarp();
#pragma unroll
      for (int i = 0; i < 4; i++) xb[i] = lds4(myslot + 2048 + (i * 8 + (lane & 7)) * 16);
      TS(14);
#pragma unroll
      for (int i = 0; i < 32; i++) gu[i >> 4][(i >> 2) & 3][i & 3] = 0.f;
#pragma unroll
      for (int ks = 0; ks < 8; ks++) {
#pragma unroll
        for (int i = 0; i < 4; i++) mma16816(gu[ks & 1][i], wa[ks][i], (ks & 1) ? xb[ks >> 1].z : xb[ks >> 1].x, (ks & 1) ? xb[ks >> 1].w : xb[ks >> 1].y);
        if (ks == 3) {
          uint32_t dd = da; asm volatile("" : "+r"(dd) : "f"(gu[0][0][0]));
          static_for<0, 8>([&](auto ic) { constexpr int i = decltype(ic)::value; ldsm4t_o<4096 + (i & 1) * 2048>(dd ^ ((i >> 1) << 5), wd[4 + (i >> 1)][i & 1]); });
        }
      }
    }
    {
      float o[4];
#pragma unroll
      for (int j = 0; j < 4; j++) {
        const float s0 = gu[0][0][j] + gu[1][0][j], s1 = gu[0][1][j] + gu[1][1][j], s2 = gu[0][2][j] + gu[1][2][j], s3 = gu[0][3][j] + gu[1][3][j];
        o[j] = t == 0 ? s0 : t == 1 ? s1 : t == 2 ? s2 : s3;
      }
      sts2f(myslot + 1024 + (t * 16 + g) * 8, o[0], o[1]);
      sts2f(myslot + 1024 + (t * 16 + g + 8) * 8, o[2], o[3]);
    }
    bar_sync(1, 256);
    {
      float g0 = 0.f, g1 = 0.f, u0 = 0.f, u1 = 0.f;
      static_for<0, 8>([&](auto wc) { constexpr int w = decltype(wc)::value;
        const float2 a = lds2f_o<sb + ((DT >> (5 * w)) & 31) * UNIT + 1024>(own + lane * 8), c = lds2f_o<sb + ((DT >> (5 * w)) & 31) * UNIT + 1280>(own + lane * 8);
        g0 += a.x; g1 += a.y; u0 += c.x; u1 += c.y; });
      const uint32_t act = pack2(g0 * rcp(1.f + ex2(-1.4426950408889634f * g0)) * u0, g1 * rcp(1.f + ex2(-1.4426950408889634f * g1)) * u1);
      uint32_t bq[4];
#pragma unroll
      for (int i = 0; i < 4; i++) {
        const uint32_t lo = __shfl_sync(~0u, act, i * 8 + 2 * t), hi = __shfl_sync(~0u, act, i * 8 + 2 * t + 1);
        bq[i] = __byte_perm(lo, hi, (g & 1) ? 0x7632 : 0x5410);
      }
      TS(16);
      float ya[8][4];
#pragma unroll
      for (int i = 0; i < 8; i++) { ya[i][0] = 0.f; ya[i][1] = 0.f; ya[i][2] = 0.f; ya[i][3] = 0.f; }
#pragma unroll
      for (int ks = 0; ks < 2; ks++)
#pragma unroll
        for (int i = 0; i < 8; i++) mma16816(ya[i], wd[i][ks], bq[ks * 2], bq[ks * 2 + 1]);
      if (fidx >= 0) {
        uint2* yp = (uint2*)&P.s->ybuf[((wid * 16 + t * 2) * NFFN + fidx) * 4] + g;
#pragma unroll
        for (int h = 0; h < 2; h++) {
          float o[4];
#pragma unroll
          for (int j = 0; j < 4; j++) o[j] = t == 0 ? ya[h * 4][j] : t == 1 ? ya[h * 4 + 1][j] : t == 2 ? ya[h * 4 + 2][j] : ya[h * 4 + 3][j];
          st_rlx2(yp + h * (8 * NFFN * 8), __float_as_uint(o[0]), __float_as_uint(o[1]));
          st_rlx2(yp + h * (8 * NFFN * 8) + NFFN * 8, __float_as_uint(o[2]), __float_as_uint(o[3]));
        }
      }
    }
    TS(17);
    const long long ty = clock64();
    {
      while (clock64() - ty < YDELAY) {}
      uint4 v0, v1 = make_uint4(0, 0, 0, 0);
#pragma unroll 1
      for (int it = 0;; it++) {
        v0 = ld_rlx4(&P.s->ybuf[b * NFFN * 4 + tid]);
        if (tid < 192) v1 = ld_rlx4(&P.s->ybuf[b * NFFN * 4 + 256 + tid]);
        if (!__any_sync(~0u, max(max4(0, v0), max4(0, v1)) == SENT)) break;
        SPINCHK(it, 8);
      }
      TS(18);
      float y0 = __uint_as_float(v0.x) + __uint_as_float(v1.x), y1 = __uint_as_float(v0.y) + __uint_as_float(v1.y);
      float y2 = __uint_as_float(v0.z) + __uint_as_float(v1.z), y3 = __uint_as_float(v0.w) + __uint_as_float(v1.w);
      float z0 = ((lane & 16) ? y2 : y0) + __shfl_xor_sync(~0u, (lane & 16) ? y0 : y2, 16), z1 = ((lane & 16) ? y3 : y1) + __shfl_xor_sync(~0u, (lane & 16) ? y1 : y3, 16);
      z0 = ((lane & 8) ? z1 : z0) + __shfl_xor_sync(~0u, (lane & 8) ? z0 : z1, 8);
      z0 += __shfl_xor_sync(~0u, z0, 4);
      const uint32_t yx = msc + 128;
      if (!(lane & 4)) sts1(yx + wid * 64 + (t * 4 + (lane >> 3)) * 4, __float_as_uint(z0));
      bar_sync(1, 256);
      if (tid < 16) {
        float y = 0.f;
#pragma unroll
        for (int w = 0; w < 8; w++) y += __uint_as_float(lds1(yx + w * 64 + tid * 4));
        for (int it = 0; max(fn, fh) == SENT; it++) { fn = ld_rlx(fq); fh = ld_rlx(fq + 64); SPINCHK(it, 9); }
        const uint32_t key = (tid & 1) ? sel.z : sel.x;
        const float r = __uint_as_float(key ^ (~(uint32_t)((int)key >> 31) | 0x80000000u));
        const float base = (tid & 2) ? bf_hi(fh) + bf_hi(fn) : bf_lo(fh) + bf_lo(fn);
        P.out[(size_t)(2047 - (key & 2047)) * D_ + b * 8 + (tid >> 1)] = __float2bfloat16(fmaf(y, rcp(1.f + ex2(-1.4426950408889634f * r)), base));
      }
      if (b == 0 && tid == 32) P.s->epoch = lds1(mb + B_SW) & 255;
    }
    TS(19); TSG(31);
    if (warp == 0) TS_DUMP(wg);
  }
}

typedef CUresult (*EncodeFn)(CUtensorMap*, CUtensorMapDataType, cuuint32_t, void*, const cuuint64_t*, const cuuint64_t*, const cuuint32_t*,
                             const cuuint32_t*, CUtensorMapInterleave, CUtensorMapSwizzle, CUtensorMapL2promotion, CUtensorMapFloatOOBfill);
void make_map(EncodeFn enc, CUtensorMap* m, const void* p, int rank, std::initializer_list<cuuint64_t> dims, std::initializer_list<cuuint64_t> str,
              std::initializer_list<cuuint32_t> box, CUtensorMapSwizzle sw) {
  const cuuint32_t es[4] = {1, 1, 1, 1};
  enc(m, CU_TENSOR_MAP_DATA_TYPE_BFLOAT16, rank, const_cast<void*>(p), dims.begin(), str.begin(), box.begin(), es, CU_TENSOR_MAP_INTERLEAVE_NONE, sw,
      CU_TENSOR_MAP_L2_PROMOTION_L2_128B, CU_TENSOR_MAP_FLOAT_OOB_FILL_NONE);
}

}

extern "C" void kernel_launch(void* const* d_in, const int* in_sizes, int n_in, void* d_out, int out_size) {
  (void)in_sizes; (void)n_in; (void)out_size;
  Ptrs P;
  P.x = (const __nv_bfloat16*)d_in[0]; P.wqkv = (const __nv_bfloat16*)d_in[1]; P.wo = (const __nv_bfloat16*)d_in[2];
  P.wr = (const __nv_bfloat16*)d_in[4]; P.wg = (const __nv_bfloat16*)d_in[5]; P.wu = (const __nv_bfloat16*)d_in[6];
  P.wd = (const __nv_bfloat16*)d_in[7]; P.out = (__nv_bfloat16*)d_out;
  cudaGetSymbolAddress((void**)&P.s, g_scratch);
  void* fn = nullptr;
  cudaDriverEntryPointQueryResult q;
  cudaGetDriverEntryPoint("cuTensorMapEncodeTiled", &fn, cudaEnableDefault, &q);
  EncodeFn enc = (EncodeFn)fn;
  Maps T;
  constexpr CUtensorMapSwizzle S128 = CU_TENSOR_MAP_SWIZZLE_128B, S64 = CU_TENSOR_MAP_SWIZZLE_64B;
  make_map(enc, &T.m[M_X], P.x, 2, {D_, S_}, {D_ * 2}, {64, 128}, S128);
  make_map(enc, &T.m[M_W], P.wqkv, 3, {D_, D_, 3}, {3 * D_ * 2, D_ * 2}, {64, 64, 2}, S128);
  make_map(enc, &T.m[M_Q], P.wqkv, 2, {3 * D_, D_}, {3 * D_ * 2}, {64, 64}, S128);
  make_map(enc, &T.m[M_O], P.wo, 4, {64, 64, 16, 16}, {D_ * 2, 64 * D_ * 2, 128}, {64, 64, 1, 2}, S128);
  make_map(enc, &T.m[M_S], P.wo, 4, {64, 64, 16, 16}, {D_ * 2, 64 * D_ * 2, 128}, {64, 16, 4, 2}, S128);
  make_map(enc, &T.m[M_G], P.wg, 3, {F_, D_, 1}, {F_ * 2, F_ * 2 * D_}, {32, 128, 1}, S64);
  make_map(enc, &T.m[M_U], P.wu, 3, {F_, D_, 1}, {F_ * 2, F_ * 2 * D_}, {32, 128, 1}, S64);
  make_map(enc, &T.m[M_D], P.wd, 3, {64, F_, 16}, {D_ * 2, 128}, {64, 32, 2}, S128);
  cudaFuncSetAttribute(fused_kernel, cudaFuncAttributeMaxDynamicSharedMemorySize, SMEM_BYTES);
  fused_kernel<<<NCTA, 384, SMEM_BYTES>>>(P, T);
}
```

```cpp
#include <cuda_runtime.h>
#include <cuda.h>
#include <cuda_bf16.h>
#include <stdint.h>
#include <type_traits>
#include <initializer_list>

namespace {

constexpr int S_ = 2048, D_ = 1024, F_ = 3584;
constexpr int NCTA = 128, NFFN = 112;
constexpr uint32_t SENT = 0xFFFFFFFFu;
constexpr int SPIN_LIMIT = 1 << 20;

#define ADELAY 0
#define ADELAY2 100
#define PFA 6
#define PF0 8
#define WPF0 8
#define DPER 1200
#define PDEPTH 2
#define PSTART 4000
#define PPER 1700
#define PEARLY 5
#define PLEAD 0
#define RST 1
#define PSUB 2
#define HOLDP 1
#define QHOLD 1
#define NPULL 12
#define CDELAY 0
#define NOUTW 3
#define YDELAY 500
#define EFX 0
#define EFW 1
#define EFF 1
#define KLEAD 13
#define GDELAY 1000
#define NDIR 6
#define PULL0 5
#define FD0 400
#define FD1 800
#define SPF 1
#define MPF 1
#define TLBW 2
#define GORD 0
#define GSPLIT 2
#define EFW0 0
#define EFX0 0
#define EFWK 8
#define PSLEEP 20
#define P3PULL 1
#define RST2 4
#define KDELAY 450
#define AEARLY 1
#define BHOLD 4
#define SDELAY 150
#define FSTAG 150
#define OFL 0
#define CHKF 1
#define BEV 1
#define DLATE 4
#define P3GATE 3
#define ACCSW 1
#define B45 (B_BF + 8)
#define PSTOP 3
#define DMASK 0x5550
#define PFST 1
#define W0OFF 2
#define MAPM 2
#define XWPF 0
constexpr uint32_t STAGE_B = 57344;
constexpr uint32_t OFF_STATS = 229376;
constexpr uint32_t OFF_COLSUM = 231424;
constexpr uint32_t OFF_BARS = 232192;
constexpr uint32_t SMEM_BYTES = 232448;
constexpr uint32_t B_FULL = 0, B_EMPTY = 32, B_E = 64, B_AUX = 128, B_EVA = 136, B_EVB = 144, B_BF = 152, B_LATE = 232, B_FFN = 240, B_SW = 248;
constexpr uint32_t B_OUT = B_FULL, B_SEL = B_FULL + 8, B_WR = B_FULL + 16, B_FFD = B_FULL + 24, B_E16 = B_EMPTY + 16, B_KVB = B_EMPTY + 8, B_DUMMY = B_SW + 4,
                   B_GATE = B_EMPTY + 24, B_ID = B_BF + 56, B_KVP = B_BF + 64, B_F15 = B_BF + 72;
#define B_HOLD B_F15
#define HOLDPAR 0
constexpr uint32_t UNIT = 8192;
constexpr uint32_t sb = 1024;
constexpr uint32_t bars = sb + OFF_BARS;
constexpr uint64_t tab5(int a, int b, int c, int d, int e, int f, int g, int h, int i = 0, int j = 0) {
  return (uint64_t)a | (uint64_t)b << 5 | (uint64_t)c << 10 | (uint64_t)d << 15 | (uint64_t)e << 20 | (uint64_t)f << 25 | (uint64_t)g << 30 | (uint64_t)h << 35 |
         (uint64_t)i << 40 | (uint64_t)j << 45;
}
constexpr uint64_t BT0 = tab5(4, 11, 18, 25, 7, 9, 16, 0), BT1 = tab5(4, 11, 18, 25, 21, 23, 2, 0);
constexpr uint64_t GT0 = tab5(2, 21, 23, 18, 0, 25, 14, 7), GT1 = tab5(16, 7, 9, 18, 0, 25, 14, 21);
constexpr uint64_t DT0 = tab5(6, 13, 20, 27, 9, 10, 16, 17), DT1 = tab5(6, 13, 20, 27, 23, 24, 2, 3);
__device__ __forceinline__ uint32_t unit_of(uint64_t tab, int i) { return ((uint32_t)(tab >> (5 * i)) & 31) * UNIT; }
__device__ __forceinline__ uint32_t ring_of(int p, int w) { return (p & 1) * (2 * STAGE_B) + ((p & 2) ? 49152 + w * STAGE_B : w * UNIT); }
constexpr uint32_t OFF_LNP = OFF_STATS + 1024;

struct Scratch {
  uint4 obuf[32 * 64 * 128];
  uint4 kvp[16 * 8 * 256];
  uint4 zp[16 * 8 * 16];
  uint4 ybuf[NCTA * NFFN * 4];
  uint4 st1[S_];
  uint4 csp[16 * 8 * 48];
  uint4 st2[S_];
  uint4 hsel[32 * 256];
  uint32_t cand[8 * 32];
  uint32_t ocnt[16 * 32];
  unsigned epoch;
};
__device__ __align__(1024) Scratch g_scratch;
#define TS_DECL
#define TS(i)
#define TSG(i)
#define TSV(i, v)
#define TSD(i)
#define RTS_DECL
#define RTS(i)
#define RTS_DUMP
#define TS_DUMP(slot)
#define PTS(i)
#define g_dbgv(i, v)

__device__ __forceinline__ uint32_t smem_u32(const void* p) { return (uint32_t)__cvta_generic_to_shared(p); }
__device__ __forceinline__ void mbar_init(uint32_t bar, uint32_t cnt) { asm volatile("mbarrier.init.shared::cta.b64 [%0], %1;" :: "r"(bar), "r"(cnt) : "memory"); }
__device__ __forceinline__ void mbar_expect_tx(uint32_t bar, uint32_t bytes) { asm volatile("mbarrier.arrive.expect_tx.shared::cta.b64 _, [%0], %1;" :: "r"(bar), "r"(bytes) : "memory"); }
__device__ __forceinline__ void mbar_arrive(uint32_t bar) { asm volatile("mbarrier.arrive.shared::cta.b64 _, [%0];" :: "r"(bar) : "memory"); }
#define SPINCHK(it, code) if ((it) > SPIN_LIMIT) break
__device__ __forceinline__ void mbar_wait(uint32_t bar, uint32_t parity) {
  asm volatile("{\n.reg .pred p;\n.reg .u32 c;\nmov.u32 c, 0;\n"
               "WL:\nmbarrier.try_wait.parity.shared::cta.b64 p, [%0], %1;\n@p bra WD;\n"
               "add.u32 c, c, 1;\nsetp.lt.u32 p, c, 1048576;\n@p bra WL;\nWD:\n}" :: "r"(bar), "r"(parity) : "memory");
}
__device__ __forceinline__ bool mbar_test(uint32_t bar, uint32_t parity) {
  uint32_t ok;
  asm volatile("{\n.reg .pred p;\nmbarrier.test_wait.parity.shared::cta.b64 p, [%1], %2;\nselp.u32 %0, 1, 0, p;\n}" : "=r"(ok) : "r"(bar), "r"(parity) : "memory");
  return ok;
}
__device__ __forceinline__ uint64_t l2_stream() { uint64_t p; asm("createpolicy.fractional.L2::evict_first.b64 %0, 1.0;" : "=l"(p)); return p; }
__device__ __forceinline__ void tma_2d(uint32_t dst, const CUtensorMap* tm, int c0, int c1, uint32_t bar, bool stream) {
  if (stream) asm volatile("cp.async.bulk.tensor.2d.shared::cluster.global.mbarrier::complete_tx::bytes.L2::cache_hint [%0], [%1, {%3, %4}], [%2], %5;"
                           :: "r"(dst), "l"(tm), "r"(bar), "r"(c0), "r"(c1), "l"(l2_stream()) : "memory");
  else asm volatile("cp.async.bulk.tensor.2d.shared::cluster.global.mbarrier::complete_tx::bytes [%0], [%1, {%3, %4}], [%2];"
                    :: "r"(dst), "l"(tm), "r"(bar), "r"(c0), "r"(c1) : "memory");
}
__device__ __forceinline__ void tma_3d(uint32_t dst, const CUtensorMap* tm, int c0, int c1, int c2, uint32_t bar, bool stream) {
  if (stream) asm volatile("cp.async.bulk.tensor.3d.shared::cluster.global.mbarrier::complete_tx::bytes.L2::cache_hint [%0], [%1, {%3, %4, %5}], [%2], %6;"
                           :: "r"(dst), "l"(tm), "r"(bar), "r"(c0), "r"(c1), "r"(c2), "l"(l2_stream()) : "memory");
  else asm volatile("cp.async.bulk.tensor.3d.shared::cluster.global.mbarrier::complete_tx::bytes [%0], [%1, {%3, %4, %5}], [%2];"
                    :: "r"(dst), "l"(tm), "r"(bar), "r"(c0), "r"(c1), "r"(c2) : "memory");
}
__device__ __forceinline__ void tma_pf_3d(const CUtensorMap* tm, int c0, int c1, int c2) {
  asm volatile("cp.async.bulk.prefetch.tensor.3d.L2.global [%0, {%1, %2, %3}];" :: "l"(tm), "r"(c0), "r"(c1), "r"(c2) : "memory");
}
__device__ __forceinline__ void tma_4d(uint32_t dst, const CUtensorMap* tm, int c0, int c1, int c2, int c3, uint32_t bar) {
  asm volatile("cp.async.bulk.tensor.4d.shared::cluster.global.mbarrier::complete_tx::bytes [%0], [%1, {%3, %4, %5, %6}], [%2];"
               :: "r"(dst), "l"(tm), "r"(bar), "r"(c0), "r"(c1), "r"(c2), "r"(c3) : "memory");
}
__device__ __forceinline__ void tma_2d_mc(uint32_t dst, const CUtensorMap* tm, int c0, int c1, uint32_t bar, bool stream) {
  if (stream) asm volatile("cp.async.bulk.tensor.2d.shared::cluster.global.mbarrier::complete_tx::bytes.multicast::cluster.L2::cache_hint [%0], [%1, {%3, %4}], [%2], %5, %6;"
                           :: "r"(dst), "l"(tm), "r"(bar), "r"(c0), "r"(c1), "h"((uint16_t)3), "l"(l2_stream()) : "memory");
  else asm volatile("cp.async.bulk.tensor.2d.shared::cluster.global.mbarrier::complete_tx::bytes.multicast::cluster [%0], [%1, {%3, %4}], [%2], %5;"
                    :: "r"(dst), "l"(tm), "r"(bar), "r"(c0), "r"(c1), "h"((uint16_t)3) : "memory");
}
__device__ __forceinline__ bool elect_one() {
  uint32_t p;
  asm volatile("{\n.reg .pred q;\nelect.sync _|q, 0xFFFFFFFF;\nselp.u32 %0, 1, 0, q;\n}" : "=r"(p));
  return p;
}
__device__ __forceinline__ void bulk_load_mc(uint32_t dst, const void* src, uint32_t bytes, uint32_t bar) {
  asm volatile("cp.async.bulk.shared::cluster.global.mbarrier::complete_tx::bytes.multicast::cluster [%0], [%1], %2, [%3], %4;"
               :: "r"(dst), "l"(src), "r"(bytes), "r"(bar), "h"((uint16_t)3) : "memory");
}
__device__ __forceinline__ void bulk_load(uint32_t dst, const void* src, uint32_t bytes, uint32_t bar) {
  asm volatile("cp.async.bulk.shared::cluster.global.mbarrier::complete_tx::bytes [%0], [%1], %2, [%3];" :: "r"(dst), "l"(src), "r"(bytes), "r"(bar) : "memory");
}
__device__ __forceinline__ void bulk_store(void* dst, uint32_t src, uint32_t bytes) {
  asm volatile("cp.async.bulk.global.shared::cta.bulk_group [%0], [%1], %2;" :: "l"(dst), "r"(src), "r"(bytes) : "memory");
}
__device__ __forceinline__ void mbar_arrive_rem(uint32_t bar) { asm volatile("mbarrier.arrive.shared::cluster.b64 _, [%0];" :: "r"(bar) : "memory"); }
__device__ __forceinline__ void st_async4(uint32_t addr, const uint4& v, uint32_t bar) {
  asm volatile("st.async.shared::cluster.mbarrier::complete_tx::bytes.v4.b32 [%0], {%1,%2,%3,%4}, [%5];" :: "r"(addr), "r"(v.x), "r"(v.y), "r"(v.z), "r"(v.w), "r"(bar) : "memory");
}
template <uint32_t O> __device__ __forceinline__ void ldsm4_o(uint32_t addr, uint32_t& a, uint32_t& b, uint32_t& c, uint32_t& d) {
  asm volatile("ldmatrix.sync.aligned.m8n8.x4.shared.b16 {%0,%1,%2,%3}, [%4+%5];" : "=r"(a), "=r"(b), "=r"(c), "=r"(d) : "r"(addr), "n"(O) : "memory");
}
template <uint32_t O> __device__ __forceinline__ void ldsm4t_o(uint32_t addr, uint32_t (&r)[4]) {
  asm volatile("ldmatrix.sync.aligned.m8n8.x4.trans.shared.b16 {%0,%1,%2,%3}, [%4+%5];" : "=r"(r[0]), "=r"(r[1]), "=r"(r[2]), "=r"(r[3]) : "r"(addr), "n"(O) : "memory");
}
__device__ __forceinline__ void mma16816(float (&c)[4], const uint32_t (&a)[4], uint32_t b0, uint32_t b1) {
  asm("mma.sync.aligned.m16n8k16.row.col.f32.bf16.bf16.f32 {%0,%1,%2,%3}, {%4,%5,%6,%7}, {%8,%9}, {%0,%1,%2,%3};"
      : "+f"(c[0]), "+f"(c[1]), "+f"(c[2]), "+f"(c[3]) : "r"(a[0]), "r"(a[1]), "r"(a[2]), "r"(a[3]), "r"(b0), "r"(b1));
}
__device__ __forceinline__ void l2_prefetch(const void* p) { asm volatile("prefetch.global.L2 [%0];" :: "l"(p) : "memory"); }
__device__ __forceinline__ uint32_t ld_line(const void* p) { uint32_t v; asm volatile("ld.global.cg.L2::128B.u32 %0, [%1];" : "=r"(v) : "l"(p) : "memory"); return v; }
__device__ __forceinline__ void tmap_prefetch(const CUtensorMap* tm) { asm volatile("prefetch.tensormap [%0];" :: "l"(tm) : "memory"); }
__device__ __forceinline__ void wg_fence() { asm volatile("wgmma.fence.sync.aligned;" ::: "memory"); }
__device__ __forceinline__ void wg_commit() { asm volatile("wgmma.commit_group.sync.aligned;" ::: "memory"); }
template <int N> __device__ __forceinline__ void wg_wait() { asm volatile("wgmma.wait_group.sync.aligned %0;" :: "n"(N) : "memory"); }
template <int N> __device__ __forceinline__ void pin(float (&d)[N]) {
#pragma unroll
  for (int i = 0; i < N; i++) asm volatile("" : "+f"(d[i]) :: "memory");
}
__device__ __forceinline__ void pin4(uint4& v) { asm volatile("" : "+r"(v.x), "+r"(v.y), "+r"(v.z), "+r"(v.w) :: "memory"); }
template <uint32_t SBO, uint32_t SWZ> __device__ __forceinline__ uint64_t dsc(uint32_t lo) { return ((uint64_t)((SBO >> 4) | (SWZ << 30)) << 32) | lo; }
__host__ __device__ constexpr uint32_t dlo(uint32_t addr, uint32_t lbo) { return (addr >> 4) | ((lbo >> 4) << 16); }
__device__ __forceinline__ void bar_sync(int id, int n) { asm volatile("bar.sync %0, %1;" :: "r"(id), "r"(n) : "memory"); }
__device__ __forceinline__ void bar_arrive(int id, int n) { asm volatile("bar.arrive %0, %1;" :: "r"(id), "r"(n) : "memory"); }
__device__ __forceinline__ void fence_async_smem() { asm volatile("fence.proxy.async.shared::cta;" ::: "memory"); }
__device__ __forceinline__ void fence_gpu() { asm volatile("fence.acq_rel.gpu;" ::: "memory"); }
__device__ __forceinline__ uint4 ld_cg4(const void* p) { uint4 v; asm volatile("ld.global.cg.v4.u32 {%0,%1,%2,%3}, [%4];" : "=r"(v.x), "=r"(v.y), "=r"(v.z), "=r"(v.w) : "l"(p) : "memory"); return v; }
__device__ __forceinline__ uint4 ld_rlx4(const void* p) { uint4 v; asm volatile("ld.relaxed.gpu.global.v4.u32 {%0,%1,%2,%3}, [%4];" : "=r"(v.x), "=r"(v.y), "=r"(v.z), "=r"(v.w) : "l"(p) : "memory"); return v; }
__device__ __forceinline__ uint32_t ld_rlx(const void* p) { uint32_t v; asm volatile("ld.relaxed.gpu.global.u32 %0, [%1];" : "=r"(v) : "l"(p) : "memory"); return v; }
__device__ __forceinline__ void st_rlx4(void* p, uint4 v) { asm volatile("st.relaxed.gpu.global.v4.u32 [%0], {%1,%2,%3,%4};" :: "l"(p), "r"(v.x), "r"(v.y), "r"(v.z), "r"(v.w) : "memory"); }
__device__ __forceinline__ void st_rlx2(void* p, uint32_t a, uint32_t b) { asm volatile("st.relaxed.gpu.global.v2.u32 [%0], {%1,%2};" :: "l"(p), "r"(a), "r"(b) : "memory"); }
__device__ __forceinline__ void st_rlx(void* p, uint32_t a) { asm volatile("st.relaxed.gpu.global.u32 [%0], %1;" :: "l"(p), "r"(a) : "memory"); }
__device__ __forceinline__ void red4(void* p, float a, float b, float c, float d) { asm volatile("red.relaxed.gpu.global.add.v4.f32 [%0], {%1,%2,%3,%4};" :: "l"(p), "f"(a), "f"(b), "f"(c), "f"(d) : "memory"); }
__device__ __forceinline__ uint32_t pack2(float lo, float hi) { uint32_t r; asm("cvt.rn.bf16x2.f32 %0, %1, %2;" : "=r"(r) : "f"(hi), "f"(lo)); return r; }
__device__ __forceinline__ float bf_lo(uint32_t v) { return __uint_as_float(v << 16); }
__device__ __forceinline__ float bf_hi(uint32_t v) { return __uint_as_float(v & 0xFFFF0000u); }
__device__ __forceinline__ void stsm4(uint32_t addr, uint32_t a, uint32_t b, uint32_t c, uint32_t d) {
  asm volatile("stmatrix.sync.aligned.m8n8.x4.shared.b16 [%0], {%1,%2,%3,%4};" :: "r"(addr), "r"(a), "r"(b), "r"(c), "r"(d) : "memory");
}
template <uint32_t O> __device__ __forceinline__ void stsm4_o(uint32_t addr, uint32_t a, uint32_t b, uint32_t c, uint32_t d) {
  asm volatile("stmatrix.sync.aligned.m8n8.x4.shared.b16 [%0+%5], {%1,%2,%3,%4};" :: "r"(addr), "r"(a), "r"(b), "r"(c), "r"(d), "n"(O) : "memory");
}
__device__ __forceinline__ void sts4(uint32_t addr, uint32_t a, uint32_t b, uint32_t c, uint32_t d) { asm volatile("st.shared.v4.u32 [%0], {%1,%2,%3,%4};" :: "r"(addr), "r"(a), "r"(b), "r"(c), "r"(d) : "memory"); }
__device__ __forceinline__ void sts2f(uint32_t addr, float a, float b) { asm volatile("st.shared.v2.f32 [%0], {%1,%2};" :: "r"(addr), "f"(a), "f"(b) : "memory"); }
__device__ __forceinline__ void sts1(uint32_t addr, uint32_t a) { asm volatile("st.shared.u32 [%0], %1;" :: "r"(addr), "r"(a) : "memory"); }
__device__ __forceinline__ float2 lds2f(uint32_t addr) { float2 v; asm volatile("ld.shared.v2.f32 {%0,%1}, [%2];" : "=f"(v.x), "=f"(v.y) : "r"(addr) : "memory"); return v; }
template <uint32_t O> __device__ __forceinline__ float2 lds2f_o(uint32_t addr) { float2 v; asm volatile("ld.shared.v2.f32 {%0,%1}, [%2+%3];" : "=f"(v.x), "=f"(v.y) : "r"(addr), "n"(O) : "memory"); return v; }
template <int I, int N, class F> __device__ __forceinline__ void static_for(F&& f) { if constexpr (I < N) { f(std::integral_constant<int, I>{}); static_for<I + 1, N>(f); } }
__device__ __forceinline__ uint4 lds4(uint32_t addr) { uint4 v; asm volatile("ld.shared.v4.u32 {%0,%1,%2,%3}, [%4];" : "=r"(v.x), "=r"(v.y), "=r"(v.z), "=r"(v.w) : "r"(addr) : "memory"); return v; }
__device__ __forceinline__ uint32_t lds1(uint32_t addr) { uint32_t v; asm volatile("ld.shared.u32 %0, [%1];" : "=r"(v) : "r"(addr) : "memory"); return v; }
__device__ __forceinline__ float ex2(float x) { float y; asm("ex2.approx.ftz.f32 %0, %1;" : "=f"(y) : "f"(x)); return y; }
__device__ __forceinline__ uint32_t max4(uint32_t m, const uint4& v) { return __vimax3_u32(__vimax3_u32(m, v.x, v.y), v.z, v.w); }
__device__ __forceinline__ float rsq(float x) { float y; asm("rsqrt.approx.ftz.f32 %0, %1;" : "=f"(y) : "f"(x)); return y; }
__device__ __forceinline__ float rcp(float x) { float y; asm("rcp.approx.ftz.f32 %0, %1;" : "=f"(y) : "f"(x)); return y; }
__device__ __forceinline__ uint2 ld_rlx2(const void* p) { uint2 v; asm volatile("ld.relaxed.gpu.global.v2.u32 {%0,%1}, [%2];" : "=r"(v.x), "=r"(v.y) : "l"(p) : "memory"); return v; }
template <uint32_t O> __device__ __forceinline__ uint4 lds4_o(uint32_t addr) { uint4 v; asm volatile("ld.shared.v4.u32 {%0,%1,%2,%3}, [%4+%5];" : "=r"(v.x), "=r"(v.y), "=r"(v.z), "=r"(v.w) : "r"(addr), "n"(O) : "memory"); return v; }
__device__ __forceinline__ uint32_t phi2(float u0, float u1, float rl, uint32_t r2) {
  uint32_t pu, r;
  asm("cvt.rn.relu.bf16x2.f32 %0, %1, %2;" : "=r"(pu) : "f"(u1), "f"(u0));
  asm("fma.rn.bf16x2 %0, %1, %2, %3;" : "=r"(r) : "r"(pu), "r"(r2), "r"(pack2(__saturatef(ex2(u0 * rl) + 1e-6f), __saturatef(ex2(u1 * rl) + 1e-6f))));
  return r;
}
__device__ __forceinline__ uint32_t dup2(float r) { uint32_t v; asm("cvt.rn.relu.bf16x2.f32 %0, %1, %1;" : "=r"(v) : "f"(r)); return v; }
__device__ __forceinline__ uint32_t zero_after(const uint32_t (&v)[16]) {
  uint32_t z = 0;
#pragma unroll
  for (int i = 0; i < 16; i++) z |= v[i];
  return z & 0x80008000u;
}
__device__ __forceinline__ uint32_t hadd2(uint32_t a, uint32_t b) { uint32_t v; asm("add.rn.bf16x2 %0, %1, %2;" : "=r"(v) : "r"(a), "r"(b)); return v; }
__device__ __forceinline__ void sched_fence() { asm volatile("{\n.reg .pred p;\n.reg .u64 c;\nSF:\nmov.u64 c, %clock64;\nsetp.eq.u64 p, c, 0;\n@p bra SF;\n}" ::: "memory"); }
__device__ __forceinline__ uint4 ld_gen4(const void* p) { uint4 v; asm volatile("ld.relaxed.gpu.v4.u32 {%0,%1,%2,%3}, [%4];" : "=r"(v.x), "=r"(v.y), "=r"(v.z), "=r"(v.w) : "l"(p) : "memory"); return v; }
__device__ __forceinline__ uint2 ld_gen2(const void* p) { uint2 v; asm volatile("ld.relaxed.gpu.v2.u32 {%0,%1}, [%2];" : "=r"(v.x), "=r"(v.y) : "l"(p) : "memory"); return v; }
__device__ __forceinline__ uint32_t lane_id() { uint32_t v; asm volatile("mov.u32 %0, %%laneid;" : "=r"(v)); return v; }
template <int A, int B, int N> __device__ __forceinline__ void pinr(float (&d)[N]) {
#pragma unroll
  for (int i = A; i < B; i++) asm volatile("" : "+f"(d[i]) :: "memory");
}
template <int N> __device__ __forceinline__ void pinu(uint32_t (&d)[N]) {
#pragma unroll
  for (int i = 0; i < N; i++) asm volatile("" : "+r"(d[i]) :: "memory");
}

template<int TA, int TB, int OFF, int SZ> __device__ __forceinline__ void wgmma_n192_ss(float (&d)[SZ], uint64_t da, uint64_t db, int scale_d) {
  asm volatile("{\n.reg .pred p;\nsetp.ne.b32 p, %98, 0;\n"
    "wgmma.mma_async.sync.aligned.m64n192k16.f32.bf16.bf16 {%0,%1,%2,%3,%4,%5,%6,%7,%8,%9,%10,%11,%12,%13,%14,%15,%16,%17,%18,%19,%20,%21,%22,%23,%24,%25,%26,%27,%28,%29,%30,%31,%32,%33,%34,%35,%36,%37,%38,%39,%40,%41,%42,%43,%44,%45,%46,%47,%48,%49,%50,%51,%52,%53,%54,%55,%56,%57,%58,%59,%60,%61,%62,%63,%64,%65,%66,%67,%68,%69,%70,%71,%72,%73,%74,%75,%76,%77,%78,%79,%80,%81,%82,%83,%84,%85,%86,%87,%88,%89,%90,%91,%92,%93,%94,%95}, %96, %97, p, 1, 1, %99, %100;\n}\n"
    : "+f"(d[OFF+0]), "+f"(d[OFF+1]), "+f"(d[OFF+2]), "+f"(d[OFF+3]), "+f"(d[OFF+4]), "+f"(d[OFF+5]), "+f"(d[OFF+6]), "+f"(d[OFF+7]),
      "+f"(d[OFF+8]), "+f"(d[OFF+9]), "+f"(d[OFF+10]), "+f"(d[OFF+11]), "+f"(d[OFF+12]), "+f"(d[OFF+13]), "+f"(d[OFF+14]), "+f"(d[OFF+15]),
      "+f"(d[OFF+16]), "+f"(d[OFF+17]), "+f"(d[OFF+18]), "+f"(d[OFF+19]), "+f"(d[OFF+20]), "+f"(d[OFF+21]), "+f"(d[OFF+22]), "+f"(d[OFF+23]),
      "+f"(d[OFF+24]), "+f"(d[OFF+25]), "+f"(d[OFF+26]), "+f"(d[OFF+27]), "+f"(d[OFF+28]), "+f"(d[OFF+29]), "+f"(d[OFF+30]), "+f"(d[OFF+31]),
      "+f"(d[OFF+32]), "+f"(d[OFF+33]), "+f"(d[OFF+34]), "+f"(d[OFF+35]), "+f"(d[OFF+36]), "+f"(d[OFF+37]), "+f"(d[OFF+38]), "+f"(d[OFF+39]),
      "+f"(d[OFF+40]), "+f"(d[OFF+41]), "+f"(d[OFF+42]), "+f"(d[OFF+43]), "+f"(d[OFF+44]), "+f"(d[OFF+45]), "+f"(d[OFF+46]), "+f"(d[OFF+47]),
      "+f"(d[OFF+48]), "+f"(d[OFF+49]), "+f"(d[OFF+50]), "+f"(d[OFF+51]), "+f"(d[OFF+52]), "+f"(d[OFF+53]), "+f"(d[OFF+54]), "+f"(d[OFF+55]),
      "+f"(d[OFF+56]), "+f"(d[OFF+57]), "+f"(d[OFF+58]), "+f"(d[OFF+59]), "+f"(d[OFF+60]), "+f"(d[OFF+61]), "+f"(d[OFF+62]), "+f"(d[OFF+63]),
      "+f"(d[OFF+64]), "+f"(d[OFF+65]), "+f"(d[OFF+66]), "+f"(d[OFF+67]), "+f"(d[OFF+68]), "+f"(d[OFF+69]), "+f"(d[OFF+70]), "+f"(d[OFF+71]),
      "+f"(d[OFF+72]), "+f"(d[OFF+73]), "+f"(d[OFF+74]), "+f"(d[OFF+75]), "+f"(d[OFF+76]), "+f"(d[OFF+77]), "+f"(d[OFF+78]), "+f"(d[OFF+79]),
      "+f"(d[OFF+80]), "+f"(d[OFF+81]), "+f"(d[OFF+82]), "+f"(d[OFF+83]), "+f"(d[OFF+84]), "+f"(d[OFF+85]), "+f"(d[OFF+86]), "+f"(d[OFF+87]),
      "+f"(d[OFF+88]), "+f"(d[OFF+89]), "+f"(d[OFF+90]), "+f"(d[OFF+91]), "+f"(d[OFF+92]), "+f"(d[OFF+93]), "+f"(d[OFF+94]), "+f"(d[OFF+95])
    : "l"(da), "l"(db), "r"(scale_d), "n"(TA), "n"(TB));
}
template<int TA, int TB, int OFF, int SZ> __device__ __forceinline__ void wgmma_n128_ss(float (&d)[SZ], uint64_t da, uint64_t db, int scale_d) {
  asm volatile("{\n.reg .pred p;\nsetp.ne.b32 p, %66, 0;\n"
    "wgmma.mma_async.sync.aligned.m64n128k16.f32.bf16.bf16 {%0,%1,%2,%3,%4,%5,%6,%7,%8,%9,%10,%11,%12,%13,%14,%15,%16,%17,%18,%19,%20,%21,%22,%23,%24,%25,%26,%27,%28,%29,%30,%31,%32,%33,%34,%35,%36,%37,%38,%39,%40,%41,%42,%43,%44,%45,%46,%47,%48,%49,%50,%51,%52,%53,%54,%55,%56,%57,%58,%59,%60,%61,%62,%63}, %64, %65, p, 1, 1, %67, %68;\n}\n"
    : "+f"(d[OFF+0]), "+f"(d[OFF+1]), "+f"(d[OFF+2]), "+f"(d[OFF+3]), "+f"(d[OFF+4]), "+f"(d[OFF+5]), "+f"(d[OFF+6]), "+f"(d[OFF+7]),
      "+f"(d[OFF+8]), "+f"(d[OFF+9]), "+f"(d[OFF+10]), "+f"(d[OFF+11]), "+f"(d[OFF+12]), "+f"(d[OFF+13]), "+f"(d[OFF+14]), "+f"(d[OFF+15]),
      "+f"(d[OFF+16]), "+f"(d[OFF+17]), "+f"(d[OFF+18]), "+f"(d[OFF+19]), "+f"(d[OFF+20]), "+f"(d[OFF+21]), "+f"(d[OFF+22]), "+f"(d[OFF+23]),
      "+f"(d[OFF+24]), "+f"(d[OFF+25]), "+f"(d[OFF+26]), "+f"(d[OFF+27]), "+f"(d[OFF+28]), "+f"(d[OFF+29]), "+f"(d[OFF+30]), "+f"(d[OFF+31]),
      "+f"(d[OFF+32]), "+f"(d[OFF+33]), "+f"(d[OFF+34]), "+f"(d[OFF+35]), "+f"(d[OFF+36]), "+f"(d[OFF+37]), "+f"(d[OFF+38]), "+f"(d[OFF+39]),
      "+f"(d[OFF+40]), "+f"(d[OFF+41]), "+f"(d[OFF+42]), "+f"(d[OFF+43]), "+f"(d[OFF+44]), "+f"(d[OFF+45]), "+f"(d[OFF+46]), "+f"(d[OFF+47]),
      "+f"(d[OFF+48]), "+f"(d[OFF+49]), "+f"(d[OFF+50]), "+f"(d[OFF+51]), "+f"(d[OFF+52]), "+f"(d[OFF+53]), "+f"(d[OFF+54]), "+f"(d[OFF+55]),
      "+f"(d[OFF+56]), "+f"(d[OFF+57]), "+f"(d[OFF+58]), "+f"(d[OFF+59]), "+f"(d[OFF+60]), "+f"(d[OFF+61]), "+f"(d[OFF+62]), "+f"(d[OFF+63])
    : "l"(da), "l"(db), "r"(scale_d), "n"(TA), "n"(TB));
}
template<int TA, int TB, int OFF, int SZ> __device__ __forceinline__ void wgmma_n64_ss(float (&d)[SZ], uint64_t da, uint64_t db, int scale_d) {
  asm volatile("{\n.reg .pred p;\nsetp.ne.b32 p, %34, 0;\n"
    "wgmma.mma_async.sync.aligned.m64n64k16.f32.bf16.bf16 {%0,%1,%2,%3,%4,%5,%6,%7,%8,%9,%10,%11,%12,%13,%14,%15,%16,%17,%18,%19,%20,%21,%22,%23,%24,%25,%26,%27,%28,%29,%30,%31}, %32, %33, p, 1, 1, %35, %36;\n}\n"
    : "+f"(d[OFF+0]), "+f"(d[OFF+1]), "+f"(d[OFF+2]), "+f"(d[OFF+3]), "+f"(d[OFF+4]), "+f"(d[OFF+5]), "+f"(d[OFF+6]), "+f"(d[OFF+7]),
      "+f"(d[OFF+8]), "+f"(d[OFF+9]), "+f"(d[OFF+10]), "+f"(d[OFF+11]), "+f"(d[OFF+12]), "+f"(d[OFF+13]), "+f"(d[OFF+14]), "+f"(d[OFF+15]),
      "+f"(d[OFF+16]), "+f"(d[OFF+17]), "+f"(d[OFF+18]), "+f"(d[OFF+19]), "+f"(d[OFF+20]), "+f"(d[OFF+21]), "+f"(d[OFF+22]), "+f"(d[OFF+23]),
      "+f"(d[OFF+24]), "+f"(d[OFF+25]), "+f"(d[OFF+26]), "+f"(d[OFF+27]), "+f"(d[OFF+28]), "+f"(d[OFF+29]), "+f"(d[OFF+30]), "+f"(d[OFF+31])
    : "l"(da), "l"(db), "r"(scale_d), "n"(TA), "n"(TB));
}
template<int TA, int TB, int OFF, int SZ> __device__ __forceinline__ void wgmma_n72_ss(float (&d)[SZ], uint64_t da, uint64_t db, int scale_d) {
  asm volatile("{\n.reg .pred p;\nsetp.ne.b32 p, %38, 0;\n"
    "wgmma.mma_async.sync.aligned.m64n72k16.f32.bf16.bf16 {%0,%1,%2,%3,%4,%5,%6,%7,%8,%9,%10,%11,%12,%13,%14,%15,%16,%17,%18,%19,%20,%21,%22,%23,%24,%25,%26,%27,%28,%29,%30,%31,%32,%33,%34,%35}, %36, %37, p, 1, 1, %39, %40;\n}\n"
    : "+f"(d[OFF+0]), "+f"(d[OFF+1]), "+f"(d[OFF+2]), "+f"(d[OFF+3]), "+f"(d[OFF+4]), "+f"(d[OFF+5]), "+f"(d[OFF+6]), "+f"(d[OFF+7]),
      "+f"(d[OFF+8]), "+f"(d[OFF+9]), "+f"(d[OFF+10]), "+f"(d[OFF+11]), "+f"(d[OFF+12]), "+f"(d[OFF+13]), "+f"(d[OFF+14]), "+f"(d[OFF+15]),
      "+f"(d[OFF+16]), "+f"(d[OFF+17]), "+f"(d[OFF+18]), "+f"(d[OFF+19]), "+f"(d[OFF+20]), "+f"(d[OFF+21]), "+f"(d[OFF+22]), "+f"(d[OFF+23]),
      "+f"(d[OFF+24]), "+f"(d[OFF+25]), "+f"(d[OFF+26]), "+f"(d[OFF+27]), "+f"(d[OFF+28]), "+f"(d[OFF+29]), "+f"(d[OFF+30]), "+f"(d[OFF+31]),
      "+f"(d[OFF+32]), "+f"(d[OFF+33]), "+f"(d[OFF+34]), "+f"(d[OFF+35])
    : "l"(da), "l"(db), "r"(scale_d), "n"(TA), "n"(TB));
}
template<int TB, int OFF, int SZ> __device__ __forceinline__ void wgmma_n64_rs(float (&d)[SZ], uint32_t a0, uint32_t a1, uint32_t a2, uint32_t a3, uint64_t db, int scale_d) {
  asm volatile("{\n.reg .pred p;\nsetp.ne.b32 p, %37, 0;\n"
    "wgmma.mma_async.sync.aligned.m64n64k16.f32.bf16.bf16 {%0,%1,%2,%3,%4,%5,%6,%7,%8,%9,%10,%11,%12,%13,%14,%15,%16,%17,%18,%19,%20,%21,%22,%23,%24,%25,%26,%27,%28,%29,%30,%31}, {%32,%33,%34,%35}, %36, p, 1, 1, %38;\n}\n"
    : "+f"(d[OFF+0]), "+f"(d[OFF+1]), "+f"(d[OFF+2]), "+f"(d[OFF+3]), "+f"(d[OFF+4]), "+f"(d[OFF+5]), "+f"(d[OFF+6]), "+f"(d[OFF+7]),
      "+f"(d[OFF+8]), "+f"(d[OFF+9]), "+f"(d[OFF+10]), "+f"(d[OFF+11]), "+f"(d[OFF+12]), "+f"(d[OFF+13]), "+f"(d[OFF+14]), "+f"(d[OFF+15]),
      "+f"(d[OFF+16]), "+f"(d[OFF+17]), "+f"(d[OFF+18]), "+f"(d[OFF+19]), "+f"(d[OFF+20]), "+f"(d[OFF+21]), "+f"(d[OFF+22]), "+f"(d[OFF+23]),
      "+f"(d[OFF+24]), "+f"(d[OFF+25]), "+f"(d[OFF+26]), "+f"(d[OFF+27]), "+f"(d[OFF+28]), "+f"(d[OFF+29]), "+f"(d[OFF+30]), "+f"(d[OFF+31])
    : "r"(a0), "r"(a1), "r"(a2), "r"(a3), "l"(db), "r"(scale_d), "n"(TB));
}
template<int TB, int OFF, int SZ> __device__ __forceinline__ void wgmma_n40_rs(float (&d)[SZ], uint32_t a0, uint32_t a1, uint32_t a2, uint32_t a3, uint64_t db, int scale_d) {
  asm volatile("{\n.reg .pred p;\nsetp.ne.b32 p, %25, 0;\n"
    "wgmma.mma_async.sync.aligned.m64n40k16.f32.bf16.bf16 {%0,%1,%2,%3,%4,%5,%6,%7,%8,%9,%10,%11,%12,%13,%14,%15,%16,%17,%18,%19}, {%20,%21,%22,%23}, %24, p, 1, 1, %26;\n}\n"
    : "+f"(d[OFF+0]), "+f"(d[OFF+1]), "+f"(d[OFF+2]), "+f"(d[OFF+3]), "+f"(d[OFF+4]), "+f"(d[OFF+5]), "+f"(d[OFF+6]), "+f"(d[OFF+7]),
      "+f"(d[OFF+8]), "+f"(d[OFF+9]), "+f"(d[OFF+10]), "+f"(d[OFF+11]), "+f"(d[OFF+12]), "+f"(d[OFF+13]), "+f"(d[OFF+14]), "+f"(d[OFF+15]),
      "+f"(d[OFF+16]), "+f"(d[OFF+17]), "+f"(d[OFF+18]), "+f"(d[OFF+19])
    : "r"(a0), "r"(a1), "r"(a2), "r"(a3), "l"(db), "r"(scale_d), "n"(TB));
}
template<int TB, int OFF, int SZ> __device__ __forceinline__ void wgmma_n128_rs(float (&d)[SZ], uint32_t a0, uint32_t a1, uint32_t a2, uint32_t a3, uint64_t db, int scale_d) {
  asm volatile("{\n.reg .pred p;\nsetp.ne.b32 p, %69, 0;\n"
    "wgmma.mma_async.sync.aligned.m64n128k16.f32.bf16.bf16 {%0,%1,%2,%3,%4,%5,%6,%7,%8,%9,%10,%11,%12,%13,%14,%15,%16,%17,%18,%19,%20,%21,%22,%23,%24,%25,%26,%27,%28,%29,%30,%31,%32,%33,%34,%35,%36,%37,%38,%39,%40,%41,%42,%43,%44,%45,%46,%47,%48,%49,%50,%51,%52,%53,%54,%55,%56,%57,%58,%59,%60,%61,%62,%63}, {%64,%65,%66,%67}, %68, p, 1, 1, %70;\n}\n"
    : "+f"(d[OFF+0]), "+f"(d[OFF+1]), "+f"(d[OFF+2]), "+f"(d[OFF+3]), "+f"(d[OFF+4]), "+f"(d[OFF+5]), "+f"(d[OFF+6]), "+f"(d[OFF+7]),
      "+f"(d[OFF+8]), "+f"(d[OFF+9]), "+f"(d[OFF+10]), "+f"(d[OFF+11]), "+f"(d[OFF+12]), "+f"(d[OFF+13]), "+f"(d[OFF+14]), "+f"(d[OFF+15]),
      "+f"(d[OFF+16]), "+f"(d[OFF+17]), "+f"(d[OFF+18]), "+f"(d[OFF+19]), "+f"(d[OFF+20]), "+f"(d[OFF+21]), "+f"(d[OFF+22]), "+f"(d[OFF+23]),
      "+f"(d[OFF+24]), "+f"(d[OFF+25]), "+f"(d[OFF+26]), "+f"(d[OFF+27]), "+f"(d[OFF+28]), "+f"(d[OFF+29]), "+f"(d[OFF+30]), "+f"(d[OFF+31]),
      "+f"(d[OFF+32]), "+f"(d[OFF+33]), "+f"(d[OFF+34]), "+f"(d[OFF+35]), "+f"(d[OFF+36]), "+f"(d[OFF+37]), "+f"(d[OFF+38]), "+f"(d[OFF+39]),
      "+f"(d[OFF+40]), "+f"(d[OFF+41]), "+f"(d[OFF+42]), "+f"(d[OFF+43]), "+f"(d[OFF+44]), "+f"(d[OFF+45]), "+f"(d[OFF+46]), "+f"(d[OFF+47]),
      "+f"(d[OFF+48]), "+f"(d[OFF+49]), "+f"(d[OFF+50]), "+f"(d[OFF+51]), "+f"(d[OFF+52]), "+f"(d[OFF+53]), "+f"(d[OFF+54]), "+f"(d[OFF+55]),
      "+f"(d[OFF+56]), "+f"(d[OFF+57]), "+f"(d[OFF+58]), "+f"(d[OFF+59]), "+f"(d[OFF+60]), "+f"(d[OFF+61]), "+f"(d[OFF+62]), "+f"(d[OFF+63])
    : "r"(a0), "r"(a1), "r"(a2), "r"(a3), "l"(db), "r"(scale_d), "n"(TB));
}

struct Ptrs { const __nv_bfloat16 *x, *wqkv, *wo, *wr, *wg, *wu, *wd; __nv_bfloat16* out; Scratch* s; };

enum { M_X, M_W, M_Q, M_O, M_S, M_G, M_U, M_D, M_L, M_N };
struct Maps { CUtensorMap m[M_N]; };

__global__ void __cluster_dims__(2, 1, 1) __launch_bounds__(384, 1) fused_kernel(const Ptrs P, const __grid_constant__ Maps T) {
  extern __shared__ __align__(1024) uint8_t smem_raw[];
  TS_DECL; TS(0); TSG(30);
  if (MPF == 1 && threadIdx.x == 0) { tmap_prefetch(&T.m[M_W]); tmap_prefetch(&T.m[M_Q]); tmap_prefetch(&T.m[M_X]); }
  if (MPF == 2 && threadIdx.x < 3) l2_prefetch(&T.m[threadIdx.x]);
  if (MPF == 3 && (threadIdx.x & 31) == 0 && threadIdx.x < 96) tmap_prefetch(&T.m[threadIdx.x >> 5]);
  const int tid = threadIdx.x, wid = __shfl_sync(~0u, tid >> 5, 0), wg = wid >> 2, lane = lane_id();
  const uint32_t rank = blockIdx.x & 1, own = rank << 24;
  const uint32_t sm = own + sb, mb = own + bars;
  int b0;
  { const int j = blockIdx.x >> 1, u = j - 36, q = (u * 37) >> 8;
    b0 = (j < 4 ? j * 16 + 64 : u < 0 ? j * 2 - 8 : q * 2 + u * 2 + 66) + rank; }
#define IDS(B) \
  const int b = (B), rb = b >> 4, cg = b & 15, hf = cg >> 3, s3 = cg & 7, c3 = s3 ^ ((rb & 1) << 2), jp = cg >> 1, km = (~c3 & 6) << 1; \
  const int fidx = jp == rb ? -1 : b - 2 * rb - (jp > rb ? 2 : 0); \
  auto kcol = [&](int kb) { return (kb ^ (kb < 8 ? km & 8 : km)) * 64; }; \
  auto src_of = [&](int p) { return p == 0 ? s3 : p == 15 ? s3 ^ 1 : (((jp & 3) ^ ((p - 7) >> 1)) << 1) + ((p - 1) & 1); }; \
  auto frag_of = [&](int p) { return p < 9 ? (p - 1) * 512 : 4096 + src_of(p) * 512; }; \
  (void)hf; (void)fidx; (void)kcol; (void)frag_of
  auto get_b = [&]() { return __shfl_sync(~0u, (int)lds1(mb + B_ID), 0); };
  IDS(b0);
  auto load_w = [&](uint32_t st, int kc, uint32_t bar, bool last) { tma_3d(st + 32768, &T.m[M_W], cg * 64, kc, 1, bar, last); tma_2d(st + 49152, &T.m[M_Q], cg * 64, kc, bar, last); };
  const uint32_t tk = clock64();
  if (SPF && tid < 80) {
    const int i = tid - 32;
    l2_prefetch(tid < 32 ? P.x + (rb * 256 + (hf * 4 + (cg & 3)) * 32 + tid) * D_ + kcol(0) : P.wqkv + (kcol(0) + (rb >> 1) * 16 + (i & 15)) * 3072 + (i >> 4) * 1024 + cg * 64);
  }
  RTS_DECL;
  if (wid == 8) {
    if (elect_one()) {
      if (smem_u32(smem_raw) != sm) asm volatile("trap;");
#pragma unroll
      for (int s = 0; s < 4; s++) mbar_init(mb + B_FULL + 8 * s, 1);
      asm volatile("fence.mbarrier_init.release.cluster;" ::: "memory");
      fence_async_smem();
      mbar_expect_tx(mb + B_FULL, STAGE_B);
      load_w(sm, kcol(0), mb + B_FULL, EFW0);
      tma_2d(sm, &T.m[M_X], kcol(0), rb * 256, mb + B_FULL, EFX0);
      tma_2d(sm + 16384, &T.m[M_X], kcol(0), rb * 256 + 128, mb + B_FULL, EFX0);
      RTS(0);
    }
  } else if (wid == 9) {
    if (elect_one()) {
#pragma unroll
      for (int i = 4; i < 31; i++) if (8 * i != B_ID) mbar_init(mb + 8 * i, i < 8 ? 8 : i < 16 ? 16 : i == 16 ? 64 : i == 17 ? 8 : i == 18 ? 4 : 1);
      asm volatile("fence.mbarrier_init.release.cluster;" ::: "memory");
      fence_async_smem();
    }
  } else if (wid == 11) {
#pragma unroll
    for (int i = 0; i < 4; i++) sts4(sm + OFF_STATS + i * 512 + lane * 16, SENT, SENT, SENT, SENT);
    sts1(mb + B_ID, b);
    fence_async_smem();
  }
  __syncthreads();
  asm volatile("barrier.cluster.arrive.relaxed.aligned;\nbarrier.cluster.wait.aligned;" ::: "memory");

  if (wg == 2) {
    asm volatile("setmaxnreg.dec.sync.aligned.u32 56;");
    if (wid == 8) {
      if (elect_one()) {
#pragma unroll 1
        for (int kb = 1; kb < 15; kb++) {
          const uint32_t fb = mb + B_FULL + 8 * (kb & 3), st = sm + (kb & 3) * STAGE_B;
          const int kc = kcol(kb);
          if (kb < 4) while ((uint32_t)clock64() - tk < FD0 + kb * FD1) {}
          else mbar_wait(fb + B_EMPTY, ((kb >> 2) & 1) ^ 1);
          mbar_expect_tx(fb, STAGE_B);
          tma_2d_mc(st + rank * 16384, &T.m[M_X], kc, rb * 256 + rank * 128, fb, EFX);
          load_w(st, kc, fb, EFW && kb >= EFWK);
          if (kb >= 8 && kb < 11) asm volatile("mbarrier.arrive.shared::cta.b64 _, [%0], %1;" :: "r"(fb + B_EMPTY), "r"(4) : "memory");
        }
        {
          const uint32_t st = sm + 3 * STAGE_B, fa = mb + B_FULL + 24, fb = mb + B_F15;
          const int kc = kcol(15);
          mbar_wait(fa, 0);
          mbar_expect_tx(fa, 32768); mbar_expect_tx(fb, 24576);
          if (rank) { mbar_wait(mb + B_EMPTY + 24, 0); tma_2d_mc(st + 16384, &T.m[M_X], kc, rb * 256 + 128, fa, EFX); }
          mbar_wait(mb + B_EMPTY, 1);
          tma_3d(st + 32768, &T.m[M_W], cg * 64, kc, 1, fa, EFW);
          if (!rank) { mbar_wait(mb + B_EMPTY + 24, 0); tma_2d_mc(st, &T.m[M_X], kc, rb * 256, fb, EFX); }
          tma_2d(st + 49152, &T.m[M_Q], cg * 64, kc, fb, EFW);
        }
        const uint4* kp = &P.s->kvp[cg * 8 * 256], *zq = &P.s->zp[cg * 8 * 16], *src = &P.s->obuf[(rb * 4 + rank * 2 + hf) * 64 * 128];
        const uint32_t* cnt = &P.s->ocnt[(rb * 2 + (hf ^ 1)) * 32];
        mbar_expect_tx(mb + B_KVP, 32768 + 2048);
        asm volatile("" : "+l"(kp), "+l"(zq), "+l"(src), "+l"(cnt));
        mbar_wait(mb + B_EVB, 0);
        { const uint32_t t1 = clock64(); while ((uint32_t)clock64() - t1 < KDELAY) {} }
        bulk_load(sm + rank * (2 * STAGE_B) + STAGE_B, kp, 32768, mb + B_KVP);
        bulk_load(sm + rank * (2 * STAGE_B) + UNIT, zq, 2048, mb + B_KVP);
        mbar_wait(mb + B_E, 0);
        RTS(3);
        for (int it = 0; ld_rlx(cnt) != 7; it++) SPINCHK(it, 10);
        const uint32_t t0 = clock64();
        while ((uint32_t)clock64() - t0 < ADELAY) {}
        RTS(4);
#pragma unroll
        for (int p = 1; p < 5; p++) {
          if (p == 3) while ((uint32_t)clock64() - t0 < ADELAY2) {}
          bulk_load_mc(sm + ring_of(p, rank), src + (p - 1) * 512, UNIT, mb + B_BF + 8 * p);
        }
#pragma unroll 1
        for (int p = 5; p < 15; p++) {
          uint32_t dst = sm + ring_of(p, rank), bar = mb + B_BF + 8 * (p % 7);
          const uint4* q = src + frag_of(p);
          asm volatile("" : "+r"(dst), "+r"(bar), "+l"(q));
          mbar_wait(mb + B_E + 8 * ((p - 4) & 7), p >= 12);
          bulk_load_mc(dst, q, UNIT, bar);
        }
        asm volatile("mbarrier.arrive.shared::cta.b64 _, [%0], 8;" :: "r"(mb + B_GATE) : "memory");
        const uint4* s15 = &P.s->obuf[(rb * 4 + hf) * 64 * 128 + frag_of(15)];
        RTS_DUMP;
        mbar_wait(mb + B_E + 24, 1);
        bulk_load(sm + ring_of(15, 0), s15, UNIT, mb + B_BF + 8); bulk_load(sm + ring_of(15, 1), s15 + 2 * 64 * 128, UNIT, mb + B_BF + 8);
      }
    } else if (wid == 11) {
      IDS(get_b());
      mbar_wait(mb + B_FULL + 24, 0);
      mbar_wait(mb + B_FULL + 8 * (PULL0 & 3), PULL0 >> 2);
      int pr = fidx >= 0 ? 0 : 24;
#pragma unroll 1
      for (int ph = 0; ph < 2; ph++) {
#pragma unroll 1
        while (pr < 24) {
          const bool gu = pr < 16;
          const uint32_t d = gu ? 64 * F_ * 2 : 8192;
          const uint32_t o = (gu ? (rank * 32 + lane) * (F_ * 2) + (fidx >> 1) * 128 : (fidx - 2) * 65536 + lane * 256) + pr * d;
          const char* q0 = (const char*)(gu ? P.wg : P.wd) + o, *q1 = gu ? (const char*)P.wu + o : q0 + 128;
#pragma unroll 1
          do {
            if (ph == 1) { l2_prefetch(q0); __nanosleep(PSLEEP); l2_prefetch(q1); __nanosleep(PSLEEP); }
            else {
              if (mbar_test(mb + B_HOLD, 0)) goto next;
              asm volatile("cp.async.ca.shared.global.L2::128B [%0], [%1], 4;\ncp.async.commit_group;\ncp.async.wait_group %3;\n"
                           "cp.async.ca.shared.global.L2::128B [%0], [%2], 4;\ncp.async.commit_group;\ncp.async.wait_group %3;" :: "r"(mb + B_DUMMY), "l"(q0), "l"(q1), "n"(PDEPTH) : "memory");
            }
            q0 += d; q1 += d;
          } while (++pr & 7);
        }
      next:
        if (lane == 0) { PTS(1 + ph); g_dbgv(3 + 2 * ph, pr); }
      }
      asm volatile("cp.async.wait_all;" ::: "memory");
      if (P3PULL && fidx >= 0 && elect_one()) {
        mbar_wait(mb + B_BF + 8 * P3GATE, 0);
#pragma unroll 1
        for (int i = 0; i < 8; i++) {
          mbar_expect_tx(mb + B_LATE, 1024);
#pragma unroll
          for (int j = 0; j < 4; j++) tma_2d(sm + OFF_STATS + 768, &T.m[M_L], 0, fidx * 512 + i * 64 + j * 16, mb + B_LATE, false);
          mbar_wait(mb + B_LATE, ~i & 1);
        }
        PTS(4);
      }
    } else {
      const uint32_t eb = (lane << 24) + bars + B_EMPTY;
      float c[6];
      if (wid == 10) {
        float sx[4] = {0.f, 0.f, 0.f, 0.f}, qx[4] = {0.f, 0.f, 0.f, 0.f};
        const uint32_t xa = sm + ((hf * 4 + (cg & 3)) * 32 + lane) * 128 + ((lane & 7) << 4);
#pragma unroll 1
        for (int kb = 0; kb < 8; kb++) {
          uint4 xv[8];
          const uint32_t so = xa + (kb & 3) * STAGE_B;
          mbar_wait(mb + B_FULL + 8 * (kb & 3), kb >> 2);
#pragma unroll
          for (int i = 0; i < 8; i++) xv[i] = lds4(so ^ (i << 4));
#pragma unroll
          for (int i = 0; i < 8; i++) {
            const uint32_t e[4] = {xv[i].x, xv[i].y, xv[i].z, xv[i].w};
#pragma unroll
            for (int j = 0; j < 4; j++) {
              const float d0 = bf_lo(e[j]), d1 = bf_hi(e[j]);
              sx[j] += d0 + d1; qx[j] = fmaf(d0, d0, fmaf(d1, d1, qx[j]));
            }
          }
          __syncwarp();
          if (lane < 2) mbar_arrive_rem(eb + 8 * (kb & 3));
          if (kb == RST2) {
        {
          const uint32_t ep = ld_rlx(&P.s->epoch);
          float s = 0.f;
#pragma unroll
          for (int i = 0; i < 4; i++) {
            const uint4 v = ld_cg4((const uint4*)P.wr + lane + i * 32);
            s += (bf_lo(v.x) + bf_hi(v.x)) + (bf_lo(v.y) + bf_hi(v.y)) + (bf_lo(v.z) + bf_hi(v.z)) + (bf_lo(v.w) + bf_hi(v.w));
          }
#pragma unroll
          for (int o = 16; o; o >>= 1) s += __shfl_xor_sync(~0u, s, o);
          if (lane == 0) sts1(mb + B_SW, (__float_as_uint(s) & ~255u) | ((ep + 1) & 255));
        }
        asm volatile("cp.async.bulk.wait_group 0;\nfence.proxy.async.global;" ::: "memory");
        fence_gpu();
        if (lane == 0) PTS(0);
          }
          if (kb == RST) {
        if (elect_one()) {
#pragma unroll 1
          for (int i = 0; i < 16; i++) bulk_store(&P.s->obuf[((rb * 4 + (i >> 2)) * 64 + (((i >> 2) & 1) == hf ? 32 + s3 * 4 + (i & 3) : (i & 3) * 8 + s3)) * 128], sm + OFF_STATS, 2048);
          bulk_store(&P.s->kvp[(cg * 8 + rb) * 256], sm + OFF_STATS, 2048); bulk_store(&P.s->kvp[(cg * 8 + rb) * 256 + 128], sm + OFF_STATS, 2048);
          bulk_store(&P.s->zp[(cg * 8 + rb) * 16], sm + OFF_STATS, 256);
          if (s3 == 0) bulk_store(&P.s->ocnt[(rb * 2 + hf) * 32], sm + OFF_STATS, 128);
          asm volatile("cp.async.bulk.commit_group;" ::: "memory");
          #pragma unroll
          for (int i = M_O; i < M_N; i++) tmap_prefetch(&T.m[i]);
        }
        __syncwarp();
          }
        }
        c[0] = ((sx[0] + sx[1]) + (sx[2] + sx[3])) * (2.f / D_);
        c[1] = fmaxf(fmaf(-c[0], c[0], ((qx[0] + qx[1]) + (qx[2] + qx[3])) * (2.f / D_)), 0.f);
      } else {
        float a[12];
#pragma unroll
        for (int i = 0; i < 12; i++) a[i] = 0.f;
        const int r2 = lane >> 4, c16 = lane & 15;
        const uint32_t a0 = sm + 32768 + (rb >> 1) * 2048 + r2 * 128 + (((c16 >> 1) ^ r2) << 4) + (c16 & 1) * 8;
#pragma unroll 1
        for (int it = 0; it < 16; it++) {
          uint2 w[12];
          const int s = (it >> 1) & 3;
          const uint32_t so = a0 + s * STAGE_B + (it & 1) * 1024;
          if (!(it & 1)) { mbar_wait(mb + B_FULL + 8 * s, it >> 3); TSD(8 + (it >> 1)); }
          static_for<0, 12>([&](auto ic) { constexpr int i = decltype(ic)::value;
            const float2 v = lds2f_o<(i >> 2) * 8192 + (i & 3) * 256>(so ^ ((i & 3) << 5)); w[i] = make_uint2(__float_as_uint(v.x), __float_as_uint(v.y)); });
#pragma unroll
          for (int i = 0; i < 12; i++) { float* q = a + (i >> 2) * 4; q[0] += bf_lo(w[i].x); q[1] += bf_hi(w[i].x); q[2] += bf_lo(w[i].y); q[3] += bf_hi(w[i].y); }
          __syncwarp();
          if (lane < 2 && (it & 1)) mbar_arrive_rem(eb + 8 * s);
        }
#pragma unroll
        for (int i = 0; i < 6; i++) {
          const int o = (i >> 1) * 4 + (i & 1);
          c[i] = (r2 ? a[o + 2] : a[o]) + __shfl_xor_sync(~0u, r2 ? a[o] : a[o + 2], 16);
        }
      }
      TS(5);
      bar_sync(10, 64);
      TS(6);
      {
        const uint32_t tag = lds1(mb + B_SW) & 255;
        auto tagged = [&](float v) { return ((__float_as_uint(v) + 128) & ~255u) | tag; };
        if (wid == 9) {
#pragma unroll
          for (int sg = 0; sg < 3; sg++) {
            st_rlx2((uint2*)&P.s->csp[(cg * 8 + rb) * 48] + sg * 32 + (lane & 15) * 2 + (lane >> 4), tagged(c[sg * 2]), tagged(c[sg * 2 + 1]));
          }
        } else st_rlx2((uint2*)&P.s->st1[rb * 256 + (hf * 4 + (cg & 3)) * 32 + lane] + ((cg >> 2) & 1), tagged(c[0]), tagged(c[1]));
        { const uint32_t t0 = clock64(); while ((uint32_t)clock64() - t0 < GDELAY) {} }
#pragma unroll 1
        for (int h = wid - 9; h < 2; h++) {
          const int q = h * 24 + min(lane, 23), sd = wid == 10 ? 32 : 48;
          const uint4* gp = wid == 10 ? &P.s->st1[rb * 256 + lane] : &P.s->csp[cg * 8 * 48 + q];
          uint4 v[8];
#pragma unroll 1
          for (int it = 0;; it++) {
            uint32_t x = 0;
#pragma unroll
            for (int i = 0; i < 8; i++) v[i] = ld_rlx4(gp + i * sd);
#pragma unroll
            for (int i = 0; i < 8; i++) { v[i].x ^= tag; v[i].y ^= tag; v[i].z ^= tag; v[i].w ^= tag; x |= v[i].x | v[i].y | v[i].z | v[i].w; }
            if (!__any_sync(~0u, (x & 255) != 0)) break;
            SPINCHK(it, 3);
          }
          if (wid == 10) {
#pragma unroll
            for (int i = 0; i < 8; i++) {
              const float m0 = __uint_as_float(v[i].x), m1 = __uint_as_float(v[i].z), dm = 0.5f * (m0 - m1);
              sts2f(sm + OFF_STATS + (i * 32 + lane) * 8, -0.5f * (m0 + m1), rsq(fmaf(dm, dm, 0.5f * (__uint_as_float(v[i].y) + __uint_as_float(v[i].w))) + 1e-5f));
            }
          } else {
            float s4[4] = {0.f, 0.f, 0.f, 0.f};
#pragma unroll
            for (int i = 0; i < 8; i++) { s4[0] += __uint_as_float(v[i].x); s4[1] += __uint_as_float(v[i].y); s4[2] += __uint_as_float(v[i].z); s4[3] += __uint_as_float(v[i].w); }
            sts4(sm + OFF_COLSUM + q * 16, __float_as_uint(s4[0]), __float_as_uint(s4[1]), __float_as_uint(s4[2]), __float_as_uint(s4[3]));
          }
        }
        mbar_arrive(mb + B_AUX);
      }
      TS(2);
      IDS(get_b());
      const uint64_t btab = rank ? BT1 : BT0;
      if (wid == 9) {
        {
          const uint4 sv = make_uint4(SENT, SENT, SENT, SENT);
          uint4* y = &P.s->ybuf[b * NFFN * 4 + lane];
#pragma unroll
          for (int i = 0; i < 14; i++) y[i * 32] = sv;
          if (lane < 16) P.s->st2[b * 16 + lane] = make_uint4(0, 0, 0, 0);
          P.s->hsel[b * 64 + lane] = sv; P.s->hsel[b * 64 + 32 + lane] = sv;
          if (b < 8) P.s->cand[b * 32 + lane] = SENT;
          fence_gpu();
          __syncwarp();
          if (lane == 0) mbar_arrive(mb + B_LATE);
        }
        TS(3);
        TS_DUMP(2);
        {
          const int p = lane & 15, sl = p % 7;
          const bool sliced = p > 0 && p < 9;
          const uint32_t c = sliced ? ((p - 1) >> 1) * 16 | ((hf ^ 1) * 8 + ((p - 1) & 1) * 4) << 8 | 128 << 16 : (hf * 8 + src_of(p)) << 8;
          const uint32_t ev = mb + (p < BHOLD ? B_EVA : p < 4 ? B_KVP : p < 6 ? B45 : B_E + 8 * ((p < 7 ? 1 : p - 4) & 7) + (p >= 12));
          mbar_wait(mb + B_EVA, 0);
          sts4(sm + OFF_COLSUM + 512 + p * 16, sm + unit_of(btab, sl), mb + B_BF + 8 * sl, c, ev);
          __syncwarp();
        }
        if (elect_one()) {
#pragma unroll 1
          for (int p = 0; p < 16; p++) {
            const uint4 e = lds4(sm + OFF_COLSUM + 512 + p * 16);
            mbar_wait(e.w & ~1u, e.w & 1);
            mbar_expect_tx(e.y, p ? 4 * UNIT : 2 * UNIT);
            tma_4d(e.x, (const CUtensorMap*)((const char*)&T.m[M_O] + (e.z >> 16)), 0, e.z & 255, (e.z >> 8) & 255, c3 * 2, e.y);
          }
          PTS(16);
        }
      } else {
        const uint2 w = ld_rlx2((const uint2*)(P.wr + c3 * 128) + lane);
#pragma unroll 1
        for (int i = 0; i < 4; i++) { l2_prefetch((const char*)P.wo + b * 16384 + i * 4096 + lane * 128); __nanosleep(300); }
        const int p = lane & 15, p2 = min(p + 2, 15);
        const uint32_t t0 = dlo(sb, 8192) + (unit_of(btab, p % 7) >> 4), t1 = ring_of(p + 1, lane >> 4), t2 = mb + B_BF + 8 * (p2 % 7);
        mbar_wait(mb + B_EVB, 0);
        sts4(sm + OFF_COLSUM + lane * 16, w.x << 16, w.x & 0xFFFF0000u, w.y << 16, w.y & 0xFFFF0000u);
        sts4(sm + OFF_STATS + lane * 16, t0, t1, t2, (p2 / 7) & 1);
        __syncwarp();
        if (elect_one()) {
          mbar_arrive(mb + B_WR);
          if (fidx >= 0) {
            mbar_expect_tx(mb + B_FFN, 131072); mbar_expect_tx(mb + B_FFD, 65536);
            uint64_t gt = rank ? GT1 : GT0;
#pragma unroll 1
            for (int f = 0; f < 8; f++, gt >>= 5) {
              uint32_t d0 = sm + unit_of(gt, 0);
              asm volatile("" : "+r"(d0));
              if (f == 3) mbar_wait(mb + B_GATE, 1);
              mbar_wait(mb + (f < 3 ? B_KVB : B_E + ((f + 5) >> 1) * 8), 1);
              tma_3d(d0, &T.m[M_G], fidx * 32, f * 128, 0, mb + B_FFN, EFF);
              tma_3d(d0 + UNIT, &T.m[M_U], fidx * 32, f * 128, 0, mb + B_FFN, EFF);
            }
            PTS(17);
            gt = rank ? DT1 : DT0;
#pragma unroll 1
            for (int w = 0; w < 8; w++, gt >>= 5) {
              if (w == 2) mbar_wait(mb + B_E + 56, 1);
              if (w == 6) mbar_wait(mb + B_E16, 1);
              if (w == DLATE) mbar_wait(mb + B_OUT, 0);
              tma_3d(sm + unit_of(gt, 0), &T.m[M_D], 0, fidx * 32, 2 * w, mb + B_FFD, EFF);
            }
            PTS(18);
          }
        }
      }
    }
    __syncwarp();
    IDS(get_b());
    mbar_wait(mb + B_EVA, 0);
    mbar_wait(mb + B_OUT, 0);
    const float2 cf = lds2f(sm + OFF_STATS + 64);
    const int cand0 = 2047 - (__float_as_int(cf.x) & 2047), cand1 = 2047 - (__float_as_int(cf.y) & 2047), rr = lane >> 4;
    auto store_rows = [&](int tr, bool on) {
      const uint4 v = lds4(sm + 4 * UNIT + (tr >> 6) * STAGE_B + (tr & 63) * 256 + (((lane & 15) ^ (tr & 7)) << 4));
      const float2 pr = lds2f(sm + OFF_LNP + tr * 8);
      const float f = 1.f + pr.x, n = pr.y;
      if (on) *(uint4*)(P.out + (size_t)(rb * 256 + hf * 64 + tr + (tr & 64)) * D_ + c3 * 128 + (lane & 15) * 8) =
          make_uint4(pack2(fmaf(bf_lo(v.x), f, n), fmaf(bf_hi(v.x), f, n)), pack2(fmaf(bf_lo(v.y), f, n), fmaf(bf_hi(v.y), f, n)),
                     pack2(fmaf(bf_lo(v.z), f, n), fmaf(bf_hi(v.z), f, n)), pack2(fmaf(bf_lo(v.w), f, n), fmaf(bf_hi(v.w), f, n)));
    };
    if (wid == 8) {
      { const long long t0 = clock64(); while (clock64() - t0 < CDELAY) {} }
      uint32_t k;
      for (int it = 0;; it++) { k = ld_rlx(&P.s->cand[c3 * 32 + lane]); if (!__any_sync(~0u, k == SENT)) break; SPINCHK(it, 12); }
      const uint32_t m1 = __reduce_max_sync(~0u, k), m2 = __reduce_max_sync(~0u, k == m1 ? 0 : k);
      if (k == m1 || k == m2) sts2f(sm + OFF_STATS + 80 + (k == m2) * 8, __uint_as_float(k), __int_as_float(lane));
      __syncwarp();
      if (lane == 0) { mbar_arrive(mb + B_SEL); PTS(13); }
      const uint32_t kc = __float_as_uint(rr ? cf.y : cf.x);
      const int c = rr ? cand1 : cand0;
      store_rows(((c >> 1) & 64) + (c & 63), kc != m1 && kc != m2);
    } else if (wid < 9 + NOUTW) {
#pragma unroll 2
      for (int tr = (wid - 9) * 2 + rr; tr < 128; tr += 2 * NOUTW) {
        const int row = rb * 256 + hf * 64 + tr + (tr & 64);
        store_rows(tr, row != cand0 && row != cand1);
      }
      if (wid == 9 && lane == 0) PTS(14);
    }
  } else {
    asm volatile("setmaxnreg.inc.sync.aligned.u32 224;");
    const int t128 = tid & 127, warp = wid & 3, g = lane >> 2, t = lane & 3;
    const uint32_t sk = rank * (2 * STAGE_B);
    uint4 ost[2][4];
    uint4* od1;
    int b1;
    const uint32_t eb = (lane << 24) + bars + B_E;
    float acc[64], wf[32];
    {
      float acc0[96], acc1[96];
#pragma unroll
      for (int i = 0; i < 96; i++) { acc0[i] = 0.f; acc1[i] = 0.f; }
      const uint32_t xo0 = dlo(sb, 16) + (wg * 2 + hf) * 512, xo1 = dlo(sb, 16) + (wg * 2 + (hf ^ 1)) * 512;
      constexpr uint32_t ST = STAGE_B >> 4, WD = dlo(sb + 49152, 8192), WV = dlo(sb + 32768, 8192);
      const uint32_t eb0 = (t128 << 24) + bars + B_EMPTY;
#pragma unroll 1
      for (int kb = 0; kb < 12; kb++) {
        const int s = kb & 3;
        mbar_wait(mb + B_FULL + 8 * s, (kb >> 2) & 1);
        if (kb == 0) TS(1);
        if (kb == 0 && !wg) bar_sync(2, 256);
        pin(acc0); pin(acc1);
        wg_fence();
#pragma unroll
        for (int k = 0; k < 4; k++) {
          const uint64_t db = dsc<1024, 1>(WV + s * ST + k * 128);
          wgmma_n192_ss<0, 1, 0>(acc0, dsc<1024, 1>(s * ST + xo0 + k * 2), db, 1);
          wgmma_n192_ss<0, 1, 0>(acc1, dsc<1024, 1>(s * ST + xo1 + k * 2), db, 1);
        }
        wg_commit();
        if (kb == 0 && wg) bar_arrive(2, 256);
        wg_wait<0>();
        pin(acc0); pin(acc1);
        if (t128 < 2 && kb < 11) mbar_arrive_rem(eb0 + 8 * s);
      }
      mbar_wait(mb + B_FULL, 1);
      if (t128 < 8) mbar_arrive_rem(t128 < 4 ? (wg << 24) + bars + B_EMPTY + 24 : mb + B_EMPTY);
      TS(2);
      mbar_wait(mb + B_AUX, 0);
      float rs[2][2], nm[2][2];
#pragma unroll
      for (int m = 0; m < 2; m++)
#pragma unroll
        for (int h = 0; h < 2; h++) { const float2 v = lds2f(sm + OFF_STATS + ((wg * 2 + (m ^ hf)) * 64 + warp * 16 + h * 8 + g) * 8); nm[m][h] = v.x; rs[m][h] = v.y; }
      auto center = [&](auto jc) {
        constexpr int j = decltype(jc)::value;
        const float2 cs = lds2f_o<sb + OFF_COLSUM + j * 32>(own + t * 8);
        acc1[j * 4] = fmaf(nm[1][0], cs.x, acc1[j * 4]); acc1[j * 4 + 1] = fmaf(nm[1][0], cs.y, acc1[j * 4 + 1]);
        acc1[j * 4 + 2] = fmaf(nm[1][1], cs.x, acc1[j * 4 + 2]); acc1[j * 4 + 3] = fmaf(nm[1][1], cs.y, acc1[j * 4 + 3]);
        acc0[j * 4] = fmaf(nm[0][0], cs.x, acc0[j * 4]); acc0[j * 4 + 1] = fmaf(nm[0][0], cs.y, acc0[j * 4 + 1]);
        acc0[j * 4 + 2] = fmaf(nm[0][1], cs.x, acc0[j * 4 + 2]); acc0[j * 4 + 3] = fmaf(nm[0][1], cs.y, acc0[j * 4 + 3]);
      };
      static_for<0, 16>(center);
      const float L2E = 1.4426950408889634f;
      uint32_t fa = sm + sk + (warp * 16 + (lane & 15)) * 128 + (((lane >> 4) ^ (lane & 7)) << 4);
      asm volatile("" : "+r"(fa));
      uint32_t xf0[32], xf1[32];
      auto pack_kv = [&](float (&a)[96], int i, float r0, float r1, uint32_t* o, uint32_t z = 0) {
        const float* p = a + i * 8;
        if (i < 4) {
          const float rl0 = __uint_as_float(__float_as_uint(r0 * L2E) | z), rl1 = __uint_as_float(__float_as_uint(r1 * L2E) | z);
          const uint32_t q0 = pack2(r0, r0), q1 = pack2(r1, r1);
          o[0] = phi2(p[0], p[1], rl0, q0); o[1] = phi2(p[2], p[3], rl1, q1); o[2] = phi2(p[4], p[5], rl0, q0); o[3] = phi2(p[6], p[7], rl1, q1);
        } else {
          r0 = __uint_as_float(__float_as_uint(r0) | z); r1 = __uint_as_float(__float_as_uint(r1) | z);
          o[0] = pack2(p[0] * r0, p[1] * r0); o[1] = pack2(p[2] * r1, p[3] * r1); o[2] = pack2(p[4] * r0, p[5] * r0); o[3] = pack2(p[6] * r1, p[7] * r1); }
      };
      auto swap_kv = [&](uint32_t (&xf)[32], uint32_t tile, int i, const uint32_t* o, uint32_t z = 0) {
        const uint32_t ad = (fa + tile * UNIT) ^ ((i & 3) << 5);
        if (i < 4) { ldsm4_o<0>(ad, xf[i * 4], xf[i * 4 + 1], xf[i * 4 + 2], xf[i * 4 + 3]); stsm4_o<0>(ad, o[0], o[1], o[2], o[3]); }
        else { ldsm4_o<STAGE_B>(ad | z, xf[i * 4], xf[i * 4 + 1], xf[i * 4 + 2], xf[i * 4 + 3]); stsm4_o<STAGE_B>(ad, o[0], o[1], o[2], o[3]); }
      };
      auto mma_q = [&](float (&a)[96], uint32_t (&xf)[32], uint32_t xo, bool ss) {
        const uint32_t r = __shfl_sync(~0u, sk >> 4, 0), o = 2 * ST - r;
#pragma unroll
        for (int j = 0; j < 8; j++) {
          if (ss) wgmma_n64_ss<0, 1, 64>(a, dsc<1024, 1>(o + (j >> 2) * ST + xo + (j & 3) * 2), dsc<1024, 1>(WD + o + (j >> 2) * ST + (j & 3) * 128), 1);
          else wgmma_n64_rs<1, 64>(a, xf[j * 4], xf[j * 4 + 1], xf[j * 4 + 2], xf[j * 4 + 3], dsc<1024, 1>(WD + r + (j >> 2) * ST + (j & 3) * 128), 1);
        }
      };
      auto epi_q = [&](float (&a)[96], float r0, float r1, uint32_t (&o)[16]) {
        const float rl0 = r0 * 1.44269511f, rl1 = r1 * 1.44269511f;
        const uint32_t q0 = dup2(r0), q1 = dup2(r1);
#pragma unroll
        for (int j = 0; j < 8; j++) { o[j * 2] = phi2(a[64 + j * 4], a[65 + j * 4], rl0, q0); o[j * 2 + 1] = phi2(a[66 + j * 4], a[67 + j * 4], rl1, q1); }
        pinu(o);
      };
      auto mma_kv1 = [&](float (&a)[96], uint32_t xo, int s) {
#pragma unroll
        for (int k = 0; k < 4; k++) wgmma_n128_ss<0, 1, 0>(a, dsc<1024, 1>(s * ST + xo + k * 2), dsc<1024, 1>(WV + s * ST + k * 128), 1);
      };
      auto epi_kv = [&](float (&a)[96], uint32_t (&xf)[32], uint32_t tile, float r0, float r1) {
        uint32_t o[8][4];
#pragma unroll
        for (int j = 3; j >= 0; j--) {
          const uint32_t z = j < 3 ? (xf[(j + 5) * 4] | (j < 2 ? o[j + 2][0] | o[j + 6][0] : 0)) & blockIdx.y : 0;
          pack_kv(a, j + 4, r0, r1, o[j + 4], z);
          swap_kv(xf, tile, j + 4, o[j + 4], (o[j + 4][2] | o[j + 4][3]) & blockIdx.y);
          pack_kv(a, j, r0, r1, o[j], z);
          swap_kv(xf, tile, j, o[j]);
        }
      };
      mbar_wait(mb + B_FULL + 8, 1);
      if (!wg) bar_sync(3, 256);
      pinr<0, 64>(acc0); pinr<0, 64>(acc1);
      wg_fence();
      mma_kv1(acc1, xo1, 0); mma_kv1(acc0, xo0, 0); mma_kv1(acc1, xo1, 1);
      if (GSPLIT == 2) mma_kv1(acc0, xo0, 1);
      mbar_wait(mb + B_FULL + 16, 1);
      wg_fence();
      mma_kv1(acc1, xo1, 2);
      mbar_wait(mb + (wg ? B_FULL + 24 : B_F15), wg);
      wg_fence();
      mma_kv1(acc1, xo1, 3);
      wg_commit();
      bar_arrive(4 - wg, 256);
      static_for<16, 24>(center);
      pinr<64, 96>(acc0); pinr<64, 96>(acc1);
      mbar_wait(mb + B_AUX, 0);
      wg_wait<0>();
      pinr<0, 64>(acc0); pinr<0, 64>(acc1);
      TS(4);
      epi_kv(acc1, xf1, wg * 2 + (hf ^ 1), rs[1][0], rs[1][1]);
      pinu(xf1);
      bar_sync(5 - wg, 256);
      wg_fence();
      if (GSPLIT == 1) mma_kv1(acc0, xo0, 1);
      mma_kv1(acc0, xo0, 2); mma_kv1(acc0, xo0, 3);
      wg_commit();
      mma_q(acc1, xf1, xo1, false);
      wg_commit();
      if (wg) bar_arrive(5, 256);
      else { fence_async_smem(); bar_arrive(6, 256); }
      if (tid >= 240) sts4(sm + OFF_STATS + (tid & 15) * 128 + ((tid & 7) << 4), 0x3F803F80u, 0x3F803F80u, 0x3F803F80u, 0x3F803F80u);
      wg_wait<1>();
      pinr<0, 64>(acc0);
      if (lane == 0) mbar_arrive(mb + B_EVA);
      TS(6);
      epi_kv(acc0, xf0, wg * 2 + hf, rs[0][0], rs[0][1]);
      fence_async_smem();
      TS(7);
      pinu(xf0);
      if (wg) {
        float ka[36];
        auto mma_kv = [&](uint32_t tile, int i, int acc) {
          const uint32_t o = (sk >> 4) + tile * 512 + i * 128;
          wgmma_n72_ss<1, 1, 0>(ka, dsc<1024, 1>(dlo(sb, 8192) + o), dsc<1024, 1>(dlo(sb + STAGE_B, OFF_STATS - STAGE_B) + o * (1u - (1u << 16))), acc);
        };
#pragma unroll
        for (int i = 0; i < 36; i++) ka[i] = 0.f;
        bar_sync(6, 256);
        wg_fence();
#pragma unroll
        for (int i = 0; i < 4; i++) {
          mma_kv(2, i, i); mma_kv(3, i, 1); mma_kv(hf ^ 1, i, 1);
#pragma unroll
          for (int j = 2 * i; j < 2 * i + 2; j++)
            wgmma_n64_rs<1, 64>(acc0, xf0[j * 4], xf0[j * 4 + 1], xf0[j * 4 + 2], xf0[j * 4 + 3], dsc<1024, 1>(WD + (sk >> 4) + (j >> 2) * ST + (j & 3) * 128), 1);
        }
        const int bk = get_b(), kq = (bk & 15) * 8 + (bk >> 4);
        uint4* dst = &P.s->kvp[kq * 256 + warp * 64 + lane];
        uint32_t* dz = (uint32_t*)&P.s->zp[kq * 16] + warp * 16 + g + t * 8;
        asm volatile("" : "+l"(dst), "+l"(dz));
        mbar_wait(mb + B_LATE, 0);
        bar_sync(7, 256);
        wg_fence();
#pragma unroll
        for (int i = 0; i < 4; i++) mma_kv(hf, i, 1);
        wg_commit();
        bar_arrive(8, 256);
        wg_wait<0>();
        pin(ka); pinr<64, 96>(acc0);
        uint32_t kw[8];
#pragma unroll
        for (int i = 0; i < 8; i++) {
          const int j = (i & 3) * 4 + (i >> 2) * 2;
          asm("{\n.reg .pred p;\nsetp.ne.u32 p, %5, 0;\n@p cvt.rn.bf16x2.f32 %0, %4, %3;\n@!p cvt.rn.bf16x2.f32 %0, %2, %1;\n}"
              : "=r"(kw[i]) : "f"(ka[j]), "f"(ka[j + 1]), "f"(ka[16 + j]), "f"(ka[17 + j]), "r"(warp & 2));
        }
        st_rlx4(dst, make_uint4(kw[0], kw[1], kw[2], kw[3]));
        st_rlx4(dst + 32, make_uint4(kw[4], kw[5], kw[6], kw[7]));
        if (t < 2) st_rlx(dz, __float_as_uint(t ? ka[34] : ka[32]));
        if (lane == 0) mbar_arrive(mb + B_EVB);
        TS(8);
      } else {
        bar_arrive(7, 256);
        bar_sync(8, 256);
        wg_fence();
        mma_q(acc0, xf0, xo0, false);
      }
      const uint32_t t1 = clock64(), kvb = 2 * STAGE_B + (2 + (hf ^ 1)) * UNIT - sk;
      b1 = get_b();
      uint32_t* of = &P.s->ocnt[(b1 >> 3) * 32];
      od1 = &P.s->obuf[(((b1 >> 4) * 4 + wg * 2 + (hf ^ 1)) * 64 + (b1 & 7)) * 128 + t128];
      uint32_t ka0 = sm + kvb + wid * 1024 + (lane & 7) * 128 + (((lane >> 3) ^ (lane & 7)) << 4), ka1 = sm + kvb + wid * 1024 + (t * 2 + g) * 128 + ((4 ^ (t * 2 + g)) << 4);
      const uint8_t* g0 = smem_raw + sk + STAGE_B + tid * 16, *g1 = smem_raw + sk + UNIT + g * 256 + wid * 32 + t * 8;
      const uint8_t* h0 = (const uint8_t*)&P.s->kvp[(b1 & 15) * 8 * 256 + tid], *h1 = (const uint8_t*)&P.s->zp[((b1 & 15) * 8 + g) * 16] + wid * 32 + t * 8;
      asm volatile("" : "+r"(ka0), "+r"(ka1), "+l"(g0), "+l"(g1), "+l"(h0), "+l"(h1), "+l"(of), "+l"(od1));
      while ((uint32_t)clock64() - t1 < SDELAY) {}
      if (!wg) bar_sync(9, 256);
      wg_fence();
      mma_q(acc1, xf1, xo1, true);
      wg_commit();
      if (wg) bar_arrive(9, 256);
      wg_wait<0>();
      pinr<64, 96>(acc1); pinr<64, 96>(acc0);
      TS(9);
      uint32_t pq[16];
      epi_q(acc1, rs[1][0], rs[1][1], pq);
      bar_sync(11 + wg + zero_after(pq), 128);
      wg_fence();
      mma_q(acc0, xf0, xo0, true);
      wg_commit();
      TS(5);
      {
        uint4 gv[8]; uint2 gz;
        uint32_t m[8], a[4];
        float z0, z1;
#pragma unroll
        for (int s = 0; s < 8; s++) { m[s] = ~blockIdx.y; asm volatile("" : "=r"(gv[s].x), "=r"(gv[s].y), "=r"(gv[s].z), "=r"(gv[s].w), "+r"(m[s])); }
        mbar_wait(mb + B_KVP, 0);
        TS(28);
        wg_wait<0>();
        pinr<64, 96>(acc0);
        if (lane == 0) mbar_arrive(mb + B_KVB);
#pragma unroll 1
        for (int it = 0; it < SPIN_LIMIT; it++) {
          gz = ld_gen2(g1);
#pragma unroll
          for (int s = 0; s < 8; s++) if (m[s] == SENT) gv[s] = ld_gen4(g0 + s * 4096);
          g0 = h0; g1 = h1;
          uint32_t mm = max(gz.x, gz.y);
          z0 = __uint_as_float(gz.x); z1 = __uint_as_float(gz.y);
#pragma unroll
          for (int o = 4; o < 32; o <<= 1) { z0 += __shfl_xor_sync(~0u, z0, o); z1 += __shfl_xor_sync(~0u, z1, o); }
#pragma unroll
          for (int s = 0; s < 8; s++) m[s] = max4(0, gv[s]);
#pragma unroll
          for (int s = 0; s < 8; s += 2) mm = __vimax3_u32(mm, m[s], m[s + 1]);
          a[0] = hadd2(hadd2(hadd2(gv[0].x, gv[1].x), hadd2(gv[2].x, gv[3].x)), hadd2(hadd2(gv[4].x, gv[5].x), hadd2(gv[6].x, gv[7].x)));
          a[1] = hadd2(hadd2(hadd2(gv[0].y, gv[1].y), hadd2(gv[2].y, gv[3].y)), hadd2(hadd2(gv[4].y, gv[5].y), hadd2(gv[6].y, gv[7].y)));
          a[2] = hadd2(hadd2(hadd2(gv[0].z, gv[1].z), hadd2(gv[2].z, gv[3].z)), hadd2(hadd2(gv[4].z, gv[5].z), hadd2(gv[6].z, gv[7].z)));
          a[3] = hadd2(hadd2(hadd2(gv[0].w, gv[1].w), hadd2(gv[2].w, gv[3].w)), hadd2(hadd2(gv[4].w, gv[5].w), hadd2(gv[6].w, gv[7].w)));
          pinu(a);
          if (!__any_sync(~0u, mm == SENT)) break;
          TSV(20, 1);
        }
        TS(23);
        stsm4(ka0, a[0], a[1], a[2], a[3]);
        const uint32_t zz = pack2(g ? z1 : z0, g ? z1 : z0);
        if (lane < 8) sts4(ka1, zz, zz, zz, zz);
        fence_async_smem();
        bar_sync(1, 256);
        if (tid == 0) asm volatile("red.relaxed.gpu.global.add.u32 [%0], 1;" :: "l"(of) : "memory");
      }
      TS(21);
      auto make_o = [&](uint4 (&o)[4], auto first) {
        float oa[2][20];
        wg_fence();
#pragma unroll
        for (int ks = 0; ks < 4; ks++)
          wgmma_n40_rs<1, 0>(oa[ks >> 1], pq[ks * 4], pq[ks * 4 + 1], pq[ks * 4 + 2], pq[ks * 4 + 3], dsc<1024, 1>(dlo(sb, 8192) + (kvb >> 4) + ks * 128), ks & 1);
        wg_commit();
        if constexpr (!decltype(first)::value) {
          pinu(xf0);
#pragma unroll
          for (int q = 0; q < 32; q++) { acc[q * 2] = bf_lo(xf0[q]); acc[q * 2 + 1] = bf_hi(xf0[q]); }
          pin(acc);
          mbar_wait(mb + B_BF, 0);
        }
        wg_wait<0>();
        pin(oa[0]); pin(oa[1]);
        if (decltype(first)::value && lane < 2) mbar_arrive_rem(eb);
#pragma unroll
        for (int h = 0; h < 2; h++) {
          const float (&d)[20] = oa[h];
          const float i0 = rcp(d[16] + 1e-6f), i1 = rcp(d[18] + 1e-6f);
#pragma unroll
          for (int k2 = 0; k2 < 2; k2++) {
            o[h * 2 + k2] = make_uint4(pack2(d[k2 * 8] * i0, d[k2 * 8 + 1] * i0), pack2(d[k2 * 8 + 2] * i1, d[k2 * 8 + 3] * i1),
                                       pack2(d[k2 * 8 + 4] * i0, d[k2 * 8 + 5] * i0), pack2(d[k2 * 8 + 6] * i1, d[k2 * 8 + 7] * i1));
            if (decltype(first)::value && !h) st_rlx4(od1 + k2 * 1024, o[k2]);
          }
          if (decltype(first)::value && !h) { sched_fence(); TS(24); }
        }
      };
      make_o(ost[1], std::true_type{});
      epi_q(acc0, rs[0][0], rs[0][1], pq);
      if (AEARLY) { st_rlx4(od1 + 2048, ost[1][2]); st_rlx4(od1 + 3072, ost[1][3]); }
      make_o(ost[0], std::false_type{});
    }
   {
    IDS(b1);
    const int mb3 = rb * 4 + wg * 2 + hf;
    const int row0 = mb3 * 64 + warp * 16 + g;
    {
      uint4 abuf[3][4];
      const uint4* const ain = &P.s->obuf[mb3 * 64 * 128 + t128];
      uint4* const od0 = &P.s->obuf[(mb3 * 64 + 32 + s3 * 4) * 128 + t128];
#pragma unroll
      for (int i = 0; i < 4; i++) pin4(ost[0][i]);
      wg_fence();
#pragma unroll
      for (int k = 0; k < 4; k++) wgmma_n128_rs<1, 0>(acc, ost[0][k].x, ost[0][k].y, ost[0][k].z, ost[0][k].w, dsc<1024, 1>(dlo(sb + 4 * UNIT, 8192) + k * 128), 1);
      wg_commit();
      TS(29);
      if (!AEARLY) { st_rlx4(od1 + 2048, ost[1][2]); st_rlx4(od1 + 3072, ost[1][3]); }
      uint32_t la = sm + t128 * 16, ev = eb + 8;
      asm volatile("" : "+r"(la), "+r"(ev));
      auto fetch = [&](uint32_t off, uint4 (&a)[4]) { const uint32_t ra = la + off; a[0] = lds4_o<0>(ra); a[1] = lds4_o<2048>(ra); a[2] = lds4_o<4096>(ra); a[3] = lds4_o<6144>(ra); };
      auto check = [&](int p, uint4 (&a)[4]) {
        if (__any_sync(~0u, max(max4(max4(0, a[0]), a[1]), max4(max4(0, a[2]), a[3])) == SENT)) {
          int pl = p; asm volatile("" : "+r"(pl));
          const uint4* q = ain + frag_of(pl);
#pragma unroll 1
          for (int it = 0;; it++) {
            uint32_t mm = 0;
#pragma unroll
            for (int i = 0; i < 4; i++) { const uint32_t m = max4(0, a[i]); mm = max(mm, m); if (m == SENT) a[i] = ld_rlx4(q + i * 128); }
            if (!__any_sync(~0u, mm == SENT)) break;
            TSV(27, p < 3 ? 1 : p < 5 ? 100 : 10000);
            SPINCHK(it, 5);
          }
        }
        if (lane < 2) mbar_arrive_rem(ev);
        ev = (ev & ~0x38u) | ((ev + 8) & 0x38u);
      };
      auto mma = [&](int p, uint32_t bs, uint4 (&a)[4]) {
#pragma unroll
        for (int i = 0; i < 4; i++) pin4(a[i]);
        wg_fence();
#pragma unroll
        for (int k = 0; k < 4; k++) wgmma_n128_rs<1, 0>(acc, a[k].x, a[k].y, a[k].z, a[k].w, dsc<1024, 1>(bs + k * 128), 1);
        wg_commit();
      };
      uint32_t ta = sm + OFF_STATS + wg * 256 + 48;
      mbar_wait(mb + B_WR, 0);
      uint4 tp = lds4(ta);
      mbar_wait(mb + B_BF + 8, 0);
      TS(3);
      fetch(ring_of(1, wg), abuf[1]);
      check(1, abuf[1]);
      mma(1, dlo(sb + 11 * UNIT, 8192), abuf[1]);
      TS(25);
      mbar_wait(mb + B_BF + 16, 0);
      fetch(ring_of(2, wg), abuf[2]);
      st_rlx4(od0, ost[0][0]); st_rlx4(od0 + 128, ost[0][1]);
      check(2, abuf[2]);
      mbar_wait(mb + B_BF + 24, 0);
      fetch(ring_of(3, wg), abuf[0]);
      mma(2, dlo(sb + 18 * UNIT, 8192), abuf[2]);
      st_rlx4(od0 + 256, ost[0][2]); st_rlx4(od0 + 384, ost[0][3]);
      wg_wait<2>();
      check(3, abuf[0]);
      mbar_wait(mb + B_BF + 32, 0);
      TS(26);
#pragma unroll 1
      for (int p = 3; p < 15; p += 3) {
        static_for<0, 3>([&](auto jc) {
          constexpr int j = decltype(jc)::value;
          const uint4 tc = tp;
          const uint32_t bs = __shfl_sync(~0u, tc.x, 0);
          wg_wait<1>();
#pragma unroll
          for (int i = 0; i < 4; i++) pin4(abuf[(j + 1) % 3][i]);
          tp = lds4_o<16 * j + 16>(ta);
          fetch(tc.y, abuf[(j + 1) % 3]);
          mma(p + j, bs, abuf[j]);
          if (!CHKF) mbar_wait(tc.z, tc.w);
          check(p + j + 1, abuf[(j + 1) % 3]);
          if (CHKF) mbar_wait(tc.z, tc.w);
        });
        ta += 48;
      }
      mma(15, __shfl_sync(~0u, tp.x, 0), abuf[0]);
      wg_wait<2>();
      if (lane == 0) mbar_arrive(mb + B_E16);
      static_for<0, 16>([&](auto jc) { constexpr int j = decltype(jc)::value; const float2 v = lds2f_o<sb + OFF_COLSUM + j * 32>(own + t * 8); wf[j * 2] = v.x; wf[j * 2 + 1] = v.y; });
      pin(wf);
      wg_wait<0>();
      pin(acc);
#pragma unroll
      for (int i = 0; i < 4; i++) { pin4(abuf[0][i]); pin4(abuf[1][i]); pin4(abuf[2][i]); }
    }
    TS(10);
    {
      float s0 = 0.f, q0 = 0.f, e0 = 0.f, s1 = 0.f, q1 = 0.f, e1 = 0.f;
#pragma unroll
      for (int j = 0; j < 16; j++) {
        const float a = acc[j * 4], c = acc[j * 4 + 1], d = acc[j * 4 + 2], e = acc[j * 4 + 3];
        s0 += a + c; q0 = fmaf(a, a, fmaf(c, c, q0)); e0 = fmaf(a, wf[j * 2], fmaf(c, wf[j * 2 + 1], e0));
        s1 += d + e; q1 = fmaf(d, d, fmaf(e, e, q1)); e1 = fmaf(d, wf[j * 2], fmaf(e, wf[j * 2 + 1], e1));
      }
      const bool od = t & 1;
      float s = (od ? s1 : s0) + __shfl_xor_sync(~0u, od ? s0 : s1, 1);
      float q = (od ? q1 : q0) + __shfl_xor_sync(~0u, od ? q0 : q1, 1);
      float e = (od ? e1 : e0) + __shfl_xor_sync(~0u, od ? e0 : e1, 1);
      s += __shfl_xor_sync(~0u, s, 2); q += __shfl_xor_sync(~0u, q, 2); e += __shfl_xor_sync(~0u, e, 2);
      if (t < 2) red4(&P.s->st2[row0 + t * 8], s, q, e, 1.f);
    }
    TS(11);
    const uint32_t msc = sm + OFF_STATS;
    const uint32_t hst = sm + 4 * UNIT + wg * STAGE_B + warp * 4096, myslot = sm + unit_of(rank ? DT1 : DT0, wid);
    bar_sync(1, 256);
#pragma unroll
    for (int j = 0; j < 8; j++)
      stsm4(hst + (lane & 15) * 256 + (((2 * j + (lane >> 4)) ^ (lane & 7)) << 4), pack2(acc[j * 8], acc[j * 8 + 1]), pack2(acc[j * 8 + 2], acc[j * 8 + 3]),
            pack2(acc[j * 8 + 4], acc[j * 8 + 5]), pack2(acc[j * 8 + 6], acc[j * 8 + 7]));
    uint32_t wa[8][4][4], wd[8][2][4];
    const uint32_t a0 = sm + unit_of(rank ? GT1 : GT0, wid) + ((lane >> 4) * 8 + (lane & 7)) * 64 + ((((lane >> 3) & 1) ^ ((lane >> 1) & 3)) << 4);
    auto load_gu = [&](auto ic) { constexpr int i = decltype(ic)::value; ldsm4t_o<(i >> 2) * 1024 + ((i >> 1) & 1) * 8192>(a0 ^ ((i & 1) << 5), wa[i >> 2][i & 3]); };
    {
      const int row = mb3 * 64 + warp * 16 + (lane & 15);
      uint4 v;
#pragma unroll 1
      for (int it = 0;; it++) {
        v = ld_rlx4(&P.s->st2[row]);
        TSV(22, 1);
        if (!__any_sync(~0u, v.w != 0x41000000u)) break;
        SPINCHK(it, 6);
      }
      TS(12);
      const float sw = __uint_as_float((lds1(mb + B_SW) & ~255u) | 128);
      const float mean = __uint_as_float(v.x) * (1.f / D_);
      const float rstd = rsq(fmaxf(fmaf(-mean, mean, __uint_as_float(v.y) * (1.f / D_)), 0.f) + 1e-5f);
      const uint32_t u = __float_as_uint(rstd * fmaf(-mean, sw, __uint_as_float(v.z)));
      uint32_t k = min(((u ^ ((uint32_t)((int)u >> 31) | 0x80000000u)) & ~2047u), 0xFFFFF000u) | (2047 - row);
      uint32_t m1 = __reduce_max_sync(~0u, k), m2 = __reduce_max_sync(~0u, k == m1 ? 0 : k);
      if (lane < 16) sts2f(sm + OFF_LNP + (wid * 16 + lane) * 8, rstd, -mean * rstd);
      if (lane == 0) sts2f(msc + wid * 8, __uint_as_float(m1), __uint_as_float(m2));
      bar_sync(1, 256);
      k = lds1(msc + (lane & 15) * 4);
      m1 = __reduce_max_sync(~0u, k); m2 = __reduce_max_sync(~0u, k == m1 ? 0 : k);
      const int grp = rb * 2 + hf, c0 = 2047 - (m1 & 2047), c1 = 2047 - (m2 & 2047);
      if (tid == 0) {
        st_rlx2(&P.s->cand[c3 * 32 + grp * 2], m1, m2);
        sts2f(msc + 64, __uint_as_float(m1), __uint_as_float(m2));
        mbar_arrive(mb + B_OUT);
      }
      if ((c0 >> 4) == mb3 * 4 + warp || (c1 >> 4) == mb3 * 4 + warp) {
        const int ra = (lane & 4) ? c1 : c0, rd = (lane & 16) ? c1 : c0;
        uint32_t h0, h1, h2, h3;
        ldsm4_o<0>(hst + (ra & 15) * 256 + ((((lane & 3) * 4 + (lane >> 3)) ^ (ra & 7)) << 4), h0, h1, h2, h3);
        const float2 pr = lds2f(sm + OFF_LNP + (wid * 16 + (rd & 15)) * 8);
        if ((rd >> 4) == mb3 * 4 + warp) {
          uint4* d = &P.s->hsel[(grp * 2 + (lane >> 4)) * 256 + c3 * 32 + t * 4 + (g & 3)];
          st_rlx4(d, make_uint4(pack2(fmaf(bf_lo(h0), pr.x, pr.y), fmaf(bf_hi(h0), pr.x, pr.y)), pack2(fmaf(bf_lo(h1), pr.x, pr.y), fmaf(bf_hi(h1), pr.x, pr.y)),
                                pack2(fmaf(bf_lo(h2), pr.x, pr.y), fmaf(bf_hi(h2), pr.x, pr.y)), pack2(fmaf(bf_lo(h3), pr.x, pr.y), fmaf(bf_hi(h3), pr.x, pr.y))));
          st_rlx4(d + 16, make_uint4(h0, h1, h2, h3));
        }
      }
    }
    TS(13);
    if (fidx >= 0) mbar_wait(mb + B_FFN, 0);
    static_for<0, 32>(load_gu);
    const uint32_t da = myslot + ((lane >> 4) * 8 + (lane & 7)) * 128 + ((((lane >> 3) & 1) ^ (lane & 7)) << 4);
    mbar_wait(mb + B_SEL, 0);
    const uint4 sel = lds4(msc + 80);
    float gu[2][4][4];
    uint32_t fh = 0, fn = 0;
    const uint32_t* fq = (const uint32_t*)P.s->hsel + ((tid & 1) ? sel.w : sel.y) * 1024 + (b >> 4) * 128 + ((tid >> 2) & 3) * 16 + (b & 15);
    {
      uint4 xb[4];
      const uint4* xp = &P.s->hsel[((lane & 16) ? sel.w : sel.y) * 256 + wid * 32 + (lane & 15)];
      uint4 xv = ld_rlx4(xp);
      if (tid < 16) { fn = ld_rlx(fq); fh = ld_rlx(fq + 64); }
      if (fidx >= 0) mbar_wait(mb + B_FFD, 0);
      static_for<0, 8>([&](auto ic) { constexpr int i = decltype(ic)::value; ldsm4t_o<(i & 1) * 2048>(da ^ ((i >> 1) << 5), wd[i >> 1][i & 1]); });
#pragma unroll 1
      for (int it = 0; __any_sync(~0u, max4(0, xv) == SENT); it++) { xv = ld_rlx4(xp); SPINCHK(it, 7); }
      sts4(myslot + 2048 + ((lane & 3) * 8 + (lane >> 2)) * 16, xv.x, xv.y, xv.z, xv.w);
      __syncwarp();
#pragma unroll
      for (int i = 0; i < 4; i++) xb[i] = lds4(myslot + 2048 + (i * 8 + (lane & 7)) * 16);
      TS(14);
#pragma unroll
      for (int i = 0; i < 32; i++) gu[i >> 4][(i >> 2) & 3][i & 3] = 0.f;
#pragma unroll
      for (int ks = 0; ks < 8; ks++) {
#pragma unroll
        for (int i = 0; i < 4; i++) mma16816(gu[ks & 1][i], wa[ks][i], (ks & 1) ? xb[ks >> 1].z : xb[ks >> 1].x, (ks & 1) ? xb[ks >> 1].w : xb[ks >> 1].y);
        if (ks == 3) {
          uint32_t dd = da; asm volatile("" : "+r"(dd) : "f"(gu[0][0][0]));
          static_for<0, 8>([&](auto ic) { constexpr int i = decltype(ic)::value; ldsm4t_o<4096 + (i & 1) * 2048>(dd ^ ((i >> 1) << 5), wd[4 + (i >> 1)][i & 1]); });
        }
      }
    }
    {
      float o[4];
#pragma unroll
      for (int j = 0; j < 4; j++) {
        const float s0 = gu[0][0][j] + gu[1][0][j], s1 = gu[0][1][j] + gu[1][1][j], s2 = gu[0][2][j] + gu[1][2][j], s3 = gu[0][3][j] + gu[1][3][j];
        o[j] = t == 0 ? s0 : t == 1 ? s1 : t == 2 ? s2 : s3;
      }
      sts2f(myslot + 1024 + (t * 16 + g) * 8, o[0], o[1]);
      sts2f(myslot + 1024 + (t * 16 + g + 8) * 8, o[2], o[3]);
    }
    bar_sync(1, 256);
    {
      float g0 = 0.f, g1 = 0.f, u0 = 0.f, u1 = 0.f;
      static_for<0, 8>([&](auto wc) { constexpr int w = decltype(wc)::value;
        const float2 a = lds2f_o<sb + ((DT0 >> (5 * w)) & 31) * UNIT + 1024>(own + lane * 8 + (w < 4 ? 0 : w < 6 ? sk : -sk)), c = lds2f_o<sb + ((DT0 >> (5 * w)) & 31) * UNIT + 1280>(own + lane * 8 + (w < 4 ? 0 : w < 6 ? sk : -sk));
        g0 += a.x; g1 += a.y; u0 += c.x; u1 += c.y; });
      const uint32_t act = pack2(g0 * rcp(1.f + ex2(-1.4426950408889634f * g0)) * u0, g1 * rcp(1.f + ex2(-1.4426950408889634f * g1)) * u1);
      uint32_t bq[4];
#pragma unroll
      for (int i = 0; i < 4; i++) {
        const uint32_t lo = __shfl_sync(~0u, act, i * 8 + 2 * t), hi = __shfl_sync(~0u, act, i * 8 + 2 * t + 1);
        bq[i] = __byte_perm(lo, hi, (g & 1) ? 0x7632 : 0x5410);
      }
      TS(16);
      float ya[8][4];
#pragma unroll
      for (int i = 0; i < 8; i++) { ya[i][0] = 0.f; ya[i][1] = 0.f; ya[i][2] = 0.f; ya[i][3] = 0.f; }
#pragma unroll
      for (int ks = 0; ks < 2; ks++)
#pragma unroll
        for (int i = 0; i < 8; i++) mma16816(ya[i], wd[i][ks], bq[ks * 2], bq[ks * 2 + 1]);
      if (fidx >= 0) {
        uint2* yp = (uint2*)&P.s->ybuf[((wid * 16 + t * 2) * NFFN + fidx) * 4] + g;
#pragma unroll
        for (int h = 0; h < 2; h++) {
          float o[4];
#pragma unroll
          for (int j = 0; j < 4; j++) o[j] = t == 0 ? ya[h * 4][j] : t == 1 ? ya[h * 4 + 1][j] : t == 2 ? ya[h * 4 + 2][j] : ya[h * 4 + 3][j];
          st_rlx2(yp + h * (8 * NFFN * 8), __float_as_uint(o[0]), __float_as_uint(o[1]));
          st_rlx2(yp + h * (8 * NFFN * 8) + NFFN * 8, __float_as_uint(o[2]), __float_as_uint(o[3]));
        }
      }
    }
    TS(17);
    const long long ty = clock64();
    {
      while (clock64() - ty < YDELAY) {}
      uint4 v0, v1 = make_uint4(0, 0, 0, 0);
#pragma unroll 1
      for (int it = 0;; it++) {
        v0 = ld_rlx4(&P.s->ybuf[b * NFFN * 4 + tid]);
        if (tid < 192) v1 = ld_rlx4(&P.s->ybuf[b * NFFN * 4 + 256 + tid]);
        if (!__any_sync(~0u, max(max4(0, v0), max4(0, v1)) == SENT)) break;
        SPINCHK(it, 8);
      }
      TS(18);
      float y0 = __uint_as_float(v0.x) + __uint_as_float(v1.x), y1 = __uint_as_float(v0.y) + __uint_as_float(v1.y);
      float y2 = __uint_as_float(v0.z) + __uint_as_float(v1.z), y3 = __uint_as_float(v0.w) + __uint_as_float(v1.w);
      float z0 = ((lane & 16) ? y2 : y0) + __shfl_xor_sync(~0u, (lane & 16) ? y0 : y2, 16), z1 = ((lane & 16) ? y3 : y1) + __shfl_xor_sync(~0u, (lane & 16) ? y1 : y3, 16);
      z0 = ((lane & 8) ? z1 : z0) + __shfl_xor_sync(~0u, (lane & 8) ? z0 : z1, 8);
      z0 += __shfl_xor_sync(~0u, z0, 4);
      const uint32_t yx = msc + 128;
      if (!(lane & 4)) sts1(yx + wid * 64 + (t * 4 + (lane >> 3)) * 4, __float_as_uint(z0));
      bar_sync(1, 256);
      if (tid < 16) {
        float y = 0.f;
#pragma unroll
        for (int w = 0; w < 8; w++) y += __uint_as_float(lds1(yx + w * 64 + tid * 4));
        for (int it = 0; max(fn, fh) == SENT; it++) { fn = ld_rlx(fq); fh = ld_rlx(fq + 64); SPINCHK(it, 9); }
        const uint32_t key = (tid & 1) ? sel.z : sel.x;
        const float r = __uint_as_float(key ^ (~(uint32_t)((int)key >> 31) | 0x80000000u));
        const float base = (tid & 2) ? bf_hi(fh) + bf_hi(fn) : bf_lo(fh) + bf_lo(fn);
        P.out[(size_t)(2047 - (key & 2047)) * D_ + b * 8 + (tid >> 1)] = __float2bfloat16(fmaf(y, rcp(1.f + ex2(-1.4426950408889634f * r)), base));
      }
      if (b == 0 && tid == 32) P.s->epoch = lds1(mb + B_SW) & 255;
    }
    TS(19); TSG(31);
    if (warp == 0) TS_DUMP(wg);
   }
  }
}

typedef CUresult (*EncodeFn)(CUtensorMap*, CUtensorMapDataType, cuuint32_t, void*, const cuuint64_t*, const cuuint64_t*, const cuuint32_t*,
                             const cuuint32_t*, CUtensorMapInterleave, CUtensorMapSwizzle, CUtensorMapL2promotion, CUtensorMapFloatOOBfill);
void make_map(EncodeFn enc, CUtensorMap* m, const void* p, int rank, std::initializer_list<cuuint64_t> dims, std::initializer_list<cuuint64_t> str,
              std::initializer_list<cuuint32_t> box, CUtensorMapSwizzle sw) {
  const cuuint32_t es[4] = {1, 1, 1, 1};
  enc(m, CU_TENSOR_MAP_DATA_TYPE_BFLOAT16, rank, const_cast<void*>(p), dims.begin(), str.begin(), box.begin(), es, CU_TENSOR_MAP_INTERLEAVE_NONE, sw,
      CU_TENSOR_MAP_L2_PROMOTION_L2_128B, CU_TENSOR_MAP_FLOAT_OOB_FILL_NONE);
}

}

extern "C" void kernel_launch(void* const* d_in, const int* in_sizes, int n_in, void* d_out, int out_size) {
  (void)in_sizes; (void)n_in; (void)out_size;
  Ptrs P;
  P.x = (const __nv_bfloat16*)d_in[0]; P.wqkv = (const __nv_bfloat16*)d_in[1]; P.wo = (const __nv_bfloat16*)d_in[2];
  P.wr = (const __nv_bfloat16*)d_in[4]; P.wg = (const __nv_bfloat16*)d_in[5]; P.wu = (const __nv_bfloat16*)d_in[6];
  P.wd = (const __nv_bfloat16*)d_in[7]; P.out = (__nv_bfloat16*)d_out;
  cudaGetSymbolAddress((void**)&P.s, g_scratch);
  void* fn = nullptr;
  cudaDriverEntryPointQueryResult q;
  cudaGetDriverEntryPoint("cuTensorMapEncodeTiled", &fn, cudaEnableDefault, &q);
  EncodeFn enc = (EncodeFn)fn;
  Maps T;
  constexpr CUtensorMapSwizzle S128 = CU_TENSOR_MAP_SWIZZLE_128B, S64 = CU_TENSOR_MAP_SWIZZLE_64B;
  make_map(enc, &T.m[M_X], P.x, 2, {D_, S_}, {D_ * 2}, {64, 128}, S128);
  make_map(enc, &T.m[M_W], P.wqkv, 3, {D_, D_, 3}, {3 * D_ * 2, D_ * 2}, {64, 64, 2}, S128);
  make_map(enc, &T.m[M_Q], P.wqkv, 2, {3 * D_, D_}, {3 * D_ * 2}, {64, 64}, S128);
  make_map(enc, &T.m[M_O], P.wo, 4, {64, 64, 16, 16}, {D_ * 2, 64 * D_ * 2, 128}, {64, 64, 1, 2}, S128);
  make_map(enc, &T.m[M_S], P.wo, 4, {64, 64, 16, 16}, {D_ * 2, 64 * D_ * 2, 128}, {64, 16, 4, 2}, S128);
  make_map(enc, &T.m[M_G], P.wg, 3, {F_, D_, 1}, {F_ * 2, F_ * 2 * D_}, {32, 128, 1}, S64);
  make_map(enc, &T.m[M_U], P.wu, 3, {F_, D_, 1}, {F_ * 2, F_ * 2 * D_}, {32, 128, 1}, S64);
  make_map(enc, &T.m[M_D], P.wd, 3, {64, F_, 16}, {D_ * 2, 128}, {64, 32, 2}, S128);
  make_map(enc, &T.m[M_L], P.wd, 2, {64, F_ * 16}, {128}, {8, 16}, CU_TENSOR_MAP_SWIZZLE_NONE);
  cudaFuncSetAttribute(fused_kernel, cudaFuncAttributeMaxDynamicSharedMemorySize, SMEM_BYTES);
  fused_kernel<<<NCTA, 384, SMEM_BYTES>>>(P, T);
}
```

```cpp
#include <cuda_runtime.h>
#include <cuda.h>
#include <cuda_bf16.h>
#include <stdint.h>
#include <type_traits>
#include <initializer_list>

namespace {

constexpr int S_ = 2048, D_ = 1024, F_ = 3584;
constexpr int NCTA = 128, NFFN = 112;
constexpr uint32_t SENT = 0xFFFFFFFFu;
constexpr int SPIN_LIMIT = 1 << 20;

#define ADELAY 0
#define ADELAY2 100
#define PFA 6
#define PF0 8
#define WPF0 8
#define DPER 1200
#define PDEPTH 2
#define PSTART 4000
#define PPER 1700
#define PEARLY 5
#define PLEAD 0
#define RST 1
#define PSUB 2
#define HOLDP 1
#define QHOLD 1
#define NPULL 12
#define CDELAY 0
#define NOUTW 3
#define YDELAY 500
#define EFX 0
#define EFW 1
#define EFF 1
#define KLEAD 13
#define GDELAY 1000
#define NDIR 6
#define PULL0 5
#define FD0 400
#define FD1 800
#define SPF 1
#define MPF 1
#define TLBW 2
#define GORD 0
#define GSPLIT 2
#define EFW0 0
#define EFX0 0
#define EFWK 8
#define PSLEEP 20
#define P3PULL 1
#define RST2 4
#define KDELAY 450
#define AEARLY 1
#define BHOLD 4
#define SDELAY 150
#define FSTAG 150
#define OFL 0
#define CHKF 1
#define BEV 1
#define DLATE 4
#define P3GATE 3
#define ACCSW 1
#define B45 (B_BF + 8)
#define SDEL2 500
#define XDELAY 800
#define GU1 8
#define GU2 20
#define WD1 10
#define PSTOP 3
#define DMASK 0x5550
#define PFST 1
#define W0OFF 2
#define MAPM 2
#define XWPF 0
constexpr uint32_t STAGE_B = 57344;
constexpr uint32_t OFF_STATS = 229376;
constexpr uint32_t OFF_COLSUM = 231424;
constexpr uint32_t OFF_BARS = 232192;
constexpr uint32_t SMEM_BYTES = 232448;
constexpr uint32_t B_FULL = 0, B_EMPTY = 32, B_E = 64, B_AUX = 128, B_EVA = 136, B_EVB = 144, B_BF = 152, B_LATE = 232, B_FFN = 240, B_SW = 248;
constexpr uint32_t B_OUT = B_FULL, B_SEL = B_FULL + 8, B_WR = B_FULL + 16, B_FFD = B_FULL + 24, B_E16 = B_EMPTY + 16, B_KVB = B_EMPTY + 8, B_DUMMY = B_SW + 4,
                   B_GATE = B_EMPTY + 24, B_ID = B_BF + 56, B_KVP = B_BF + 64, B_F15 = B_BF + 72;
#define B_HOLD B_F15
#define HOLDPAR 0
constexpr uint32_t UNIT = 8192;
constexpr uint32_t sb = 1024;
constexpr uint32_t bars = sb + OFF_BARS;
constexpr uint64_t tab5(int a, int b, int c, int d, int e, int f, int g, int h, int i = 0, int j = 0) {
  return (uint64_t)a | (uint64_t)b << 5 | (uint64_t)c << 10 | (uint64_t)d << 15 | (uint64_t)e << 20 | (uint64_t)f << 25 | (uint64_t)g << 30 | (uint64_t)h << 35 |
         (uint64_t)i << 40 | (uint64_t)j << 45;
}
constexpr uint64_t BT0 = tab5(4, 11, 18, 25, 7, 9, 16, 0), BT1 = tab5(4, 11, 18, 25, 21, 23, 2, 0);
constexpr uint64_t GT0 = tab5(2, 21, 23, 18, 0, 25, 14, 7), GT1 = tab5(16, 7, 9, 18, 0, 25, 14, 21);
constexpr uint64_t DT0 = tab5(6, 13, 20, 27, 9, 10, 16, 17), DT1 = tab5(6, 13, 20, 27, 23, 24, 2, 3);
__device__ __forceinline__ uint32_t unit_of(uint64_t tab, int i) { return ((uint32_t)(tab >> (5 * i)) & 31) * UNIT; }
__device__ __forceinline__ uint32_t ring_of(int p, int w) { return (p & 1) * (2 * STAGE_B) + ((p & 2) ? 49152 + w * STAGE_B : w * UNIT); }
constexpr uint32_t OFF_LNP = OFF_STATS + 1024;

struct Scratch {
  uint4 obuf[32 * 64 * 128];
  uint4 kvp[16 * 8 * 256];
  uint4 zp[16 * 8 * 16];
  uint4 ybuf[NCTA * NFFN * 2];
  uint4 st1[S_];
  uint4 csp[16 * 8 * 48];
  uint4 st2[S_];
  uint4 hsel[2 * 8 * 128];
  uint32_t cand[8 * 32];
  uint32_t ocnt[16 * 32];
  unsigned epoch;
};
__device__ __align__(1024) Scratch g_scratch;
#define TS_DECL
#define TS(i)
#define TSG(i)
#define TSV(i, v)
#define TSD(i)
#define RTS_DECL
#define RTS(i)
#define RTS_DUMP
#define TS_DUMP(slot)
#define PTS(i)
#define g_dbgv(i, v)

__device__ __forceinline__ uint32_t smem_u32(const void* p) { return (uint32_t)__cvta_generic_to_shared(p); }
__device__ __forceinline__ void mbar_init(uint32_t bar, uint32_t cnt) { asm volatile("mbarrier.init.shared::cta.b64 [%0], %1;" :: "r"(bar), "r"(cnt) : "memory"); }
__device__ __forceinline__ void mbar_expect_tx(uint32_t bar, uint32_t bytes) { asm volatile("mbarrier.arrive.expect_tx.shared::cta.b64 _, [%0], %1;" :: "r"(bar), "r"(bytes) : "memory"); }
__device__ __forceinline__ void mbar_arrive(uint32_t bar) { asm volatile("mbarrier.arrive.shared::cta.b64 _, [%0];" :: "r"(bar) : "memory"); }
#define SPINCHK(it, code) if ((it) > SPIN_LIMIT) break
__device__ __forceinline__ void mbar_wait(uint32_t bar, uint32_t parity) {
  asm volatile("{\n.reg .pred p;\n.reg .u32 c;\nmov.u32 c, 0;\n"
               "WL:\nmbarrier.try_wait.parity.shared::cta.b64 p, [%0], %1;\n@p bra WD;\n"
               "add.u32 c, c, 1;\nsetp.lt.u32 p, c, 1048576;\n@p bra WL;\nWD:\n}" :: "r"(bar), "r"(parity) : "memory");
}
__device__ __forceinline__ bool mbar_test(uint32_t bar, uint32_t parity) {
  uint32_t ok;
  asm volatile("{\n.reg .pred p;\nmbarrier.test_wait.parity.shared::cta.b64 p, [%1], %2;\nselp.u32 %0, 1, 0, p;\n}" : "=r"(ok) : "r"(bar), "r"(parity) : "memory");
  return ok;
}
__device__ __forceinline__ uint64_t l2_stream() { uint64_t p; asm("createpolicy.fractional.L2::evict_first.b64 %0, 1.0;" : "=l"(p)); return p; }
__device__ __forceinline__ void tma_2d(uint32_t dst, const CUtensorMap* tm, int c0, int c1, uint32_t bar, bool stream) {
  if (stream) asm volatile("cp.async.bulk.tensor.2d.shared::cluster.global.mbarrier::complete_tx::bytes.L2::cache_hint [%0], [%1, {%3, %4}], [%2], %5;"
                           :: "r"(dst), "l"(tm), "r"(bar), "r"(c0), "r"(c1), "l"(l2_stream()) : "memory");
  else asm volatile("cp.async.bulk.tensor.2d.shared::cluster.global.mbarrier::complete_tx::bytes [%0], [%1, {%3, %4}], [%2];"
                    :: "r"(dst), "l"(tm), "r"(bar), "r"(c0), "r"(c1) : "memory");
}
__device__ __forceinline__ void tma_3d(uint32_t dst, const CUtensorMap* tm, int c0, int c1, int c2, uint32_t bar, bool stream) {
  if (stream) asm volatile("cp.async.bulk.tensor.3d.shared::cluster.global.mbarrier::complete_tx::bytes.L2::cache_hint [%0], [%1, {%3, %4, %5}], [%2], %6;"
                           :: "r"(dst), "l"(tm), "r"(bar), "r"(c0), "r"(c1), "r"(c2), "l"(l2_stream()) : "memory");
  else asm volatile("cp.async.bulk.tensor.3d.shared::cluster.global.mbarrier::complete_tx::bytes [%0], [%1, {%3, %4, %5}], [%2];"
                    :: "r"(dst), "l"(tm), "r"(bar), "r"(c0), "r"(c1), "r"(c2) : "memory");
}
__device__ __forceinline__ void tma_pf_3d(const CUtensorMap* tm, int c0, int c1, int c2) {
  asm volatile("cp.async.bulk.prefetch.tensor.3d.L2.global [%0, {%1, %2, %3}];" :: "l"(tm), "r"(c0), "r"(c1), "r"(c2) : "memory");
}
__device__ __forceinline__ void tma_4d(uint32_t dst, const CUtensorMap* tm, int c0, int c1, int c2, int c3, uint32_t bar) {
  asm volatile("cp.async.bulk.tensor.4d.shared::cluster.global.mbarrier::complete_tx::bytes [%0], [%1, {%3, %4, %5, %6}], [%2];"
               :: "r"(dst), "l"(tm), "r"(bar), "r"(c0), "r"(c1), "r"(c2), "r"(c3) : "memory");
}
__device__ __forceinline__ void tma_2d_mc(uint32_t dst, const CUtensorMap* tm, int c0, int c1, uint32_t bar, bool stream) {
  if (stream) asm volatile("cp.async.bulk.tensor.2d.shared::cluster.global.mbarrier::complete_tx::bytes.multicast::cluster.L2::cache_hint [%0], [%1, {%3, %4}], [%2], %5, %6;"
                           :: "r"(dst), "l"(tm), "r"(bar), "r"(c0), "r"(c1), "h"((uint16_t)3), "l"(l2_stream()) : "memory");
  else asm volatile("cp.async.bulk.tensor.2d.shared::cluster.global.mbarrier::complete_tx::bytes.multicast::cluster [%0], [%1, {%3, %4}], [%2], %5;"
                    :: "r"(dst), "l"(tm), "r"(bar), "r"(c0), "r"(c1), "h"((uint16_t)3) : "memory");
}
__device__ __forceinline__ bool elect_one() {
  uint32_t p;
  asm volatile("{\n.reg .pred q;\nelect.sync _|q, 0xFFFFFFFF;\nselp.u32 %0, 1, 0, q;\n}" : "=r"(p));
  return p;
}
__device__ __forceinline__ void bulk_load_mc(uint32_t dst, const void* src, uint32_t bytes, uint32_t bar) {
  asm volatile("cp.async.bulk.shared::cluster.global.mbarrier::complete_tx::bytes.multicast::cluster [%0], [%1], %2, [%3], %4;"
               :: "r"(dst), "l"(src), "r"(bytes), "r"(bar), "h"((uint16_t)3) : "memory");
}
__device__ __forceinline__ void bulk_load(uint32_t dst, const void* src, uint32_t bytes, uint32_t bar) {
  asm volatile("cp.async.bulk.shared::cluster.global.mbarrier::complete_tx::bytes [%0], [%1], %2, [%3];" :: "r"(dst), "l"(src), "r"(bytes), "r"(bar) : "memory");
}
__device__ __forceinline__ void bulk_store(void* dst, uint32_t src, uint32_t bytes) {
  asm volatile("cp.async.bulk.global.shared::cta.bulk_group [%0], [%1], %2;" :: "l"(dst), "r"(src), "r"(bytes) : "memory");
}
__device__ __forceinline__ void mbar_arrive_rem(uint32_t bar) { asm volatile("mbarrier.arrive.shared::cluster.b64 _, [%0];" :: "r"(bar) : "memory"); }
__device__ __forceinline__ void st_async4(uint32_t addr, const uint4& v, uint32_t bar) {
  asm volatile("st.async.shared::cluster.mbarrier::complete_tx::bytes.v4.b32 [%0], {%1,%2,%3,%4}, [%5];" :: "r"(addr), "r"(v.x), "r"(v.y), "r"(v.z), "r"(v.w), "r"(bar) : "memory");
}
template <uint32_t O> __device__ __forceinline__ void ldsm4_o(uint32_t addr, uint32_t& a, uint32_t& b, uint32_t& c, uint32_t& d) {
  asm volatile("ldmatrix.sync.aligned.m8n8.x4.shared.b16 {%0,%1,%2,%3}, [%4+%5];" : "=r"(a), "=r"(b), "=r"(c), "=r"(d) : "r"(addr), "n"(O) : "memory");
}
template <uint32_t O> __device__ __forceinline__ void ldsm4t_o(uint32_t addr, uint32_t (&r)[4]) {
  asm volatile("ldmatrix.sync.aligned.m8n8.x4.trans.shared.b16 {%0,%1,%2,%3}, [%4+%5];" : "=r"(r[0]), "=r"(r[1]), "=r"(r[2]), "=r"(r[3]) : "r"(addr), "n"(O) : "memory");
}
__device__ __forceinline__ void mma16816(float (&c)[4], const uint32_t (&a)[4], uint32_t b0, uint32_t b1) {
  asm("mma.sync.aligned.m16n8k16.row.col.f32.bf16.bf16.f32 {%0,%1,%2,%3}, {%4,%5,%6,%7}, {%8,%9}, {%0,%1,%2,%3};"
      : "+f"(c[0]), "+f"(c[1]), "+f"(c[2]), "+f"(c[3]) : "r"(a[0]), "r"(a[1]), "r"(a[2]), "r"(a[3]), "r"(b0), "r"(b1));
}
__device__ __forceinline__ void l2_prefetch(const void* p) { asm volatile("prefetch.global.L2 [%0];" :: "l"(p) : "memory"); }
__device__ __forceinline__ uint32_t ld_line(const void* p) { uint32_t v; asm volatile("ld.global.cg.L2::128B.u32 %0, [%1];" : "=r"(v) : "l"(p) : "memory"); return v; }
__device__ __forceinline__ void tmap_prefetch(const CUtensorMap* tm) { asm volatile("prefetch.tensormap [%0];" :: "l"(tm) : "memory"); }
__device__ __forceinline__ void wg_fence() { asm volatile("wgmma.fence.sync.aligned;" ::: "memory"); }
__device__ __forceinline__ void wg_commit() { asm volatile("wgmma.commit_group.sync.aligned;" ::: "memory"); }
template <int N> __device__ __forceinline__ void wg_wait() { asm volatile("wgmma.wait_group.sync.aligned %0;" :: "n"(N) : "memory"); }
template <int N> __device__ __forceinline__ void pin(float (&d)[N]) {
#pragma unroll
  for (int i = 0; i < N; i++) asm volatile("" : "+f"(d[i]) :: "memory");
}
__device__ __forceinline__ void pin4(uint4& v) { asm volatile("" : "+r"(v.x), "+r"(v.y), "+r"(v.z), "+r"(v.w) :: "memory"); }
template <uint32_t SBO, uint32_t SWZ> __device__ __forceinline__ uint64_t dsc(uint32_t lo) { return ((uint64_t)((SBO >> 4) | (SWZ << 30)) << 32) | lo; }
__host__ __device__ constexpr uint32_t dlo(uint32_t addr, uint32_t lbo) { return (addr >> 4) | ((lbo >> 4) << 16); }
__device__ __forceinline__ void bar_sync(int id, int n) { asm volatile("bar.sync %0, %1;" :: "r"(id), "r"(n) : "memory"); }
__device__ __forceinline__ void bar_arrive(int id, int n) { asm volatile("bar.arrive %0, %1;" :: "r"(id), "r"(n) : "memory"); }
__device__ __forceinline__ void fence_async_smem() { asm volatile("fence.proxy.async.shared::cta;" ::: "memory"); }
__device__ __forceinline__ void fence_gpu() { asm volatile("fence.acq_rel.gpu;" ::: "memory"); }
__device__ __forceinline__ uint4 ld_cg4(const void* p) { uint4 v; asm volatile("ld.global.cg.v4.u32 {%0,%1,%2,%3}, [%4];" : "=r"(v.x), "=r"(v.y), "=r"(v.z), "=r"(v.w) : "l"(p) : "memory"); return v; }
__device__ __forceinline__ uint4 ld_rlx4(const void* p) { uint4 v; asm volatile("ld.relaxed.gpu.global.v4.u32 {%0,%1,%2,%3}, [%4];" : "=r"(v.x), "=r"(v.y), "=r"(v.z), "=r"(v.w) : "l"(p) : "memory"); return v; }
__device__ __forceinline__ uint32_t ld_rlx(const void* p) { uint32_t v; asm volatile("ld.relaxed.gpu.global.u32 %0, [%1];" : "=r"(v) : "l"(p) : "memory"); return v; }
__device__ __forceinline__ void st_rlx4(void* p, uint4 v) { asm volatile("st.relaxed.gpu.global.v4.u32 [%0], {%1,%2,%3,%4};" :: "l"(p), "r"(v.x), "r"(v.y), "r"(v.z), "r"(v.w) : "memory"); }
__device__ __forceinline__ void st_rlx2(void* p, uint32_t a, uint32_t b) { asm volatile("st.relaxed.gpu.global.v2.u32 [%0], {%1,%2};" :: "l"(p), "r"(a), "r"(b) : "memory"); }
__device__ __forceinline__ void st_rlx(void* p, uint32_t a) { asm volatile("st.relaxed.gpu.global.u32 [%0], %1;" :: "l"(p), "r"(a) : "memory"); }
__device__ __forceinline__ void red4(void* p, float a, float b, float c, float d) { asm volatile("red.relaxed.gpu.global.add.v4.f32 [%0], {%1,%2,%3,%4};" :: "l"(p), "f"(a), "f"(b), "f"(c), "f"(d) : "memory"); }
__device__ __forceinline__ uint32_t pack2(float lo, float hi) { uint32_t r; asm("cvt.rn.bf16x2.f32 %0, %1, %2;" : "=r"(r) : "f"(hi), "f"(lo)); return r; }
__device__ __forceinline__ float bf_lo(uint32_t v) { return __uint_as_float(v << 16); }
__device__ __forceinline__ float bf_hi(uint32_t v) { return __uint_as_float(v & 0xFFFF0000u); }
__device__ __forceinline__ void stsm4(uint32_t addr, uint32_t a, uint32_t b, uint32_t c, uint32_t d) {
  asm volatile("stmatrix.sync.aligned.m8n8.x4.shared.b16 [%0], {%1,%2,%3,%4};" :: "r"(addr), "r"(a), "r"(b), "r"(c), "r"(d) : "memory");
}
template <uint32_t O> __device__ __forceinline__ void stsm4_o(uint32_t addr, uint32_t a, uint32_t b, uint32_t c, uint32_t d) {
  asm volatile("stmatrix.sync.aligned.m8n8.x4.shared.b16 [%0+%5], {%1,%2,%3,%4};" :: "r"(addr), "r"(a), "r"(b), "r"(c), "r"(d), "n"(O) : "memory");
}
__device__ __forceinline__ void sts4(uint32_t addr, uint32_t a, uint32_t b, uint32_t c, uint32_t d) { asm volatile("st.shared.v4.u32 [%0], {%1,%2,%3,%4};" :: "r"(addr), "r"(a), "r"(b), "r"(c), "r"(d) : "memory"); }
__device__ __forceinline__ void sts2f(uint32_t addr, float a, float b) { asm volatile("st.shared.v2.f32 [%0], {%1,%2};" :: "r"(addr), "f"(a), "f"(b) : "memory"); }
__device__ __forceinline__ void sts1(uint32_t addr, uint32_t a) { asm volatile("st.shared.u32 [%0], %1;" :: "r"(addr), "r"(a) : "memory"); }
__device__ __forceinline__ float2 lds2f(uint32_t addr) { float2 v; asm volatile("ld.shared.v2.f32 {%0,%1}, [%2];" : "=f"(v.x), "=f"(v.y) : "r"(addr) : "memory"); return v; }
template <uint32_t O> __device__ __forceinline__ float2 lds2f_o(uint32_t addr) { float2 v; asm volatile("ld.shared.v2.f32 {%0,%1}, [%2+%3];" : "=f"(v.x), "=f"(v.y) : "r"(addr), "n"(O) : "memory"); return v; }
template <int I, int N, class F> __device__ __forceinline__ void static_for(F&& f) { if constexpr (I < N) { f(std::integral_constant<int, I>{}); static_for<I + 1, N>(f); } }
__device__ __forceinline__ uint4 lds4(uint32_t addr) { uint4 v; asm volatile("ld.shared.v4.u32 {%0,%1,%2,%3}, [%4];" : "=r"(v.x), "=r"(v.y), "=r"(v.z), "=r"(v.w) : "r"(addr) : "memory"); return v; }
__device__ __forceinline__ uint32_t lds1(uint32_t addr) { uint32_t v; asm volatile("ld.shared.u32 %0, [%1];" : "=r"(v) : "r"(addr) : "memory"); return v; }
__device__ __forceinline__ float ex2(float x) { float y; asm("ex2.approx.ftz.f32 %0, %1;" : "=f"(y) : "f"(x)); return y; }
__device__ __forceinline__ uint32_t max4(uint32_t m, const uint4& v) { return __vimax3_u32(__vimax3_u32(m, v.x, v.y), v.z, v.w); }
__device__ __forceinline__ float rsq(float x) { float y; asm("rsqrt.approx.ftz.f32 %0, %1;" : "=f"(y) : "f"(x)); return y; }
__device__ __forceinline__ float rcp(float x) { float y; asm("rcp.approx.ftz.f32 %0, %1;" : "=f"(y) : "f"(x)); return y; }
__device__ __forceinline__ uint2 ld_rlx2(const void* p) { uint2 v; asm volatile("ld.relaxed.gpu.global.v2.u32 {%0,%1}, [%2];" : "=r"(v.x), "=r"(v.y) : "l"(p) : "memory"); return v; }
template <uint32_t O> __device__ __forceinline__ uint4 lds4_o(uint32_t addr) { uint4 v; asm volatile("ld.shared.v4.u32 {%0,%1,%2,%3}, [%4+%5];" : "=r"(v.x), "=r"(v.y), "=r"(v.z), "=r"(v.w) : "r"(addr), "n"(O) : "memory"); return v; }
__device__ __forceinline__ uint32_t phi2(float u0, float u1, float rl, uint32_t r2) {
  uint32_t pu, r;
  asm("cvt.rn.relu.bf16x2.f32 %0, %1, %2;" : "=r"(pu) : "f"(u1), "f"(u0));
  asm("fma.rn.bf16x2 %0, %1, %2, %3;" : "=r"(r) : "r"(pu), "r"(r2), "r"(pack2(__saturatef(ex2(u0 * rl) + 1e-6f), __saturatef(ex2(u1 * rl) + 1e-6f))));
  return r;
}
__device__ __forceinline__ uint32_t dup2(float r) { uint32_t v; asm("cvt.rn.relu.bf16x2.f32 %0, %1, %1;" : "=r"(v) : "f"(r)); return v; }
__device__ __forceinline__ uint32_t zero_after(const uint32_t (&v)[16]) {
  uint32_t z = 0;
#pragma unroll
  for (int i = 0; i < 16; i++) z |= v[i];
  return z & 0x80008000u;
}
__device__ __forceinline__ uint32_t hadd2(uint32_t a, uint32_t b) { uint32_t v; asm("add.rn.bf16x2 %0, %1, %2;" : "=r"(v) : "r"(a), "r"(b)); return v; }
__device__ __forceinline__ void sched_fence() { asm volatile("{\n.reg .pred p;\n.reg .u64 c;\nSF:\nmov.u64 c, %clock64;\nsetp.eq.u64 p, c, 0;\n@p bra SF;\n}" ::: "memory"); }
__device__ __forceinline__ uint4 ld_gen4(const void* p) { uint4 v; asm volatile("ld.relaxed.gpu.v4.u32 {%0,%1,%2,%3}, [%4];" : "=r"(v.x), "=r"(v.y), "=r"(v.z), "=r"(v.w) : "l"(p) : "memory"); return v; }
__device__ __forceinline__ uint2 ld_gen2(const void* p) { uint2 v; asm volatile("ld.relaxed.gpu.v2.u32 {%0,%1}, [%2];" : "=r"(v.x), "=r"(v.y) : "l"(p) : "memory"); return v; }
__device__ __forceinline__ uint32_t lane_id() { uint32_t v; asm volatile("mov.u32 %0, %%laneid;" : "=r"(v)); return v; }
template <int A, int B, int N> __device__ __forceinline__ void pinr(float (&d)[N]) {
#pragma unroll
  for (int i = A; i < B; i++) asm volatile("" : "+f"(d[i]) :: "memory");
}
template <int N> __device__ __forceinline__ void pinu(uint32_t (&d)[N]) {
#pragma unroll
  for (int i = 0; i < N; i++) asm volatile("" : "+r"(d[i]) :: "memory");
}

template<int TA, int TB, int OFF, int SZ> __device__ __forceinline__ void wgmma_n192_ss(float (&d)[SZ], uint64_t da, uint64_t db, int scale_d) {
  asm volatile("{\n.reg .pred p;\nsetp.ne.b32 p, %98, 0;\n"
    "wgmma.mma_async.sync.aligned.m64n192k16.f32.bf16.bf16 {%0,%1,%2,%3,%4,%5,%6,%7,%8,%9,%10,%11,%12,%13,%14,%15,%16,%17,%18,%19,%20,%21,%22,%23,%24,%25,%26,%27,%28,%29,%30,%31,%32,%33,%34,%35,%36,%37,%38,%39,%40,%41,%42,%43,%44,%45,%46,%47,%48,%49,%50,%51,%52,%53,%54,%55,%56,%57,%58,%59,%60,%61,%62,%63,%64,%65,%66,%67,%68,%69,%70,%71,%72,%73,%74,%75,%76,%77,%78,%79,%80,%81,%82,%83,%84,%85,%86,%87,%88,%89,%90,%91,%92,%93,%94,%95}, %96, %97, p, 1, 1, %99, %100;\n}\n"
    : "+f"(d[OFF+0]), "+f"(d[OFF+1]), "+f"(d[OFF+2]), "+f"(d[OFF+3]), "+f"(d[OFF+4]), "+f"(d[OFF+5]), "+f"(d[OFF+6]), "+f"(d[OFF+7]),
      "+f"(d[OFF+8]), "+f"(d[OFF+9]), "+f"(d[OFF+10]), "+f"(d[OFF+11]), "+f"(d[OFF+12]), "+f"(d[OFF+13]), "+f"(d[OFF+14]), "+f"(d[OFF+15]),
      "+f"(d[OFF+16]), "+f"(d[OFF+17]), "+f"(d[OFF+18]), "+f"(d[OFF+19]), "+f"(d[OFF+20]), "+f"(d[OFF+21]), "+f"(d[OFF+22]), "+f"(d[OFF+23]),
      "+f"(d[OFF+24]), "+f"(d[OFF+25]), "+f"(d[OFF+26]), "+f"(d[OFF+27]), "+f"(d[OFF+28]), "+f"(d[OFF+29]), "+f"(d[OFF+30]), "+f"(d[OFF+31]),
      "+f"(d[OFF+32]), "+f"(d[OFF+33]), "+f"(d[OFF+34]), "+f"(d[OFF+35]), "+f"(d[OFF+36]), "+f"(d[OFF+37]), "+f"(d[OFF+38]), "+f"(d[OFF+39]),
      "+f"(d[OFF+40]), "+f"(d[OFF+41]), "+f"(d[OFF+42]), "+f"(d[OFF+43]), "+f"(d[OFF+44]), "+f"(d[OFF+45]), "+f"(d[OFF+46]), "+f"(d[OFF+47]),
      "+f"(d[OFF+48]), "+f"(d[OFF+49]), "+f"(d[OFF+50]), "+f"(d[OFF+51]), "+f"(d[OFF+52]), "+f"(d[OFF+53]), "+f"(d[OFF+54]), "+f"(d[OFF+55]),
      "+f"(d[OFF+56]), "+f"(d[OFF+57]), "+f"(d[OFF+58]), "+f"(d[OFF+59]), "+f"(d[OFF+60]), "+f"(d[OFF+61]), "+f"(d[OFF+62]), "+f"(d[OFF+63]),
      "+f"(d[OFF+64]), "+f"(d[OFF+65]), "+f"(d[OFF+66]), "+f"(d[OFF+67]), "+f"(d[OFF+68]), "+f"(d[OFF+69]), "+f"(d[OFF+70]), "+f"(d[OFF+71]),
      "+f"(d[OFF+72]), "+f"(d[OFF+73]), "+f"(d[OFF+74]), "+f"(d[OFF+75]), "+f"(d[OFF+76]), "+f"(d[OFF+77]), "+f"(d[OFF+78]), "+f"(d[OFF+79]),
      "+f"(d[OFF+80]), "+f"(d[OFF+81]), "+f"(d[OFF+82]), "+f"(d[OFF+83]), "+f"(d[OFF+84]), "+f"(d[OFF+85]), "+f"(d[OFF+86]), "+f"(d[OFF+87]),
      "+f"(d[OFF+88]), "+f"(d[OFF+89]), "+f"(d[OFF+90]), "+f"(d[OFF+91]), "+f"(d[OFF+92]), "+f"(d[OFF+93]), "+f"(d[OFF+94]), "+f"(d[OFF+95])
    : "l"(da), "l"(db), "r"(scale_d), "n"(TA), "n"(TB));
}
template<int TA, int TB, int OFF, int SZ> __device__ __forceinline__ void wgmma_n128_ss(float (&d)[SZ], uint64_t da, uint64_t db, int scale_d) {
  asm volatile("{\n.reg .pred p;\nsetp.ne.b32 p, %66, 0;\n"
    "wgmma.mma_async.sync.aligned.m64n128k16.f32.bf16.bf16 {%0,%1,%2,%3,%4,%5,%6,%7,%8,%9,%10,%11,%12,%13,%14,%15,%16,%17,%18,%19,%20,%21,%22,%23,%24,%25,%26,%27,%28,%29,%30,%31,%32,%33,%34,%35,%36,%37,%38,%39,%40,%41,%42,%43,%44,%45,%46,%47,%48,%49,%50,%51,%52,%53,%54,%55,%56,%57,%58,%59,%60,%61,%62,%63}, %64, %65, p, 1, 1, %67, %68;\n}\n"
    : "+f"(d[OFF+0]), "+f"(d[OFF+1]), "+f"(d[OFF+2]), "+f"(d[OFF+3]), "+f"(d[OFF+4]), "+f"(d[OFF+5]), "+f"(d[OFF+6]), "+f"(d[OFF+7]),
      "+f"(d[OFF+8]), "+f"(d[OFF+9]), "+f"(d[OFF+10]), "+f"(d[OFF+11]), "+f"(d[OFF+12]), "+f"(d[OFF+13]), "+f"(d[OFF+14]), "+f"(d[OFF+15]),
      "+f"(d[OFF+16]), "+f"(d[OFF+17]), "+f"(d[OFF+18]), "+f"(d[OFF+19]), "+f"(d[OFF+20]), "+f"(d[OFF+21]), "+f"(d[OFF+22]), "+f"(d[OFF+23]),
      "+f"(d[OFF+24]), "+f"(d[OFF+25]), "+f"(d[OFF+26]), "+f"(d[OFF+27]), "+f"(d[OFF+28]), "+f"(d[OFF+29]), "+f"(d[OFF+30]), "+f"(d[OFF+31]),
      "+f"(d[OFF+32]), "+f"(d[OFF+33]), "+f"(d[OFF+34]), "+f"(d[OFF+35]), "+f"(d[OFF+36]), "+f"(d[OFF+37]), "+f"(d[OFF+38]), "+f"(d[OFF+39]),
      "+f"(d[OFF+40]), "+f"(d[OFF+41]), "+f"(d[OFF+42]), "+f"(d[OFF+43]), "+f"(d[OFF+44]), "+f"(d[OFF+45]), "+f"(d[OFF+46]), "+f"(d[OFF+47]),
      "+f"(d[OFF+48]), "+f"(d[OFF+49]), "+f"(d[OFF+50]), "+f"(d[OFF+51]), "+f"(d[OFF+52]), "+f"(d[OFF+53]), "+f"(d[OFF+54]), "+f"(d[OFF+55]),
      "+f"(d[OFF+56]), "+f"(d[OFF+57]), "+f"(d[OFF+58]), "+f"(d[OFF+59]), "+f"(d[OFF+60]), "+f"(d[OFF+61]), "+f"(d[OFF+62]), "+f"(d[OFF+63])
    : "l"(da), "l"(db), "r"(scale_d), "n"(TA), "n"(TB));
}
template<int TA, int TB, int OFF, int SZ> __device__ __forceinline__ void wgmma_n64_ss(float (&d)[SZ], uint64_t da, uint64_t db, int scale_d) {
  asm volatile("{\n.reg .pred p;\nsetp.ne.b32 p, %34, 0;\n"
    "wgmma.mma_async.sync.aligned.m64n64k16.f32.bf16.bf16 {%0,%1,%2,%3,%4,%5,%6,%7,%8,%9,%10,%11,%12,%13,%14,%15,%16,%17,%18,%19,%20,%21,%22,%23,%24,%25,%26,%27,%28,%29,%30,%31}, %32, %33, p, 1, 1, %35, %36;\n}\n"
    : "+f"(d[OFF+0]), "+f"(d[OFF+1]), "+f"(d[OFF+2]), "+f"(d[OFF+3]), "+f"(d[OFF+4]), "+f"(d[OFF+5]), "+f"(d[OFF+6]), "+f"(d[OFF+7]),
      "+f"(d[OFF+8]), "+f"(d[OFF+9]), "+f"(d[OFF+10]), "+f"(d[OFF+11]), "+f"(d[OFF+12]), "+f"(d[OFF+13]), "+f"(d[OFF+14]), "+f"(d[OFF+15]),
      "+f"(d[OFF+16]), "+f"(d[OFF+17]), "+f"(d[OFF+18]), "+f"(d[OFF+19]), "+f"(d[OFF+20]), "+f"(d[OFF+21]), "+f"(d[OFF+22]), "+f"(d[OFF+23]),
      "+f"(d[OFF+24]), "+f"(d[OFF+25]), "+f"(d[OFF+26]), "+f"(d[OFF+27]), "+f"(d[OFF+28]), "+f"(d[OFF+29]), "+f"(d[OFF+30]), "+f"(d[OFF+31])
    : "l"(da), "l"(db), "r"(scale_d), "n"(TA), "n"(TB));
}
template<int TA, int TB, int OFF, int SZ> __device__ __forceinline__ void wgmma_n72_ss(float (&d)[SZ], uint64_t da, uint64_t db, int scale_d) {
  asm volatile("{\n.reg .pred p;\nsetp.ne.b32 p, %38, 0;\n"
    "wgmma.mma_async.sync.aligned.m64n72k16.f32.bf16.bf16 {%0,%1,%2,%3,%4,%5,%6,%7,%8,%9,%10,%11,%12,%13,%14,%15,%16,%17,%18,%19,%20,%21,%22,%23,%24,%25,%26,%27,%28,%29,%30,%31,%32,%33,%34,%35}, %36, %37, p, 1, 1, %39, %40;\n}\n"
    : "+f"(d[OFF+0]), "+f"(d[OFF+1]), "+f"(d[OFF+2]), "+f"(d[OFF+3]), "+f"(d[OFF+4]), "+f"(d[OFF+5]), "+f"(d[OFF+6]), "+f"(d[OFF+7]),
      "+f"(d[OFF+8]), "+f"(d[OFF+9]), "+f"(d[OFF+10]), "+f"(d[OFF+11]), "+f"(d[OFF+12]), "+f"(d[OFF+13]), "+f"(d[OFF+14]), "+f"(d[OFF+15]),
      "+f"(d[OFF+16]), "+f"(d[OFF+17]), "+f"(d[OFF+18]), "+f"(d[OFF+19]), "+f"(d[OFF+20]), "+f"(d[OFF+21]), "+f"(d[OFF+22]), "+f"(d[OFF+23]),
      "+f"(d[OFF+24]), "+f"(d[OFF+25]), "+f"(d[OFF+26]), "+f"(d[OFF+27]), "+f"(d[OFF+28]), "+f"(d[OFF+29]), "+f"(d[OFF+30]), "+f"(d[OFF+31]),
      "+f"(d[OFF+32]), "+f"(d[OFF+33]), "+f"(d[OFF+34]), "+f"(d[OFF+35])
    : "l"(da), "l"(db), "r"(scale_d), "n"(TA), "n"(TB));
}
template<int TB, int OFF, int SZ> __device__ __forceinline__ void wgmma_n64_rs(float (&d)[SZ], uint32_t a0, uint32_t a1, uint32_t a2, uint32_t a3, uint64_t db, int scale_d) {
  asm volatile("{\n.reg .pred p;\nsetp.ne.b32 p, %37, 0;\n"
    "wgmma.mma_async.sync.aligned.m64n64k16.f32.bf16.bf16 {%0,%1,%2,%3,%4,%5,%6,%7,%8,%9,%10,%11,%12,%13,%14,%15,%16,%17,%18,%19,%20,%21,%22,%23,%24,%25,%26,%27,%28,%29,%30,%31}, {%32,%33,%34,%35}, %36, p, 1, 1, %38;\n}\n"
    : "+f"(d[OFF+0]), "+f"(d[OFF+1]), "+f"(d[OFF+2]), "+f"(d[OFF+3]), "+f"(d[OFF+4]), "+f"(d[OFF+5]), "+f"(d[OFF+6]), "+f"(d[OFF+7]),
      "+f"(d[OFF+8]), "+f"(d[OFF+9]), "+f"(d[OFF+10]), "+f"(d[OFF+11]), "+f"(d[OFF+12]), "+f"(d[OFF+13]), "+f"(d[OFF+14]), "+f"(d[OFF+15]),
      "+f"(d[OFF+16]), "+f"(d[OFF+17]), "+f"(d[OFF+18]), "+f"(d[OFF+19]), "+f"(d[OFF+20]), "+f"(d[OFF+21]), "+f"(d[OFF+22]), "+f"(d[OFF+23]),
      "+f"(d[OFF+24]), "+f"(d[OFF+25]), "+f"(d[OFF+26]), "+f"(d[OFF+27]), "+f"(d[OFF+28]), "+f"(d[OFF+29]), "+f"(d[OFF+30]), "+f"(d[OFF+31])
    : "r"(a0), "r"(a1), "r"(a2), "r"(a3), "l"(db), "r"(scale_d), "n"(TB));
}
template<int TB, int OFF, int SZ> __device__ __forceinline__ void wgmma_n40_rs(float (&d)[SZ], uint32_t a0, uint32_t a1, uint32_t a2, uint32_t a3, uint64_t db, int scale_d) {
  asm volatile("{\n.reg .pred p;\nsetp.ne.b32 p, %25, 0;\n"
    "wgmma.mma_async.sync.aligned.m64n40k16.f32.bf16.bf16 {%0,%1,%2,%3,%4,%5,%6,%7,%8,%9,%10,%11,%12,%13,%14,%15,%16,%17,%18,%19}, {%20,%21,%22,%23}, %24, p, 1, 1, %26;\n}\n"
    : "+f"(d[OFF+0]), "+f"(d[OFF+1]), "+f"(d[OFF+2]), "+f"(d[OFF+3]), "+f"(d[OFF+4]), "+f"(d[OFF+5]), "+f"(d[OFF+6]), "+f"(d[OFF+7]),
      "+f"(d[OFF+8]), "+f"(d[OFF+9]), "+f"(d[OFF+10]), "+f"(d[OFF+11]), "+f"(d[OFF+12]), "+f"(d[OFF+13]), "+f"(d[OFF+14]), "+f"(d[OFF+15]),
      "+f"(d[OFF+16]), "+f"(d[OFF+17]), "+f"(d[OFF+18]), "+f"(d[OFF+19])
    : "r"(a0), "r"(a1), "r"(a2), "r"(a3), "l"(db), "r"(scale_d), "n"(TB));
}
template<int TB, int OFF, int SZ> __device__ __forceinline__ void wgmma_n128_rs(float (&d)[SZ], uint32_t a0, uint32_t a1, uint32_t a2, uint32_t a3, uint64_t db, int scale_d) {
  asm volatile("{\n.reg .pred p;\nsetp.ne.b32 p, %69, 0;\n"
    "wgmma.mma_async.sync.aligned.m64n128k16.f32.bf16.bf16 {%0,%1,%2,%3,%4,%5,%6,%7,%8,%9,%10,%11,%12,%13,%14,%15,%16,%17,%18,%19,%20,%21,%22,%23,%24,%25,%26,%27,%28,%29,%30,%31,%32,%33,%34,%35,%36,%37,%38,%39,%40,%41,%42,%43,%44,%45,%46,%47,%48,%49,%50,%51,%52,%53,%54,%55,%56,%57,%58,%59,%60,%61,%62,%63}, {%64,%65,%66,%67}, %68, p, 1, 1, %70;\n}\n"
    : "+f"(d[OFF+0]), "+f"(d[OFF+1]), "+f"(d[OFF+2]), "+f"(d[OFF+3]), "+f"(d[OFF+4]), "+f"(d[OFF+5]), "+f"(d[OFF+6]), "+f"(d[OFF+7]),
      "+f"(d[OFF+8]), "+f"(d[OFF+9]), "+f"(d[OFF+10]), "+f"(d[OFF+11]), "+f"(d[OFF+12]), "+f"(d[OFF+13]), "+f"(d[OFF+14]), "+f"(d[OFF+15]),
      "+f"(d[OFF+16]), "+f"(d[OFF+17]), "+f"(d[OFF+18]), "+f"(d[OFF+19]), "+f"(d[OFF+20]), "+f"(d[OFF+21]), "+f"(d[OFF+22]), "+f"(d[OFF+23]),
      "+f"(d[OFF+24]), "+f"(d[OFF+25]), "+f"(d[OFF+26]), "+f"(d[OFF+27]), "+f"(d[OFF+28]), "+f"(d[OFF+29]), "+f"(d[OFF+30]), "+f"(d[OFF+31]),
      "+f"(d[OFF+32]), "+f"(d[OFF+33]), "+f"(d[OFF+34]), "+f"(d[OFF+35]), "+f"(d[OFF+36]), "+f"(d[OFF+37]), "+f"(d[OFF+38]), "+f"(d[OFF+39]),
      "+f"(d[OFF+40]), "+f"(d[OFF+41]), "+f"(d[OFF+42]), "+f"(d[OFF+43]), "+f"(d[OFF+44]), "+f"(d[OFF+45]), "+f"(d[OFF+46]), "+f"(d[OFF+47]),
      "+f"(d[OFF+48]), "+f"(d[OFF+49]), "+f"(d[OFF+50]), "+f"(d[OFF+51]), "+f"(d[OFF+52]), "+f"(d[OFF+53]), "+f"(d[OFF+54]), "+f"(d[OFF+55]),
      "+f"(d[OFF+56]), "+f"(d[OFF+57]), "+f"(d[OFF+58]), "+f"(d[OFF+59]), "+f"(d[OFF+60]), "+f"(d[OFF+61]), "+f"(d[OFF+62]), "+f"(d[OFF+63])
    : "r"(a0), "r"(a1), "r"(a2), "r"(a3), "l"(db), "r"(scale_d), "n"(TB));
}

struct Ptrs { const __nv_bfloat16 *x, *wqkv, *wo, *wr, *wg, *wu, *wd; __nv_bfloat16* out; Scratch* s; };

enum { M_X, M_W, M_Q, M_O, M_S, M_G, M_U, M_D, M_L, M_N };
struct Maps { CUtensorMap m[M_N]; };

__global__ void __cluster_dims__(2, 1, 1) __launch_bounds__(384, 1) fused_kernel(const Ptrs P, const __grid_constant__ Maps T) {
  extern __shared__ __align__(1024) uint8_t smem_raw[];
  TS_DECL; TS(0); TSG(30);
  if (MPF == 1 && threadIdx.x == 0) { tmap_prefetch(&T.m[M_W]); tmap_prefetch(&T.m[M_Q]); tmap_prefetch(&T.m[M_X]); }
  if (MPF == 2 && threadIdx.x < 3) l2_prefetch(&T.m[threadIdx.x]);
  if (MPF == 3 && (threadIdx.x & 31) == 0 && threadIdx.x < 96) tmap_prefetch(&T.m[threadIdx.x >> 5]);
  const int tid = threadIdx.x, wid = __shfl_sync(~0u, tid >> 5, 0), wg = wid >> 2, lane = lane_id();
  const uint32_t rank = blockIdx.x & 1, own = rank << 24;
  const uint32_t sm = own + sb, mb = own + bars;
  int b0;
  { const int j = blockIdx.x >> 1, u = j - 36, q = (u * 37) >> 8;
    b0 = (j < 4 ? j * 16 + 64 : u < 0 ? j * 2 - 8 : q * 2 + u * 2 + 66) + rank; }
#define IDS(B) \
  const int b = (B), rb = b >> 4, cg = b & 15, hf = cg >> 3, s3 = cg & 7, c3 = s3 ^ ((rb & 1) << 2), jp = cg >> 1, km = (~c3 & 6) << 1; \
  const int fidx = jp == rb ? -1 : b - 2 * rb - (jp > rb ? 2 : 0); \
  auto kcol = [&](int kb) { return (kb ^ (kb < 8 ? km & 8 : km)) * 64; }; \
  auto src_of = [&](int p) { return p == 0 ? s3 : p == 15 ? s3 ^ 1 : (((jp & 3) ^ ((p - 7) >> 1)) << 1) + ((p - 1) & 1); }; \
  auto frag_of = [&](int p) { return p < 9 ? (p - 1) * 512 : 4096 + src_of(p) * 512; }; \
  (void)hf; (void)fidx; (void)kcol; (void)frag_of
  auto get_b = [&]() { return __shfl_sync(~0u, (int)lds1(mb + B_ID), 0); };
  IDS(b0);
  auto load_w = [&](uint32_t st, int kc, uint32_t bar, bool last) { tma_3d(st + 32768, &T.m[M_W], cg * 64, kc, 1, bar, last); tma_2d(st + 49152, &T.m[M_Q], cg * 64, kc, bar, last); };
  const uint32_t tk = clock64();
  if (SPF && tid < 80) {
    const int i = tid - 32;
    l2_prefetch(tid < 32 ? P.x + (rb * 256 + (hf * 4 + (cg & 3)) * 32 + tid) * D_ + kcol(0) : P.wqkv + (kcol(0) + (rb >> 1) * 16 + (i & 15)) * 3072 + (i >> 4) * 1024 + cg * 64);
  }
  RTS_DECL;
  if (wid == 8) {
    if (elect_one()) {
      if (smem_u32(smem_raw) != sm) asm volatile("trap;");
#pragma unroll
      for (int s = 0; s < 4; s++) mbar_init(mb + B_FULL + 8 * s, 1);
      asm volatile("fence.mbarrier_init.release.cluster;" ::: "memory");
      fence_async_smem();
      mbar_expect_tx(mb + B_FULL, STAGE_B);
      load_w(sm, kcol(0), mb + B_FULL, EFW0);
      tma_2d(sm, &T.m[M_X], kcol(0), rb * 256, mb + B_FULL, EFX0);
      tma_2d(sm + 16384, &T.m[M_X], kcol(0), rb * 256 + 128, mb + B_FULL, EFX0);
      RTS(0);
    }
  } else if (wid == 9) {
    if (elect_one()) {
#pragma unroll
      for (int i = 4; i < 31; i++) if (8 * i != B_ID) mbar_init(mb + 8 * i, i < 8 ? 8 : i < 16 ? 16 : i == 16 ? 64 : i == 17 ? 8 : i == 18 ? 4 : 1);
      asm volatile("fence.mbarrier_init.release.cluster;" ::: "memory");
      fence_async_smem();
    }
  } else if (wid == 11) {
#pragma unroll
    for (int i = 0; i < 4; i++) sts4(sm + OFF_STATS + i * 512 + lane * 16, SENT, SENT, SENT, SENT);
    sts1(mb + B_ID, b);
    fence_async_smem();
  }
  __syncthreads();
  asm volatile("barrier.cluster.arrive.relaxed.aligned;\nbarrier.cluster.wait.aligned;" ::: "memory");

  if (wg == 2) {
    asm volatile("setmaxnreg.dec.sync.aligned.u32 56;");
    if (wid == 8) {
      if (elect_one()) {
#pragma unroll 1
        for (int kb = 1; kb < 15; kb++) {
          const uint32_t fb = mb + B_FULL + 8 * (kb & 3), st = sm + (kb & 3) * STAGE_B;
          const int kc = kcol(kb);
          if (kb < 4) while ((uint32_t)clock64() - tk < FD0 + kb * FD1) {}
          else mbar_wait(fb + B_EMPTY, ((kb >> 2) & 1) ^ 1);
          mbar_expect_tx(fb, STAGE_B);
          tma_2d_mc(st + rank * 16384, &T.m[M_X], kc, rb * 256 + rank * 128, fb, EFX);
          load_w(st, kc, fb, EFW && kb >= EFWK);
          if (kb >= 8 && kb < 11) asm volatile("mbarrier.arrive.shared::cta.b64 _, [%0], %1;" :: "r"(fb + B_EMPTY), "r"(4) : "memory");
        }
        {
          const uint32_t st = sm + 3 * STAGE_B, fa = mb + B_FULL + 24, fb = mb + B_F15;
          const int kc = kcol(15);
          mbar_wait(fa, 0);
          mbar_expect_tx(fa, 32768); mbar_expect_tx(fb, 24576);
          if (rank) { mbar_wait(mb + B_EMPTY + 24, 0); tma_2d_mc(st + 16384, &T.m[M_X], kc, rb * 256 + 128, fa, EFX); }
          mbar_wait(mb + B_EMPTY, 1);
          tma_3d(st + 32768, &T.m[M_W], cg * 64, kc, 1, fa, EFW);
          if (!rank) { mbar_wait(mb + B_EMPTY + 24, 0); tma_2d_mc(st, &T.m[M_X], kc, rb * 256, fb, EFX); }
          tma_2d(st + 49152, &T.m[M_Q], cg * 64, kc, fb, EFW);
        }
        const uint4* kp = &P.s->kvp[cg * 8 * 256], *zq = &P.s->zp[cg * 8 * 16], *src = &P.s->obuf[(rb * 4 + rank * 2 + hf) * 64 * 128];
        const uint32_t* cnt = &P.s->ocnt[(rb * 2 + (hf ^ 1)) * 32];
        mbar_expect_tx(mb + B_KVP, 32768 + 2048);
        asm volatile("" : "+l"(kp), "+l"(zq), "+l"(src), "+l"(cnt));
        mbar_wait(mb + B_EVB, 0);
        { const uint32_t t1 = clock64(); while ((uint32_t)clock64() - t1 < KDELAY) {} }
        bulk_load(sm + rank * (2 * STAGE_B) + STAGE_B, kp, 32768, mb + B_KVP);
        bulk_load(sm + rank * (2 * STAGE_B) + UNIT, zq, 2048, mb + B_KVP);
        mbar_wait(mb + B_E, 0);
        RTS(3);
        for (int it = 0; ld_rlx(cnt) != 7; it++) SPINCHK(it, 10);
        const uint32_t t0 = clock64();
        while ((uint32_t)clock64() - t0 < ADELAY) {}
        RTS(4);
#pragma unroll
        for (int p = 1; p < 5; p++) {
          if (p == 3) while ((uint32_t)clock64() - t0 < ADELAY2) {}
          bulk_load_mc(sm + ring_of(p, rank), src + (p - 1) * 512, UNIT, mb + B_BF + 8 * p);
        }
#pragma unroll 1
        for (int p = 5; p < 15; p++) {
          uint32_t dst = sm + ring_of(p, rank), bar = mb + B_BF + 8 * (p % 7);
          const uint4* q = src + frag_of(p);
          asm volatile("" : "+r"(dst), "+r"(bar), "+l"(q));
          mbar_wait(mb + B_E + 8 * ((p - 4) & 7), p >= 12);
          bulk_load_mc(dst, q, UNIT, bar);
        }
        asm volatile("mbarrier.arrive.shared::cta.b64 _, [%0], 8;" :: "r"(mb + B_GATE) : "memory");
        const uint4* s15 = &P.s->obuf[(rb * 4 + hf) * 64 * 128 + frag_of(15)];
        RTS_DUMP;
        mbar_wait(mb + B_E + 24, 1);
        bulk_load(sm + ring_of(15, 0), s15, UNIT, mb + B_BF + 8); bulk_load(sm + ring_of(15, 1), s15 + 2 * 64 * 128, UNIT, mb + B_BF + 8);
      }
    } else if (wid == 11) {
      IDS(get_b());
      mbar_wait(mb + B_FULL + 24, 0);
      mbar_wait(mb + B_FULL + 8 * (PULL0 & 3), PULL0 >> 2);
      int pr = fidx >= 0 ? 0 : 24;
#pragma unroll 1
      for (int ph = 0; ph < 2; ph++) {
#pragma unroll 1
        while (pr < 24) {
          const bool gu = pr < 16;
          const uint32_t d = gu ? 64 * F_ * 2 : 8192;
          const uint32_t o = (gu ? (rank * 32 + lane) * (F_ * 2) + (fidx >> 1) * 128 : (fidx - 2) * 65536 + lane * 256) + pr * d;
          const char* q0 = (const char*)(gu ? P.wg : P.wd) + o, *q1 = gu ? (const char*)P.wu + o : q0 + 128;
#pragma unroll 1
          do {
            if (ph == 1) { l2_prefetch(q0); __nanosleep(PSLEEP); l2_prefetch(q1); __nanosleep(PSLEEP); }
            else {
              if (mbar_test(mb + B_HOLD, 0)) goto next;
              asm volatile("cp.async.ca.shared.global.L2::128B [%0], [%1], 4;\ncp.async.commit_group;\ncp.async.wait_group %3;\n"
                           "cp.async.ca.shared.global.L2::128B [%0], [%2], 4;\ncp.async.commit_group;\ncp.async.wait_group %3;" :: "r"(mb + B_DUMMY), "l"(q0), "l"(q1), "n"(PDEPTH) : "memory");
            }
            q0 += d; q1 += d;
          } while (++pr & 7);
        }
      next:
        if (lane == 0) { PTS(1 + ph); g_dbgv(3 + 2 * ph, pr); }
      }
      asm volatile("cp.async.wait_all;" ::: "memory");
      if (P3PULL && fidx >= 0 && elect_one()) {
        mbar_wait(mb + B_BF + 8 * P3GATE, 0);
#pragma unroll 1
        for (int i = 0; i < 8; i++) {
          mbar_expect_tx(mb + B_LATE, 1024);
#pragma unroll
          for (int j = 0; j < 4; j++) tma_2d(sm + OFF_STATS + 768, &T.m[M_L], 0, fidx * 512 + i * 64 + j * 16, mb + B_LATE, false);
          mbar_wait(mb + B_LATE, ~i & 1);
        }
        PTS(4);
      }
    } else {
      const uint32_t eb = (lane << 24) + bars + B_EMPTY;
      float c[6];
      if (wid == 10) {
        float sx[4] = {0.f, 0.f, 0.f, 0.f}, qx[4] = {0.f, 0.f, 0.f, 0.f};
        const uint32_t xa = sm + ((hf * 4 + (cg & 3)) * 32 + lane) * 128 + ((lane & 7) << 4);
#pragma unroll 1
        for (int kb = 0; kb < 8; kb++) {
          uint4 xv[8];
          const uint32_t so = xa + (kb & 3) * STAGE_B;
          mbar_wait(mb + B_FULL + 8 * (kb & 3), kb >> 2);
#pragma unroll
          for (int i = 0; i < 8; i++) xv[i] = lds4(so ^ (i << 4));
#pragma unroll
          for (int i = 0; i < 8; i++) {
            const uint32_t e[4] = {xv[i].x, xv[i].y, xv[i].z, xv[i].w};
#pragma unroll
            for (int j = 0; j < 4; j++) {
              const float d0 = bf_lo(e[j]), d1 = bf_hi(e[j]);
              sx[j] += d0 + d1; qx[j] = fmaf(d0, d0, fmaf(d1, d1, qx[j]));
            }
          }
          __syncwarp();
          if (lane < 2) mbar_arrive_rem(eb + 8 * (kb & 3));
          if (kb == RST2) {
        {
          const uint32_t ep = ld_rlx(&P.s->epoch);
          float s = 0.f;
#pragma unroll
          for (int i = 0; i < 4; i++) {
            const uint4 v = ld_cg4((const uint4*)P.wr + lane + i * 32);
            s += (bf_lo(v.x) + bf_hi(v.x)) + (bf_lo(v.y) + bf_hi(v.y)) + (bf_lo(v.z) + bf_hi(v.z)) + (bf_lo(v.w) + bf_hi(v.w));
          }
#pragma unroll
          for (int o = 16; o; o >>= 1) s += __shfl_xor_sync(~0u, s, o);
          if (lane == 0) sts1(mb + B_SW, (__float_as_uint(s) & ~255u) | ((ep + 1) & 255));
        }
        asm volatile("cp.async.bulk.wait_group 0;\nfence.proxy.async.global;" ::: "memory");
        fence_gpu();
        if (lane == 0) PTS(0);
          }
          if (kb == RST) {
        if (elect_one()) {
#pragma unroll 1
          for (int i = 0; i < 16; i++) bulk_store(&P.s->obuf[((rb * 4 + (i >> 2)) * 64 + (((i >> 2) & 1) == hf ? 32 + s3 * 4 + (i & 3) : (i & 3) * 8 + s3)) * 128], sm + OFF_STATS, 2048);
          bulk_store(&P.s->kvp[(cg * 8 + rb) * 256], sm + OFF_STATS, 2048); bulk_store(&P.s->kvp[(cg * 8 + rb) * 256 + 128], sm + OFF_STATS, 2048);
          bulk_store(&P.s->zp[(cg * 8 + rb) * 16], sm + OFF_STATS, 256);
          if (s3 == 0) bulk_store(&P.s->ocnt[(rb * 2 + hf) * 32], sm + OFF_STATS, 128);
          asm volatile("cp.async.bulk.commit_group;" ::: "memory");
          #pragma unroll
          for (int i = M_O; i < M_N; i++) tmap_prefetch(&T.m[i]);
        }
        __syncwarp();
          }
        }
        c[0] = ((sx[0] + sx[1]) + (sx[2] + sx[3])) * (2.f / D_);
        c[1] = fmaxf(fmaf(-c[0], c[0], ((qx[0] + qx[1]) + (qx[2] + qx[3])) * (2.f / D_)), 0.f);
      } else {
        float a[12];
#pragma unroll
        for (int i = 0; i < 12; i++) a[i] = 0.f;
        const int r2 = lane >> 4, c16 = lane & 15;
        const uint32_t a0 = sm + 32768 + (rb >> 1) * 2048 + r2 * 128 + (((c16 >> 1) ^ r2) << 4) + (c16 & 1) * 8;
#pragma unroll 1
        for (int it = 0; it < 16; it++) {
          uint2 w[12];
          const int s = (it >> 1) & 3;
          const uint32_t so = a0 + s * STAGE_B + (it & 1) * 1024;
          if (!(it & 1)) { mbar_wait(mb + B_FULL + 8 * s, it >> 3); TSD(8 + (it >> 1)); }
          static_for<0, 12>([&](auto ic) { constexpr int i = decltype(ic)::value;
            const float2 v = lds2f_o<(i >> 2) * 8192 + (i & 3) * 256>(so ^ ((i & 3) << 5)); w[i] = make_uint2(__float_as_uint(v.x), __float_as_uint(v.y)); });
#pragma unroll
          for (int i = 0; i < 12; i++) { float* q = a + (i >> 2) * 4; q[0] += bf_lo(w[i].x); q[1] += bf_hi(w[i].x); q[2] += bf_lo(w[i].y); q[3] += bf_hi(w[i].y); }
          __syncwarp();
          if (lane < 2 && (it & 1)) mbar_arrive_rem(eb + 8 * s);
        }
#pragma unroll
        for (int i = 0; i < 6; i++) {
          const int o = (i >> 1) * 4 + (i & 1);
          c[i] = (r2 ? a[o + 2] : a[o]) + __shfl_xor_sync(~0u, r2 ? a[o] : a[o + 2], 16);
        }
      }
      TS(5);
      bar_sync(10, 64);
      TS(6);
      {
        const uint32_t tag = lds1(mb + B_SW) & 255;
        auto tagged = [&](float v) { return ((__float_as_uint(v) + 128) & ~255u) | tag; };
        if (wid == 9) {
#pragma unroll
          for (int sg = 0; sg < 3; sg++) {
            st_rlx2((uint2*)&P.s->csp[(cg * 8 + rb) * 48] + sg * 32 + (lane & 15) * 2 + (lane >> 4), tagged(c[sg * 2]), tagged(c[sg * 2 + 1]));
          }
        } else st_rlx2((uint2*)&P.s->st1[rb * 256 + (hf * 4 + (cg & 3)) * 32 + lane] + ((cg >> 2) & 1), tagged(c[0]), tagged(c[1]));
        { const uint32_t t0 = clock64(); while ((uint32_t)clock64() - t0 < GDELAY) {} }
#pragma unroll 1
        for (int h = wid - 9; h < 2; h++) {
          const int q = h * 24 + min(lane, 23), sd = wid == 10 ? 32 : 48;
          const uint4* gp = wid == 10 ? &P.s->st1[rb * 256 + lane] : &P.s->csp[cg * 8 * 48 + q];
          uint4 v[8];
#pragma unroll 1
          for (int it = 0;; it++) {
            uint32_t x = 0;
#pragma unroll
            for (int i = 0; i < 8; i++) v[i] = ld_rlx4(gp + i * sd);
#pragma unroll
            for (int i = 0; i < 8; i++) { v[i].x ^= tag; v[i].y ^= tag; v[i].z ^= tag; v[i].w ^= tag; x |= v[i].x | v[i].y | v[i].z | v[i].w; }
            if (!__any_sync(~0u, (x & 255) != 0)) break;
            SPINCHK(it, 3);
          }
          if (wid == 10) {
#pragma unroll
            for (int i = 0; i < 8; i++) {
              const float m0 = __uint_as_float(v[i].x), m1 = __uint_as_float(v[i].z), dm = 0.5f * (m0 - m1);
              sts2f(sm + OFF_STATS + (i * 32 + lane) * 8, -0.5f * (m0 + m1), rsq(fmaf(dm, dm, 0.5f * (__uint_as_float(v[i].y) + __uint_as_float(v[i].w))) + 1e-5f));
            }
          } else {
            float s4[4] = {0.f, 0.f, 0.f, 0.f};
#pragma unroll
            for (int i = 0; i < 8; i++) { s4[0] += __uint_as_float(v[i].x); s4[1] += __uint_as_float(v[i].y); s4[2] += __uint_as_float(v[i].z); s4[3] += __uint_as_float(v[i].w); }
            sts4(sm + OFF_COLSUM + q * 16, __float_as_uint(s4[0]), __float_as_uint(s4[1]), __float_as_uint(s4[2]), __float_as_uint(s4[3]));
          }
        }
        mbar_arrive(mb + B_AUX);
      }
      TS(2);
      IDS(get_b());
      const uint64_t btab = rank ? BT1 : BT0;
      if (wid == 9) {
        {
          const uint4 sv = make_uint4(SENT, SENT, SENT, SENT);
          uint4* y = &P.s->ybuf[b * NFFN * 2 + lane];
#pragma unroll
          for (int i = 0; i < 7; i++) y[i * 32] = sv;
          if (lane < 16) P.s->st2[b * 16 + lane] = make_uint4(0, 0, 0, 0); else P.s->hsel[b * 16 + lane - 16] = sv;
          if (b < 8) P.s->cand[b * 32 + lane] = SENT;
          fence_gpu();
          __syncwarp();
          if (lane == 0) mbar_arrive(mb + B_LATE);
        }
        TS(3);
        TS_DUMP(2);
        {
          const int p = lane & 15, sl = p % 7;
          const bool sliced = p > 0 && p < 9;
          const uint32_t c = sliced ? ((p - 1) >> 1) * 16 | ((hf ^ 1) * 8 + ((p - 1) & 1) * 4) << 8 | 128 << 16 : (hf * 8 + src_of(p)) << 8;
          const uint32_t ev = mb + (p < BHOLD ? B_EVA : p < 4 ? B_KVP : p < 6 ? B45 : B_E + 8 * ((p < 7 ? 1 : p - 4) & 7) + (p >= 12));
          mbar_wait(mb + B_EVA, 0);
          sts4(sm + OFF_COLSUM + 512 + p * 16, sm + unit_of(btab, sl), mb + B_BF + 8 * sl, c, ev);
          __syncwarp();
        }
        if (elect_one()) {
#pragma unroll 1
          for (int p = 0; p < 16; p++) {
            const uint4 e = lds4(sm + OFF_COLSUM + 512 + p * 16);
            mbar_wait(e.w & ~1u, e.w & 1);
            mbar_expect_tx(e.y, p ? 4 * UNIT : 2 * UNIT);
            tma_4d(e.x, (const CUtensorMap*)((const char*)&T.m[M_O] + (e.z >> 16)), 0, e.z & 255, (e.z >> 8) & 255, c3 * 2, e.y);
          }
          PTS(16);
        }
      } else {
        const uint2 w = ld_rlx2((const uint2*)(P.wr + c3 * 128) + lane);
#pragma unroll 1
        for (int i = 0; i < 4; i++) { l2_prefetch((const char*)P.wo + b * 16384 + i * 4096 + lane * 128); __nanosleep(300); }
        const int p = lane & 15, p2 = min(p + 2, 15);
        const uint32_t t0 = dlo(sb, 8192) + (unit_of(btab, p % 7) >> 4), t1 = ring_of(p + 1, lane >> 4), t2 = mb + B_BF + 8 * (p2 % 7);
        mbar_wait(mb + B_EVB, 0);
        sts4(sm + OFF_COLSUM + lane * 16, w.x << 16, w.x & 0xFFFF0000u, w.y << 16, w.y & 0xFFFF0000u);
        sts4(sm + OFF_STATS + lane * 16, t0, t1, t2, (p2 / 7) & 1);
        __syncwarp();
        if (elect_one()) {
          mbar_arrive(mb + B_WR);
          if (fidx >= 0) {
            mbar_expect_tx(mb + B_FFN, 131072); mbar_expect_tx(mb + B_FFD, 32768);
            uint64_t gt = rank ? GT1 : GT0;
#pragma unroll 1
            for (int f = 0; f < 8; f++, gt >>= 5) {
              uint32_t d0 = sm + unit_of(gt, 0);
              asm volatile("" : "+r"(d0));
              if (f == 3) mbar_wait(mb + B_GATE, 1);
              mbar_wait(mb + (f < 3 ? B_KVB : B_E + ((f + 5) >> 1) * 8), 1);
              tma_3d(d0, &T.m[M_G], fidx * 32, f * 128, 0, mb + B_FFN, EFF);
              tma_3d(d0 + UNIT, &T.m[M_U], fidx * 32, f * 128, 0, mb + B_FFN, EFF);
            }
            PTS(17);
            mbar_expect_tx(mb + B_KVP, 32768);
#pragma unroll
            for (int w = 0; w < 8; w++) {
              if (w == 2) mbar_wait(mb + B_E + 56, 1);
              if (w == 6) mbar_wait(mb + B_E16, 1);
              if (w == DLATE) mbar_wait(mb + B_EVA, 1);
              tma_3d(sm + ((DT0 >> (5 * w)) & 31) * UNIT + (w < 4 ? 0 : w < 6 ? 14 * UNIT : -14 * UNIT) * rank, &T.m[M_D], 0, fidx * 32, 2 * w, mb + (w < 4 ? B_FFD : B_KVP), EFF);
            }
            PTS(18);
          }
        }
      }
    }
    __syncwarp();
    IDS(get_b());
    mbar_wait(mb + B_EVB, 0);
    mbar_wait(mb + B_OUT, 0);
    const float2 cf = lds2f(sm + OFF_STATS + 64);
    const int cand0 = 2047 - (__float_as_int(cf.x) & 2047), cand1 = 2047 - (__float_as_int(cf.y) & 2047), rr = lane >> 4;
    auto store_rows = [&](int tr, bool on) {
      const uint4 v = lds4(sm + 4 * UNIT + (tr >> 6) * STAGE_B + (tr & 63) * 256 + (((lane & 15) ^ (tr & 7)) << 4));
      const float2 pr = lds2f(sm + OFF_LNP + tr * 8);
      const float f = 1.f + pr.x, n = pr.y;
      if (on) *(uint4*)(P.out + (size_t)(rb * 256 + hf * 64 + tr + (tr & 64)) * D_ + c3 * 128 + (lane & 15) * 8) =
          make_uint4(pack2(fmaf(bf_lo(v.x), f, n), fmaf(bf_hi(v.x), f, n)), pack2(fmaf(bf_lo(v.y), f, n), fmaf(bf_hi(v.y), f, n)),
                     pack2(fmaf(bf_lo(v.z), f, n), fmaf(bf_hi(v.z), f, n)), pack2(fmaf(bf_lo(v.w), f, n), fmaf(bf_hi(v.w), f, n)));
    };
    if (wid == 8) {
      mbar_wait(mb + B_SEL, 0);
      const float2 sel = lds2f(sm + OFF_STATS + 80);
      const uint32_t kc = __float_as_uint(rr ? cf.y : cf.x);
      const int c = rr ? cand1 : cand0;
      store_rows(((c >> 1) & 64) + (c & 63), kc != __float_as_uint(sel.x) && kc != __float_as_uint(sel.y) && (c >> 8) == rb && ((c >> 6) & 1) == hf);
    } else if (wid < 9 + NOUTW) {
#pragma unroll 2
      for (int tr = (wid - 9) * 2 + rr; tr < 128; tr += 2 * NOUTW) {
        const int row = rb * 256 + hf * 64 + tr + (tr & 64);
        store_rows(tr, row != cand0 && row != cand1);
      }
      if (wid == 9 && lane == 0) PTS(14);
    }
  } else {
    asm volatile("setmaxnreg.inc.sync.aligned.u32 224;");
    const int t128 = tid & 127, warp = wid & 3, g = lane >> 2, t = lane & 3;
    const uint32_t sk = rank * (2 * STAGE_B);
    uint4 ost[2][4];
    uint4* od1;
    int b1;
    const uint32_t eb = (lane << 24) + bars + B_E;
    float acc[64], wf[32];
    {
      float acc0[96], acc1[96];
#pragma unroll
      for (int i = 0; i < 96; i++) { acc0[i] = 0.f; acc1[i] = 0.f; }
      const uint32_t xo0 = dlo(sb, 16) + (wg * 2 + hf) * 512, xo1 = dlo(sb, 16) + (wg * 2 + (hf ^ 1)) * 512;
      constexpr uint32_t ST = STAGE_B >> 4, WD = dlo(sb + 49152, 8192), WV = dlo(sb + 32768, 8192);
      const uint32_t eb0 = (t128 << 24) + bars + B_EMPTY;
#pragma unroll 1
      for (int kb = 0; kb < 12; kb++) {
        const int s = kb & 3;
        mbar_wait(mb + B_FULL + 8 * s, (kb >> 2) & 1);
        if (kb == 0) TS(1);
        if (kb == 0 && !wg) bar_sync(2, 256);
        pin(acc0); pin(acc1);
        wg_fence();
#pragma unroll
        for (int k = 0; k < 4; k++) {
          const uint64_t db = dsc<1024, 1>(WV + s * ST + k * 128);
          wgmma_n192_ss<0, 1, 0>(acc0, dsc<1024, 1>(s * ST + xo0 + k * 2), db, 1);
          wgmma_n192_ss<0, 1, 0>(acc1, dsc<1024, 1>(s * ST + xo1 + k * 2), db, 1);
        }
        wg_commit();
        if (kb == 0 && wg) bar_arrive(2, 256);
        wg_wait<0>();
        pin(acc0); pin(acc1);
        if (t128 < 2 && kb < 11) mbar_arrive_rem(eb0 + 8 * s);
      }
      mbar_wait(mb + B_FULL, 1);
      if (t128 < 8) mbar_arrive_rem(t128 < 4 ? (wg << 24) + bars + B_EMPTY + 24 : mb + B_EMPTY);
      TS(2);
      mbar_wait(mb + B_AUX, 0);
      float rs[2][2], nm[2][2];
#pragma unroll
      for (int m = 0; m < 2; m++)
#pragma unroll
        for (int h = 0; h < 2; h++) { const float2 v = lds2f(sm + OFF_STATS + ((wg * 2 + (m ^ hf)) * 64 + warp * 16 + h * 8 + g) * 8); nm[m][h] = v.x; rs[m][h] = v.y; }
      auto center = [&](auto jc) {
        constexpr int j = decltype(jc)::value;
        const float2 cs = lds2f_o<sb + OFF_COLSUM + j * 32>(own + t * 8);
        acc1[j * 4] = fmaf(nm[1][0], cs.x, acc1[j * 4]); acc1[j * 4 + 1] = fmaf(nm[1][0], cs.y, acc1[j * 4 + 1]);
        acc1[j * 4 + 2] = fmaf(nm[1][1], cs.x, acc1[j * 4 + 2]); acc1[j * 4 + 3] = fmaf(nm[1][1], cs.y, acc1[j * 4 + 3]);
        acc0[j * 4] = fmaf(nm[0][0], cs.x, acc0[j * 4]); acc0[j * 4 + 1] = fmaf(nm[0][0], cs.y, acc0[j * 4 + 1]);
        acc0[j * 4 + 2] = fmaf(nm[0][1], cs.x, acc0[j * 4 + 2]); acc0[j * 4 + 3] = fmaf(nm[0][1], cs.y, acc0[j * 4 + 3]);
      };
      static_for<0, 16>(center);
      const float L2E = 1.4426950408889634f;
      uint32_t fa = sm + sk + (warp * 16 + (lane & 15)) * 128 + (((lane >> 4) ^ (lane & 7)) << 4);
      asm volatile("" : "+r"(fa));
      uint32_t xf0[32], xf1[32];
      auto pack_kv = [&](float (&a)[96], int i, float r0, float r1, uint32_t* o, uint32_t z = 0) {
        const float* p = a + i * 8;
        if (i < 4) {
          const float rl0 = __uint_as_float(__float_as_uint(r0 * L2E) | z), rl1 = __uint_as_float(__float_as_uint(r1 * L2E) | z);
          const uint32_t q0 = pack2(r0, r0), q1 = pack2(r1, r1);
          o[0] = phi2(p[0], p[1], rl0, q0); o[1] = phi2(p[2], p[3], rl1, q1); o[2] = phi2(p[4], p[5], rl0, q0); o[3] = phi2(p[6], p[7], rl1, q1);
        } else {
          r0 = __uint_as_float(__float_as_uint(r0) | z); r1 = __uint_as_float(__float_as_uint(r1) | z);
          o[0] = pack2(p[0] * r0, p[1] * r0); o[1] = pack2(p[2] * r1, p[3] * r1); o[2] = pack2(p[4] * r0, p[5] * r0); o[3] = pack2(p[6] * r1, p[7] * r1); }
      };
      auto swap_kv = [&](uint32_t (&xf)[32], uint32_t tile, int i, const uint32_t* o, uint32_t z = 0) {
        const uint32_t ad = (fa + tile * UNIT) ^ ((i & 3) << 5);
        if (i < 4) { ldsm4_o<0>(ad, xf[i * 4], xf[i * 4 + 1], xf[i * 4 + 2], xf[i * 4 + 3]); stsm4_o<0>(ad, o[0], o[1], o[2], o[3]); }
        else { ldsm4_o<STAGE_B>(ad | z, xf[i * 4], xf[i * 4 + 1], xf[i * 4 + 2], xf[i * 4 + 3]); stsm4_o<STAGE_B>(ad, o[0], o[1], o[2], o[3]); }
      };
      auto mma_q = [&](float (&a)[96], uint32_t (&xf)[32], uint32_t xo, bool ss) {
        const uint32_t r = __shfl_sync(~0u, sk >> 4, 0), o = 2 * ST - r;
#pragma unroll
        for (int j = 0; j < 8; j++) {
          if (ss) wgmma_n64_ss<0, 1, 64>(a, dsc<1024, 1>(o + (j >> 2) * ST + xo + (j & 3) * 2), dsc<1024, 1>(WD + o + (j >> 2) * ST + (j & 3) * 128), 1);
          else wgmma_n64_rs<1, 64>(a, xf[j * 4], xf[j * 4 + 1], xf[j * 4 + 2], xf[j * 4 + 3], dsc<1024, 1>(WD + r + (j >> 2) * ST + (j & 3) * 128), 1);
        }
      };
      auto epi_q = [&](float (&a)[96], float r0, float r1, uint32_t (&o)[16]) {
        const float rl0 = r0 * 1.44269511f, rl1 = r1 * 1.44269511f;
        const uint32_t q0 = dup2(r0), q1 = dup2(r1);
#pragma unroll
        for (int j = 0; j < 8; j++) { o[j * 2] = phi2(a[64 + j * 4], a[65 + j * 4], rl0, q0); o[j * 2 + 1] = phi2(a[66 + j * 4], a[67 + j * 4], rl1, q1); }
        pinu(o);
      };
      auto mma_kv1 = [&](float (&a)[96], uint32_t xo, int s) {
#pragma unroll
        for (int k = 0; k < 4; k++) wgmma_n128_ss<0, 1, 0>(a, dsc<1024, 1>(s * ST + xo + k * 2), dsc<1024, 1>(WV + s * ST + k * 128), 1);
      };
      auto epi_kv = [&](float (&a)[96], uint32_t (&xf)[32], uint32_t tile, float r0, float r1) {
        uint32_t o[8][4];
#pragma unroll
        for (int j = 3; j >= 0; j--) {
          const uint32_t z = j < 3 ? (xf[(j + 5) * 4] | (j < 2 ? o[j + 2][0] | o[j + 6][0] : 0)) & blockIdx.y : 0;
          pack_kv(a, j + 4, r0, r1, o[j + 4], z);
          swap_kv(xf, tile, j + 4, o[j + 4], (o[j + 4][2] | o[j + 4][3]) & blockIdx.y);
          pack_kv(a, j, r0, r1, o[j], z);
          swap_kv(xf, tile, j, o[j]);
        }
      };
      mbar_wait(mb + B_FULL + 8, 1);
      if (!wg) bar_sync(3, 256);
      pinr<0, 64>(acc0); pinr<0, 64>(acc1);
      wg_fence();
      mma_kv1(acc1, xo1, 0); mma_kv1(acc0, xo0, 0); mma_kv1(acc1, xo1, 1);
      if (GSPLIT == 2) mma_kv1(acc0, xo0, 1);
      mbar_wait(mb + B_FULL + 16, 1);
      wg_fence();
      mma_kv1(acc1, xo1, 2);
      mbar_wait(mb + (wg ? B_FULL + 24 : B_F15), wg);
      wg_fence();
      mma_kv1(acc1, xo1, 3);
      wg_commit();
      bar_arrive(4 - wg, 256);
      static_for<16, 24>(center);
      pinr<64, 96>(acc0); pinr<64, 96>(acc1);
      mbar_wait(mb + B_AUX, 0);
      wg_wait<0>();
      pinr<0, 64>(acc0); pinr<0, 64>(acc1);
      TS(4);
      epi_kv(acc1, xf1, wg * 2 + (hf ^ 1), rs[1][0], rs[1][1]);
      pinu(xf1);
      bar_sync(5 - wg, 256);
      wg_fence();
      if (GSPLIT == 1) mma_kv1(acc0, xo0, 1);
      mma_kv1(acc0, xo0, 2); mma_kv1(acc0, xo0, 3);
      wg_commit();
      mma_q(acc1, xf1, xo1, false);
      wg_commit();
      if (wg) bar_arrive(5, 256);
      else { fence_async_smem(); bar_arrive(6, 256); }
      if (tid >= 240) sts4(sm + OFF_STATS + (tid & 15) * 128 + ((tid & 7) << 4), 0x3F803F80u, 0x3F803F80u, 0x3F803F80u, 0x3F803F80u);
      wg_wait<1>();
      pinr<0, 64>(acc0);
      if (lane == 0) mbar_arrive(mb + B_EVA);
      TS(6);
      epi_kv(acc0, xf0, wg * 2 + hf, rs[0][0], rs[0][1]);
      fence_async_smem();
      TS(7);
      pinu(xf0);
      if (wg) {
        float ka[36];
        auto mma_kv = [&](uint32_t tile, int i, int acc) {
          const uint32_t o = (sk >> 4) + tile * 512 + i * 128;
          wgmma_n72_ss<1, 1, 0>(ka, dsc<1024, 1>(dlo(sb, 8192) + o), dsc<1024, 1>(dlo(sb + STAGE_B, OFF_STATS - STAGE_B) + o * (1u - (1u << 16))), acc);
        };
#pragma unroll
        for (int i = 0; i < 36; i++) ka[i] = 0.f;
        bar_sync(6, 256);
        wg_fence();
#pragma unroll
        for (int i = 0; i < 4; i++) {
          mma_kv(2, i, i); mma_kv(3, i, 1); mma_kv(hf ^ 1, i, 1);
#pragma unroll
          for (int j = 2 * i; j < 2 * i + 2; j++)
            wgmma_n64_rs<1, 64>(acc0, xf0[j * 4], xf0[j * 4 + 1], xf0[j * 4 + 2], xf0[j * 4 + 3], dsc<1024, 1>(WD + (sk >> 4) + (j >> 2) * ST + (j & 3) * 128), 1);
        }
        const int bk = get_b(), kq = (bk & 15) * 8 + (bk >> 4);
        uint4* dst = &P.s->kvp[kq * 256 + warp * 64 + lane];
        uint32_t* dz = (uint32_t*)&P.s->zp[kq * 16] + warp * 16 + g + t * 8;
        asm volatile("" : "+l"(dst), "+l"(dz));
        mbar_wait(mb + B_LATE, 0);
        bar_sync(7, 256);
        wg_fence();
#pragma unroll
        for (int i = 0; i < 4; i++) mma_kv(hf, i, 1);
        wg_commit();
        bar_arrive(8, 256);
        wg_wait<0>();
        pin(ka); pinr<64, 96>(acc0);
        uint32_t kw[8];
#pragma unroll
        for (int i = 0; i < 8; i++) {
          const int j = (i & 3) * 4 + (i >> 2) * 2;
          asm("{\n.reg .pred p;\nsetp.ne.u32 p, %5, 0;\n@p cvt.rn.bf16x2.f32 %0, %4, %3;\n@!p cvt.rn.bf16x2.f32 %0, %2, %1;\n}"
              : "=r"(kw[i]) : "f"(ka[j]), "f"(ka[j + 1]), "f"(ka[16 + j]), "f"(ka[17 + j]), "r"(warp & 2));
        }
        st_rlx4(dst, make_uint4(kw[0], kw[1], kw[2], kw[3]));
        st_rlx4(dst + 32, make_uint4(kw[4], kw[5], kw[6], kw[7]));
        if (t < 2) st_rlx(dz, __float_as_uint(t ? ka[34] : ka[32]));
        if (lane == 0) mbar_arrive(mb + B_EVB);
        TS(8);
      } else {
        bar_arrive(7, 256);
        bar_sync(8, 256);
        wg_fence();
        mma_q(acc0, xf0, xo0, false);
      }
      const uint32_t t1 = clock64(), kvb = 2 * STAGE_B + (2 + (hf ^ 1)) * UNIT - sk;
      b1 = get_b();
      uint32_t* of = &P.s->ocnt[(b1 >> 3) * 32];
      od1 = &P.s->obuf[(((b1 >> 4) * 4 + wg * 2 + (hf ^ 1)) * 64 + (b1 & 7)) * 128 + t128];
      uint32_t ka0 = sm + kvb + wid * 1024 + (lane & 7) * 128 + (((lane >> 3) ^ (lane & 7)) << 4), ka1 = sm + kvb + wid * 1024 + (t * 2 + g) * 128 + ((4 ^ (t * 2 + g)) << 4);
      const uint8_t* g0 = smem_raw + sk + STAGE_B + tid * 16, *g1 = smem_raw + sk + UNIT + g * 256 + wid * 32 + t * 8;
      const uint8_t* h0 = (const uint8_t*)&P.s->kvp[(b1 & 15) * 8 * 256 + tid], *h1 = (const uint8_t*)&P.s->zp[((b1 & 15) * 8 + g) * 16] + wid * 32 + t * 8;
      asm volatile("" : "+r"(ka0), "+r"(ka1), "+l"(g0), "+l"(g1), "+l"(h0), "+l"(h1), "+l"(of), "+l"(od1));
      while ((uint32_t)clock64() - t1 < SDELAY) {}
      if (!wg) bar_sync(9, 256);
      wg_fence();
      mma_q(acc1, xf1, xo1, true);
      wg_commit();
      if (wg) bar_arrive(9, 256);
      wg_wait<0>();
      pinr<64, 96>(acc1); pinr<64, 96>(acc0);
      uint32_t pq[16];
      epi_q(acc1, rs[1][0], rs[1][1], pq);
      bar_sync(11 + wg + zero_after(pq), 128);
      wg_fence();
      mma_q(acc0, xf0, xo0, true);
      wg_commit();
      TS(5);
      {
        uint4 gv[8]; uint2 gz;
        uint32_t m[8], a[4];
        float z0, z1;
#pragma unroll
        for (int s = 0; s < 8; s++) { m[s] = ~blockIdx.y; asm volatile("" : "=r"(gv[s].x), "=r"(gv[s].y), "=r"(gv[s].z), "=r"(gv[s].w), "+r"(m[s])); }
        mbar_wait(mb + B_KVP, 0);
        TS(28);
        wg_wait<0>();
        pinr<64, 96>(acc0);
        if (lane == 0) mbar_arrive(mb + B_KVB);
#pragma unroll 1
        for (int it = 0; it < SPIN_LIMIT; it++) {
          gz = ld_gen2(g1);
#pragma unroll
          for (int s = 0; s < 8; s++) if (m[s] == SENT) gv[s] = ld_gen4(g0 + s * 4096);
          g0 = h0; g1 = h1;
          uint32_t mm = max(gz.x, gz.y);
          z0 = __uint_as_float(gz.x); z1 = __uint_as_float(gz.y);
#pragma unroll
          for (int o = 4; o < 32; o <<= 1) { z0 += __shfl_xor_sync(~0u, z0, o); z1 += __shfl_xor_sync(~0u, z1, o); }
#pragma unroll
          for (int s = 0; s < 8; s++) m[s] = max4(0, gv[s]);
#pragma unroll
          for (int s = 0; s < 8; s += 2) mm = __vimax3_u32(mm, m[s], m[s + 1]);
          a[0] = hadd2(hadd2(hadd2(gv[0].x, gv[1].x), hadd2(gv[2].x, gv[3].x)), hadd2(hadd2(gv[4].x, gv[5].x), hadd2(gv[6].x, gv[7].x)));
          a[1] = hadd2(hadd2(hadd2(gv[0].y, gv[1].y), hadd2(gv[2].y, gv[3].y)), hadd2(hadd2(gv[4].y, gv[5].y), hadd2(gv[6].y, gv[7].y)));
          a[2] = hadd2(hadd2(hadd2(gv[0].z, gv[1].z), hadd2(gv[2].z, gv[3].z)), hadd2(hadd2(gv[4].z, gv[5].z), hadd2(gv[6].z, gv[7].z)));
          a[3] = hadd2(hadd2(hadd2(gv[0].w, gv[1].w), hadd2(gv[2].w, gv[3].w)), hadd2(hadd2(gv[4].w, gv[5].w), hadd2(gv[6].w, gv[7].w)));
          pinu(a);
          if (!__any_sync(~0u, mm == SENT)) break;
          TSV(20, 1);
        }
        TS(23);
        stsm4(ka0, a[0], a[1], a[2], a[3]);
        const uint32_t zz = pack2(g ? z1 : z0, g ? z1 : z0);
        if (lane < 8) sts4(ka1, zz, zz, zz, zz);
        fence_async_smem();
        bar_sync(1, 256);
        if (tid == 0) asm volatile("red.relaxed.gpu.global.add.u32 [%0], 1;" :: "l"(of) : "memory");
      }
      TS(21);
      auto make_o = [&](uint4 (&o)[4], auto first) {
        float oa[2][20];
        wg_fence();
#pragma unroll
        for (int ks = 0; ks < 4; ks++)
          wgmma_n40_rs<1, 0>(oa[ks >> 1], pq[ks * 4], pq[ks * 4 + 1], pq[ks * 4 + 2], pq[ks * 4 + 3], dsc<1024, 1>(dlo(sb, 8192) + (kvb >> 4) + ks * 128), ks & 1);
        wg_commit();
        if constexpr (!decltype(first)::value) {
          pinu(xf0);
#pragma unroll
          for (int q = 0; q < 32; q++) { acc[q * 2] = bf_lo(xf0[q]); acc[q * 2 + 1] = bf_hi(xf0[q]); }
          pin(acc);
          mbar_wait(mb + B_BF, 0);
        }
        wg_wait<0>();
        pin(oa[0]); pin(oa[1]);
        if (decltype(first)::value && lane < 2) mbar_arrive_rem(eb);
#pragma unroll
        for (int h = 0; h < 2; h++) {
          const float (&d)[20] = oa[h];
          const float i0 = rcp(d[16] + 1e-6f), i1 = rcp(d[18] + 1e-6f);
#pragma unroll
          for (int k2 = 0; k2 < 2; k2++) {
            o[h * 2 + k2] = make_uint4(pack2(d[k2 * 8] * i0, d[k2 * 8 + 1] * i0), pack2(d[k2 * 8 + 2] * i1, d[k2 * 8 + 3] * i1),
                                       pack2(d[k2 * 8 + 4] * i0, d[k2 * 8 + 5] * i0), pack2(d[k2 * 8 + 6] * i1, d[k2 * 8 + 7] * i1));
            if (decltype(first)::value && !h) st_rlx4(od1 + k2 * 1024, o[k2]);
          }
          if (decltype(first)::value && !h) { sched_fence(); TS(24); }
        }
      };
      make_o(ost[1], std::true_type{});
      epi_q(acc0, rs[0][0], rs[0][1], pq);
      if (AEARLY) { st_rlx4(od1 + 2048, ost[1][2]); st_rlx4(od1 + 3072, ost[1][3]); }
      make_o(ost[0], std::false_type{});
    }
   {
    IDS(b1);
    const int mb3 = rb * 4 + wg * 2 + hf;
    const int row0 = mb3 * 64 + warp * 16 + g;
    {
      uint4 abuf[3][4];
      const uint4* const ain = &P.s->obuf[mb3 * 64 * 128 + t128];
      uint4* const od0 = &P.s->obuf[(mb3 * 64 + 32 + s3 * 4) * 128 + t128];
#pragma unroll
      for (int i = 0; i < 4; i++) pin4(ost[0][i]);
      wg_fence();
#pragma unroll
      for (int k = 0; k < 4; k++) wgmma_n128_rs<1, 0>(acc, ost[0][k].x, ost[0][k].y, ost[0][k].z, ost[0][k].w, dsc<1024, 1>(dlo(sb + 4 * UNIT, 8192) + k * 128), 1);
      wg_commit();
      TS(29);
      if (!AEARLY) { st_rlx4(od1 + 2048, ost[1][2]); st_rlx4(od1 + 3072, ost[1][3]); }
      uint32_t la = sm + t128 * 16, ev = eb + 8;
      asm volatile("" : "+r"(la), "+r"(ev));
      auto fetch = [&](uint32_t off, uint4 (&a)[4]) { const uint32_t ra = la + off; a[0] = lds4_o<0>(ra); a[1] = lds4_o<2048>(ra); a[2] = lds4_o<4096>(ra); a[3] = lds4_o<6144>(ra); };
      auto check = [&](int p, uint4 (&a)[4]) {
        if (__any_sync(~0u, max(max4(max4(0, a[0]), a[1]), max4(max4(0, a[2]), a[3])) == SENT)) {
          int pl = p; asm volatile("" : "+r"(pl));
          const uint4* q = ain + frag_of(pl);
#pragma unroll 1
          for (int it = 0;; it++) {
            uint32_t mm = 0;
#pragma unroll
            for (int i = 0; i < 4; i++) { const uint32_t m = max4(0, a[i]); mm = max(mm, m); if (m == SENT) a[i] = ld_rlx4(q + i * 128); }
            if (!__any_sync(~0u, mm == SENT)) break;
            TSV(27, p < 3 ? 1 : p < 5 ? 100 : 10000);
            SPINCHK(it, 5);
          }
        }
        if (lane < 2) mbar_arrive_rem(ev);
        ev = (ev & ~0x38u) | ((ev + 8) & 0x38u);
      };
      auto mma = [&](int p, uint32_t bs, uint4 (&a)[4]) {
#pragma unroll
        for (int i = 0; i < 4; i++) pin4(a[i]);
        wg_fence();
#pragma unroll
        for (int k = 0; k < 4; k++) wgmma_n128_rs<1, 0>(acc, a[k].x, a[k].y, a[k].z, a[k].w, dsc<1024, 1>(bs + k * 128), 1);
        wg_commit();
      };
      uint32_t ta = sm + OFF_STATS + wg * 256 + 48;
      mbar_wait(mb + B_WR, 0);
      uint4 tp = lds4(ta);
      mbar_wait(mb + B_BF + 8, 0);
      TS(3);
      fetch(ring_of(1, wg), abuf[1]);
      check(1, abuf[1]);
      mma(1, dlo(sb + 11 * UNIT, 8192), abuf[1]);
      TS(25);
      mbar_wait(mb + B_BF + 16, 0);
      fetch(ring_of(2, wg), abuf[2]);
      st_rlx4(od0, ost[0][0]); st_rlx4(od0 + 128, ost[0][1]);
      check(2, abuf[2]);
      mbar_wait(mb + B_BF + 24, 0);
      fetch(ring_of(3, wg), abuf[0]);
      mma(2, dlo(sb + 18 * UNIT, 8192), abuf[2]);
      st_rlx4(od0 + 256, ost[0][2]); st_rlx4(od0 + 384, ost[0][3]);
      wg_wait<2>();
      check(3, abuf[0]);
      mbar_wait(mb + B_BF + 32, 0);
      TS(26);
#pragma unroll 1
      for (int p = 3; p < 15; p += 3) {
        static_for<0, 3>([&](auto jc) {
          constexpr int j = decltype(jc)::value;
          const uint4 tc = tp;
          const uint32_t bs = __shfl_sync(~0u, tc.x, 0);
          wg_wait<1>();
#pragma unroll
          for (int i = 0; i < 4; i++) pin4(abuf[(j + 1) % 3][i]);
          tp = lds4_o<16 * j + 16>(ta);
          fetch(tc.y, abuf[(j + 1) % 3]);
          mma(p + j, bs, abuf[j]);
          if (!CHKF) mbar_wait(tc.z, tc.w);
          check(p + j + 1, abuf[(j + 1) % 3]);
          if (CHKF) mbar_wait(tc.z, tc.w);
        });
        ta += 48;
      }
      mma(15, __shfl_sync(~0u, tp.x, 0), abuf[0]);
      wg_wait<2>();
      if (lane == 0) mbar_arrive(mb + B_E16);
      static_for<0, 16>([&](auto jc) { constexpr int j = decltype(jc)::value; const float2 v = lds2f_o<sb + OFF_COLSUM + j * 32>(own + t * 8); wf[j * 2] = v.x; wf[j * 2 + 1] = v.y; });
      pin(wf);
      wg_wait<0>();
      pin(acc);
#pragma unroll
      for (int i = 0; i < 4; i++) { pin4(abuf[0][i]); pin4(abuf[1][i]); pin4(abuf[2][i]); }
    }
    TS(10);
    {
      float s0 = 0.f, q0 = 0.f, e0 = 0.f, s1 = 0.f, q1 = 0.f, e1 = 0.f;
#pragma unroll
      for (int j = 0; j < 16; j++) {
        const float a = acc[j * 4], c = acc[j * 4 + 1], d = acc[j * 4 + 2], e = acc[j * 4 + 3];
        s0 += a + c; q0 = fmaf(a, a, fmaf(c, c, q0)); e0 = fmaf(a, wf[j * 2], fmaf(c, wf[j * 2 + 1], e0));
        s1 += d + e; q1 = fmaf(d, d, fmaf(e, e, q1)); e1 = fmaf(d, wf[j * 2], fmaf(e, wf[j * 2 + 1], e1));
      }
      const bool od = t & 1;
      float s = (od ? s1 : s0) + __shfl_xor_sync(~0u, od ? s0 : s1, 1);
      float q = (od ? q1 : q0) + __shfl_xor_sync(~0u, od ? q0 : q1, 1);
      float e = (od ? e1 : e0) + __shfl_xor_sync(~0u, od ? e0 : e1, 1);
      s += __shfl_xor_sync(~0u, s, 2); q += __shfl_xor_sync(~0u, q, 2); e += __shfl_xor_sync(~0u, e, 2);
      if (t < 2) red4(&P.s->st2[row0 + t * 8], s, q, e, 1.f);
    }
    TS(11);
    const uint32_t ts = clock64();
    const uint32_t msc = sm + OFF_STATS;
    const uint32_t hst = sm + 4 * UNIT + wg * STAGE_B + warp * 4096, gslot = sm + unit_of(rank ? GT1 : GT0, wid);
    bar_sync(1, 256);
#pragma unroll
    for (int j = 0; j < 8; j++)
      stsm4(hst + (lane & 15) * 256 + (((2 * j + (lane >> 4)) ^ (lane & 7)) << 4), pack2(acc[j * 8], acc[j * 8 + 1]), pack2(acc[j * 8 + 2], acc[j * 8 + 3]),
            pack2(acc[j * 8 + 4], acc[j * 8 + 5]), pack2(acc[j * 8 + 6], acc[j * 8 + 7]));
    uint32_t wa[8][4][4], wd[8][2][4];
    const uint32_t a0 = gslot + ((lane >> 4) * 8 + (lane & 7)) * 64 + ((((lane >> 3) & 1) ^ ((lane >> 1) & 3)) << 4);
    auto load_gu = [&](auto ic) { constexpr int i = decltype(ic)::value; ldsm4t_o<(i >> 2) * 1024 + ((i >> 1) & 1) * 8192>(a0 ^ ((i & 1) << 5), wa[i >> 2][i & 3]); };
    uint32_t tx;
    {
      const int row = rb * 256 + tid;
      const uint4* sp = &P.s->st2[row], *sq = &P.s->st2[row ^ 256];
      const float sw = __uint_as_float((lds1(mb + B_SW) & ~255u) | 128);
      uint4 v[2];
      if (fidx >= 0) mbar_wait(mb + B_FFN, 0);
      TS(15);
      static_for<0, GU1>(load_gu);
      while ((uint32_t)clock64() - ts < SDEL2) {}
      v[0] = ld_rlx4(sp); v[1] = ld_rlx4(sq);
      static_for<GU1, GU2>(load_gu);
#pragma unroll 1
      for (int it = 0; __any_sync(~0u, min(v[0].w, v[1].w) != 0x41000000u) && it < SPIN_LIMIT; it++) {
        if (v[0].w != 0x41000000u) v[0] = ld_rlx4(sp);
        if (v[1].w != 0x41000000u) v[1] = ld_rlx4(sq);
        TSV(22, 1);
      }
      if (lane == 0) mbar_arrive(mb + B_EVA);
      TS(12);
      uint32_t k[2];
#pragma unroll
      for (int i = 0; i < 2; i++) {
        const float mean = __uint_as_float(v[i].x) * (1.f / D_);
        const float rstd = rsq(fmaxf(fmaf(-mean, mean, __uint_as_float(v[i].y) * (1.f / D_)), 0.f) + 1e-5f);
        const uint32_t u = __float_as_uint(rstd * fmaf(-mean, sw, __uint_as_float(v[i].z)));
        k[i] = min(((u ^ ((uint32_t)((int)u >> 31) | 0x80000000u)) & ~2047u), 0xFFFFF000u) | (2047 - (row ^ (i << 8)));
        if (i == 0 && (warp >> 1) == hf) sts2f(sm + OFF_LNP + (wg * 64 + (tid & 63)) * 8, rstd, -mean * rstd);
      }
      const uint32_t hi = max(k[0], k[1]);
      uint32_t m1 = __reduce_max_sync(~0u, hi), m2 = __reduce_max_sync(~0u, hi == m1 ? min(k[0], k[1]) : hi);
      if (lane == 0) sts2f(msc + wid * 8, __uint_as_float(m1), __uint_as_float(m2));
      bar_sync(1, 256);
      const uint32_t kk = lds1(msc + (lane & 15) * 4);
      m1 = __reduce_max_sync(~0u, kk); m2 = __reduce_max_sync(~0u, kk == m1 ? 0 : kk);
      const int c0 = 2047 - (m1 & 2047), c1 = 2047 - (m2 & 2047);
      if ((c0 >> 4) == mb3 * 4 + warp || (c1 >> 4) == mb3 * 4 + warp) {
        const int ra = (lane & 4) ? c1 : c0, rd = (lane & 16) ? c1 : c0;
        uint32_t h0, h1, h2, h3;
        ldsm4_o<0>(hst + (ra & 15) * 256 + ((((lane & 3) * 4 + (lane >> 3)) ^ (ra & 7)) << 4), h0, h1, h2, h3);
        const float2 pr = lds2f(sm + OFF_LNP + (wid * 16 + (rd & 15)) * 8);
        if ((rd >> 4) == mb3 * 4 + warp) {
          const int slot = (rb & 6) + (lane >> 4);
          uint4* d = &P.s->hsel[c3 * 128 + (g & 3) * 32 + slot * 4 + t];
          st_rlx4(d, make_uint4(pack2(fmaf(bf_lo(h0), pr.x, pr.y), fmaf(bf_hi(h0), pr.x, pr.y)), pack2(fmaf(bf_lo(h1), pr.x, pr.y), fmaf(bf_hi(h1), pr.x, pr.y)),
                                pack2(fmaf(bf_lo(h2), pr.x, pr.y), fmaf(bf_hi(h2), pr.x, pr.y)), pack2(fmaf(bf_lo(h3), pr.x, pr.y), fmaf(bf_hi(h3), pr.x, pr.y))));
          if (!(lane & 15)) st_rlx(&P.s->cand[c3 * 32 + slot], (lane & 16) ? m2 : m1);
          st_rlx4(d + 1024, make_uint4(h0, h1, h2, h3));
        }
      }
      tx = clock64();
      if (tid == 0) { sts2f(msc + 64, __uint_as_float(m1), __uint_as_float(m2)); mbar_arrive(mb + B_OUT); }
    }
    TS(13);
    static_for<GU2, 32>(load_gu);
    const uint32_t dl = sm + (wid & 1) * 4096 + ((lane >> 4) * 8 + (lane & 7)) * 128 + ((((lane >> 3) & 1) ^ (lane & 7)) << 4);
    uint32_t da = dl + unit_of(DT0, wid >> 1), db = dl + unit_of(rank ? DT1 : DT0, 4 + (wid >> 1));
    uint32_t* yp = (uint32_t*)&P.s->ybuf[((wid * 8 + t * 2) * NFFN + fidx) * 2] + g;
    uint32_t k1, k2;
    uint2 key;
    {
      float gu[2][4][4];
      uint4 xb[4];
      uint32_t m[4];
      const uint4* xp = &P.s->hsel[wid * 128 + lane];
      const uint2* kp = (const uint2*)&P.s->cand[wid * 32] + t;
      uint32_t ps = gslot + g * 32;
      asm volatile("" : "+l"(xp), "+l"(kp), "+l"(yp), "+r"(db), "+r"(ps));
      if (fidx >= 0) mbar_wait(mb + B_FFD, 0);
      static_for<0, 8>([&](auto ic) { constexpr int i = decltype(ic)::value; ldsm4t_o<(i & 1) * 2048>(da ^ ((i >> 1) << 5), wd[i >> 1][i & 1]); });
      TS(9);
      while ((uint32_t)clock64() - tx < XDELAY) {}
      key = ld_rlx2(kp);
#pragma unroll
      for (int i = 0; i < 4; i++) xb[i] = ld_rlx4(xp + i * 32);
      if (fidx >= 0) mbar_wait(mb + B_KVP, 1);
#pragma unroll 1
      for (int it = 0; it < SPIN_LIMIT; it++) {
#pragma unroll
        for (int i = 0; i < 4; i++) m[i] = max4(0, xb[i]);
        if (!__any_sync(~0u, __vimax3_u32(__vimax3_u32(max(key.x, key.y), m[0], m[1]), m[2], m[3]) == SENT)) break;
        key = ld_rlx2(kp);
#pragma unroll
        for (int i = 0; i < 4; i++) if (m[i] == SENT) xb[i] = ld_rlx4(xp + i * 32);
        TSV(20, 100);
      }
      TS(14);
      const uint32_t hi = max(key.x, key.y);
      k1 = __reduce_max_sync(~0u, hi); k2 = __reduce_max_sync(~0u, hi == k1 ? min(key.x, key.y) : hi);
#pragma unroll
      for (int i = 0; i < 32; i++) gu[i >> 4][(i >> 2) & 3][i & 3] = 0.f;
#pragma unroll
      for (int ks = 0; ks < 8; ks++) {
#pragma unroll
        for (int i = 0; i < 4; i++) mma16816(gu[ks & 1][i], wa[ks][i], (ks & 1) ? xb[ks >> 1].z : xb[ks >> 1].x, (ks & 1) ? xb[ks >> 1].w : xb[ks >> 1].y);
        if (ks == 1) {
          const uint32_t dd = db | (__float_as_uint(gu[1][3][0]) & blockIdx.y);
          static_for<0, 8>([&](auto ic) { constexpr int i = decltype(ic)::value; ldsm4t_o<(i & 1) * 2048>(dd ^ ((i >> 1) << 5), wd[4 + (i >> 1)][i & 1]); });
        }
      }
#pragma unroll
      for (int c = 0; c < 2; c++) {
        const uint32_t kc = c ? key.y : key.x;
        float o[8];
#pragma unroll
        for (int j = 0; j < 8; j++) o[j] = gu[0][(j >> 2) + (j & 1) * 2][(j & 2) + c] + gu[1][(j >> 2) + (j & 1) * 2][(j & 2) + c];
        asm volatile("{\n.reg .pred p;\nsetp.ge.u32 p, %9, %10;\n@p st.shared.v4.f32 [%0], {%1,%2,%3,%4};\n@p st.shared.v4.f32 [%0+16], {%5,%6,%7,%8};\n}"
                     :: "r"(ps + (kc == k1 ? 0 : 256)), "f"(o[0]), "f"(o[1]), "f"(o[2]), "f"(o[3]), "f"(o[4]), "f"(o[5]), "f"(o[6]), "f"(o[7]), "r"(kc), "r"(k2) : "memory");
      }
    }
    bar_sync(1, 256);
    {
      float g0 = 0.f, g1 = 0.f, u0 = 0.f, u1 = 0.f;
      static_for<0, 8>([&](auto wc) { constexpr int w = decltype(wc)::value;
        constexpr uint32_t o = sb + ((GT0 >> (5 * w)) & 31) * UNIT;
        const uint32_t ad = own + lane * 8 + (w == 0 || w == 7 ? sk : w < 3 ? -sk : 0);
        const float2 a = lds2f_o<o>(ad), c = lds2f_o<o + 256>(ad);
        g0 += a.x; u0 += a.y; g1 += c.x; u1 += c.y; });
      const uint32_t act = pack2(g0 * rcp(1.f + ex2(-1.4426950408889634f * g0)) * u0, g1 * rcp(1.f + ex2(-1.4426950408889634f * g1)) * u1);
      uint32_t bq[4];
#pragma unroll
      for (int i = 0; i < 4; i++) {
        const uint32_t lo = __shfl_sync(~0u, act, 8 * t + i), hi = __shfl_sync(~0u, act, 8 * t + 4 + i);
        bq[i] = __byte_perm(lo, hi, (g & 1) ? 0x7632 : 0x5410);
      }
      TS(16);
      float ya[8][4];
#pragma unroll
      for (int i = 0; i < 8; i++) { ya[i][0] = 0.f; ya[i][1] = 0.f; ya[i][2] = 0.f; ya[i][3] = 0.f; }
#pragma unroll
      for (int ks = 0; ks < 2; ks++)
#pragma unroll
        for (int i = 0; i < 8; i++) mma16816(ya[i], wd[i][ks], bq[ks * 2], bq[ks * 2 + 1]);
#pragma unroll
      for (int h = 0; h < 2; h++) {
        float o[4];
#pragma unroll
        for (int j = 0; j < 4; j++) o[j] = t == 0 ? ya[h * 4][j] : t == 1 ? ya[h * 4 + 1][j] : t == 2 ? ya[h * 4 + 2][j] : ya[h * 4 + 3][j];
        asm volatile("{\n.reg .pred p;\nsetp.ge.s32 p, %3, 0;\n@p st.relaxed.gpu.global.u32 [%0], %1;\n@p st.relaxed.gpu.global.u32 [%0+%4], %2;\n}"
                     :: "l"(yp + h * (64 * NFFN * 8)), "r"(pack2(o[0], o[1])), "r"(pack2(o[2], o[3])), "r"(fidx), "n"(NFFN * 32) : "memory");
      }
    }
    if (tid == 0) { sts2f(msc + 80, __uint_as_float(k1), __uint_as_float(k2)); mbar_arrive(mb + B_SEL); }
    TS(17);
    const uint32_t ty = clock64();
    if (wid < 7) {
      const uint4* yq = &P.s->ybuf[b * NFFN * 2 + tid];
      const uint32_t ks = (tid & 1) ? k2 : k1, grp = 3 - ((ks >> 9) & 3);
      const int fs = grp * 2 + (__shfl_sync(~0u, key.y, grp) == ks);
      const uint32_t* fq = (const uint32_t*)P.s->hsel + (((b >> 4) * 4 + ((b >> 2) & 3)) * 32 + fs * 4 + ((tid >> 2) & 3)) * 4 + (b & 3);
      float gate = rcp(1.f + ex2(-1.4426950408889634f * __uint_as_float(ks ^ (~(uint32_t)((int)ks >> 31) | 0x80000000u))));
      __nv_bfloat16* op = P.out + (size_t)(2047 - (ks & 2047)) * D_ + b * 8 + (tid >> 1);
      asm volatile("" : "+l"(yq), "+l"(fq), "+l"(op), "+f"(gate));
      while ((uint32_t)clock64() - ty < YDELAY) {}
      uint4 v;
      uint32_t fn = 0, fh = 0;
#pragma unroll 1
      for (int it = 0; it < SPIN_LIMIT; it++) {
        v = ld_rlx4(yq);
        if (wid == 0) { fn = ld_rlx(fq); fh = ld_rlx(fq + 4096); }
        TSV(22, 100);
        if (!__any_sync(~0u, max4(max(fn, fh), v) == SENT)) break;
      }
      const float base = (tid & 2) ? bf_hi(fh) + bf_hi(fn) : bf_lo(fh) + bf_lo(fn);
      TS(18);
      const bool p4 = lane & 16, p3 = lane & 8, p2 = lane & 4;
      const uint32_t w0 = __shfl_xor_sync(~0u, p4 ? v.x : v.z, 16), w1 = __shfl_xor_sync(~0u, p4 ? v.y : v.w, 16), o0 = p4 ? v.z : v.x, o1 = p4 ? v.w : v.y;
      const float y0 = bf_lo(o0) + bf_lo(w0), y1 = bf_hi(o0) + bf_hi(w0), y2 = bf_lo(o1) + bf_lo(w1), y3 = bf_hi(o1) + bf_hi(w1);
      const float z0 = (p3 ? y2 : y0) + __shfl_xor_sync(~0u, p3 ? y0 : y2, 8), z1 = (p3 ? y3 : y1) + __shfl_xor_sync(~0u, p3 ? y1 : y3, 8);
      float z = (p2 ? z1 : z0) + __shfl_xor_sync(~0u, p2 ? z0 : z1, 4);
      z += __shfl_xor_sync(~0u, z, 2);
      const uint32_t yx = msc + 128;
      if (!(lane & 2)) sts1(yx + wid * 64 + ((lane & 1) * 8 + (lane >> 2)) * 4, __float_as_uint(z));
      bar_sync(13, 224);
      if (tid < 16) {
        float y = 0.f;
#pragma unroll
        for (int w = 0; w < 7; w++) y += __uint_as_float(lds1(yx + w * 64 + tid * 4));
        *op = __float2bfloat16(fmaf(y, gate, base));
      }
      if (b == 0 && tid == 32) P.s->epoch = lds1(mb + B_SW) & 255;
    }
    TS(19); TSG(31);
    if (warp == 0) TS_DUMP(wg);
   }
  }
}

typedef CUresult (*EncodeFn)(CUtensorMap*, CUtensorMapDataType, cuuint32_t, void*, const cuuint64_t*, const cuuint64_t*, const cuuint32_t*,
                             const cuuint32_t*, CUtensorMapInterleave, CUtensorMapSwizzle, CUtensorMapL2promotion, CUtensorMapFloatOOBfill);
void make_map(EncodeFn enc, CUtensorMap* m, const void* p, int rank, std::initializer_list<cuuint64_t> dims, std::initializer_list<cuuint64_t> str,
              std::initializer_list<cuuint32_t> box, CUtensorMapSwizzle sw) {
  const cuuint32_t es[4] = {1, 1, 1, 1};
  enc(m, CU_TENSOR_MAP_DATA_TYPE_BFLOAT16, rank, const_cast<void*>(p), dims.begin(), str.begin(), box.begin(), es, CU_TENSOR_MAP_INTERLEAVE_NONE, sw,
      CU_TENSOR_MAP_L2_PROMOTION_L2_128B, CU_TENSOR_MAP_FLOAT_OOB_FILL_NONE);
}

}

extern "C" void kernel_launch(void* const* d_in, const int* in_sizes, int n_in, void* d_out, int out_size) {
  (void)in_sizes; (void)n_in; (void)out_size;
  Ptrs P;
  P.x = (const __nv_bfloat16*)d_in[0]; P.wqkv = (const __nv_bfloat16*)d_in[1]; P.wo = (const __nv_bfloat16*)d_in[2];
  P.wr = (const __nv_bfloat16*)d_in[4]; P.wg = (const __nv_bfloat16*)d_in[5]; P.wu = (const __nv_bfloat16*)d_in[6];
  P.wd = (const __nv_bfloat16*)d_in[7]; P.out = (__nv_bfloat16*)d_out;
  cudaGetSymbolAddress((void**)&P.s, g_scratch);
  void* fn = nullptr;
  cudaDriverEntryPointQueryResult q;
  cudaGetDriverEntryPoint("cuTensorMapEncodeTiled", &fn, cudaEnableDefault, &q);
  EncodeFn enc = (EncodeFn)fn;
  Maps T;
  constexpr CUtensorMapSwizzle S128 = CU_TENSOR_MAP_SWIZZLE_128B, S64 = CU_TENSOR_MAP_SWIZZLE_64B;
  make_map(enc, &T.m[M_X], P.x, 2, {D_, S_}, {D_ * 2}, {64, 128}, S128);
  make_map(enc, &T.m[M_W], P.wqkv, 3, {D_, D_, 3}, {3 * D_ * 2, D_ * 2}, {64, 64, 2}, S128);
  make_map(enc, &T.m[M_Q], P.wqkv, 2, {3 * D_, D_}, {3 * D_ * 2}, {64, 64}, S128);
  make_map(enc, &T.m[M_O], P.wo, 4, {64, 64, 16, 16}, {D_ * 2, 64 * D_ * 2, 128}, {64, 64, 1, 2}, S128);
  make_map(enc, &T.m[M_S], P.wo, 4, {64, 64, 16, 16}, {D_ * 2, 64 * D_ * 2, 128}, {64, 16, 4, 2}, S128);
  make_map(enc, &T.m[M_G], P.wg, 3, {F_, D_, 1}, {F_ * 2, F_ * 2 * D_}, {32, 128, 1}, S64);
  make_map(enc, &T.m[M_U], P.wu, 3, {F_, D_, 1}, {F_ * 2, F_ * 2 * D_}, {32, 128, 1}, S64);
  make_map(enc, &T.m[M_D], P.wd, 3, {64, F_, 16}, {D_ * 2, 128}, {64, 32, 2}, S128);
  make_map(enc, &T.m[M_L], P.wd, 2, {64, F_ * 16}, {128}, {8, 16}, CU_TENSOR_MAP_SWIZZLE_NONE);
  cudaFuncSetAttribute(fused_kernel, cudaFuncAttributeMaxDynamicSharedMemorySize, SMEM_BYTES);
  fused_kernel<<<NCTA, 384, SMEM_BYTES>>>(P, T);
}
```

```cpp
#include <cuda_runtime.h>
#include <cuda.h>
#include <cuda_bf16.h>
#include <stdint.h>
#include <type_traits>
#include <initializer_list>

namespace {

constexpr int S_ = 2048, D_ = 1024, F_ = 3584;
constexpr int NCTA = 128, NFFN = 112;
constexpr uint32_t SENT = 0xFFFFFFFFu;
constexpr int SPIN_LIMIT = 1 << 20;

#define ADELAY 0
#define ADELAY2 100
#define PFA 6
#define PF0 8
#define WPF0 8
#define DPER 1200
#define PDEPTH 2
#define PSTART 4000
#define PPER 1700
#define PEARLY 5
#define PLEAD 0
#define RST 1
#define PSUB 2
#define HOLDP 1
#define QHOLD 1
#define NPULL 12
#define CDELAY 0
#define NOUTW 3
#define YDELAY 650
#define EFX 0
#define EFW 1
#define EFF 1
#define KLEAD 13
#define GDELAY 1000
#define NDIR 6
#define PULL0 3
#define FD0 400
#define FD1 800
#define SPF 1
#define MPF 1
#define TLBW 2
#define GORD 0
#define GSPLIT 2
#define EFW0 0
#define EFX0 0
#define EFWK 8
#define PSLEEP 20
#define P3PULL 1
#define RST2 4
#define KDELAY 450
#define AEARLY 0
#define BHOLD 4
#define SDELAY 100
#define FSTAG 150
#define OFL 0
#define CHKF 1
#define BEV 1
#define DLATE 4
#define P3GATE 3
#define ACCSW 1
#define B45 B_E
#define SDEL2 500
#define XDELAY 500
#define GU1 8
#define GU2 20
#define WD1 10
#define ODELAY 0
#define NOOUT 0
constexpr int OUNR =
  2;
#define P3N 2
#define HALFMAP 1
#define KWARP 7
#define FEARLY 1
#define MFIRST 350
#define MKV 950
#define MO 850
#define MST 1450
#define MSTE 13
#define AFIRST 0
#define MWIDE 0
#define PLAG 8
#define PSTEP 0
#define PSTOP 3
#define DMASK 0x5550
#define PFST 1
#define W0OFF 2
#define MAPM 2
#define XWPF 0
constexpr uint32_t STAGE_B = 57344;
constexpr uint32_t OFF_STATS = 229376;
constexpr uint32_t OFF_COLSUM = 231424;
constexpr uint32_t OFF_BARS = 232192;
constexpr uint32_t SMEM_BYTES = 232448;
constexpr uint32_t B_FULL = 0, B_EMPTY = 32, B_E = 64, B_AUX = 128, B_EVA = 136, B_EVB = 144, B_BF = 152, B_LATE = 232, B_FFN = 240, B_SW = 248;
constexpr uint32_t B_OUT = B_FULL, B_SEL = B_FULL + 8, B_WR = B_FULL + 16, B_FFD = B_FULL + 24, B_E16 = B_EMPTY + 16, B_KVB = B_EMPTY + 8, B_DUMMY = B_SW + 4,
                   B_GATE = B_EMPTY + 24, B_ID = B_BF + 56, B_KVP = B_BF + 64, B_F15 = B_BF + 72;
#define B_HOLD B_F15
#define HOLDPAR 0
constexpr uint32_t UNIT = 8192;
constexpr uint32_t sb = 1024;
constexpr uint32_t bars = sb + OFF_BARS;
constexpr uint64_t tab5(int a, int b, int c, int d, int e, int f, int g, int h, int i = 0, int j = 0) {
  return (uint64_t)a | (uint64_t)b << 5 | (uint64_t)c << 10 | (uint64_t)d << 15 | (uint64_t)e << 20 | (uint64_t)f << 25 | (uint64_t)g << 30 | (uint64_t)h << 35 |
         (uint64_t)i << 40 | (uint64_t)j << 45;
}
constexpr uint64_t BT0 = tab5(4, 11, 18, 25, 7, 9, 16, 0), BT1 = tab5(4, 11, 18, 25, 21, 23, 2, 0);
constexpr uint64_t GT0 = tab5(2, 21, 23, 18, 0, 25, 14, 7), GT1 = tab5(16, 7, 9, 18, 0, 25, 14, 21);
constexpr uint64_t DT0 = tab5(6, 13, 20, 27, 9, 10, 16, 17), DT1 = tab5(6, 13, 20, 27, 23, 24, 2, 3);
__device__ __forceinline__ uint32_t unit_of(uint64_t tab, int i) { return ((uint32_t)(tab >> (5 * i)) & 31) * UNIT; }
__device__ __forceinline__ uint32_t ring_of(int p, int w) { return (p & 1) * (2 * STAGE_B) + ((p & 2) ? 49152 + w * STAGE_B : w * UNIT); }
constexpr uint32_t OFF_LNP = OFF_STATS + 1024;

struct Scratch {
  uint4 obuf[32 * 64 * 128];
  uint4 kvp[16 * 8 * 256];
  uint4 zp[16 * 8 * 16];
  uint4 ybuf[NCTA * NFFN * 2];
  uint4 st1[S_];
  uint4 csp[16 * 8 * 48];
  uint4 st2[S_];
  uint4 hsel[2 * 8 * 128];
  uint32_t cand[8 * 32];
  uint32_t when[32 * 32];
  unsigned epoch;
};
__device__ __align__(1024) Scratch g_scratch;
#define TS_DECL
#define TS(i)
#define TSG(i)
#define TSV(i, v)
#define TSD(i)
#define RTS_DECL
#define RTS(i)
#define RTS_DUMP
#define TS_DUMP(slot)
#define PTS(i)
#define g_dbgv(i, v)

#define SPANS(i)
__device__ __forceinline__ uint32_t smem_u32(const void* p) { return (uint32_t)__cvta_generic_to_shared(p); }
__device__ __forceinline__ void mbar_init(uint32_t bar, uint32_t cnt) { asm volatile("mbarrier.init.shared::cta.b64 [%0], %1;" :: "r"(bar), "r"(cnt) : "memory"); }
__device__ __forceinline__ void mbar_expect_tx(uint32_t bar, uint32_t bytes) { asm volatile("mbarrier.arrive.expect_tx.shared::cta.b64 _, [%0], %1;" :: "r"(bar), "r"(bytes) : "memory"); }
__device__ __forceinline__ void mbar_arrive(uint32_t bar) { asm volatile("mbarrier.arrive.shared::cta.b64 _, [%0];" :: "r"(bar) : "memory"); }
#define SPINCHK(it, code) if ((it) > SPIN_LIMIT) break
__device__ __forceinline__ void mbar_wait(uint32_t bar, uint32_t parity) {
  asm volatile("{\n.reg .pred p;\n.reg .u32 c;\nmov.u32 c, 0;\n"
               "WL:\nmbarrier.try_wait.parity.shared::cta.b64 p, [%0], %1;\n@p bra WD;\n"
               "add.u32 c, c, 1;\nsetp.lt.u32 p, c, 1048576;\n@p bra WL;\nWD:\n}" :: "r"(bar), "r"(parity) : "memory");
}
__device__ __forceinline__ bool mbar_test(uint32_t bar, uint32_t parity) {
  uint32_t ok;
  asm volatile("{\n.reg .pred p;\nmbarrier.test_wait.parity.shared::cta.b64 p, [%1], %2;\nselp.u32 %0, 1, 0, p;\n}" : "=r"(ok) : "r"(bar), "r"(parity) : "memory");
  return ok;
}
__device__ __forceinline__ uint64_t l2_stream() { uint64_t p; asm("createpolicy.fractional.L2::evict_first.b64 %0, 1.0;" : "=l"(p)); return p; }
__device__ __forceinline__ void tma_2d(uint32_t dst, const CUtensorMap* tm, int c0, int c1, uint32_t bar, bool stream) {
  if (stream) asm volatile("cp.async.bulk.tensor.2d.shared::cluster.global.mbarrier::complete_tx::bytes.L2::cache_hint [%0], [%1, {%3, %4}], [%2], %5;"
                           :: "r"(dst), "l"(tm), "r"(bar), "r"(c0), "r"(c1), "l"(l2_stream()) : "memory");
  else asm volatile("cp.async.bulk.tensor.2d.shared::cluster.global.mbarrier::complete_tx::bytes [%0], [%1, {%3, %4}], [%2];"
                    :: "r"(dst), "l"(tm), "r"(bar), "r"(c0), "r"(c1) : "memory");
}
__device__ __forceinline__ void tma_3d(uint32_t dst, const CUtensorMap* tm, int c0, int c1, int c2, uint32_t bar, bool stream) {
  if (stream) asm volatile("cp.async.bulk.tensor.3d.shared::cluster.global.mbarrier::complete_tx::bytes.L2::cache_hint [%0], [%1, {%3, %4, %5}], [%2], %6;"
                           :: "r"(dst), "l"(tm), "r"(bar), "r"(c0), "r"(c1), "r"(c2), "l"(l2_stream()) : "memory");
  else asm volatile("cp.async.bulk.tensor.3d.shared::cluster.global.mbarrier::complete_tx::bytes [%0], [%1, {%3, %4, %5}], [%2];"
                    :: "r"(dst), "l"(tm), "r"(bar), "r"(c0), "r"(c1), "r"(c2) : "memory");
}
__device__ __forceinline__ void tma_pf_3d(const CUtensorMap* tm, int c0, int c1, int c2) {
  asm volatile("cp.async.bulk.prefetch.tensor.3d.L2.global [%0, {%1, %2, %3}];" :: "l"(tm), "r"(c0), "r"(c1), "r"(c2) : "memory");
}
__device__ __forceinline__ void tma_4d(uint32_t dst, const CUtensorMap* tm, int c0, int c1, int c2, int c3, uint32_t bar) {
  asm volatile("cp.async.bulk.tensor.4d.shared::cluster.global.mbarrier::complete_tx::bytes [%0], [%1, {%3, %4, %5, %6}], [%2];"
               :: "r"(dst), "l"(tm), "r"(bar), "r"(c0), "r"(c1), "r"(c2), "r"(c3) : "memory");
}
__device__ __forceinline__ void tma_2d_mc(uint32_t dst, const CUtensorMap* tm, int c0, int c1, uint32_t bar, bool stream) {
  if (stream) asm volatile("cp.async.bulk.tensor.2d.shared::cluster.global.mbarrier::complete_tx::bytes.multicast::cluster.L2::cache_hint [%0], [%1, {%3, %4}], [%2], %5, %6;"
                           :: "r"(dst), "l"(tm), "r"(bar), "r"(c0), "r"(c1), "h"((uint16_t)3), "l"(l2_stream()) : "memory");
  else asm volatile("cp.async.bulk.tensor.2d.shared::cluster.global.mbarrier::complete_tx::bytes.multicast::cluster [%0], [%1, {%3, %4}], [%2], %5;"
                    :: "r"(dst), "l"(tm), "r"(bar), "r"(c0), "r"(c1), "h"((uint16_t)3) : "memory");
}
__device__ __forceinline__ bool elect_one() {
  uint32_t p;
  asm volatile("{\n.reg .pred q;\nelect.sync _|q, 0xFFFFFFFF;\nselp.u32 %0, 1, 0, q;\n}" : "=r"(p));
  return p;
}
__device__ __forceinline__ void bulk_load_mc(uint32_t dst, const void* src, uint32_t bytes, uint32_t bar) {
  asm volatile("cp.async.bulk.shared::cluster.global.mbarrier::complete_tx::bytes.multicast::cluster [%0], [%1], %2, [%3], %4;"
               :: "r"(dst), "l"(src), "r"(bytes), "r"(bar), "h"((uint16_t)3) : "memory");
}
__device__ __forceinline__ void bulk_load(uint32_t dst, const void* src, uint32_t bytes, uint32_t bar) {
  asm volatile("cp.async.bulk.shared::cluster.global.mbarrier::complete_tx::bytes [%0], [%1], %2, [%3];" :: "r"(dst), "l"(src), "r"(bytes), "r"(bar) : "memory");
}
__device__ __forceinline__ void bulk_store(void* dst, uint32_t src, uint32_t bytes) {
  asm volatile("cp.async.bulk.global.shared::cta.bulk_group [%0], [%1], %2;" :: "l"(dst), "r"(src), "r"(bytes) : "memory");
}
__device__ __forceinline__ void mbar_arrive_rem(uint32_t bar) { asm volatile("mbarrier.arrive.shared::cluster.b64 _, [%0];" :: "r"(bar) : "memory"); }
__device__ __forceinline__ void st_async4(uint32_t addr, const uint4& v, uint32_t bar) {
  asm volatile("st.async.shared::cluster.mbarrier::complete_tx::bytes.v4.b32 [%0], {%1,%2,%3,%4}, [%5];" :: "r"(addr), "r"(v.x), "r"(v.y), "r"(v.z), "r"(v.w), "r"(bar) : "memory");
}
template <uint32_t O> __device__ __forceinline__ void ldsm4_o(uint32_t addr, uint32_t& a, uint32_t& b, uint32_t& c, uint32_t& d) {
  asm volatile("ldmatrix.sync.aligned.m8n8.x4.shared.b16 {%0,%1,%2,%3}, [%4+%5];" : "=r"(a), "=r"(b), "=r"(c), "=r"(d) : "r"(addr), "n"(O) : "memory");
}
template <uint32_t O> __device__ __forceinline__ void ldsm4t_o(uint32_t addr, uint32_t (&r)[4]) {
  asm volatile("ldmatrix.sync.aligned.m8n8.x4.trans.shared.b16 {%0,%1,%2,%3}, [%4+%5];" : "=r"(r[0]), "=r"(r[1]), "=r"(r[2]), "=r"(r[3]) : "r"(addr), "n"(O) : "memory");
}
__device__ __forceinline__ void mma16816(float (&c)[4], const uint32_t (&a)[4], uint32_t b0, uint32_t b1) {
  asm("mma.sync.aligned.m16n8k16.row.col.f32.bf16.bf16.f32 {%0,%1,%2,%3}, {%4,%5,%6,%7}, {%8,%9}, {%0,%1,%2,%3};"
      : "+f"(c[0]), "+f"(c[1]), "+f"(c[2]), "+f"(c[3]) : "r"(a[0]), "r"(a[1]), "r"(a[2]), "r"(a[3]), "r"(b0), "r"(b1));
}
__device__ __forceinline__ void l2_prefetch(const void* p) { asm volatile("prefetch.global.L2 [%0];" :: "l"(p) : "memory"); }
__device__ __forceinline__ uint32_t ld_line(const void* p) { uint32_t v; asm volatile("ld.global.cg.L2::128B.u32 %0, [%1];" : "=r"(v) : "l"(p) : "memory"); return v; }
__device__ __forceinline__ void tmap_prefetch(const CUtensorMap* tm) { asm volatile("prefetch.tensormap [%0];" :: "l"(tm) : "memory"); }
__device__ __forceinline__ void wg_fence() { asm volatile("wgmma.fence.sync.aligned;" ::: "memory"); }
__device__ __forceinline__ void wg_commit() { asm volatile("wgmma.commit_group.sync.aligned;" ::: "memory"); }
template <int N> __device__ __forceinline__ void wg_wait() { asm volatile("wgmma.wait_group.sync.aligned %0;" :: "n"(N) : "memory"); }
template <int N> __device__ __forceinline__ void pin(float (&d)[N]) {
#pragma unroll
  for (int i = 0; i < N; i++) asm volatile("" : "+f"(d[i]) :: "memory");
}
__device__ __forceinline__ void pin4(uint4& v) { asm volatile("" : "+r"(v.x), "+r"(v.y), "+r"(v.z), "+r"(v.w) :: "memory"); }
template <uint32_t SBO, uint32_t SWZ> __device__ __forceinline__ uint64_t dsc(uint32_t lo) { return ((uint64_t)((SBO >> 4) | (SWZ << 30)) << 32) | lo; }
__host__ __device__ constexpr uint32_t dlo(uint32_t addr, uint32_t lbo) { return (addr >> 4) | ((lbo >> 4) << 16); }
__device__ __forceinline__ void bar_sync(int id, int n) { asm volatile("bar.sync %0, %1;" :: "r"(id), "r"(n) : "memory"); }
__device__ __forceinline__ void bar_arrive(int id, int n) { asm volatile("bar.arrive %0, %1;" :: "r"(id), "r"(n) : "memory"); }
__device__ __forceinline__ void fence_async_smem() { asm volatile("fence.proxy.async.shared::cta;" ::: "memory"); }
__device__ __forceinline__ void fence_gpu() { asm volatile("fence.acq_rel.gpu;" ::: "memory"); }
__device__ __forceinline__ uint4 ld_cg4(const void* p) { uint4 v; asm volatile("ld.global.cg.v4.u32 {%0,%1,%2,%3}, [%4];" : "=r"(v.x), "=r"(v.y), "=r"(v.z), "=r"(v.w) : "l"(p) : "memory"); return v; }
__device__ __forceinline__ uint4 ld_rlx4(const void* p) { uint4 v; asm volatile("ld.relaxed.gpu.global.v4.u32 {%0,%1,%2,%3}, [%4];" : "=r"(v.x), "=r"(v.y), "=r"(v.z), "=r"(v.w) : "l"(p) : "memory"); return v; }
__device__ __forceinline__ uint32_t ld_rlx(const void* p) { uint32_t v; asm volatile("ld.relaxed.gpu.global.u32 %0, [%1];" : "=r"(v) : "l"(p) : "memory"); return v; }
__device__ __forceinline__ void st_rlx4(void* p, uint4 v) { asm volatile("st.relaxed.gpu.global.v4.u32 [%0], {%1,%2,%3,%4};" :: "l"(p), "r"(v.x), "r"(v.y), "r"(v.z), "r"(v.w) : "memory"); }
__device__ __forceinline__ void st_rlx2(void* p, uint32_t a, uint32_t b) { asm volatile("st.relaxed.gpu.global.v2.u32 [%0], {%1,%2};" :: "l"(p), "r"(a), "r"(b) : "memory"); }
__device__ __forceinline__ void st_rlx(void* p, uint32_t a) { asm volatile("st.relaxed.gpu.global.u32 [%0], %1;" :: "l"(p), "r"(a) : "memory"); }
__device__ __forceinline__ void red4(void* p, float a, float b, float c, float d) { asm volatile("red.relaxed.gpu.global.add.v4.f32 [%0], {%1,%2,%3,%4};" :: "l"(p), "f"(a), "f"(b), "f"(c), "f"(d) : "memory"); }
__device__ __forceinline__ uint32_t pack2(float lo, float hi) { uint32_t r; asm("cvt.rn.bf16x2.f32 %0, %1, %2;" : "=r"(r) : "f"(hi), "f"(lo)); return r; }
__device__ __forceinline__ float bf_lo(uint32_t v) { return __uint_as_float(v << 16); }
__device__ __forceinline__ float bf_hi(uint32_t v) { return __uint_as_float(v & 0xFFFF0000u); }
__device__ __forceinline__ void stsm4(uint32_t addr, uint32_t a, uint32_t b, uint32_t c, uint32_t d) {
  asm volatile("stmatrix.sync.aligned.m8n8.x4.shared.b16 [%0], {%1,%2,%3,%4};" :: "r"(addr), "r"(a), "r"(b), "r"(c), "r"(d) : "memory");
}
template <uint32_t O> __device__ __forceinline__ void stsm4_o(uint32_t addr, uint32_t a, uint32_t b, uint32_t c, uint32_t d) {
  asm volatile("stmatrix.sync.aligned.m8n8.x4.shared.b16 [%0+%5], {%1,%2,%3,%4};" :: "r"(addr), "r"(a), "r"(b), "r"(c), "r"(d), "n"(O) : "memory");
}
__device__ __forceinline__ void sts4(uint32_t addr, uint32_t a, uint32_t b, uint32_t c, uint32_t d) { asm volatile("st.shared.v4.u32 [%0], {%1,%2,%3,%4};" :: "r"(addr), "r"(a), "r"(b), "r"(c), "r"(d) : "memory"); }
__device__ __forceinline__ void sts2f(uint32_t addr, float a, float b) { asm volatile("st.shared.v2.f32 [%0], {%1,%2};" :: "r"(addr), "f"(a), "f"(b) : "memory"); }
__device__ __forceinline__ void sts1(uint32_t addr, uint32_t a) { asm volatile("st.shared.u32 [%0], %1;" :: "r"(addr), "r"(a) : "memory"); }
__device__ __forceinline__ float2 lds2f(uint32_t addr) { float2 v; asm volatile("ld.shared.v2.f32 {%0,%1}, [%2];" : "=f"(v.x), "=f"(v.y) : "r"(addr) : "memory"); return v; }
template <uint32_t O> __device__ __forceinline__ float2 lds2f_o(uint32_t addr) { float2 v; asm volatile("ld.shared.v2.f32 {%0,%1}, [%2+%3];" : "=f"(v.x), "=f"(v.y) : "r"(addr), "n"(O) : "memory"); return v; }
template <int I, int N, class F> __device__ __forceinline__ void static_for(F&& f) { if constexpr (I < N) { f(std::integral_constant<int, I>{}); static_for<I + 1, N>(f); } }
__device__ __forceinline__ uint4 lds4(uint32_t addr) { uint4 v; asm volatile("ld.shared.v4.u32 {%0,%1,%2,%3}, [%4];" : "=r"(v.x), "=r"(v.y), "=r"(v.z), "=r"(v.w) : "r"(addr) : "memory"); return v; }
__device__ __forceinline__ uint32_t lds1(uint32_t addr) { uint32_t v; asm volatile("ld.shared.u32 %0, [%1];" : "=r"(v) : "r"(addr) : "memory"); return v; }
__device__ __forceinline__ float ex2(float x) { float y; asm("ex2.approx.ftz.f32 %0, %1;" : "=f"(y) : "f"(x)); return y; }
__device__ __forceinline__ uint32_t max4(uint32_t m, const uint4& v) { return __vimax3_u32(__vimax3_u32(m, v.x, v.y), v.z, v.w); }
__device__ __forceinline__ float rsq(float x) { float y; asm("rsqrt.approx.ftz.f32 %0, %1;" : "=f"(y) : "f"(x)); return y; }
__device__ __forceinline__ float rcp(float x) { float y; asm("rcp.approx.ftz.f32 %0, %1;" : "=f"(y) : "f"(x)); return y; }
__device__ __forceinline__ uint2 ld_rlx2(const void* p) { uint2 v; asm volatile("ld.relaxed.gpu.global.v2.u32 {%0,%1}, [%2];" : "=r"(v.x), "=r"(v.y) : "l"(p) : "memory"); return v; }
template <uint32_t O> __device__ __forceinline__ uint4 lds4_o(uint32_t addr) { uint4 v; asm volatile("ld.shared.v4.u32 {%0,%1,%2,%3}, [%4+%5];" : "=r"(v.x), "=r"(v.y), "=r"(v.z), "=r"(v.w) : "r"(addr), "n"(O) : "memory"); return v; }
__device__ __forceinline__ uint32_t phi2(float u0, float u1, float rl, uint32_t r2) {
  uint32_t pu, r;
  asm("cvt.rn.relu.bf16x2.f32 %0, %1, %2;" : "=r"(pu) : "f"(u1), "f"(u0));
  asm("fma.rn.bf16x2 %0, %1, %2, %3;" : "=r"(r) : "r"(pu), "r"(r2), "r"(pack2(__saturatef(ex2(u0 * rl) + 1e-6f), __saturatef(ex2(u1 * rl) + 1e-6f))));
  return r;
}
__device__ __forceinline__ uint32_t dup2(float r) { uint32_t v; asm("cvt.rn.relu.bf16x2.f32 %0, %1, %1;" : "=r"(v) : "f"(r)); return v; }
__device__ __forceinline__ uint32_t zero_after(const uint32_t (&v)[16]) {
  uint32_t z = 0;
#pragma unroll
  for (int i = 0; i < 16; i++) z |= v[i];
  return z & 0x80008000u;
}
__device__ __forceinline__ uint32_t hadd2(uint32_t a, uint32_t b) { uint32_t v; asm("add.rn.bf16x2 %0, %1, %2;" : "=r"(v) : "r"(a), "r"(b)); return v; }
__device__ __forceinline__ void sched_fence() { asm volatile("{\n.reg .pred p;\n.reg .u64 c;\nSF:\nmov.u64 c, %clock64;\nsetp.eq.u64 p, c, 0;\n@p bra SF;\n}" ::: "memory"); }
__device__ __forceinline__ uint4 ld_gen4(const void* p) { uint4 v; asm volatile("ld.relaxed.gpu.v4.u32 {%0,%1,%2,%3}, [%4];" : "=r"(v.x), "=r"(v.y), "=r"(v.z), "=r"(v.w) : "l"(p) : "memory"); return v; }
__device__ __forceinline__ uint2 ld_gen2(const void* p) { uint2 v; asm volatile("ld.relaxed.gpu.v2.u32 {%0,%1}, [%2];" : "=r"(v.x), "=r"(v.y) : "l"(p) : "memory"); return v; }
__device__ __forceinline__ uint32_t now_ns() { uint32_t v; asm volatile("mov.u32 %0, %%globaltimer_lo;" : "=r"(v) :: "memory"); return v; }
__device__ __forceinline__ void meet(uint32_t* mine, const uint4* all, int first, int after, uint32_t bar) {
  const uint32_t t0 = now_ns() & ~1u;
  if ((threadIdx.x & 31) == 0) st_rlx(mine, t0);
  while ((int)(now_ns() - t0) < first) {}
  uint4 v;
#pragma unroll 1
  for (int it = 0; it < SPIN_LIMIT; it++) { v = ld_rlx4(all); if (!__any_sync(~0u, max4(0, v) == SENT)) break; }
  const int d = min(__reduce_max_sync(~0u, max(max((int)(v.x - t0), (int)(v.y - t0)), max((int)(v.z - t0), (int)(v.w - t0)))), 100000) + after;
  mbar_wait(bar, 0);
  while ((int)(now_ns() - t0) < d) {}
}
__device__ __forceinline__ uint32_t lane_id() { uint32_t v; asm volatile("mov.u32 %0, %%laneid;" : "=r"(v)); return v; }
template <int A, int B, int N> __device__ __forceinline__ void pinr(float (&d)[N]) {
#pragma unroll
  for (int i = A; i < B; i++) asm volatile("" : "+f"(d[i]) :: "memory");
}
template <int N> __device__ __forceinline__ void pinu(uint32_t (&d)[N]) {
#pragma unroll
  for (int i = 0; i < N; i++) asm volatile("" : "+r"(d[i]) :: "memory");
}

template<int TA, int TB, int OFF, int SZ> __device__ __forceinline__ void wgmma_n192_ss(float (&d)[SZ], uint64_t da, uint64_t db, int scale_d) {
  asm volatile("{\n.reg .pred p;\nsetp.ne.b32 p, %98, 0;\n"
    "wgmma.mma_async.sync.aligned.m64n192k16.f32.bf16.bf16 {%0,%1,%2,%3,%4,%5,%6,%7,%8,%9,%10,%11,%12,%13,%14,%15,%16,%17,%18,%19,%20,%21,%22,%23,%24,%25,%26,%27,%28,%29,%30,%31,%32,%33,%34,%35,%36,%37,%38,%39,%40,%41,%42,%43,%44,%45,%46,%47,%48,%49,%50,%51,%52,%53,%54,%55,%56,%57,%58,%59,%60,%61,%62,%63,%64,%65,%66,%67,%68,%69,%70,%71,%72,%73,%74,%75,%76,%77,%78,%79,%80,%81,%82,%83,%84,%85,%86,%87,%88,%89,%90,%91,%92,%93,%94,%95}, %96, %97, p, 1, 1, %99, %100;\n}\n"
    : "+f"(d[OFF+0]), "+f"(d[OFF+1]), "+f"(d[OFF+2]), "+f"(d[OFF+3]), "+f"(d[OFF+4]), "+f"(d[OFF+5]), "+f"(d[OFF+6]), "+f"(d[OFF+7]),
      "+f"(d[OFF+8]), "+f"(d[OFF+9]), "+f"(d[OFF+10]), "+f"(d[OFF+11]), "+f"(d[OFF+12]), "+f"(d[OFF+13]), "+f"(d[OFF+14]), "+f"(d[OFF+15]),
      "+f"(d[OFF+16]), "+f"(d[OFF+17]), "+f"(d[OFF+18]), "+f"(d[OFF+19]), "+f"(d[OFF+20]), "+f"(d[OFF+21]), "+f"(d[OFF+22]), "+f"(d[OFF+23]),
      "+f"(d[OFF+24]), "+f"(d[OFF+25]), "+f"(d[OFF+26]), "+f"(d[OFF+27]), "+f"(d[OFF+28]), "+f"(d[OFF+29]), "+f"(d[OFF+30]), "+f"(d[OFF+31]),
      "+f"(d[OFF+32]), "+f"(d[OFF+33]), "+f"(d[OFF+34]), "+f"(d[OFF+35]), "+f"(d[OFF+36]), "+f"(d[OFF+37]), "+f"(d[OFF+38]), "+f"(d[OFF+39]),
      "+f"(d[OFF+40]), "+f"(d[OFF+41]), "+f"(d[OFF+42]), "+f"(d[OFF+43]), "+f"(d[OFF+44]), "+f"(d[OFF+45]), "+f"(d[OFF+46]), "+f"(d[OFF+47]),
      "+f"(d[OFF+48]), "+f"(d[OFF+49]), "+f"(d[OFF+50]), "+f"(d[OFF+51]), "+f"(d[OFF+52]), "+f"(d[OFF+53]), "+f"(d[OFF+54]), "+f"(d[OFF+55]),
      "+f"(d[OFF+56]), "+f"(d[OFF+57]), "+f"(d[OFF+58]), "+f"(d[OFF+59]), "+f"(d[OFF+60]), "+f"(d[OFF+61]), "+f"(d[OFF+62]), "+f"(d[OFF+63]),
      "+f"(d[OFF+64]), "+f"(d[OFF+65]), "+f"(d[OFF+66]), "+f"(d[OFF+67]), "+f"(d[OFF+68]), "+f"(d[OFF+69]), "+f"(d[OFF+70]), "+f"(d[OFF+71]),
      "+f"(d[OFF+72]), "+f"(d[OFF+73]), "+f"(d[OFF+74]), "+f"(d[OFF+75]), "+f"(d[OFF+76]), "+f"(d[OFF+77]), "+f"(d[OFF+78]), "+f"(d[OFF+79]),
      "+f"(d[OFF+80]), "+f"(d[OFF+81]), "+f"(d[OFF+82]), "+f"(d[OFF+83]), "+f"(d[OFF+84]), "+f"(d[OFF+85]), "+f"(d[OFF+86]), "+f"(d[OFF+87]),
      "+f"(d[OFF+88]), "+f"(d[OFF+89]), "+f"(d[OFF+90]), "+f"(d[OFF+91]), "+f"(d[OFF+92]), "+f"(d[OFF+93]), "+f"(d[OFF+94]), "+f"(d[OFF+95])
    : "l"(da), "l"(db), "r"(scale_d), "n"(TA), "n"(TB));
}
template<int TA, int TB, int OFF, int SZ> __device__ __forceinline__ void wgmma_n128_ss(float (&d)[SZ], uint64_t da, uint64_t db, int scale_d) {
  asm volatile("{\n.reg .pred p;\nsetp.ne.b32 p, %66, 0;\n"
    "wgmma.mma_async.sync.aligned.m64n128k16.f32.bf16.bf16 {%0,%1,%2,%3,%4,%5,%6,%7,%8,%9,%10,%11,%12,%13,%14,%15,%16,%17,%18,%19,%20,%21,%22,%23,%24,%25,%26,%27,%28,%29,%30,%31,%32,%33,%34,%35,%36,%37,%38,%39,%40,%41,%42,%43,%44,%45,%46,%47,%48,%49,%50,%51,%52,%53,%54,%55,%56,%57,%58,%59,%60,%61,%62,%63}, %64, %65, p, 1, 1, %67, %68;\n}\n"
    : "+f"(d[OFF+0]), "+f"(d[OFF+1]), "+f"(d[OFF+2]), "+f"(d[OFF+3]), "+f"(d[OFF+4]), "+f"(d[OFF+5]), "+f"(d[OFF+6]), "+f"(d[OFF+7]),
      "+f"(d[OFF+8]), "+f"(d[OFF+9]), "+f"(d[OFF+10]), "+f"(d[OFF+11]), "+f"(d[OFF+12]), "+f"(d[OFF+13]), "+f"(d[OFF+14]), "+f"(d[OFF+15]),
      "+f"(d[OFF+16]), "+f"(d[OFF+17]), "+f"(d[OFF+18]), "+f"(d[OFF+19]), "+f"(d[OFF+20]), "+f"(d[OFF+21]), "+f"(d[OFF+22]), "+f"(d[OFF+23]),
      "+f"(d[OFF+24]), "+f"(d[OFF+25]), "+f"(d[OFF+26]), "+f"(d[OFF+27]), "+f"(d[OFF+28]), "+f"(d[OFF+29]), "+f"(d[OFF+30]), "+f"(d[OFF+31]),
      "+f"(d[OFF+32]), "+f"(d[OFF+33]), "+f"(d[OFF+34]), "+f"(d[OFF+35]), "+f"(d[OFF+36]), "+f"(d[OFF+37]), "+f"(d[OFF+38]), "+f"(d[OFF+39]),
      "+f"(d[OFF+40]), "+f"(d[OFF+41]), "+f"(d[OFF+42]), "+f"(d[OFF+43]), "+f"(d[OFF+44]), "+f"(d[OFF+45]), "+f"(d[OFF+46]), "+f"(d[OFF+47]),
      "+f"(d[OFF+48]), "+f"(d[OFF+49]), "+f"(d[OFF+50]), "+f"(d[OFF+51]), "+f"(d[OFF+52]), "+f"(d[OFF+53]), "+f"(d[OFF+54]), "+f"(d[OFF+55]),
      "+f"(d[OFF+56]), "+f"(d[OFF+57]), "+f"(d[OFF+58]), "+f"(d[OFF+59]), "+f"(d[OFF+60]), "+f"(d[OFF+61]), "+f"(d[OFF+62]), "+f"(d[OFF+63])
    : "l"(da), "l"(db), "r"(scale_d), "n"(TA), "n"(TB));
}
template<int TA, int TB, int OFF, int SZ> __device__ __forceinline__ void wgmma_n64_ss(float (&d)[SZ], uint64_t da, uint64_t db, int scale_d) {
  asm volatile("{\n.reg .pred p;\nsetp.ne.b32 p, %34, 0;\n"
    "wgmma.mma_async.sync.aligned.m64n64k16.f32.bf16.bf16 {%0,%1,%2,%3,%4,%5,%6,%7,%8,%9,%10,%11,%12,%13,%14,%15,%16,%17,%18,%19,%20,%21,%22,%23,%24,%25,%26,%27,%28,%29,%30,%31}, %32, %33, p, 1, 1, %35, %36;\n}\n"
    : "+f"(d[OFF+0]), "+f"(d[OFF+1]), "+f"(d[OFF+2]), "+f"(d[OFF+3]), "+f"(d[OFF+4]), "+f"(d[OFF+5]), "+f"(d[OFF+6]), "+f"(d[OFF+7]),
      "+f"(d[OFF+8]), "+f"(d[OFF+9]), "+f"(d[OFF+10]), "+f"(d[OFF+11]), "+f"(d[OFF+12]), "+f"(d[OFF+13]), "+f"(d[OFF+14]), "+f"(d[OFF+15]),
      "+f"(d[OFF+16]), "+f"(d[OFF+17]), "+f"(d[OFF+18]), "+f"(d[OFF+19]), "+f"(d[OFF+20]), "+f"(d[OFF+21]), "+f"(d[OFF+22]), "+f"(d[OFF+23]),
      "+f"(d[OFF+24]), "+f"(d[OFF+25]), "+f"(d[OFF+26]), "+f"(d[OFF+27]), "+f"(d[OFF+28]), "+f"(d[OFF+29]), "+f"(d[OFF+30]), "+f"(d[OFF+31])
    : "l"(da), "l"(db), "r"(scale_d), "n"(TA), "n"(TB));
}
template<int TA, int TB, int OFF, int SZ> __device__ __forceinline__ void wgmma_n72_ss(float (&d)[SZ], uint64_t da, uint64_t db, int scale_d) {
  asm volatile("{\n.reg .pred p;\nsetp.ne.b32 p, %38, 0;\n"
    "wgmma.mma_async.sync.aligned.m64n72k16.f32.bf16.bf16 {%0,%1,%2,%3,%4,%5,%6,%7,%8,%9,%10,%11,%12,%13,%14,%15,%16,%17,%18,%19,%20,%21,%22,%23,%24,%25,%26,%27,%28,%29,%30,%31,%32,%33,%34,%35}, %36, %37, p, 1, 1, %39, %40;\n}\n"
    : "+f"(d[OFF+0]), "+f"(d[OFF+1]), "+f"(d[OFF+2]), "+f"(d[OFF+3]), "+f"(d[OFF+4]), "+f"(d[OFF+5]), "+f"(d[OFF+6]), "+f"(d[OFF+7]),
      "+f"(d[OFF+8]), "+f"(d[OFF+9]), "+f"(d[OFF+10]), "+f"(d[OFF+11]), "+f"(d[OFF+12]), "+f"(d[OFF+13]), "+f"(d[OFF+14]), "+f"(d[OFF+15]),
      "+f"(d[OFF+16]), "+f"(d[OFF+17]), "+f"(d[OFF+18]), "+f"(d[OFF+19]), "+f"(d[OFF+20]), "+f"(d[OFF+21]), "+f"(d[OFF+22]), "+f"(d[OFF+23]),
      "+f"(d[OFF+24]), "+f"(d[OFF+25]), "+f"(d[OFF+26]), "+f"(d[OFF+27]), "+f"(d[OFF+28]), "+f"(d[OFF+29]), "+f"(d[OFF+30]), "+f"(d[OFF+31]),
      "+f"(d[OFF+32]), "+f"(d[OFF+33]), "+f"(d[OFF+34]), "+f"(d[OFF+35])
    : "l"(da), "l"(db), "r"(scale_d), "n"(TA), "n"(TB));
}
template<int TB, int OFF, int SZ> __device__ __forceinline__ void wgmma_n64_rs(float (&d)[SZ], uint32_t a0, uint32_t a1, uint32_t a2, uint32_t a3, uint64_t db, int scale_d) {
  asm volatile("{\n.reg .pred p;\nsetp.ne.b32 p, %37, 0;\n"
    "wgmma.mma_async.sync.aligned.m64n64k16.f32.bf16.bf16 {%0,%1,%2,%3,%4,%5,%6,%7,%8,%9,%10,%11,%12,%13,%14,%15,%16,%17,%18,%19,%20,%21,%22,%23,%24,%25,%26,%27,%28,%29,%30,%31}, {%32,%33,%34,%35}, %36, p, 1, 1, %38;\n}\n"
    : "+f"(d[OFF+0]), "+f"(d[OFF+1]), "+f"(d[OFF+2]), "+f"(d[OFF+3]), "+f"(d[OFF+4]), "+f"(d[OFF+5]), "+f"(d[OFF+6]), "+f"(d[OFF+7]),
      "+f"(d[OFF+8]), "+f"(d[OFF+9]), "+f"(d[OFF+10]), "+f"(d[OFF+11]), "+f"(d[OFF+12]), "+f"(d[OFF+13]), "+f"(d[OFF+14]), "+f"(d[OFF+15]),
      "+f"(d[OFF+16]), "+f"(d[OFF+17]), "+f"(d[OFF+18]), "+f"(d[OFF+19]), "+f"(d[OFF+20]), "+f"(d[OFF+21]), "+f"(d[OFF+22]), "+f"(d[OFF+23]),
      "+f"(d[OFF+24]), "+f"(d[OFF+25]), "+f"(d[OFF+26]), "+f"(d[OFF+27]), "+f"(d[OFF+28]), "+f"(d[OFF+29]), "+f"(d[OFF+30]), "+f"(d[OFF+31])
    : "r"(a0), "r"(a1), "r"(a2), "r"(a3), "l"(db), "r"(scale_d), "n"(TB));
}
template<int TB, int OFF, int SZ> __device__ __forceinline__ void wgmma_n40_rs(float (&d)[SZ], uint32_t a0, uint32_t a1, uint32_t a2, uint32_t a3, uint64_t db, int scale_d) {
  asm volatile("{\n.reg .pred p;\nsetp.ne.b32 p, %25, 0;\n"
    "wgmma.mma_async.sync.aligned.m64n40k16.f32.bf16.bf16 {%0,%1,%2,%3,%4,%5,%6,%7,%8,%9,%10,%11,%12,%13,%14,%15,%16,%17,%18,%19}, {%20,%21,%22,%23}, %24, p, 1, 1, %26;\n}\n"
    : "+f"(d[OFF+0]), "+f"(d[OFF+1]), "+f"(d[OFF+2]), "+f"(d[OFF+3]), "+f"(d[OFF+4]), "+f"(d[OFF+5]), "+f"(d[OFF+6]), "+f"(d[OFF+7]),
      "+f"(d[OFF+8]), "+f"(d[OFF+9]), "+f"(d[OFF+10]), "+f"(d[OFF+11]), "+f"(d[OFF+12]), "+f"(d[OFF+13]), "+f"(d[OFF+14]), "+f"(d[OFF+15]),
      "+f"(d[OFF+16]), "+f"(d[OFF+17]), "+f"(d[OFF+18]), "+f"(d[OFF+19])
    : "r"(a0), "r"(a1), "r"(a2), "r"(a3), "l"(db), "r"(scale_d), "n"(TB));
}
template<int TB, int OFF, int SZ> __device__ __forceinline__ void wgmma_n128_rs(float (&d)[SZ], uint32_t a0, uint32_t a1, uint32_t a2, uint32_t a3, uint64_t db, int scale_d) {
  asm volatile("{\n.reg .pred p;\nsetp.ne.b32 p, %69, 0;\n"
    "wgmma.mma_async.sync.aligned.m64n128k16.f32.bf16.bf16 {%0,%1,%2,%3,%4,%5,%6,%7,%8,%9,%10,%11,%12,%13,%14,%15,%16,%17,%18,%19,%20,%21,%22,%23,%24,%25,%26,%27,%28,%29,%30,%31,%32,%33,%34,%35,%36,%37,%38,%39,%40,%41,%42,%43,%44,%45,%46,%47,%48,%49,%50,%51,%52,%53,%54,%55,%56,%57,%58,%59,%60,%61,%62,%63}, {%64,%65,%66,%67}, %68, p, 1, 1, %70;\n}\n"
    : "+f"(d[OFF+0]), "+f"(d[OFF+1]), "+f"(d[OFF+2]), "+f"(d[OFF+3]), "+f"(d[OFF+4]), "+f"(d[OFF+5]), "+f"(d[OFF+6]), "+f"(d[OFF+7]),
      "+f"(d[OFF+8]), "+f"(d[OFF+9]), "+f"(d[OFF+10]), "+f"(d[OFF+11]), "+f"(d[OFF+12]), "+f"(d[OFF+13]), "+f"(d[OFF+14]), "+f"(d[OFF+15]),
      "+f"(d[OFF+16]), "+f"(d[OFF+17]), "+f"(d[OFF+18]), "+f"(d[OFF+19]), "+f"(d[OFF+20]), "+f"(d[OFF+21]), "+f"(d[OFF+22]), "+f"(d[OFF+23]),
      "+f"(d[OFF+24]), "+f"(d[OFF+25]), "+f"(d[OFF+26]), "+f"(d[OFF+27]), "+f"(d[OFF+28]), "+f"(d[OFF+29]), "+f"(d[OFF+30]), "+f"(d[OFF+31]),
      "+f"(d[OFF+32]), "+f"(d[OFF+33]), "+f"(d[OFF+34]), "+f"(d[OFF+35]), "+f"(d[OFF+36]), "+f"(d[OFF+37]), "+f"(d[OFF+38]), "+f"(d[OFF+39]),
      "+f"(d[OFF+40]), "+f"(d[OFF+41]), "+f"(d[OFF+42]), "+f"(d[OFF+43]), "+f"(d[OFF+44]), "+f"(d[OFF+45]), "+f"(d[OFF+46]), "+f"(d[OFF+47]),
      "+f"(d[OFF+48]), "+f"(d[OFF+49]), "+f"(d[OFF+50]), "+f"(d[OFF+51]), "+f"(d[OFF+52]), "+f"(d[OFF+53]), "+f"(d[OFF+54]), "+f"(d[OFF+55]),
      "+f"(d[OFF+56]), "+f"(d[OFF+57]), "+f"(d[OFF+58]), "+f"(d[OFF+59]), "+f"(d[OFF+60]), "+f"(d[OFF+61]), "+f"(d[OFF+62]), "+f"(d[OFF+63])
    : "r"(a0), "r"(a1), "r"(a2), "r"(a3), "l"(db), "r"(scale_d), "n"(TB));
}

struct Ptrs { const __nv_bfloat16 *x, *wqkv, *wo, *wr, *wg, *wu, *wd; __nv_bfloat16* out; Scratch* s; };

enum { M_X, M_W, M_Q, M_O, M_S, M_G, M_U, M_D, M_L, M_N };
struct Maps { CUtensorMap m[M_N]; };

__global__ void __cluster_dims__(2, 1, 1) __launch_bounds__(384, 1) fused_kernel(const Ptrs P, const __grid_constant__ Maps T) {
  extern __shared__ __align__(1024) uint8_t smem_raw[];
  TS_DECL; TS(0); TSG(30);
  if (threadIdx.x == 320) SPANS(0);
  if (MPF == 1 && threadIdx.x == 0) { tmap_prefetch(&T.m[M_W]); tmap_prefetch(&T.m[M_Q]); tmap_prefetch(&T.m[M_X]); }
  if (MPF == 2 && threadIdx.x < 3) l2_prefetch(&T.m[threadIdx.x]);
  if (MPF == 3 && (threadIdx.x & 31) == 0 && threadIdx.x < 96) tmap_prefetch(&T.m[threadIdx.x >> 5]);
  const int tid = threadIdx.x, wid = __shfl_sync(~0u, tid >> 5, 0), wg = wid >> 2, lane = lane_id();
  const uint32_t rank = blockIdx.x & 1, own = rank << 24;
  const uint32_t sm = own + sb, mb = own + bars;
  int b0;
  { const int j = blockIdx.x >> 1, u = j - 36, q = (u * 37) >> 8;
    b0 = j < 4 ? j * 16 + 64 : u < 0 ? j * 2 - 8 : q * 2 + u * 2 + 66;
    if (HALFMAP) b0 = (b0 & 15) | (b0 & 48) << 1 | (b0 & 64) >> 2;
    b0 += rank; }
#define IDS(B) \
  const int b = (B), rb = b >> 4, cg = b & 15, hf = cg >> 3, s3 = cg & 7, c3 = s3 ^ ((rb & 1) << 2), jp = cg >> 1, km = (~c3 & 6) << 1; \
  const int fidx = jp == rb ? -1 : b - 2 * rb - (jp > rb ? 2 : 0); \
  auto kcol = [&](int kb) { return (kb ^ (kb < 8 ? km & 8 : km)) * 64; }; \
  auto src_of = [&](int p) { return p == 0 ? s3 : p == 15 ? s3 ^ 1 : (((jp & 3) ^ ((p - 7) >> 1)) << 1) + ((p - 1) & 1); }; \
  auto frag_of = [&](int p) { return p < 9 ? (p - 1) * 512 : 4096 + src_of(p) * 512; }; \
  (void)hf; (void)fidx; (void)kcol; (void)frag_of
  auto get_b = [&]() { return __shfl_sync(~0u, (int)lds1(mb + B_ID), 0); };
  IDS(b0);
  auto load_w = [&](uint32_t st, int kc, uint32_t bar, bool last) { tma_3d(st + 32768, &T.m[M_W], cg * 64, kc, 1, bar, last); tma_2d(st + 49152, &T.m[M_Q], cg * 64, kc, bar, last); };
  const uint32_t tk = clock64();
  if (SPF && tid < 80) {
    const int i = tid - 32;
    l2_prefetch(tid < 32 ? P.x + (rb * 256 + (hf * 4 + (cg & 3)) * 32 + tid) * D_ + kcol(0) : P.wqkv + (kcol(0) + (rb >> 1) * 16 + (i & 15)) * 3072 + (i >> 4) * 1024 + cg * 64);
  }
  RTS_DECL;
  if (wid == 8) {
    if (elect_one()) {
      if (smem_u32(smem_raw) != sm) asm volatile("trap;");
#pragma unroll
      for (int s = 0; s < 4; s++) mbar_init(mb + B_FULL + 8 * s, 1);
      asm volatile("fence.mbarrier_init.release.cluster;" ::: "memory");
      fence_async_smem();
      mbar_expect_tx(mb + B_FULL, STAGE_B);
      load_w(sm, kcol(0), mb + B_FULL, EFW0);
      tma_2d(sm, &T.m[M_X], kcol(0), rb * 256, mb + B_FULL, EFX0);
      tma_2d(sm + 16384, &T.m[M_X], kcol(0), rb * 256 + 128, mb + B_FULL, EFX0);
      RTS(0);
    }
  } else if (wid == 9) {
    if (elect_one()) {
#pragma unroll
      for (int i = 4; i < 31; i++) if (8 * i != B_ID) mbar_init(mb + 8 * i, i < 8 ? 8 : i < 16 ? 16 : i == 16 ? 64 : i == 17 ? 8 : i == 18 ? 4 : 1);
      asm volatile("fence.mbarrier_init.release.cluster;" ::: "memory");
      fence_async_smem();
    }
  } else if (wid == 11) {
#pragma unroll
    for (int i = 0; i < 4; i++) sts4(sm + OFF_STATS + i * 512 + lane * 16, SENT, SENT, SENT, SENT);
    sts1(mb + B_ID, b);
    fence_async_smem();
  }
  __syncthreads();
  asm volatile("barrier.cluster.arrive.relaxed.aligned;\nbarrier.cluster.wait.aligned;" ::: "memory");

  if (wg == 2) {
    asm volatile("setmaxnreg.dec.sync.aligned.u32 56;");
    if (wid == 8) {
      if (elect_one()) {
#pragma unroll 1
        for (int kb = 1; kb < 15; kb++) {
          const uint32_t fb = mb + B_FULL + 8 * (kb & 3), st = sm + (kb & 3) * STAGE_B;
          const int kc = kcol(kb);
          if (kb < 4) while ((uint32_t)clock64() - tk < FD0 + kb * FD1) {}
          else mbar_wait(fb + B_EMPTY, ((kb >> 2) & 1) ^ 1);
          mbar_expect_tx(fb, STAGE_B);
          tma_2d_mc(st + rank * 16384, &T.m[M_X], kc, rb * 256 + rank * 128, fb, EFX);
          load_w(st, kc, fb, EFW && kb >= EFWK);
          if (kb >= 8 && kb < 11) asm volatile("mbarrier.arrive.shared::cta.b64 _, [%0], %1;" :: "r"(fb + B_EMPTY), "r"(4) : "memory");
        }
        {
          const uint32_t st = sm + 3 * STAGE_B, fa = mb + B_FULL + 24, fb = mb + B_F15;
          const int kc = kcol(15);
          mbar_wait(fa, 0);
          mbar_expect_tx(fa, 32768); mbar_expect_tx(fb, 24576);
          if (rank) { mbar_wait(mb + B_EMPTY + 24, 0); tma_2d_mc(st + 16384, &T.m[M_X], kc, rb * 256 + 128, fa, EFX); }
          mbar_wait(mb + B_EMPTY, 1);
          tma_3d(st + 32768, &T.m[M_W], cg * 64, kc, 1, fa, EFW);
          if (!rank) { mbar_wait(mb + B_EMPTY + 24, 0); tma_2d_mc(st, &T.m[M_X], kc, rb * 256, fb, EFX); }
          tma_2d(st + 49152, &T.m[M_Q], cg * 64, kc, fb, EFW);
        }
        mbar_expect_tx(mb + B_KVP, 32768 + 2048);
      }
      __syncwarp();
      const uint4* kp = &P.s->kvp[cg * 8 * 256], *zq = &P.s->zp[cg * 8 * 16], *src = &P.s->obuf[(rb * 4 + rank * 2 + hf) * 64 * 128];
      asm volatile("" : "+l"(kp), "+l"(zq), "+l"(src));
      mbar_wait(mb + B_EVA, 0);
      meet(&P.s->when[cg * 32 + rb], (const uint4*)&P.s->when[cg * 32] + (lane & 1), MFIRST, MKV, mb + B_EVB);
      if (elect_one()) {
        bulk_load(sm + rank * (2 * STAGE_B) + STAGE_B, kp, 32768, mb + B_KVP);
        bulk_load(sm + rank * (2 * STAGE_B) + UNIT, zq, 2048, mb + B_KVP);
      }
      RTS(1);
      mbar_wait(mb + B_KVP, 0);
      RTS(2);
      meet(&P.s->when[(16 + rb * 2 + hf) * 32 + s3], (const uint4*)&P.s->when[(16 + (MWIDE == 2 ? lane >> 1 : (MWIDE ? (lane & 6) + (rb & 1) : rb) * 2 + (hf ^ 1))) * 32] + (lane & 1), MFIRST, MO, mb + B_E);
      RTS(3);
      if (elect_one()) {
        const uint32_t t0 = clock64();
        RTS(4);
#pragma unroll
        for (int p = 1; p < 5; p++) {
          if (p == 3) while ((uint32_t)clock64() - t0 < ADELAY2) {}
          bulk_load_mc(sm + ring_of(p, rank), src + (p - 1) * 512, UNIT, mb + B_BF + 8 * p);
        }
#pragma unroll 1
        for (int p = 5; p < 15; p++) {
          uint32_t dst = sm + ring_of(p, rank), bar = mb + B_BF + 8 * (p % 7);
          const uint4* q = src + frag_of(p);
          asm volatile("" : "+r"(dst), "+r"(bar), "+l"(q));
          mbar_wait(mb + B_E + 8 * ((p - 4) & 7), p >= 12);
          bulk_load_mc(dst, q, UNIT, bar);
        }
        asm volatile("mbarrier.arrive.shared::cta.b64 _, [%0], 8;" :: "r"(mb + B_GATE) : "memory");
        const uint4* s15 = &P.s->obuf[(rb * 4 + hf) * 64 * 128 + frag_of(15)];
        RTS_DUMP;
        mbar_wait(mb + B_E + 24, 1);
        bulk_load(sm + ring_of(15, 0), s15, UNIT, mb + B_BF + 8); bulk_load(sm + ring_of(15, 1), s15 + 2 * 64 * 128, UNIT, mb + B_BF + 8);
      }
    } else if (wid == 11) {
      IDS(get_b());
      if (fidx >= 0) {
        const uint32_t o = (rank * 32 + lane) * (F_ * 2) + (fidx >> 1) * 128;
        const char* q0 = (const char*)P.wg + o, *q1 = (const char*)P.wu + o;
        mbar_wait(mb + B_FULL + 24, 0);
        mbar_wait(mb + B_FULL + 8 * (PULL0 & 3), PULL0 >> 2);
#pragma unroll 1
        for (int r = 0; r < 16; r++, q0 += 64 * F_ * 2, q1 += 64 * F_ * 2) {
          if (mbar_test(mb + B_HOLD, 0)) { l2_prefetch(q0); l2_prefetch(q1); continue; }
          asm volatile("cp.async.ca.shared.global.L2::128B [%0], [%1], 4;\ncp.async.commit_group;\ncp.async.wait_group %3;\n"
                       "cp.async.ca.shared.global.L2::128B [%0], [%2], 4;\ncp.async.commit_group;\ncp.async.wait_group %3;" :: "r"(mb + B_DUMMY), "l"(q0), "l"(q1), "n"(PDEPTH) : "memory");
          if (lane == 0) g_dbgv(3, r + 1);
        }
        mbar_wait(mb + B_F15, 0);
        bar_sync(15, 288);
        if (lane == 0) PTS(1);
        q0 = (const char*)P.wd + fidx * 65536 + lane * 128;
        const uint32_t bar = mb + B_BF + 48;
        if (lane == 0) mbar_expect_tx(bar, 8192);
#pragma unroll 1
        for (int i = 0; i < 16 + PLAG; i++) {
          if (i < 16) l2_prefetch(q0 + i * 4096);
          if (i >= PLAG && elect_one()) tma_2d(sm + OFF_COLSUM, &T.m[M_L], 0, fidx * 512 + (i - PLAG) * 32, bar, false);
          const uint32_t t1 = clock64();
          while ((uint32_t)clock64() - t1 < PSTEP) {}
        }
        mbar_wait(bar, 0);
        __syncwarp();
        if (lane == 0) { mbar_arrive(bar); PTS(4); }
        asm volatile("cp.async.wait_all;" ::: "memory");
      } else bar_arrive(15, 288);
      bar_arrive(14, 64);
    } else {
      const uint32_t eb = (lane << 24) + bars + B_EMPTY;
      float c[6];
      if (wid == 10) {
        float sx[4] = {0.f, 0.f, 0.f, 0.f}, qx[4] = {0.f, 0.f, 0.f, 0.f};
        const uint32_t xa = sm + ((hf * 4 + (cg & 3)) * 32 + lane) * 128 + ((lane & 7) << 4);
#pragma unroll 1
        for (int kb = 0; kb < 8; kb++) {
          uint4 xv[8];
          const uint32_t so = xa + (kb & 3) * STAGE_B;
          mbar_wait(mb + B_FULL + 8 * (kb & 3), kb >> 2);
#pragma unroll
          for (int i = 0; i < 8; i++) xv[i] = lds4(so ^ (i << 4));
#pragma unroll
          for (int i = 0; i < 8; i++) {
            const uint32_t e[4] = {xv[i].x, xv[i].y, xv[i].z, xv[i].w};
#pragma unroll
            for (int j = 0; j < 4; j++) {
              const float d0 = bf_lo(e[j]), d1 = bf_hi(e[j]);
              sx[j] += d0 + d1; qx[j] = fmaf(d0, d0, fmaf(d1, d1, qx[j]));
            }
          }
          __syncwarp();
          if (lane < 2) mbar_arrive_rem(eb + 8 * (kb & 3));
          if (kb == RST2) {
        {
          const uint32_t ep = ld_rlx(&P.s->epoch);
          float s = 0.f;
#pragma unroll
          for (int i = 0; i < 4; i++) {
            const uint4 v = ld_cg4((const uint4*)P.wr + lane + i * 32);
            s += (bf_lo(v.x) + bf_hi(v.x)) + (bf_lo(v.y) + bf_hi(v.y)) + (bf_lo(v.z) + bf_hi(v.z)) + (bf_lo(v.w) + bf_hi(v.w));
          }
#pragma unroll
          for (int o = 16; o; o >>= 1) s += __shfl_xor_sync(~0u, s, o);
          if (lane == 0) sts1(mb + B_SW, (__float_as_uint(s) & ~255u) | ((ep + 1) & 255));
        }
        asm volatile("cp.async.bulk.wait_group 0;\nfence.proxy.async.global;" ::: "memory");
        fence_gpu();
        if (lane == 0) PTS(0);
          }
          if (kb == RST) {
        if (elect_one()) {
#pragma unroll 1
          for (int i = 0; i < 16; i++) bulk_store(&P.s->obuf[((rb * 4 + (i >> 2)) * 64 + (((i >> 2) & 1) == hf ? 32 + s3 * 4 + (i & 3) : (i & 3) * 8 + s3)) * 128], sm + OFF_STATS, 2048);
          bulk_store(&P.s->kvp[(cg * 8 + rb) * 256], sm + OFF_STATS, 2048); bulk_store(&P.s->kvp[(cg * 8 + rb) * 256 + 128], sm + OFF_STATS, 2048);
          bulk_store(&P.s->zp[(cg * 8 + rb) * 16], sm + OFF_STATS, 256);
          if (s3 == 0) bulk_store(&P.s->when[(16 + rb * 2 + hf) * 32], sm + OFF_STATS, 128);
          if (rb == 0) bulk_store(&P.s->when[cg * 32], sm + OFF_STATS, 128);
          asm volatile("cp.async.bulk.commit_group;" ::: "memory");
          #pragma unroll
          for (int i = M_O; i < M_N; i++) tmap_prefetch(&T.m[i]);
        }
        __syncwarp();
          }
        }
        c[0] = ((sx[0] + sx[1]) + (sx[2] + sx[3])) * (2.f / D_);
        c[1] = fmaxf(fmaf(-c[0], c[0], ((qx[0] + qx[1]) + (qx[2] + qx[3])) * (2.f / D_)), 0.f);
      } else {
        float a[12];
#pragma unroll
        for (int i = 0; i < 12; i++) a[i] = 0.f;
        const int r2 = lane >> 4, c16 = lane & 15;
        const uint32_t a0 = sm + 32768 + (rb >> 1) * 2048 + r2 * 128 + (((c16 >> 1) ^ r2) << 4) + (c16 & 1) * 8;
#pragma unroll 1
        for (int it = 0; it < 16; it++) {
          uint2 w[12];
          const int s = (it >> 1) & 3;
          const uint32_t so = a0 + s * STAGE_B + (it & 1) * 1024;
          if (!(it & 1)) { mbar_wait(mb + B_FULL + 8 * s, it >> 3); TSD(8 + (it >> 1)); }
          static_for<0, 12>([&](auto ic) { constexpr int i = decltype(ic)::value;
            const float2 v = lds2f_o<(i >> 2) * 8192 + (i & 3) * 256>(so ^ ((i & 3) << 5)); w[i] = make_uint2(__float_as_uint(v.x), __float_as_uint(v.y)); });
#pragma unroll
          for (int i = 0; i < 12; i++) { float* q = a + (i >> 2) * 4; q[0] += bf_lo(w[i].x); q[1] += bf_hi(w[i].x); q[2] += bf_lo(w[i].y); q[3] += bf_hi(w[i].y); }
          __syncwarp();
          if (lane < 2 && (it & 1)) mbar_arrive_rem(eb + 8 * s);
        }
#pragma unroll
        for (int i = 0; i < 6; i++) {
          const int o = (i >> 1) * 4 + (i & 1);
          c[i] = (r2 ? a[o + 2] : a[o]) + __shfl_xor_sync(~0u, r2 ? a[o] : a[o + 2], 16);
        }
      }
      TS(5);
      bar_sync(10, 64);
      TS(6);
      {
        const uint32_t tag = lds1(mb + B_SW) & 255;
        auto tagged = [&](float v) { return ((__float_as_uint(v) + 128) & ~255u) | tag; };
        if (wid == 9) {
#pragma unroll
          for (int sg = 0; sg < 3; sg++) {
            st_rlx2((uint2*)&P.s->csp[(cg * 8 + rb) * 48] + sg * 32 + (lane & 15) * 2 + (lane >> 4), tagged(c[sg * 2]), tagged(c[sg * 2 + 1]));
          }
        } else st_rlx2((uint2*)&P.s->st1[rb * 256 + (hf * 4 + (cg & 3)) * 32 + lane] + ((cg >> 2) & 1), tagged(c[0]), tagged(c[1]));
        { const uint32_t t0 = clock64(); while ((uint32_t)clock64() - t0 < GDELAY) {} }
#pragma unroll 1
        for (int h = wid - 9; h < 2; h++) {
          const int q = h * 24 + min(lane, 23), sd = wid == 10 ? 32 : 48;
          const uint4* gp = wid == 10 ? &P.s->st1[rb * 256 + lane] : &P.s->csp[cg * 8 * 48 + q];
          uint4 v[8];
#pragma unroll 1
          for (int it = 0;; it++) {
            uint32_t x = 0;
#pragma unroll
            for (int i = 0; i < 8; i++) v[i] = ld_rlx4(gp + i * sd);
#pragma unroll
            for (int i = 0; i < 8; i++) { v[i].x ^= tag; v[i].y ^= tag; v[i].z ^= tag; v[i].w ^= tag; x |= v[i].x | v[i].y | v[i].z | v[i].w; }
            if (!__any_sync(~0u, (x & 255) != 0)) break;
            SPINCHK(it, 3);
          }
          if (wid == 10) {
#pragma unroll
            for (int i = 0; i < 8; i++) {
              const float m0 = __uint_as_float(v[i].x), m1 = __uint_as_float(v[i].z), dm = 0.5f * (m0 - m1);
              sts2f(sm + OFF_STATS + (i * 32 + lane) * 8, -0.5f * (m0 + m1), rsq(fmaf(dm, dm, 0.5f * (__uint_as_float(v[i].y) + __uint_as_float(v[i].w))) + 1e-5f));
            }
          } else {
            float s4[4] = {0.f, 0.f, 0.f, 0.f};
#pragma unroll
            for (int i = 0; i < 8; i++) { s4[0] += __uint_as_float(v[i].x); s4[1] += __uint_as_float(v[i].y); s4[2] += __uint_as_float(v[i].z); s4[3] += __uint_as_float(v[i].w); }
            sts4(sm + OFF_COLSUM + q * 16, __float_as_uint(s4[0]), __float_as_uint(s4[1]), __float_as_uint(s4[2]), __float_as_uint(s4[3]));
          }
        }
        mbar_arrive(mb + B_AUX);
      }
      TS(2);
      IDS(get_b());
      const uint64_t btab = rank ? BT1 : BT0;
      if (wid == 9) {
        {
          const uint4 sv = make_uint4(SENT, SENT, SENT, SENT);
          uint4* y = &P.s->ybuf[b * NFFN * 2 + lane];
#pragma unroll
          for (int i = 0; i < 7; i++) y[i * 32] = sv;
          if (lane < 16) P.s->st2[b * 16 + lane] = make_uint4(0, 0, 0, 0); else P.s->hsel[b * 16 + lane - 16] = sv;
          if (b < 8) P.s->cand[b * 32 + lane] = SENT;
          fence_gpu();
          __syncwarp();
          if (lane == 0) mbar_arrive(mb + B_LATE);
        }
        TS(3);
        TS_DUMP(2);
        {
          const int p = lane & 15, sl = p % 7;
          const bool sliced = p > 0 && p < 9;
          const uint32_t c = sliced ? ((p - 1) >> 1) * 16 | ((hf ^ 1) * 8 + ((p - 1) & 1) * 4) << 8 | 128 << 16 : (hf * 8 + src_of(p)) << 8;
          const uint32_t ev = mb + (p < BHOLD ? B_EVA : p < 4 ? B_KVP : p < 6 ? B45 : B_E + 8 * ((p < 7 ? 1 : p - 4) & 7) + (p >= 12));
          mbar_wait(mb + B_EVA, 0);
          sts4(sm + OFF_COLSUM + 512 + p * 16, sm + unit_of(btab, sl), mb + B_BF + 8 * sl, c, ev);
          __syncwarp();
        }
        if (elect_one()) {
#pragma unroll 1
          for (int p = 0; p < 16; p++) {
            const uint4 e = lds4(sm + OFF_COLSUM + 512 + p * 16);
            if (p == 4) mbar_wait(mb + B_WR, 0);
            mbar_wait(e.w & ~1u, e.w & 1);
            mbar_expect_tx(e.y, p ? 4 * UNIT : 2 * UNIT);
            tma_4d(e.x, (const CUtensorMap*)((const char*)&T.m[M_O] + (e.z >> 16)), 0, e.z & 255, (e.z >> 8) & 255, c3 * 2, e.y);
          }
          PTS(16);
        }
      } else {
        const uint2 w = ld_rlx2((const uint2*)(P.wr + c3 * 128) + lane);
#pragma unroll 1
        for (int i = 0; i < 4; i++) { l2_prefetch((const char*)P.wo + b * 16384 + i * 4096 + lane * 128); __nanosleep(300); }
        const int p = lane & 15, p2 = min(p + 2, 15);
        const uint32_t t0 = dlo(sb, 8192) + (unit_of(btab, p % 7) >> 4), t1 = ring_of(p + 1, lane >> 4), t2 = mb + B_BF + 8 * (p2 % 7);
        mbar_wait(mb + B_EVB, 0);
        bar_sync(14, 64);
        sts4(sm + OFF_COLSUM + lane * 16, w.x << 16, w.x & 0xFFFF0000u, w.y << 16, w.y & 0xFFFF0000u);
        sts4(sm + OFF_STATS + lane * 16, t0, t1, t2, (p2 / 7) & 1);
        __syncwarp();
        if (elect_one()) {
          mbar_arrive(mb + B_WR);
          if (fidx >= 0) {
            mbar_expect_tx(mb + B_FFN, 131072); mbar_expect_tx(mb + B_FFD, 32768);
            uint64_t gt = rank ? GT1 : GT0;
#pragma unroll 1
            for (int f = 0; f < 8; f++, gt >>= 5) {
              uint32_t d0 = sm + unit_of(gt, 0);
              asm volatile("" : "+r"(d0));
              if (f == 3) mbar_wait(mb + B_GATE, 1);
              mbar_wait(mb + (f < FEARLY ? B_KVB : B_E + (f < 3 ? 3 + 2 * f : (f + 5) >> 1) * 8), f < FEARLY || f >= 3);
              tma_3d(d0, &T.m[M_G], fidx * 32, f * 128, 0, mb + B_FFN, EFF);
              tma_3d(d0 + UNIT, &T.m[M_U], fidx * 32, f * 128, 0, mb + B_FFN, EFF);
            }
            PTS(17);
            mbar_expect_tx(mb + B_KVP, 32768);
#pragma unroll
            for (int w = 0; w < 8; w++) {
              if (w == 2) mbar_wait(mb + B_E + 56, 1);
              if (w == 6) mbar_wait(mb + B_E16, 1);
              if (w == DLATE) mbar_wait(mb + B_EVA, 1);
              tma_3d(sm + ((DT0 >> (5 * w)) & 31) * UNIT + (w < 4 ? 0 : w < 6 ? 14 * UNIT : -14 * UNIT) * rank, &T.m[M_D], 0, fidx * 32, 2 * w, mb + (w < 4 ? B_FFD : B_KVP), EFF);
            }
            PTS(18);
          }
        }
      }
    }
    __syncwarp();
    IDS(get_b());
    mbar_wait(mb + B_EVB, 0);
    mbar_wait(mb + B_OUT, 0);
    const float2 cf = lds2f(sm + OFF_STATS + 64);
    const int cand0 = 2047 - (__float_as_int(cf.x) & 2047), cand1 = 2047 - (__float_as_int(cf.y) & 2047), rr = lane >> 4;
    auto store_rows = [&](int tr, bool on) {
      const uint4 v = lds4(sm + 4 * UNIT + (tr >> 6) * STAGE_B + (tr & 63) * 256 + (((lane & 15) ^ (tr & 7)) << 4));
      const float2 pr = lds2f(sm + OFF_LNP + tr * 8);
      const float f = 1.f + pr.x, n = pr.y;
      if (on) *(uint4*)(P.out + (size_t)(rb * 256 + hf * 64 + tr + (tr & 64)) * D_ + c3 * 128 + (lane & 15) * 8) =
          make_uint4(pack2(fmaf(bf_lo(v.x), f, n), fmaf(bf_hi(v.x), f, n)), pack2(fmaf(bf_lo(v.y), f, n), fmaf(bf_hi(v.y), f, n)),
                     pack2(fmaf(bf_lo(v.z), f, n), fmaf(bf_hi(v.z), f, n)), pack2(fmaf(bf_lo(v.w), f, n), fmaf(bf_hi(v.w), f, n)));
    };
    if (wid == 8) {
      mbar_wait(mb + B_SEL, 0);
      const float2 sel = lds2f(sm + OFF_STATS + 80);
      const uint32_t kc = __float_as_uint(rr ? cf.y : cf.x);
      const int c = rr ? cand1 : cand0;
      store_rows(((c >> 1) & 64) + (c & 63), kc != __float_as_uint(sel.x) && kc != __float_as_uint(sel.y) && (c >> 8) == rb && ((c >> 6) & 1) == hf);
    } else if (wid < 9 + NOUTW) {
      if (ODELAY) { const uint32_t t0 = clock64(); while ((uint32_t)clock64() - t0 < ODELAY) {} }
#pragma unroll OUNR
      for (int tr = (wid - 9) * 2 + rr; tr < 128; tr += 2 * NOUTW) {
        const int row = rb * 256 + hf * 64 + tr + (tr & 64);
        store_rows(tr, row != cand0 && row != cand1 && !NOOUT);
      }
      if (wid == 9 && lane == 0) { PTS(14); SPANS(2); }
    }
  } else {
    asm volatile("setmaxnreg.inc.sync.aligned.u32 224;");
    const int t128 = tid & 127, warp = wid & 3, g = lane >> 2, t = lane & 3;
    const uint32_t sk = rank * (2 * STAGE_B);
    uint4 ost[2][4];
    uint4* od1;
    int b1;
    const uint32_t eb = (lane << 24) + bars + B_E;
    float acc[64], wf[32];
    {
      float acc0[96], acc1[96];
#pragma unroll
      for (int i = 0; i < 96; i++) { acc0[i] = 0.f; acc1[i] = 0.f; }
      const uint32_t xo0 = dlo(sb, 16) + (wg * 2 + hf) * 512, xo1 = dlo(sb, 16) + (wg * 2 + (hf ^ 1)) * 512;
      constexpr uint32_t ST = STAGE_B >> 4, WD = dlo(sb + 49152, 8192), WV = dlo(sb + 32768, 8192);
      const uint32_t eb0 = (t128 << 24) + bars + B_EMPTY;
#pragma unroll 1
      for (int kb = 0; kb < 12; kb++) {
        const int s = kb & 3;
        mbar_wait(mb + B_FULL + 8 * s, (kb >> 2) & 1);
        if (kb == 0) TS(1);
        if (kb == 0 && !wg) bar_sync(2, 256);
        pin(acc0); pin(acc1);
        wg_fence();
#pragma unroll
        for (int k = 0; k < 4; k++) {
          const uint64_t db = dsc<1024, 1>(WV + s * ST + k * 128);
          wgmma_n192_ss<0, 1, 0>(acc0, dsc<1024, 1>(s * ST + xo0 + k * 2), db, 1);
          wgmma_n192_ss<0, 1, 0>(acc1, dsc<1024, 1>(s * ST + xo1 + k * 2), db, 1);
        }
        wg_commit();
        if (kb == 0 && wg) bar_arrive(2, 256);
        wg_wait<0>();
        pin(acc0); pin(acc1);
        if (t128 < 2 && kb < 11) mbar_arrive_rem(eb0 + 8 * s);
      }
      mbar_wait(mb + B_FULL, 1);
      if (t128 < 8) mbar_arrive_rem(t128 < 4 ? (wg << 24) + bars + B_EMPTY + 24 : mb + B_EMPTY);
      TS(2);
      mbar_wait(mb + B_AUX, 0);
      float rs[2][2], nm[2][2];
#pragma unroll
      for (int m = 0; m < 2; m++)
#pragma unroll
        for (int h = 0; h < 2; h++) { const float2 v = lds2f(sm + OFF_STATS + ((wg * 2 + (m ^ hf)) * 64 + warp * 16 + h * 8 + g) * 8); nm[m][h] = v.x; rs[m][h] = v.y; }
      auto center = [&](auto jc) {
        constexpr int j = decltype(jc)::value;
        const float2 cs = lds2f_o<sb + OFF_COLSUM + j * 32>(own + t * 8);
        acc1[j * 4] = fmaf(nm[1][0], cs.x, acc1[j * 4]); acc1[j * 4 + 1] = fmaf(nm[1][0], cs.y, acc1[j * 4 + 1]);
        acc1[j * 4 + 2] = fmaf(nm[1][1], cs.x, acc1[j * 4 + 2]); acc1[j * 4 + 3] = fmaf(nm[1][1], cs.y, acc1[j * 4 + 3]);
        acc0[j * 4] = fmaf(nm[0][0], cs.x, acc0[j * 4]); acc0[j * 4 + 1] = fmaf(nm[0][0], cs.y, acc0[j * 4 + 1]);
        acc0[j * 4 + 2] = fmaf(nm[0][1], cs.x, acc0[j * 4 + 2]); acc0[j * 4 + 3] = fmaf(nm[0][1], cs.y, acc0[j * 4 + 3]);
      };
      static_for<0, 16>(center);
      const float L2E = 1.4426950408889634f;
      uint32_t fa = sm + sk + (warp * 16 + (lane & 15)) * 128 + (((lane >> 4) ^ (lane & 7)) << 4);
      asm volatile("" : "+r"(fa));
      uint32_t xf0[32], xf1[32];
      auto pack_kv = [&](float (&a)[96], int i, float r0, float r1, uint32_t* o, uint32_t z = 0) {
        const float* p = a + i * 8;
        if (i < 4) {
          const float rl0 = __uint_as_float(__float_as_uint(r0 * L2E) | z), rl1 = __uint_as_float(__float_as_uint(r1 * L2E) | z);
          const uint32_t q0 = pack2(r0, r0), q1 = pack2(r1, r1);
          o[0] = phi2(p[0], p[1], rl0, q0); o[1] = phi2(p[2], p[3], rl1, q1); o[2] = phi2(p[4], p[5], rl0, q0); o[3] = phi2(p[6], p[7], rl1, q1);
        } else {
          r0 = __uint_as_float(__float_as_uint(r0) | z); r1 = __uint_as_float(__float_as_uint(r1) | z);
          o[0] = pack2(p[0] * r0, p[1] * r0); o[1] = pack2(p[2] * r1, p[3] * r1); o[2] = pack2(p[4] * r0, p[5] * r0); o[3] = pack2(p[6] * r1, p[7] * r1); }
      };
      auto swap_kv = [&](uint32_t (&xf)[32], uint32_t tile, int i, const uint32_t* o, uint32_t z = 0) {
        const uint32_t ad = (fa + tile * UNIT) ^ ((i & 3) << 5);
        if (i < 4) { ldsm4_o<0>(ad, xf[i * 4], xf[i * 4 + 1], xf[i * 4 + 2], xf[i * 4 + 3]); stsm4_o<0>(ad, o[0], o[1], o[2], o[3]); }
        else { ldsm4_o<STAGE_B>(ad | z, xf[i * 4], xf[i * 4 + 1], xf[i * 4 + 2], xf[i * 4 + 3]); stsm4_o<STAGE_B>(ad, o[0], o[1], o[2], o[3]); }
      };
      auto mma_q = [&](float (&a)[96], uint32_t (&xf)[32], uint32_t xo, bool ss) {
        const uint32_t r = __shfl_sync(~0u, sk >> 4, 0), o = 2 * ST - r;
#pragma unroll
        for (int j = 0; j < 8; j++) {
          if (ss) wgmma_n64_ss<0, 1, 64>(a, dsc<1024, 1>(o + (j >> 2) * ST + xo + (j & 3) * 2), dsc<1024, 1>(WD + o + (j >> 2) * ST + (j & 3) * 128), 1);
          else wgmma_n64_rs<1, 64>(a, xf[j * 4], xf[j * 4 + 1], xf[j * 4 + 2], xf[j * 4 + 3], dsc<1024, 1>(WD + r + (j >> 2) * ST + (j & 3) * 128), 1);
        }
      };
      auto epi_q = [&](float (&a)[96], float r0, float r1, uint32_t (&o)[16]) {
        const float rl0 = r0 * 1.44269511f, rl1 = r1 * 1.44269511f;
        const uint32_t q0 = dup2(r0), q1 = dup2(r1);
#pragma unroll
        for (int j = 0; j < 8; j++) { o[j * 2] = phi2(a[64 + j * 4], a[65 + j * 4], rl0, q0); o[j * 2 + 1] = phi2(a[66 + j * 4], a[67 + j * 4], rl1, q1); }
        pinu(o);
      };
      auto mma_kv1 = [&](float (&a)[96], uint32_t xo, int s) {
#pragma unroll
        for (int k = 0; k < 4; k++) wgmma_n128_ss<0, 1, 0>(a, dsc<1024, 1>(s * ST + xo + k * 2), dsc<1024, 1>(WV + s * ST + k * 128), 1);
      };
      auto epi_kv = [&](float (&a)[96], uint32_t (&xf)[32], uint32_t tile, float r0, float r1) {
        uint32_t o[8][4];
#pragma unroll
        for (int j = 3; j >= 0; j--) {
          const uint32_t z = j < 3 ? (xf[(j + 5) * 4] | (j < 2 ? o[j + 2][0] | o[j + 6][0] : 0)) & blockIdx.y : 0;
          pack_kv(a, j + 4, r0, r1, o[j + 4], z);
          swap_kv(xf, tile, j + 4, o[j + 4], (o[j + 4][2] | o[j + 4][3]) & blockIdx.y);
          pack_kv(a, j, r0, r1, o[j], z);
          swap_kv(xf, tile, j, o[j]);
        }
      };
      bar_arrive(15, 288);
      mbar_wait(mb + B_FULL + 8, 1);
      if (!wg) bar_sync(3, 256);
      pinr<0, 64>(acc0); pinr<0, 64>(acc1);
      wg_fence();
      mma_kv1(acc1, xo1, 0); mma_kv1(acc0, xo0, 0); mma_kv1(acc1, xo1, 1);
      if (GSPLIT == 2) mma_kv1(acc0, xo0, 1);
      mbar_wait(mb + B_FULL + 16, 1);
      wg_fence();
      mma_kv1(acc1, xo1, 2);
      mbar_wait(mb + (wg ? B_FULL + 24 : B_F15), wg);
      wg_fence();
      mma_kv1(acc1, xo1, 3);
      wg_commit();
      bar_arrive(4 - wg, 256);
      static_for<16, 24>(center);
      pinr<64, 96>(acc0); pinr<64, 96>(acc1);
      mbar_wait(mb + B_FULL + 8, 1);
      wg_wait<0>();
      pinr<0, 64>(acc0); pinr<0, 64>(acc1);
      epi_kv(acc1, xf1, wg * 2 + (hf ^ 1), rs[1][0], rs[1][1]);
      pinu(xf1);
      bar_sync(5 - wg, 256);
      wg_fence();
      if (GSPLIT == 1) mma_kv1(acc0, xo0, 1);
      mma_kv1(acc0, xo0, 2); mma_kv1(acc0, xo0, 3);
      wg_commit();
      mma_q(acc1, xf1, xo1, false);
      wg_commit();
      if (wg) bar_arrive(5, 256);
      else { fence_async_smem(); bar_arrive(6, 256); }
      if (tid >= 240) sts4(sm + OFF_STATS + (tid & 15) * 128 + ((tid & 7) << 4), 0x3F803F80u, 0x3F803F80u, 0x3F803F80u, 0x3F803F80u);
      wg_wait<1>();
      pinr<0, 64>(acc0);
      if (lane == 0) mbar_arrive(mb + B_EVA);
      TS(6);
      epi_kv(acc0, xf0, wg * 2 + hf, rs[0][0], rs[0][1]);
      fence_async_smem();
      pinu(xf0);
      if (!wg) bar_arrive(7, 256);
      const uint32_t kvb = 2 * STAGE_B + (2 + (hf ^ 1)) * UNIT - sk;
      b1 = get_b();
      od1 = &P.s->obuf[(((b1 >> 4) * 4 + wg * 2 + (hf ^ 1)) * 64 + (b1 & 7)) * 128 + t128];
      uint32_t ka0 = sm + kvb + wid * 1024 + (lane & 7) * 128 + (((lane >> 3) ^ (lane & 7)) << 4), ka1 = sm + kvb + wid * 1024 + (t * 2 + g) * 128 + ((4 ^ (t * 2 + g)) << 4);
      const uint8_t* g0 = smem_raw + sk + STAGE_B + tid * 16, *g1 = smem_raw + sk + UNIT + g * 256 + wid * 32 + t * 8;
      const uint8_t* h0 = (const uint8_t*)&P.s->kvp[(b1 & 15) * 8 * 256 + tid], *h1 = (const uint8_t*)&P.s->zp[((b1 & 15) * 8 + g) * 16] + wid * 32 + t * 8;
      asm volatile("" : "+r"(ka0), "+r"(ka1), "+l"(g0), "+l"(g1), "+l"(h0), "+l"(h1), "+l"(od1));
      if (wg) {
        float ka[36];
        auto mma_kv = [&](uint32_t tile, int i, int acc) {
          const uint32_t o = (sk >> 4) + tile * 512 + i * 128;
          wgmma_n72_ss<1, 1, 0>(ka, dsc<1024, 1>(dlo(sb, 8192) + o), dsc<1024, 1>(dlo(sb + STAGE_B, OFF_STATS - STAGE_B) + o * (1u - (1u << 16))), acc);
        };
#pragma unroll
        for (int i = 0; i < 36; i++) ka[i] = 0.f;
        bar_sync(6, 256);
        wg_fence();
#pragma unroll
        for (int i = 0; i < 4; i++) {
          mma_kv(2, i, i); mma_kv(3, i, 1); mma_kv(hf ^ 1, i, 1);
#pragma unroll
          for (int j = 2 * i; j < 2 * i + 2; j++)
            wgmma_n64_rs<1, 64>(acc0, xf0[j * 4], xf0[j * 4 + 1], xf0[j * 4 + 2], xf0[j * 4 + 3], dsc<1024, 1>(WD + (sk >> 4) + (j >> 2) * ST + (j & 3) * 128), 1);
        }
        const int kq = (b1 & 15) * 8 + (b1 >> 4);
        uint4* dst = &P.s->kvp[kq * 256 + warp * 64 + lane];
        uint32_t* dz = (uint32_t*)&P.s->zp[kq * 16] + warp * 16 + g + t * 8;
        asm volatile("" : "+l"(dst), "+l"(dz));
        mbar_wait(mb + B_LATE, 0);
        bar_sync(7, 256);
        wg_fence();
#pragma unroll
        for (int i = 0; i < 4; i++) mma_kv(hf, i, 1);
        wg_commit();
        bar_arrive(8, 256);
        wg_wait<0>();
        pin(ka); pinr<64, 96>(acc0);
        uint32_t kw[8];
#pragma unroll
        for (int i = 0; i < 8; i++) {
          const int j = (i & 3) * 4 + (i >> 2) * 2;
          asm("{\n.reg .pred p;\nsetp.ne.u32 p, %5, 0;\n@p cvt.rn.bf16x2.f32 %0, %4, %3;\n@!p cvt.rn.bf16x2.f32 %0, %2, %1;\n}"
              : "=r"(kw[i]) : "f"(ka[j]), "f"(ka[j + 1]), "f"(ka[16 + j]), "f"(ka[17 + j]), "r"(warp & 2));
        }
        st_rlx4(dst, make_uint4(kw[0], kw[1], kw[2], kw[3]));
        st_rlx4(dst + 32, make_uint4(kw[4], kw[5], kw[6], kw[7]));
        if (t < 2) st_rlx(dz, __float_as_uint(t ? ka[34] : ka[32]));
        if (lane == 0) mbar_arrive(mb + B_EVB);
        TS(8);
        const uint32_t t1 = clock64();
        while ((uint32_t)clock64() - t1 < SDELAY) {}
      } else {
        bar_sync(8, 256);
        wg_fence();
        mma_q(acc0, xf0, xo0, false);
      }
      if (!wg) bar_sync(9, 256);
      wg_fence();
      mma_q(acc1, xf1, xo1, true);
      wg_commit();
      if (wg) bar_arrive(9, 256);
      wg_wait<0>();
      pinr<64, 96>(acc1); pinr<64, 96>(acc0);
      TS(7);
      uint32_t pq[16];
      epi_q(acc1, rs[1][0], rs[1][1], pq);
      bar_sync(11 + wg + zero_after(pq), 128);
      wg_fence();
      mma_q(acc0, xf0, xo0, true);
      wg_commit();
      TS(5);
      {
        uint4 gv[8]; uint2 gz;
        uint32_t m[8], a[4];
        float z0, z1;
#pragma unroll
        for (int s = 0; s < 8; s++) { m[s] = ~blockIdx.y; asm volatile("" : "=r"(gv[s].x), "=r"(gv[s].y), "=r"(gv[s].z), "=r"(gv[s].w), "+r"(m[s])); }
        mbar_wait(mb + B_KVP, 0);
        TS(28);
#pragma unroll 1
        for (int it = 0; it < SPIN_LIMIT; it++) {
          gz = ld_gen2(g1);
#pragma unroll
          for (int s = 0; s < 8; s++) if (m[s] == SENT) gv[s] = ld_gen4(g0 + s * 4096);
          g0 = h0; g1 = h1;
          uint32_t mm = max(gz.x, gz.y);
          z0 = __uint_as_float(gz.x); z1 = __uint_as_float(gz.y);
#pragma unroll
          for (int o = 4; o < 32; o <<= 1) { z0 += __shfl_xor_sync(~0u, z0, o); z1 += __shfl_xor_sync(~0u, z1, o); }
#pragma unroll
          for (int s = 0; s < 8; s++) m[s] = max4(0, gv[s]);
#pragma unroll
          for (int s = 0; s < 8; s += 2) mm = __vimax3_u32(mm, m[s], m[s + 1]);
          a[0] = hadd2(hadd2(hadd2(gv[0].x, gv[1].x), hadd2(gv[2].x, gv[3].x)), hadd2(hadd2(gv[4].x, gv[5].x), hadd2(gv[6].x, gv[7].x)));
          a[1] = hadd2(hadd2(hadd2(gv[0].y, gv[1].y), hadd2(gv[2].y, gv[3].y)), hadd2(hadd2(gv[4].y, gv[5].y), hadd2(gv[6].y, gv[7].y)));
          a[2] = hadd2(hadd2(hadd2(gv[0].z, gv[1].z), hadd2(gv[2].z, gv[3].z)), hadd2(hadd2(gv[4].z, gv[5].z), hadd2(gv[6].z, gv[7].z)));
          a[3] = hadd2(hadd2(hadd2(gv[0].w, gv[1].w), hadd2(gv[2].w, gv[3].w)), hadd2(hadd2(gv[4].w, gv[5].w), hadd2(gv[6].w, gv[7].w)));
          pinu(a);
          if (!__any_sync(~0u, mm == SENT)) break;
          TSV(20, 1);
        }
        TS(23);
        wg_wait<0>();
        pinr<64, 96>(acc0);
        if (lane == 0) mbar_arrive(mb + B_KVB);
        stsm4(ka0, a[0], a[1], a[2], a[3]);
        const uint32_t zz = pack2(g ? z1 : z0, g ? z1 : z0);
        if (lane < 8) sts4(ka1, zz, zz, zz, zz);
        fence_async_smem();
        bar_sync(1, 256);
      }
      TS(21);
      auto make_o = [&](uint4 (&o)[4], auto first) {
        float oa[2][20];
        wg_fence();
#pragma unroll
        for (int ks = 0; ks < 4; ks++)
          wgmma_n40_rs<1, 0>(oa[ks >> 1], pq[ks * 4], pq[ks * 4 + 1], pq[ks * 4 + 2], pq[ks * 4 + 3], dsc<1024, 1>(dlo(sb, 8192) + (kvb >> 4) + ks * 128), ks & 1);
        wg_commit();
        if constexpr (!decltype(first)::value) {
          pinu(xf0);
#pragma unroll
          for (int q = 0; q < 32; q++) { acc[q * 2] = bf_lo(xf0[q]); acc[q * 2 + 1] = bf_hi(xf0[q]); }
          pin(acc);
          mbar_wait(mb + B_BF, 0);
        }
        wg_wait<0>();
        pin(oa[0]); pin(oa[1]);
        if (decltype(first)::value && lane < 2) mbar_arrive_rem(eb);
#pragma unroll
        for (int h = 0; h < 2; h++) {
          const float (&d)[20] = oa[h];
          const float i0 = rcp(d[16] + 1e-6f), i1 = rcp(d[18] + 1e-6f);
#pragma unroll
          for (int k2 = 0; k2 < 2; k2++) {
            o[h * 2 + k2] = make_uint4(pack2(d[k2 * 8] * i0, d[k2 * 8 + 1] * i0), pack2(d[k2 * 8 + 2] * i1, d[k2 * 8 + 3] * i1),
                                       pack2(d[k2 * 8 + 4] * i0, d[k2 * 8 + 5] * i0), pack2(d[k2 * 8 + 6] * i1, d[k2 * 8 + 7] * i1));
            if (decltype(first)::value && !h && k2 <= AFIRST) st_rlx4(od1 + k2 * 1024, o[k2]);
            if (decltype(first)::value && !h && k2 == AFIRST) { sched_fence(); TS(24); }
          }
        }
      };
      make_o(ost[1], std::true_type{});
      if (!AFIRST) { st_rlx4(od1 + 1024 + ((ost[1][2].x | ost[1][3].w) & blockIdx.y), ost[1][1]); sched_fence(); }
      epi_q(acc0, rs[0][0], rs[0][1], pq);
      if (AEARLY) { st_rlx4(od1 + 2048, ost[1][2]); st_rlx4(od1 + 3072, ost[1][3]); }
      make_o(ost[0], std::false_type{});
    }
   {
    IDS(b1);
    const int mb3 = rb * 4 + wg * 2 + hf;
    const int row0 = mb3 * 64 + warp * 16 + g;
    {
      uint4 abuf[3][4];
      const uint4* const ain = &P.s->obuf[mb3 * 64 * 128 + t128];
      uint4* const od0 = &P.s->obuf[(mb3 * 64 + 32 + s3 * 4) * 128 + t128];
#pragma unroll
      for (int i = 0; i < 4; i++) pin4(ost[0][i]);
      wg_fence();
#pragma unroll
      for (int k = 0; k < 4; k++) wgmma_n128_rs<1, 0>(acc, ost[0][k].x, ost[0][k].y, ost[0][k].z, ost[0][k].w, dsc<1024, 1>(dlo(sb + 4 * UNIT, 8192) + k * 128), 1);
      wg_commit();
      TS(29);
      if (!AEARLY) { st_rlx4(od1 + 2048, ost[1][2]); st_rlx4(od1 + 3072, ost[1][3]); }
      uint32_t la = sm + t128 * 16, ev = eb + 8;
      asm volatile("" : "+r"(la), "+r"(ev));
      auto fetch = [&](uint32_t off, uint4 (&a)[4]) { const uint32_t ra = la + off; a[0] = lds4_o<0>(ra); a[1] = lds4_o<2048>(ra); a[2] = lds4_o<4096>(ra); a[3] = lds4_o<6144>(ra); };
      auto check = [&](int p, uint4 (&a)[4]) {
        if (__any_sync(~0u, max(max4(max4(0, a[0]), a[1]), max4(max4(0, a[2]), a[3])) == SENT)) {
          int pl = p; asm volatile("" : "+r"(pl));
          const uint4* q = ain + frag_of(pl);
#pragma unroll 1
          for (int it = 0;; it++) {
            uint32_t mm = 0;
#pragma unroll
            for (int i = 0; i < 4; i++) { const uint32_t m = max4(0, a[i]); mm = max(mm, m); if (m == SENT) a[i] = ld_rlx4(q + i * 128); }
            if (!__any_sync(~0u, mm == SENT)) break;
            TSV(27, p < 3 ? 1 : p < 5 ? 100 : 10000);
            SPINCHK(it, 5);
          }
        }
        if (lane < 2) mbar_arrive_rem(ev);
        ev = (ev & ~0x38u) | ((ev + 8) & 0x38u);
      };
      auto mma = [&](int p, uint32_t bs, uint4 (&a)[4]) {
#pragma unroll
        for (int i = 0; i < 4; i++) pin4(a[i]);
        wg_fence();
#pragma unroll
        for (int k = 0; k < 4; k++) wgmma_n128_rs<1, 0>(acc, a[k].x, a[k].y, a[k].z, a[k].w, dsc<1024, 1>(bs + k * 128), 1);
        wg_commit();
      };
      uint32_t ta = sm + OFF_STATS + wg * 256 + 48;
      mbar_wait(mb + B_WR, 0);
      uint4 tp = lds4(ta);
      mbar_wait(mb + B_BF + 8, 0);
      TS(3);
      fetch(ring_of(1, wg), abuf[1]);
      check(1, abuf[1]);
      mbar_wait(mb + B_BF + 16, 0);
      fetch(ring_of(2, wg), abuf[2]);
      mma(1, dlo(sb + 11 * UNIT, 8192), abuf[1]);
      TS(25);
      st_rlx4(od0, ost[0][0]); st_rlx4(od0 + 128, ost[0][1]);
      check(2, abuf[2]);
      mbar_wait(mb + B_BF + 24, 0);
      fetch(ring_of(3, wg), abuf[0]);
      mma(2, dlo(sb + 18 * UNIT, 8192), abuf[2]);
      st_rlx4(od0 + 256, ost[0][2]); st_rlx4(od0 + 384, ost[0][3]);
      wg_wait<2>();
      check(3, abuf[0]);
      mbar_wait(mb + B_BF + 32, 0);
      TS(26);
#pragma unroll 1
      for (int p = 3; p < 15; p += 3) {
        static_for<0, 3>([&](auto jc) {
          constexpr int j = decltype(jc)::value;
          const uint4 tc = tp;
          const uint32_t bs = __shfl_sync(~0u, tc.x, 0);
          wg_wait<1>();
#pragma unroll
          for (int i = 0; i < 4; i++) pin4(abuf[(j + 1) % 3][i]);
          tp = lds4_o<16 * j + 16>(ta);
          fetch(tc.y, abuf[(j + 1) % 3]);
          mma(p + j, bs, abuf[j]);
          if (!CHKF) mbar_wait(tc.z, tc.w);
          check(p + j + 1, abuf[(j + 1) % 3]);
          if (CHKF) mbar_wait(tc.z, tc.w);
        });
        ta += 48;
      }
      mma(15, __shfl_sync(~0u, tp.x, 0), abuf[0]);
      wg_wait<2>();
      if (lane == 0) mbar_arrive(mb + B_E16);
      static_for<0, 16>([&](auto jc) { constexpr int j = decltype(jc)::value; const float2 v = lds2f_o<sb + OFF_COLSUM + j * 32>(own + t * 8); wf[j * 2] = v.x; wf[j * 2 + 1] = v.y; });
      pin(wf);
      wg_wait<0>();
      pin(acc);
#pragma unroll
      for (int i = 0; i < 4; i++) { pin4(abuf[0][i]); pin4(abuf[1][i]); pin4(abuf[2][i]); }
    }
    TS(10);
    {
      float s0 = 0.f, q0 = 0.f, e0 = 0.f, s1 = 0.f, q1 = 0.f, e1 = 0.f;
#pragma unroll
      for (int j = 0; j < 16; j++) {
        const float a = acc[j * 4], c = acc[j * 4 + 1], d = acc[j * 4 + 2], e = acc[j * 4 + 3];
        s0 += a + c; q0 = fmaf(a, a, fmaf(c, c, q0)); e0 = fmaf(a, wf[j * 2], fmaf(c, wf[j * 2 + 1], e0));
        s1 += d + e; q1 = fmaf(d, d, fmaf(e, e, q1)); e1 = fmaf(d, wf[j * 2], fmaf(e, wf[j * 2 + 1], e1));
      }
      const bool od = t & 1;
      float s = (od ? s1 : s0) + __shfl_xor_sync(~0u, od ? s0 : s1, 1);
      float q = (od ? q1 : q0) + __shfl_xor_sync(~0u, od ? q0 : q1, 1);
      float e = (od ? e1 : e0) + __shfl_xor_sync(~0u, od ? e0 : e1, 1);
      s += __shfl_xor_sync(~0u, s, 2); q += __shfl_xor_sync(~0u, q, 2); e += __shfl_xor_sync(~0u, e, 2);
      if (t < 2) red4(&P.s->st2[row0 + t * 8], s, q, e, 1.f);
    }
    TS(11);
    const uint32_t ts = clock64();
    const uint32_t msc = sm + OFF_STATS;
    const uint32_t hst = sm + 4 * UNIT + wg * STAGE_B + warp * 4096, gslot = sm + unit_of(rank ? GT1 : GT0, wid);
    bar_sync(1, 256);
#pragma unroll
    for (int j = 0; j < 8; j++)
      stsm4(hst + (lane & 15) * 256 + (((2 * j + (lane >> 4)) ^ (lane & 7)) << 4), pack2(acc[j * 8], acc[j * 8 + 1]), pack2(acc[j * 8 + 2], acc[j * 8 + 3]),
            pack2(acc[j * 8 + 4], acc[j * 8 + 5]), pack2(acc[j * 8 + 6], acc[j * 8 + 7]));
    uint32_t wa[8][4][4], wd[8][2][4];
    const uint32_t a0 = gslot + ((lane >> 4) * 8 + (lane & 7)) * 64 + ((((lane >> 3) & 1) ^ ((lane >> 1) & 3)) << 4);
    auto load_gu = [&](auto ic) { constexpr int i = decltype(ic)::value; ldsm4t_o<(i >> 2) * 1024 + ((i >> 1) & 1) * 8192>(a0 ^ ((i & 1) << 5), wa[i >> 2][i & 3]); };
    uint32_t tx;
    {
      const int row = rb * 256 + tid;
      const uint4* sp = &P.s->st2[row], *sq = &P.s->st2[row ^ 256];
      const float sw = __uint_as_float((lds1(mb + B_SW) & ~255u) | 128);
      uint4 v[2];
      if (fidx >= 0) mbar_wait(mb + B_FFN, 0);
      static_for<0, GU1>(load_gu);
      while ((uint32_t)clock64() - ts < SDEL2) {}
      v[0] = ld_rlx4(sp); v[1] = ld_rlx4(sq);
      TS(15);
      static_for<GU1, GU2>(load_gu);
#pragma unroll 1
      for (int it = 0; __any_sync(~0u, min(v[0].w, v[1].w) != 0x41000000u) && it < SPIN_LIMIT; it++) {
        if (v[0].w != 0x41000000u) v[0] = ld_rlx4(sp);
        if (v[1].w != 0x41000000u) v[1] = ld_rlx4(sq);
        TSV(22, 1);
      }
      if (lane == 0) mbar_arrive(mb + B_EVA);
      TS(12);
      uint32_t k[2];
#pragma unroll
      for (int i = 0; i < 2; i++) {
        const float mean = __uint_as_float(v[i].x) * (1.f / D_);
        const float rstd = rsq(fmaxf(fmaf(-mean, mean, __uint_as_float(v[i].y) * (1.f / D_)), 0.f) + 1e-5f);
        const uint32_t u = __float_as_uint(rstd * fmaf(-mean, sw, __uint_as_float(v[i].z)));
        k[i] = min(((u ^ ((uint32_t)((int)u >> 31) | 0x80000000u)) & ~2047u), 0xFFFFF000u) | (2047 - (row ^ (i << 8)));
        if (i == 0 && (warp >> 1) == hf) sts2f(sm + OFF_LNP + (wg * 64 + (tid & 63)) * 8, rstd, -mean * rstd);
      }
      const uint32_t hi = max(k[0], k[1]);
      uint32_t m1 = __reduce_max_sync(~0u, hi), m2 = __reduce_max_sync(~0u, hi == m1 ? min(k[0], k[1]) : hi);
      if (lane == 0) sts2f(msc + wid * 8, __uint_as_float(m1), __uint_as_float(m2));
      bar_sync(1, 256);
      const uint32_t kk = lds1(msc + (lane & 15) * 4);
      m1 = __reduce_max_sync(~0u, kk); m2 = __reduce_max_sync(~0u, kk == m1 ? 0 : kk);
      const int c0 = 2047 - (m1 & 2047), c1 = 2047 - (m2 & 2047);
      if ((c0 >> 4) == mb3 * 4 + warp || (c1 >> 4) == mb3 * 4 + warp) {
        const int ra = (lane & 4) ? c1 : c0, rd = (lane & 16) ? c1 : c0;
        uint32_t h0, h1, h2, h3;
        ldsm4_o<0>(hst + (ra & 15) * 256 + ((((lane & 3) * 4 + (lane >> 3)) ^ (ra & 7)) << 4), h0, h1, h2, h3);
        const float2 pr = lds2f(sm + OFF_LNP + (wid * 16 + (rd & 15)) * 8);
        if ((rd >> 4) == mb3 * 4 + warp) {
          const int slot = (rb & 6) + (lane >> 4);
          uint4* d = &P.s->hsel[c3 * 128 + (g & 3) * 32 + slot * 4 + t];
          st_rlx4(d, make_uint4(pack2(fmaf(bf_lo(h0), pr.x, pr.y), fmaf(bf_hi(h0), pr.x, pr.y)), pack2(fmaf(bf_lo(h1), pr.x, pr.y), fmaf(bf_hi(h1), pr.x, pr.y)),
                                pack2(fmaf(bf_lo(h2), pr.x, pr.y), fmaf(bf_hi(h2), pr.x, pr.y)), pack2(fmaf(bf_lo(h3), pr.x, pr.y), fmaf(bf_hi(h3), pr.x, pr.y))));
          if (!(lane & 15)) st_rlx(&P.s->cand[c3 * 32 + slot], (lane & 16) ? m2 : m1);
          st_rlx4(d + 1024, make_uint4(h0, h1, h2, h3));
        }
      }
      tx = clock64();
      if (tid == 0) { sts2f(msc + 64, __uint_as_float(m1), __uint_as_float(m2)); mbar_arrive(mb + B_OUT); }
    }
    TS(13);
    static_for<GU2, 32>(load_gu);
    const uint32_t dl = sm + (wid & 1) * 4096 + ((lane >> 4) * 8 + (lane & 7)) * 128 + ((((lane >> 3) & 1) ^ (lane & 7)) << 4);
    uint32_t da = dl + unit_of(DT0, wid >> 1), db = dl + unit_of(rank ? DT1 : DT0, 4 + (wid >> 1));
    uint32_t* yp = (uint32_t*)&P.s->ybuf[((wid * 8 + t * 2) * NFFN + fidx) * 2] + g;
    uint32_t k1, k2;
    uint2 key;
    {
      float gu[2][4][4];
      uint4 xb[4];
      uint32_t m[4];
      const uint4* xp = &P.s->hsel[wid * 128 + lane];
      const uint2* kp = (const uint2*)&P.s->cand[wid * 32] + t;
      uint32_t ps = gslot + g * 32;
      asm volatile("" : "+l"(xp), "+l"(kp), "+l"(yp), "+r"(db), "+r"(ps));
      if (fidx >= 0) mbar_wait(mb + B_FFD, 0);
      static_for<0, 8>([&](auto ic) { constexpr int i = decltype(ic)::value; ldsm4t_o<(i & 1) * 2048>(da ^ ((i >> 1) << 5), wd[i >> 1][i & 1]); });
      TS(9);
      while ((uint32_t)clock64() - tx < XDELAY) {}
      key = ld_rlx2(kp);
#pragma unroll
      for (int i = 0; i < 4; i++) xb[i] = ld_rlx4(xp + i * 32);
      if (fidx >= 0) mbar_wait(mb + B_KVP, 1);
#pragma unroll 1
      for (int it = 0; it < SPIN_LIMIT; it++) {
#pragma unroll
        for (int i = 0; i < 4; i++) m[i] = max4(0, xb[i]);
        if (!__any_sync(~0u, __vimax3_u32(__vimax3_u32(max(key.x, key.y), m[0], m[1]), m[2], m[3]) == SENT)) break;
        key = ld_rlx2(kp);
#pragma unroll
        for (int i = 0; i < 4; i++) if (m[i] == SENT) xb[i] = ld_rlx4(xp + i * 32);
        TSV(20, 100);
      }
      TS(14);
      const uint32_t hi = max(key.x, key.y);
      k1 = __reduce_max_sync(~0u, hi); k2 = __reduce_max_sync(~0u, hi == k1 ? min(key.x, key.y) : hi);
#pragma unroll
      for (int i = 0; i < 32; i++) gu[i >> 4][(i >> 2) & 3][i & 3] = 0.f;
#pragma unroll
      for (int ks = 0; ks < 8; ks++) {
#pragma unroll
        for (int i = 0; i < 4; i++) mma16816(gu[ks & 1][i], wa[ks][i], (ks & 1) ? xb[ks >> 1].z : xb[ks >> 1].x, (ks & 1) ? xb[ks >> 1].w : xb[ks >> 1].y);
        if (ks == 1) {
          const uint32_t dd = db | (__float_as_uint(gu[1][3][0]) & blockIdx.y);
          static_for<0, 8>([&](auto ic) { constexpr int i = decltype(ic)::value; ldsm4t_o<(i & 1) * 2048>(dd ^ ((i >> 1) << 5), wd[4 + (i >> 1)][i & 1]); });
        }
      }
#pragma unroll
      for (int c = 0; c < 2; c++) {
        const uint32_t kc = c ? key.y : key.x;
        float o[8];
#pragma unroll
        for (int j = 0; j < 8; j++) o[j] = gu[0][(j >> 2) + (j & 1) * 2][(j & 2) + c] + gu[1][(j >> 2) + (j & 1) * 2][(j & 2) + c];
        asm volatile("{\n.reg .pred p;\nsetp.ge.u32 p, %9, %10;\n@p st.shared.v4.f32 [%0], {%1,%2,%3,%4};\n@p st.shared.v4.f32 [%0+16], {%5,%6,%7,%8};\n}"
                     :: "r"(ps + (kc == k1 ? 0 : 256)), "f"(o[0]), "f"(o[1]), "f"(o[2]), "f"(o[3]), "f"(o[4]), "f"(o[5]), "f"(o[6]), "f"(o[7]), "r"(kc), "r"(k2) : "memory");
      }
    }
    TS(4);
    bar_sync(1, 256);
    {
      float g0 = 0.f, g1 = 0.f, u0 = 0.f, u1 = 0.f;
      static_for<0, 8>([&](auto wc) { constexpr int w = decltype(wc)::value;
        constexpr uint32_t o = sb + ((GT0 >> (5 * w)) & 31) * UNIT;
        const uint32_t ad = own + lane * 8 + (w == 0 || w == 7 ? sk : w < 3 ? -sk : 0);
        const float2 a = lds2f_o<o>(ad), c = lds2f_o<o + 256>(ad);
        g0 += a.x; u0 += a.y; g1 += c.x; u1 += c.y; });
      const uint32_t act = pack2(g0 * rcp(1.f + ex2(-1.4426950408889634f * g0)) * u0, g1 * rcp(1.f + ex2(-1.4426950408889634f * g1)) * u1);
      uint32_t bq[4];
#pragma unroll
      for (int i = 0; i < 4; i++) {
        const uint32_t lo = __shfl_sync(~0u, act, 8 * t + i), hi = __shfl_sync(~0u, act, 8 * t + 4 + i);
        bq[i] = __byte_perm(lo, hi, (g & 1) ? 0x7632 : 0x5410);
      }
      TS(16);
      float ya[8][4];
#pragma unroll
      for (int i = 0; i < 8; i++) { ya[i][0] = 0.f; ya[i][1] = 0.f; ya[i][2] = 0.f; ya[i][3] = 0.f; }
#pragma unroll
      for (int ks = 0; ks < 2; ks++)
#pragma unroll
        for (int i = 0; i < 8; i++) mma16816(ya[i], wd[i][ks], bq[ks * 2], bq[ks * 2 + 1]);
#pragma unroll
      for (int h = 0; h < 2; h++) {
        float o[4];
#pragma unroll
        for (int j = 0; j < 4; j++) o[j] = t == 0 ? ya[h * 4][j] : t == 1 ? ya[h * 4 + 1][j] : t == 2 ? ya[h * 4 + 2][j] : ya[h * 4 + 3][j];
        asm volatile("{\n.reg .pred p;\nsetp.ge.s32 p, %3, 0;\n@p st.relaxed.gpu.global.u32 [%0], %1;\n@p st.relaxed.gpu.global.u32 [%0+%4], %2;\n}"
                     :: "l"(yp + h * (64 * NFFN * 8)), "r"(pack2(o[0], o[1])), "r"(pack2(o[2], o[3])), "r"(fidx), "n"(NFFN * 32) : "memory");
      }
    }
    if (tid == 0) { sts2f(msc + 80, __uint_as_float(k1), __uint_as_float(k2)); mbar_arrive(mb + B_SEL); }
    TS(17);
    const uint32_t ty = clock64();
    if (wid < 7) {
      const uint4* yq = &P.s->ybuf[b * NFFN * 2 + tid];
      const uint32_t ks = (tid & 1) ? k2 : k1, grp = 3 - ((ks >> 9) & 3);
      const int fs = grp * 2 + (__shfl_sync(~0u, key.y, grp) == ks);
      const uint32_t* fq = (const uint32_t*)P.s->hsel + (((b >> 4) * 4 + ((b >> 2) & 3)) * 32 + fs * 4 + ((tid >> 2) & 3)) * 4 + (b & 3);
      float gate = rcp(1.f + ex2(-1.4426950408889634f * __uint_as_float(ks ^ (~(uint32_t)((int)ks >> 31) | 0x80000000u))));
      __nv_bfloat16* op = P.out + (size_t)(2047 - (ks & 2047)) * D_ + b * 8 + (tid >> 1);
      asm volatile("" : "+l"(yq), "+l"(fq), "+l"(op), "+f"(gate));
      while ((uint32_t)clock64() - ty < YDELAY) {}
      uint4 v;
      uint32_t fn = 0, fh = 0;
#pragma unroll 1
      for (int it = 0; it < SPIN_LIMIT; it++) {
        v = ld_rlx4(yq);
        if (wid == 0) { fn = ld_rlx(fq); fh = ld_rlx(fq + 4096); }
        TSV(22, 100);
        if (!__any_sync(~0u, max4(max(fn, fh), v) == SENT)) break;
      }
      const float base = (tid & 2) ? bf_hi(fh) + bf_hi(fn) : bf_lo(fh) + bf_lo(fn);
      TS(18);
      const bool p4 = lane & 16, p3 = lane & 8, p2 = lane & 4;
      const uint32_t w0 = __shfl_xor_sync(~0u, p4 ? v.x : v.z, 16), w1 = __shfl_xor_sync(~0u, p4 ? v.y : v.w, 16), o0 = p4 ? v.z : v.x, o1 = p4 ? v.w : v.y;
      const float y0 = bf_lo(o0) + bf_lo(w0), y1 = bf_hi(o0) + bf_hi(w0), y2 = bf_lo(o1) + bf_lo(w1), y3 = bf_hi(o1) + bf_hi(w1);
      const float z0 = (p3 ? y2 : y0) + __shfl_xor_sync(~0u, p3 ? y0 : y2, 8), z1 = (p3 ? y3 : y1) + __shfl_xor_sync(~0u, p3 ? y1 : y3, 8);
      float z = (p2 ? z1 : z0) + __shfl_xor_sync(~0u, p2 ? z0 : z1, 4);
      z += __shfl_xor_sync(~0u, z, 2);
      const uint32_t yx = msc + 128;
      if (!(lane & 2)) sts1(yx + wid * 64 + ((lane & 1) * 8 + (lane >> 2)) * 4, __float_as_uint(z));
      bar_sync(13, 224);
      if (tid < 16) {
        float y = 0.f;
#pragma unroll
        for (int w = 0; w < 7; w++) y += __uint_as_float(lds1(yx + w * 64 + tid * 4));
        *op = __float2bfloat16(fmaf(y, gate, base));
      }
      if (b == 0 && tid == 32) P.s->epoch = lds1(mb + B_SW) & 255;
    }
    if (tid == 0) SPANS(1);
    TS(19); TSG(31);
    if (warp == 0) TS_DUMP(wg);
   }
  }
}

typedef CUresult (*EncodeFn)(CUtensorMap*, CUtensorMapDataType, cuuint32_t, void*, const cuuint64_t*, const cuuint64_t*, const cuuint32_t*,
                             const cuuint32_t*, CUtensorMapInterleave, CUtensorMapSwizzle, CUtensorMapL2promotion, CUtensorMapFloatOOBfill);
void make_map(EncodeFn enc, CUtensorMap* m, const void* p, int rank, std::initializer_list<cuuint64_t> dims, std::initializer_list<cuuint64_t> str,
              std::initializer_list<cuuint32_t> box, CUtensorMapSwizzle sw) {
  const cuuint32_t es[4] = {1, 1, 1, 1};
  enc(m, CU_TENSOR_MAP_DATA_TYPE_BFLOAT16, rank, const_cast<void*>(p), dims.begin(), str.begin(), box.begin(), es, CU_TENSOR_MAP_INTERLEAVE_NONE, sw,
      CU_TENSOR_MAP_L2_PROMOTION_L2_128B, CU_TENSOR_MAP_FLOAT_OOB_FILL_NONE);
}

}

extern "C" void kernel_launch(void* const* d_in, const int* in_sizes, int n_in, void* d_out, int out_size) {
  (void)in_sizes; (void)n_in; (void)out_size;
  Ptrs P;
  P.x = (const __nv_bfloat16*)d_in[0]; P.wqkv = (const __nv_bfloat16*)d_in[1]; P.wo = (const __nv_bfloat16*)d_in[2];
  P.wr = (const __nv_bfloat16*)d_in[4]; P.wg = (const __nv_bfloat16*)d_in[5]; P.wu = (const __nv_bfloat16*)d_in[6];
  P.wd = (const __nv_bfloat16*)d_in[7]; P.out = (__nv_bfloat16*)d_out;
  cudaGetSymbolAddress((void**)&P.s, g_scratch);
  void* fn = nullptr;
  cudaDriverEntryPointQueryResult q;
  cudaGetDriverEntryPoint("cuTensorMapEncodeTiled", &fn, cudaEnableDefault, &q);
  EncodeFn enc = (EncodeFn)fn;
  Maps T;
  constexpr CUtensorMapSwizzle S128 = CU_TENSOR_MAP_SWIZZLE_128B, S64 = CU_TENSOR_MAP_SWIZZLE_64B;
  make_map(enc, &T.m[M_X], P.x, 2, {D_, S_}, {D_ * 2}, {64, 128}, S128);
  make_map(enc, &T.m[M_W], P.wqkv, 3, {D_, D_, 3}, {3 * D_ * 2, D_ * 2}, {64, 64, 2}, S128);
  make_map(enc, &T.m[M_Q], P.wqkv, 2, {3 * D_, D_}, {3 * D_ * 2}, {64, 64}, S128);
  make_map(enc, &T.m[M_O], P.wo, 4, {64, 64, 16, 16}, {D_ * 2, 64 * D_ * 2, 128}, {64, 64, 1, 2}, S128);
  make_map(enc, &T.m[M_S], P.wo, 4, {64, 64, 16, 16}, {D_ * 2, 64 * D_ * 2, 128}, {64, 16, 4, 2}, S128);
  make_map(enc, &T.m[M_G], P.wg, 3, {F_, D_, 1}, {F_ * 2, F_ * 2 * D_}, {32, 128, 1}, S64);
  make_map(enc, &T.m[M_U], P.wu, 3, {F_, D_, 1}, {F_ * 2, F_ * 2 * D_}, {32, 128, 1}, S64);
  make_map(enc, &T.m[M_D], P.wd, 3, {64, F_, 16}, {D_ * 2, 128}, {64, 32, 2}, S128);
  make_map(enc, &T.m[M_L], P.wd, 2, {64, F_ * 16}, {128}, {8, 32}, CU_TENSOR_MAP_SWIZZLE_NONE);
  cudaFuncSetAttribute(fused_kernel, cudaFuncAttributeMaxDynamicSharedMemorySize, SMEM_BYTES);
  fused_kernel<<<NCTA, 384, SMEM_BYTES>>>(P, T);
}
```

```cpp
#include <cuda_runtime.h>
#include <cuda.h>
#include <cuda_bf16.h>
#include <stdint.h>
#include <type_traits>
#include <initializer_list>

namespace {

constexpr int S_ = 2048, D_ = 1024, F_ = 3584;
constexpr int NCTA = 128, NFFN = 112;
constexpr uint32_t SENT = 0xFFFFFFFFu;
constexpr int SPIN_LIMIT = 1 << 20;

#define ADELAY 0
#define ADELAY2 100
#define PFA 6
#define PF0 8
#define WPF0 8
#define DPER 1200
#define PDEPTH 2
#define PSTART 4000
#define PPER 1700
#define PEARLY 5
#define PLEAD 0
#define RST 1
#define PSUB 2
#define HOLDP 1
#define QHOLD 1
#define NPULL 12
#define CDELAY 0
#define NOUTW 3
#define YDELAY 650
#define EFX 0
#define EFW 1
#define EFF 1
#define KLEAD 13
#define GDELAY 1000
#define NDIR 6
#define PULL0 3
#define FD0 400
#define FD1 800
#define SPF 1
#define MPF 1
#define TLBW 2
#define GORD 0
#define GSPLIT 2
#define EFW0 0
#define EFX0 0
#define EFWK 8
#define PSLEEP 20
#define P3PULL 1
#define RST2 4
#define KDELAY 450
#define AEARLY 0
#define BHOLD 4
#define SDELAY 100
#define FSTAG 150
#define OFL 0
#define CHKF 1
#define BEV 1
#define DLATE 4
#define P3GATE 3
#define ACCSW 1
#define B45 B_E
#define SDEL2 500
#define XDELAY 500
#define GU1 8
#define GU2 20
#define WD1 10
#define ODELAY 0
#define NOOUT 0
constexpr int OUNR =
  2;
#define P3N 2
#define HALFMAP 1
#define KWARP 7
#define FEARLY 1
#define MFIRST 350
#define MKV 950
#define MO 850
#define MST 1450
#define MSTE 13
#define AFIRST 0
#define MWIDE 0
#define PLAG 8
#define PSTEP 0
#define EFA 0
#define EFO 0
#define EFB 0
#define EFXK 12
#define PSTOP 3
#define DMASK 0x5550
#define PFST 1
#define W0OFF 2
#define MAPM 2
#define XWPF 0
constexpr uint32_t STAGE_B = 57344;
constexpr uint32_t OFF_STATS = 229376;
constexpr uint32_t OFF_COLSUM = 231424;
constexpr uint32_t OFF_BARS = 232192;
constexpr uint32_t SMEM_BYTES = 232448;
constexpr uint32_t B_FULL = 0, B_EMPTY = 32, B_E = 64, B_AUX = 128, B_EVA = 136, B_EVB = 144, B_BF = 152, B_LATE = 232, B_FFN = 240, B_SW = 248;
constexpr uint32_t B_OUT = B_FULL, B_SEL = B_FULL + 8, B_WR = B_FULL + 16, B_FFD = B_FULL + 24, B_E16 = B_EMPTY + 16, B_KVB = B_EMPTY + 8, B_DUMMY = B_SW + 4,
                   B_GATE = B_EMPTY + 24, B_ID = B_BF + 56, B_KVP = B_BF + 64, B_F15 = B_BF + 72;
#define B_HOLD B_F15
#define HOLDPAR 0
constexpr uint32_t UNIT = 8192;
constexpr uint32_t sb = 1024;
constexpr uint32_t bars = sb + OFF_BARS;
constexpr uint64_t tab5(int a, int b, int c, int d, int e, int f, int g, int h, int i = 0, int j = 0) {
  return (uint64_t)a | (uint64_t)b << 5 | (uint64_t)c << 10 | (uint64_t)d << 15 | (uint64_t)e << 20 | (uint64_t)f << 25 | (uint64_t)g << 30 | (uint64_t)h << 35 |
         (uint64_t)i << 40 | (uint64_t)j << 45;
}
constexpr uint64_t BT0 = tab5(4, 11, 18, 25, 7, 9, 16, 0), BT1 = tab5(4, 11, 18, 25, 21, 23, 2, 0);
constexpr uint64_t GT0 = tab5(2, 21, 23, 18, 0, 25, 14, 7), GT1 = tab5(16, 7, 9, 18, 0, 25, 14, 21);
constexpr uint64_t DT0 = tab5(6, 13, 20, 27, 9, 10, 16, 17), DT1 = tab5(6, 13, 20, 27, 23, 24, 2, 3);
__device__ __forceinline__ uint32_t unit_of(uint64_t tab, int i) { return ((uint32_t)(tab >> (5 * i)) & 31) * UNIT; }
__device__ __forceinline__ uint32_t ring_of(int p, int w) { return (p & 1) * (2 * STAGE_B) + ((p & 2) ? 49152 + w * STAGE_B : w * UNIT); }
constexpr uint32_t OFF_LNP = OFF_STATS + 1024;

struct Scratch {
  uint4 obuf[32 * 64 * 128];
  uint4 kvp[16 * 8 * 256];
  uint4 zp[16 * 8 * 16];
  uint4 ybuf[NCTA * NFFN * 2];
  uint4 st1[S_];
  uint4 csp[16 * 8 * 48];
  uint4 st2[S_];
  uint4 hsel[2 * 8 * 128];
  uint32_t cand[8 * 32];
  uint32_t when[32 * 32];
  unsigned epoch;
};
__device__ __align__(1024) Scratch g_scratch;
#define TS_DECL
#define TS(i)
#define TSG(i)
#define TSV(i, v)
#define TSD(i)
#define RTS_DECL
#define RTS(i)
#define RTS_DUMP
#define TS_DUMP(slot)
#define PTS(i)
#define g_dbgv(i, v)

#define SPANS(i)
__device__ __forceinline__ uint32_t smem_u32(const void* p) { return (uint32_t)__cvta_generic_to_shared(p); }
__device__ __forceinline__ void mbar_init(uint32_t bar, uint32_t cnt) { asm volatile("mbarrier.init.shared::cta.b64 [%0], %1;" :: "r"(bar), "r"(cnt) : "memory"); }
__device__ __forceinline__ void mbar_expect_tx(uint32_t bar, uint32_t bytes) { asm volatile("mbarrier.arrive.expect_tx.shared::cta.b64 _, [%0], %1;" :: "r"(bar), "r"(bytes) : "memory"); }
__device__ __forceinline__ void mbar_arrive(uint32_t bar) { asm volatile("mbarrier.arrive.shared::cta.b64 _, [%0];" :: "r"(bar) : "memory"); }
#define SPINCHK(it, code) if ((it) > SPIN_LIMIT) break
__device__ __forceinline__ void mbar_wait(uint32_t bar, uint32_t parity) {
  asm volatile("{\n.reg .pred p;\n.reg .u32 c;\nmov.u32 c, 0;\n"
               "WL:\nmbarrier.try_wait.parity.shared::cta.b64 p, [%0], %1;\n@p bra WD;\n"
               "add.u32 c, c, 1;\nsetp.lt.u32 p, c, 1048576;\n@p bra WL;\nWD:\n}" :: "r"(bar), "r"(parity) : "memory");
}
__device__ __forceinline__ bool mbar_test(uint32_t bar, uint32_t parity) {
  uint32_t ok;
  asm volatile("{\n.reg .pred p;\nmbarrier.test_wait.parity.shared::cta.b64 p, [%1], %2;\nselp.u32 %0, 1, 0, p;\n}" : "=r"(ok) : "r"(bar), "r"(parity) : "memory");
  return ok;
}
__device__ __forceinline__ uint64_t l2_stream() { uint64_t p; asm("createpolicy.fractional.L2::evict_first.b64 %0, 1.0;" : "=l"(p)); return p; }
__device__ __forceinline__ void tma_2d(uint32_t dst, const CUtensorMap* tm, int c0, int c1, uint32_t bar, bool stream) {
  if (stream) asm volatile("cp.async.bulk.tensor.2d.shared::cluster.global.mbarrier::complete_tx::bytes.L2::cache_hint [%0], [%1, {%3, %4}], [%2], %5;"
                           :: "r"(dst), "l"(tm), "r"(bar), "r"(c0), "r"(c1), "l"(l2_stream()) : "memory");
  else asm volatile("cp.async.bulk.tensor.2d.shared::cluster.global.mbarrier::complete_tx::bytes [%0], [%1, {%3, %4}], [%2];"
                    :: "r"(dst), "l"(tm), "r"(bar), "r"(c0), "r"(c1) : "memory");
}
__device__ __forceinline__ void tma_3d(uint32_t dst, const CUtensorMap* tm, int c0, int c1, int c2, uint32_t bar, bool stream) {
  if (stream) asm volatile("cp.async.bulk.tensor.3d.shared::cluster.global.mbarrier::complete_tx::bytes.L2::cache_hint [%0], [%1, {%3, %4, %5}], [%2], %6;"
                           :: "r"(dst), "l"(tm), "r"(bar), "r"(c0), "r"(c1), "r"(c2), "l"(l2_stream()) : "memory");
  else asm volatile("cp.async.bulk.tensor.3d.shared::cluster.global.mbarrier::complete_tx::bytes [%0], [%1, {%3, %4, %5}], [%2];"
                    :: "r"(dst), "l"(tm), "r"(bar), "r"(c0), "r"(c1), "r"(c2) : "memory");
}
__device__ __forceinline__ void tma_pf_3d(const CUtensorMap* tm, int c0, int c1, int c2) {
  asm volatile("cp.async.bulk.prefetch.tensor.3d.L2.global [%0, {%1, %2, %3}];" :: "l"(tm), "r"(c0), "r"(c1), "r"(c2) : "memory");
}
__device__ __forceinline__ void tma_4d(uint32_t dst, const CUtensorMap* tm, int c0, int c1, int c2, int c3, uint32_t bar, bool stream) {
  if (stream) asm volatile("cp.async.bulk.tensor.4d.shared::cluster.global.mbarrier::complete_tx::bytes.L2::cache_hint [%0], [%1, {%3, %4, %5, %6}], [%2], %7;"
                           :: "r"(dst), "l"(tm), "r"(bar), "r"(c0), "r"(c1), "r"(c2), "r"(c3), "l"(l2_stream()) : "memory");
  else asm volatile("cp.async.bulk.tensor.4d.shared::cluster.global.mbarrier::complete_tx::bytes [%0], [%1, {%3, %4, %5, %6}], [%2];"
                    :: "r"(dst), "l"(tm), "r"(bar), "r"(c0), "r"(c1), "r"(c2), "r"(c3) : "memory");
}
__device__ __forceinline__ void tma_2d_mc(uint32_t dst, const CUtensorMap* tm, int c0, int c1, uint32_t bar, bool stream) {
  if (stream) asm volatile("cp.async.bulk.tensor.2d.shared::cluster.global.mbarrier::complete_tx::bytes.multicast::cluster.L2::cache_hint [%0], [%1, {%3, %4}], [%2], %5, %6;"
                           :: "r"(dst), "l"(tm), "r"(bar), "r"(c0), "r"(c1), "h"((uint16_t)3), "l"(l2_stream()) : "memory");
  else asm volatile("cp.async.bulk.tensor.2d.shared::cluster.global.mbarrier::complete_tx::bytes.multicast::cluster [%0], [%1, {%3, %4}], [%2], %5;"
                    :: "r"(dst), "l"(tm), "r"(bar), "r"(c0), "r"(c1), "h"((uint16_t)3) : "memory");
}
__device__ __forceinline__ bool elect_one() {
  uint32_t p;
  asm volatile("{\n.reg .pred q;\nelect.sync _|q, 0xFFFFFFFF;\nselp.u32 %0, 1, 0, q;\n}" : "=r"(p));
  return p;
}
__device__ __forceinline__ void bulk_load_mc(uint32_t dst, const void* src, uint32_t bytes, uint32_t bar) {
  if (EFA) asm volatile("cp.async.bulk.shared::cluster.global.mbarrier::complete_tx::bytes.multicast::cluster.L2::cache_hint [%0], [%1], %2, [%3], %4, %5;"
                        :: "r"(dst), "l"(src), "r"(bytes), "r"(bar), "h"((uint16_t)3), "l"(l2_stream()) : "memory");
  else asm volatile("cp.async.bulk.shared::cluster.global.mbarrier::complete_tx::bytes.multicast::cluster [%0], [%1], %2, [%3], %4;"
                    :: "r"(dst), "l"(src), "r"(bytes), "r"(bar), "h"((uint16_t)3) : "memory");
}
__device__ __forceinline__ void bulk_load(uint32_t dst, const void* src, uint32_t bytes, uint32_t bar) {
  asm volatile("cp.async.bulk.shared::cluster.global.mbarrier::complete_tx::bytes [%0], [%1], %2, [%3];" :: "r"(dst), "l"(src), "r"(bytes), "r"(bar) : "memory");
}
__device__ __forceinline__ void st_out(void* p, uint4 v) {
  if (EFO == 1) asm volatile("st.global.L2::cache_hint.v4.u32 [%0], {%1,%2,%3,%4}, %5;" :: "l"(p), "r"(v.x), "r"(v.y), "r"(v.z), "r"(v.w), "l"(l2_stream()) : "memory");
  else if (EFO == 2) asm volatile("st.global.cs.v4.u32 [%0], {%1,%2,%3,%4};" :: "l"(p), "r"(v.x), "r"(v.y), "r"(v.z), "r"(v.w) : "memory");
  else asm volatile("st.global.v4.u32 [%0], {%1,%2,%3,%4};" :: "l"(p), "r"(v.x), "r"(v.y), "r"(v.z), "r"(v.w) : "memory");
}
__device__ __forceinline__ void bulk_store(void* dst, uint32_t src, uint32_t bytes) {
  asm volatile("cp.async.bulk.global.shared::cta.bulk_group [%0], [%1], %2;" :: "l"(dst), "r"(src), "r"(bytes) : "memory");
}
__device__ __forceinline__ void mbar_arrive_rem(uint32_t bar) { asm volatile("mbarrier.arrive.shared::cluster.b64 _, [%0];" :: "r"(bar) : "memory"); }
__device__ __forceinline__ void st_async4(uint32_t addr, const uint4& v, uint32_t bar) {
  asm volatile("st.async.shared::cluster.mbarrier::complete_tx::bytes.v4.b32 [%0], {%1,%2,%3,%4}, [%5];" :: "r"(addr), "r"(v.x), "r"(v.y), "r"(v.z), "r"(v.w), "r"(bar) : "memory");
}
template <uint32_t O> __device__ __forceinline__ void ldsm4_o(uint32_t addr, uint32_t& a, uint32_t& b, uint32_t& c, uint32_t& d) {
  asm volatile("ldmatrix.sync.aligned.m8n8.x4.shared.b16 {%0,%1,%2,%3}, [%4+%5];" : "=r"(a), "=r"(b), "=r"(c), "=r"(d) : "r"(addr), "n"(O) : "memory");
}
template <uint32_t O> __device__ __forceinline__ void ldsm4t_o(uint32_t addr, uint32_t (&r)[4]) {
  asm volatile("ldmatrix.sync.aligned.m8n8.x4.trans.shared.b16 {%0,%1,%2,%3}, [%4+%5];" : "=r"(r[0]), "=r"(r[1]), "=r"(r[2]), "=r"(r[3]) : "r"(addr), "n"(O) : "memory");
}
__device__ __forceinline__ void mma16816(float (&c)[4], const uint32_t (&a)[4], uint32_t b0, uint32_t b1) {
  asm("mma.sync.aligned.m16n8k16.row.col.f32.bf16.bf16.f32 {%0,%1,%2,%3}, {%4,%5,%6,%7}, {%8,%9}, {%0,%1,%2,%3};"
      : "+f"(c[0]), "+f"(c[1]), "+f"(c[2]), "+f"(c[3]) : "r"(a[0]), "r"(a[1]), "r"(a[2]), "r"(a[3]), "r"(b0), "r"(b1));
}
__device__ __forceinline__ void l2_prefetch(const void* p) { asm volatile("prefetch.global.L2 [%0];" :: "l"(p) : "memory"); }
__device__ __forceinline__ uint32_t ld_line(const void* p) { uint32_t v; asm volatile("ld.global.cg.L2::128B.u32 %0, [%1];" : "=r"(v) : "l"(p) : "memory"); return v; }
__device__ __forceinline__ void tmap_prefetch(const CUtensorMap* tm) { asm volatile("prefetch.tensormap [%0];" :: "l"(tm) : "memory"); }
__device__ __forceinline__ void wg_fence() { asm volatile("wgmma.fence.sync.aligned;" ::: "memory"); }
__device__ __forceinline__ void wg_commit() { asm volatile("wgmma.commit_group.sync.aligned;" ::: "memory"); }
template <int N> __device__ __forceinline__ void wg_wait() { asm volatile("wgmma.wait_group.sync.aligned %0;" :: "n"(N) : "memory"); }
template <int N> __device__ __forceinline__ void pin(float (&d)[N]) {
#pragma unroll
  for (int i = 0; i < N; i++) asm volatile("" : "+f"(d[i]) :: "memory");
}
__device__ __forceinline__ void pin4(uint4& v) { asm volatile("" : "+r"(v.x), "+r"(v.y), "+r"(v.z), "+r"(v.w) :: "memory"); }
template <uint32_t SBO, uint32_t SWZ> __device__ __forceinline__ uint64_t dsc(uint32_t lo) { return ((uint64_t)((SBO >> 4) | (SWZ << 30)) << 32) | lo; }
__host__ __device__ constexpr uint32_t dlo(uint32_t addr, uint32_t lbo) { return (addr >> 4) | ((lbo >> 4) << 16); }
__device__ __forceinline__ void bar_sync(int id, int n) { asm volatile("bar.sync %0, %1;" :: "r"(id), "r"(n) : "memory"); }
__device__ __forceinline__ void bar_arrive(int id, int n) { asm volatile("bar.arrive %0, %1;" :: "r"(id), "r"(n) : "memory"); }
__device__ __forceinline__ void fence_async_smem() { asm volatile("fence.proxy.async.shared::cta;" ::: "memory"); }
__device__ __forceinline__ void fence_gpu() { asm volatile("fence.acq_rel.gpu;" ::: "memory"); }
__device__ __forceinline__ uint4 ld_cg4(const void* p) { uint4 v; asm volatile("ld.global.cg.v4.u32 {%0,%1,%2,%3}, [%4];" : "=r"(v.x), "=r"(v.y), "=r"(v.z), "=r"(v.w) : "l"(p) : "memory"); return v; }
__device__ __forceinline__ uint4 ld_rlx4(const void* p) { uint4 v; asm volatile("ld.relaxed.gpu.global.v4.u32 {%0,%1,%2,%3}, [%4];" : "=r"(v.x), "=r"(v.y), "=r"(v.z), "=r"(v.w) : "l"(p) : "memory"); return v; }
__device__ __forceinline__ uint32_t ld_rlx(const void* p) { uint32_t v; asm volatile("ld.relaxed.gpu.global.u32 %0, [%1];" : "=r"(v) : "l"(p) : "memory"); return v; }
__device__ __forceinline__ void st_rlx4(void* p, uint4 v) { asm volatile("st.relaxed.gpu.global.v4.u32 [%0], {%1,%2,%3,%4};" :: "l"(p), "r"(v.x), "r"(v.y), "r"(v.z), "r"(v.w) : "memory"); }
__device__ __forceinline__ void st_rlx2(void* p, uint32_t a, uint32_t b) { asm volatile("st.relaxed.gpu.global.v2.u32 [%0], {%1,%2};" :: "l"(p), "r"(a), "r"(b) : "memory"); }
__device__ __forceinline__ void st_rlx(void* p, uint32_t a) { asm volatile("st.relaxed.gpu.global.u32 [%0], %1;" :: "l"(p), "r"(a) : "memory"); }
__device__ __forceinline__ void red4(void* p, float a, float b, float c, float d) { asm volatile("red.relaxed.gpu.global.add.v4.f32 [%0], {%1,%2,%3,%4};" :: "l"(p), "f"(a), "f"(b), "f"(c), "f"(d) : "memory"); }
__device__ __forceinline__ uint32_t pack2(float lo, float hi) { uint32_t r; asm("cvt.rn.bf16x2.f32 %0, %1, %2;" : "=r"(r) : "f"(hi), "f"(lo)); return r; }
__device__ __forceinline__ float bf_lo(uint32_t v) { return __uint_as_float(v << 16); }
__device__ __forceinline__ float bf_hi(uint32_t v) { return __uint_as_float(v & 0xFFFF0000u); }
__device__ __forceinline__ void stsm4(uint32_t addr, uint32_t a, uint32_t b, uint32_t c, uint32_t d) {
  asm volatile("stmatrix.sync.aligned.m8n8.x4.shared.b16 [%0], {%1,%2,%3,%4};" :: "r"(addr), "r"(a), "r"(b), "r"(c), "r"(d) : "memory");
}
template <uint32_t O> __device__ __forceinline__ void stsm4_o(uint32_t addr, uint32_t a, uint32_t b, uint32_t c, uint32_t d) {
  asm volatile("stmatrix.sync.aligned.m8n8.x4.shared.b16 [%0+%5], {%1,%2,%3,%4};" :: "r"(addr), "r"(a), "r"(b), "r"(c), "r"(d), "n"(O) : "memory");
}
__device__ __forceinline__ void sts4(uint32_t addr, uint32_t a, uint32_t b, uint32_t c, uint32_t d) { asm volatile("st.shared.v4.u32 [%0], {%1,%2,%3,%4};" :: "r"(addr), "r"(a), "r"(b), "r"(c), "r"(d) : "memory"); }
__device__ __forceinline__ void sts2f(uint32_t addr, float a, float b) { asm volatile("st.shared.v2.f32 [%0], {%1,%2};" :: "r"(addr), "f"(a), "f"(b) : "memory"); }
__device__ __forceinline__ void sts1(uint32_t addr, uint32_t a) { asm volatile("st.shared.u32 [%0], %1;" :: "r"(addr), "r"(a) : "memory"); }
__device__ __forceinline__ float2 lds2f(uint32_t addr) { float2 v; asm volatile("ld.shared.v2.f32 {%0,%1}, [%2];" : "=f"(v.x), "=f"(v.y) : "r"(addr) : "memory"); return v; }
template <uint32_t O> __device__ __forceinline__ float2 lds2f_o(uint32_t addr) { float2 v; asm volatile("ld.shared.v2.f32 {%0,%1}, [%2+%3];" : "=f"(v.x), "=f"(v.y) : "r"(addr), "n"(O) : "memory"); return v; }
template <int I, int N, class F> __device__ __forceinline__ void static_for(F&& f) { if constexpr (I < N) { f(std::integral_constant<int, I>{}); static_for<I + 1, N>(f); } }
__device__ __forceinline__ uint4 lds4(uint32_t addr) { uint4 v; asm volatile("ld.shared.v4.u32 {%0,%1,%2,%3}, [%4];" : "=r"(v.x), "=r"(v.y), "=r"(v.z), "=r"(v.w) : "r"(addr) : "memory"); return v; }
__device__ __forceinline__ uint32_t lds1(uint32_t addr) { uint32_t v; asm volatile("ld.shared.u32 %0, [%1];" : "=r"(v) : "r"(addr) : "memory"); return v; }
__device__ __forceinline__ float ex2(float x) { float y; asm("ex2.approx.ftz.f32 %0, %1;" : "=f"(y) : "f"(x)); return y; }
__device__ __forceinline__ uint32_t max4(uint32_t m, const uint4& v) { return __vimax3_u32(__vimax3_u32(m, v.x, v.y), v.z, v.w); }
__device__ __forceinline__ float rsq(float x) { float y; asm("rsqrt.approx.ftz.f32 %0, %1;" : "=f"(y) : "f"(x)); return y; }
__device__ __forceinline__ float rcp(float x) { float y; asm("rcp.approx.ftz.f32 %0, %1;" : "=f"(y) : "f"(x)); return y; }
__device__ __forceinline__ uint2 ld_rlx2(const void* p) { uint2 v; asm volatile("ld.relaxed.gpu.global.v2.u32 {%0,%1}, [%2];" : "=r"(v.x), "=r"(v.y) : "l"(p) : "memory"); return v; }
template <uint32_t O> __device__ __forceinline__ uint4 lds4_o(uint32_t addr) { uint4 v; asm volatile("ld.shared.v4.u32 {%0,%1,%2,%3}, [%4+%5];" : "=r"(v.x), "=r"(v.y), "=r"(v.z), "=r"(v.w) : "r"(addr), "n"(O) : "memory"); return v; }
__device__ __forceinline__ uint32_t phi2(float u0, float u1, float rl, uint32_t r2) {
  uint32_t pu, r;
  asm("cvt.rn.relu.bf16x2.f32 %0, %1, %2;" : "=r"(pu) : "f"(u1), "f"(u0));
  asm("fma.rn.bf16x2 %0, %1, %2, %3;" : "=r"(r) : "r"(pu), "r"(r2), "r"(pack2(__saturatef(ex2(u0 * rl) + 1e-6f), __saturatef(ex2(u1 * rl) + 1e-6f))));
  return r;
}
__device__ __forceinline__ uint32_t dup2(float r) { uint32_t v; asm("cvt.rn.relu.bf16x2.f32 %0, %1, %1;" : "=r"(v) : "f"(r)); return v; }
__device__ __forceinline__ uint32_t zero_after(const uint32_t (&v)[16]) {
  uint32_t z = 0;
#pragma unroll
  for (int i = 0; i < 16; i++) z |= v[i];
  return z & 0x80008000u;
}
__device__ __forceinline__ uint32_t hadd2(uint32_t a, uint32_t b) { uint32_t v; asm("add.rn.bf16x2 %0, %1, %2;" : "=r"(v) : "r"(a), "r"(b)); return v; }
__device__ __forceinline__ void sched_fence() { asm volatile("{\n.reg .pred p;\n.reg .u64 c;\nSF:\nmov.u64 c, %clock64;\nsetp.eq.u64 p, c, 0;\n@p bra SF;\n}" ::: "memory"); }
__device__ __forceinline__ uint4 ld_gen4(const void* p) { uint4 v; asm volatile("ld.relaxed.gpu.v4.u32 {%0,%1,%2,%3}, [%4];" : "=r"(v.x), "=r"(v.y), "=r"(v.z), "=r"(v.w) : "l"(p) : "memory"); return v; }
__device__ __forceinline__ uint2 ld_gen2(const void* p) { uint2 v; asm volatile("ld.relaxed.gpu.v2.u32 {%0,%1}, [%2];" : "=r"(v.x), "=r"(v.y) : "l"(p) : "memory"); return v; }
__device__ __forceinline__ uint32_t now_ns() { uint32_t v; asm volatile("mov.u32 %0, %%globaltimer_lo;" : "=r"(v) :: "memory"); return v; }
__device__ __forceinline__ void meet(uint32_t* mine, const uint4* all, int first, int after, uint32_t bar) {
  const uint32_t t0 = now_ns() & ~1u;
  if ((threadIdx.x & 31) == 0) st_rlx(mine, t0);
  while ((int)(now_ns() - t0) < first) {}
  uint4 v;
#pragma unroll 1
  for (int it = 0; it < SPIN_LIMIT; it++) { v = ld_rlx4(all); if (!__any_sync(~0u, max4(0, v) == SENT)) break; }
  const int d = min(__reduce_max_sync(~0u, max(max((int)(v.x - t0), (int)(v.y - t0)), max((int)(v.z - t0), (int)(v.w - t0)))), 100000) + after;
  mbar_wait(bar, 0);
  while ((int)(now_ns() - t0) < d) {}
}
__device__ __forceinline__ uint32_t lane_id() { uint32_t v; asm volatile("mov.u32 %0, %%laneid;" : "=r"(v)); return v; }
template <int A, int B, int N> __device__ __forceinline__ void pinr(float (&d)[N]) {
#pragma unroll
  for (int i = A; i < B; i++) asm volatile("" : "+f"(d[i]) :: "memory");
}
template <int N> __device__ __forceinline__ void pinu(uint32_t (&d)[N]) {
#pragma unroll
  for (int i = 0; i < N; i++) asm volatile("" : "+r"(d[i]) :: "memory");
}

template<int TA, int TB, int OFF, int SZ> __device__ __forceinline__ void wgmma_n192_ss(float (&d)[SZ], uint64_t da, uint64_t db, int scale_d) {
  asm volatile("{\n.reg .pred p;\nsetp.ne.b32 p, %98, 0;\n"
    "wgmma.mma_async.sync.aligned.m64n192k16.f32.bf16.bf16 {%0,%1,%2,%3,%4,%5,%6,%7,%8,%9,%10,%11,%12,%13,%14,%15,%16,%17,%18,%19,%20,%21,%22,%23,%24,%25,%26,%27,%28,%29,%30,%31,%32,%33,%34,%35,%36,%37,%38,%39,%40,%41,%42,%43,%44,%45,%46,%47,%48,%49,%50,%51,%52,%53,%54,%55,%56,%57,%58,%59,%60,%61,%62,%63,%64,%65,%66,%67,%68,%69,%70,%71,%72,%73,%74,%75,%76,%77,%78,%79,%80,%81,%82,%83,%84,%85,%86,%87,%88,%89,%90,%91,%92,%93,%94,%95}, %96, %97, p, 1, 1, %99, %100;\n}\n"
    : "+f"(d[OFF+0]), "+f"(d[OFF+1]), "+f"(d[OFF+2]), "+f"(d[OFF+3]), "+f"(d[OFF+4]), "+f"(d[OFF+5]), "+f"(d[OFF+6]), "+f"(d[OFF+7]),
      "+f"(d[OFF+8]), "+f"(d[OFF+9]), "+f"(d[OFF+10]), "+f"(d[OFF+11]), "+f"(d[OFF+12]), "+f"(d[OFF+13]), "+f"(d[OFF+14]), "+f"(d[OFF+15]),
      "+f"(d[OFF+16]), "+f"(d[OFF+17]), "+f"(d[OFF+18]), "+f"(d[OFF+19]), "+f"(d[OFF+20]), "+f"(d[OFF+21]), "+f"(d[OFF+22]), "+f"(d[OFF+23]),
      "+f"(d[OFF+24]), "+f"(d[OFF+25]), "+f"(d[OFF+26]), "+f"(d[OFF+27]), "+f"(d[OFF+28]), "+f"(d[OFF+29]), "+f"(d[OFF+30]), "+f"(d[OFF+31]),
      "+f"(d[OFF+32]), "+f"(d[OFF+33]), "+f"(d[OFF+34]), "+f"(d[OFF+35]), "+f"(d[OFF+36]), "+f"(d[OFF+37]), "+f"(d[OFF+38]), "+f"(d[OFF+39]),
      "+f"(d[OFF+40]), "+f"(d[OFF+41]), "+f"(d[OFF+42]), "+f"(d[OFF+43]), "+f"(d[OFF+44]), "+f"(d[OFF+45]), "+f"(d[OFF+46]), "+f"(d[OFF+47]),
      "+f"(d[OFF+48]), "+f"(d[OFF+49]), "+f"(d[OFF+50]), "+f"(d[OFF+51]), "+f"(d[OFF+52]), "+f"(d[OFF+53]), "+f"(d[OFF+54]), "+f"(d[OFF+55]),
      "+f"(d[OFF+56]), "+f"(d[OFF+57]), "+f"(d[OFF+58]), "+f"(d[OFF+59]), "+f"(d[OFF+60]), "+f"(d[OFF+61]), "+f"(d[OFF+62]), "+f"(d[OFF+63]),
      "+f"(d[OFF+64]), "+f"(d[OFF+65]), "+f"(d[OFF+66]), "+f"(d[OFF+67]), "+f"(d[OFF+68]), "+f"(d[OFF+69]), "+f"(d[OFF+70]), "+f"(d[OFF+71]),
      "+f"(d[OFF+72]), "+f"(d[OFF+73]), "+f"(d[OFF+74]), "+f"(d[OFF+75]), "+f"(d[OFF+76]), "+f"(d[OFF+77]), "+f"(d[OFF+78]), "+f"(d[OFF+79]),
      "+f"(d[OFF+80]), "+f"(d[OFF+81]), "+f"(d[OFF+82]), "+f"(d[OFF+83]), "+f"(d[OFF+84]), "+f"(d[OFF+85]), "+f"(d[OFF+86]), "+f"(d[OFF+87]),
      "+f"(d[OFF+88]), "+f"(d[OFF+89]), "+f"(d[OFF+90]), "+f"(d[OFF+91]), "+f"(d[OFF+92]), "+f"(d[OFF+93]), "+f"(d[OFF+94]), "+f"(d[OFF+95])
    : "l"(da), "l"(db), "r"(scale_d), "n"(TA), "n"(TB));
}
template<int TA, int TB, int OFF, int SZ> __device__ __forceinline__ void wgmma_n128_ss(float (&d)[SZ], uint64_t da, uint64_t db, int scale_d) {
  asm volatile("{\n.reg .pred p;\nsetp.ne.b32 p, %66, 0;\n"
    "wgmma.mma_async.sync.aligned.m64n128k16.f32.bf16.bf16 {%0,%1,%2,%3,%4,%5,%6,%7,%8,%9,%10,%11,%12,%13,%14,%15,%16,%17,%18,%19,%20,%21,%22,%23,%24,%25,%26,%27,%28,%29,%30,%31,%32,%33,%34,%35,%36,%37,%38,%39,%40,%41,%42,%43,%44,%45,%46,%47,%48,%49,%50,%51,%52,%53,%54,%55,%56,%57,%58,%59,%60,%61,%62,%63}, %64, %65, p, 1, 1, %67, %68;\n}\n"
    : "+f"(d[OFF+0]), "+f"(d[OFF+1]), "+f"(d[OFF+2]), "+f"(d[OFF+3]), "+f"(d[OFF+4]), "+f"(d[OFF+5]), "+f"(d[OFF+6]), "+f"(d[OFF+7]),
      "+f"(d[OFF+8]), "+f"(d[OFF+9]), "+f"(d[OFF+10]), "+f"(d[OFF+11]), "+f"(d[OFF+12]), "+f"(d[OFF+13]), "+f"(d[OFF+14]), "+f"(d[OFF+15]),
      "+f"(d[OFF+16]), "+f"(d[OFF+17]), "+f"(d[OFF+18]), "+f"(d[OFF+19]), "+f"(d[OFF+20]), "+f"(d[OFF+21]), "+f"(d[OFF+22]), "+f"(d[OFF+23]),
      "+f"(d[OFF+24]), "+f"(d[OFF+25]), "+f"(d[OFF+26]), "+f"(d[OFF+27]), "+f"(d[OFF+28]), "+f"(d[OFF+29]), "+f"(d[OFF+30]), "+f"(d[OFF+31]),
      "+f"(d[OFF+32]), "+f"(d[OFF+33]), "+f"(d[OFF+34]), "+f"(d[OFF+35]), "+f"(d[OFF+36]), "+f"(d[OFF+37]), "+f"(d[OFF+38]), "+f"(d[OFF+39]),
      "+f"(d[OFF+40]), "+f"(d[OFF+41]), "+f"(d[OFF+42]), "+f"(d[OFF+43]), "+f"(d[OFF+44]), "+f"(d[OFF+45]), "+f"(d[OFF+46]), "+f"(d[OFF+47]),
      "+f"(d[OFF+48]), "+f"(d[OFF+49]), "+f"(d[OFF+50]), "+f"(d[OFF+51]), "+f"(d[OFF+52]), "+f"(d[OFF+53]), "+f"(d[OFF+54]), "+f"(d[OFF+55]),
      "+f"(d[OFF+56]), "+f"(d[OFF+57]), "+f"(d[OFF+58]), "+f"(d[OFF+59]), "+f"(d[OFF+60]), "+f"(d[OFF+61]), "+f"(d[OFF+62]), "+f"(d[OFF+63])
    : "l"(da), "l"(db), "r"(scale_d), "n"(TA), "n"(TB));
}
template<int TA, int TB, int OFF, int SZ> __device__ __forceinline__ void wgmma_n64_ss(float (&d)[SZ], uint64_t da, uint64_t db, int scale_d) {
  asm volatile("{\n.reg .pred p;\nsetp.ne.b32 p, %34, 0;\n"
    "wgmma.mma_async.sync.aligned.m64n64k16.f32.bf16.bf16 {%0,%1,%2,%3,%4,%5,%6,%7,%8,%9,%10,%11,%12,%13,%14,%15,%16,%17,%18,%19,%20,%21,%22,%23,%24,%25,%26,%27,%28,%29,%30,%31}, %32, %33, p, 1, 1, %35, %36;\n}\n"
    : "+f"(d[OFF+0]), "+f"(d[OFF+1]), "+f"(d[OFF+2]), "+f"(d[OFF+3]), "+f"(d[OFF+4]), "+f"(d[OFF+5]), "+f"(d[OFF+6]), "+f"(d[OFF+7]),
      "+f"(d[OFF+8]), "+f"(d[OFF+9]), "+f"(d[OFF+10]), "+f"(d[OFF+11]), "+f"(d[OFF+12]), "+f"(d[OFF+13]), "+f"(d[OFF+14]), "+f"(d[OFF+15]),
      "+f"(d[OFF+16]), "+f"(d[OFF+17]), "+f"(d[OFF+18]), "+f"(d[OFF+19]), "+f"(d[OFF+20]), "+f"(d[OFF+21]), "+f"(d[OFF+22]), "+f"(d[OFF+23]),
      "+f"(d[OFF+24]), "+f"(d[OFF+25]), "+f"(d[OFF+26]), "+f"(d[OFF+27]), "+f"(d[OFF+28]), "+f"(d[OFF+29]), "+f"(d[OFF+30]), "+f"(d[OFF+31])
    : "l"(da), "l"(db), "r"(scale_d), "n"(TA), "n"(TB));
}
template<int TA, int TB, int OFF, int SZ> __device__ __forceinline__ void wgmma_n72_ss(float (&d)[SZ], uint64_t da, uint64_t db, int scale_d) {
  asm volatile("{\n.reg .pred p;\nsetp.ne.b32 p, %38, 0;\n"
    "wgmma.mma_async.sync.aligned.m64n72k16.f32.bf16.bf16 {%0,%1,%2,%3,%4,%5,%6,%7,%8,%9,%10,%11,%12,%13,%14,%15,%16,%17,%18,%19,%20,%21,%22,%23,%24,%25,%26,%27,%28,%29,%30,%31,%32,%33,%34,%35}, %36, %37, p, 1, 1, %39, %40;\n}\n"
    : "+f"(d[OFF+0]), "+f"(d[OFF+1]), "+f"(d[OFF+2]), "+f"(d[OFF+3]), "+f"(d[OFF+4]), "+f"(d[OFF+5]), "+f"(d[OFF+6]), "+f"(d[OFF+7]),
      "+f"(d[OFF+8]), "+f"(d[OFF+9]), "+f"(d[OFF+10]), "+f"(d[OFF+11]), "+f"(d[OFF+12]), "+f"(d[OFF+13]), "+f"(d[OFF+14]), "+f"(d[OFF+15]),
      "+f"(d[OFF+16]), "+f"(d[OFF+17]), "+f"(d[OFF+18]), "+f"(d[OFF+19]), "+f"(d[OFF+20]), "+f"(d[OFF+21]), "+f"(d[OFF+22]), "+f"(d[OFF+23]),
      "+f"(d[OFF+24]), "+f"(d[OFF+25]), "+f"(d[OFF+26]), "+f"(d[OFF+27]), "+f"(d[OFF+28]), "+f"(d[OFF+29]), "+f"(d[OFF+30]), "+f"(d[OFF+31]),
      "+f"(d[OFF+32]), "+f"(d[OFF+33]), "+f"(d[OFF+34]), "+f"(d[OFF+35])
    : "l"(da), "l"(db), "r"(scale_d), "n"(TA), "n"(TB));
}
template<int TB, int OFF, int SZ> __device__ __forceinline__ void wgmma_n64_rs(float (&d)[SZ], uint32_t a0, uint32_t a1, uint32_t a2, uint32_t a3, uint64_t db, int scale_d) {
  asm volatile("{\n.reg .pred p;\nsetp.ne.b32 p, %37, 0;\n"
    "wgmma.mma_async.sync.aligned.m64n64k16.f32.bf16.bf16 {%0,%1,%2,%3,%4,%5,%6,%7,%8,%9,%10,%11,%12,%13,%14,%15,%16,%17,%18,%19,%20,%21,%22,%23,%24,%25,%26,%27,%28,%29,%30,%31}, {%32,%33,%34,%35}, %36, p, 1, 1, %38;\n}\n"
    : "+f"(d[OFF+0]), "+f"(d[OFF+1]), "+f"(d[OFF+2]), "+f"(d[OFF+3]), "+f"(d[OFF+4]), "+f"(d[OFF+5]), "+f"(d[OFF+6]), "+f"(d[OFF+7]),
      "+f"(d[OFF+8]), "+f"(d[OFF+9]), "+f"(d[OFF+10]), "+f"(d[OFF+11]), "+f"(d[OFF+12]), "+f"(d[OFF+13]), "+f"(d[OFF+14]), "+f"(d[OFF+15]),
      "+f"(d[OFF+16]), "+f"(d[OFF+17]), "+f"(d[OFF+18]), "+f"(d[OFF+19]), "+f"(d[OFF+20]), "+f"(d[OFF+21]), "+f"(d[OFF+22]), "+f"(d[OFF+23]),
      "+f"(d[OFF+24]), "+f"(d[OFF+25]), "+f"(d[OFF+26]), "+f"(d[OFF+27]), "+f"(d[OFF+28]), "+f"(d[OFF+29]), "+f"(d[OFF+30]), "+f"(d[OFF+31])
    : "r"(a0), "r"(a1), "r"(a2), "r"(a3), "l"(db), "r"(scale_d), "n"(TB));
}
template<int TB, int OFF, int SZ> __device__ __forceinline__ void wgmma_n40_rs(float (&d)[SZ], uint32_t a0, uint32_t a1, uint32_t a2, uint32_t a3, uint64_t db, int scale_d) {
  asm volatile("{\n.reg .pred p;\nsetp.ne.b32 p, %25, 0;\n"
    "wgmma.mma_async.sync.aligned.m64n40k16.f32.bf16.bf16 {%0,%1,%2,%3,%4,%5,%6,%7,%8,%9,%10,%11,%12,%13,%14,%15,%16,%17,%18,%19}, {%20,%21,%22,%23}, %24, p, 1, 1, %26;\n}\n"
    : "+f"(d[OFF+0]), "+f"(d[OFF+1]), "+f"(d[OFF+2]), "+f"(d[OFF+3]), "+f"(d[OFF+4]), "+f"(d[OFF+5]), "+f"(d[OFF+6]), "+f"(d[OFF+7]),
      "+f"(d[OFF+8]), "+f"(d[OFF+9]), "+f"(d[OFF+10]), "+f"(d[OFF+11]), "+f"(d[OFF+12]), "+f"(d[OFF+13]), "+f"(d[OFF+14]), "+f"(d[OFF+15]),
      "+f"(d[OFF+16]), "+f"(d[OFF+17]), "+f"(d[OFF+18]), "+f"(d[OFF+19])
    : "r"(a0), "r"(a1), "r"(a2), "r"(a3), "l"(db), "r"(scale_d), "n"(TB));
}
template<int TB, int OFF, int SZ> __device__ __forceinline__ void wgmma_n128_rs(float (&d)[SZ], uint32_t a0, uint32_t a1, uint32_t a2, uint32_t a3, uint64_t db, int scale_d) {
  asm volatile("{\n.reg .pred p;\nsetp.ne.b32 p, %69, 0;\n"
    "wgmma.mma_async.sync.aligned.m64n128k16.f32.bf16.bf16 {%0,%1,%2,%3,%4,%5,%6,%7,%8,%9,%10,%11,%12,%13,%14,%15,%16,%17,%18,%19,%20,%21,%22,%23,%24,%25,%26,%27,%28,%29,%30,%31,%32,%33,%34,%35,%36,%37,%38,%39,%40,%41,%42,%43,%44,%45,%46,%47,%48,%49,%50,%51,%52,%53,%54,%55,%56,%57,%58,%59,%60,%61,%62,%63}, {%64,%65,%66,%67}, %68, p, 1, 1, %70;\n}\n"
    : "+f"(d[OFF+0]), "+f"(d[OFF+1]), "+f"(d[OFF+2]), "+f"(d[OFF+3]), "+f"(d[OFF+4]), "+f"(d[OFF+5]), "+f"(d[OFF+6]), "+f"(d[OFF+7]),
      "+f"(d[OFF+8]), "+f"(d[OFF+9]), "+f"(d[OFF+10]), "+f"(d[OFF+11]), "+f"(d[OFF+12]), "+f"(d[OFF+13]), "+f"(d[OFF+14]), "+f"(d[OFF+15]),
      "+f"(d[OFF+16]), "+f"(d[OFF+17]), "+f"(d[OFF+18]), "+f"(d[OFF+19]), "+f"(d[OFF+20]), "+f"(d[OFF+21]), "+f"(d[OFF+22]), "+f"(d[OFF+23]),
      "+f"(d[OFF+24]), "+f"(d[OFF+25]), "+f"(d[OFF+26]), "+f"(d[OFF+27]), "+f"(d[OFF+28]), "+f"(d[OFF+29]), "+f"(d[OFF+30]), "+f"(d[OFF+31]),
      "+f"(d[OFF+32]), "+f"(d[OFF+33]), "+f"(d[OFF+34]), "+f"(d[OFF+35]), "+f"(d[OFF+36]), "+f"(d[OFF+37]), "+f"(d[OFF+38]), "+f"(d[OFF+39]),
      "+f"(d[OFF+40]), "+f"(d[OFF+41]), "+f"(d[OFF+42]), "+f"(d[OFF+43]), "+f"(d[OFF+44]), "+f"(d[OFF+45]), "+f"(d[OFF+46]), "+f"(d[OFF+47]),
      "+f"(d[OFF+48]), "+f"(d[OFF+49]), "+f"(d[OFF+50]), "+f"(d[OFF+51]), "+f"(d[OFF+52]), "+f"(d[OFF+53]), "+f"(d[OFF+54]), "+f"(d[OFF+55]),
      "+f"(d[OFF+56]), "+f"(d[OFF+57]), "+f"(d[OFF+58]), "+f"(d[OFF+59]), "+f"(d[OFF+60]), "+f"(d[OFF+61]), "+f"(d[OFF+62]), "+f"(d[OFF+63])
    : "r"(a0), "r"(a1), "r"(a2), "r"(a3), "l"(db), "r"(scale_d), "n"(TB));
}

struct Ptrs { const __nv_bfloat16 *x, *wqkv, *wo, *wr, *wg, *wu, *wd; __nv_bfloat16* out; Scratch* s; };

enum { M_X, M_W, M_Q, M_O, M_S, M_G, M_U, M_D, M_L, M_N };
struct Maps { CUtensorMap m[M_N]; };

__global__ void __cluster_dims__(2, 1, 1) __launch_bounds__(384, 1) fused_kernel(const Ptrs P, const __grid_constant__ Maps T) {
  extern __shared__ __align__(1024) uint8_t smem_raw[];
  TS_DECL; TS(0); TSG(30);
  if (threadIdx.x == 320) SPANS(0);
  if (MPF == 1 && threadIdx.x == 0) { tmap_prefetch(&T.m[M_W]); tmap_prefetch(&T.m[M_Q]); tmap_prefetch(&T.m[M_X]); }
  if (MPF == 2 && threadIdx.x < 3) l2_prefetch(&T.m[threadIdx.x]);
  if (MPF == 3 && (threadIdx.x & 31) == 0 && threadIdx.x < 96) tmap_prefetch(&T.m[threadIdx.x >> 5]);
  const int tid = threadIdx.x, wid = __shfl_sync(~0u, tid >> 5, 0), wg = wid >> 2, lane = lane_id();
  const uint32_t rank = blockIdx.x & 1, own = rank << 24;
  const uint32_t sm = own + sb, mb = own + bars;
  int b0;
  { const int j = blockIdx.x >> 1, u = j - 36, q = (u * 37) >> 8;
    b0 = j < 4 ? j * 16 + 64 : u < 0 ? j * 2 - 8 : q * 2 + u * 2 + 66;
    if (HALFMAP) b0 = (b0 & 15) | (b0 & 48) << 1 | (b0 & 64) >> 2;
    b0 += rank; }
#define IDS(B) \
  const int b = (B), rb = b >> 4, cg = b & 15, hf = cg >> 3, s3 = cg & 7, c3 = s3 ^ ((rb & 1) << 2), jp = cg >> 1, km = (~c3 & 6) << 1; \
  const int fidx = jp == rb ? -1 : b - 2 * rb - (jp > rb ? 2 : 0); \
  auto kcol = [&](int kb) { return (kb ^ (kb < 8 ? km & 8 : km)) * 64; }; \
  auto src_of = [&](int p) { return p == 0 ? s3 : p == 15 ? s3 ^ 1 : (((jp & 3) ^ ((p - 7) >> 1)) << 1) + ((p - 1) & 1); }; \
  auto frag_of = [&](int p) { return p < 9 ? (p - 1) * 512 : 4096 + src_of(p) * 512; }; \
  (void)hf; (void)fidx; (void)kcol; (void)frag_of
  auto get_b = [&]() { return __shfl_sync(~0u, (int)lds1(mb + B_ID), 0); };
  IDS(b0);
  auto load_w = [&](uint32_t st, int kc, uint32_t bar, bool last) { tma_3d(st + 32768, &T.m[M_W], cg * 64, kc, 1, bar, last); tma_2d(st + 49152, &T.m[M_Q], cg * 64, kc, bar, last); };
  const uint32_t tk = clock64();
  if (SPF && tid < 80) {
    const int i = tid - 32;
    l2_prefetch(tid < 32 ? P.x + (rb * 256 + (hf * 4 + (cg & 3)) * 32 + tid) * D_ + kcol(0) : P.wqkv + (kcol(0) + (rb >> 1) * 16 + (i & 15)) * 3072 + (i >> 4) * 1024 + cg * 64);
  }
  RTS_DECL;
  if (wid == 8) {
    if (elect_one()) {
      if (smem_u32(smem_raw) != sm) asm volatile("trap;");
#pragma unroll
      for (int s = 0; s < 4; s++) mbar_init(mb + B_FULL + 8 * s, 1);
      asm volatile("fence.mbarrier_init.release.cluster;" ::: "memory");
      fence_async_smem();
      mbar_expect_tx(mb + B_FULL, STAGE_B);
      load_w(sm, kcol(0), mb + B_FULL, EFW0);
      tma_2d(sm, &T.m[M_X], kcol(0), rb * 256, mb + B_FULL, EFX0);
      tma_2d(sm + 16384, &T.m[M_X], kcol(0), rb * 256 + 128, mb + B_FULL, EFX0);
      RTS(0);
    }
  } else if (wid == 9) {
    if (elect_one()) {
#pragma unroll
      for (int i = 4; i < 31; i++) if (8 * i != B_ID) mbar_init(mb + 8 * i, i < 8 ? 8 : i < 16 ? 16 : i == 16 ? 64 : i == 17 ? 8 : i == 18 ? 4 : 1);
      asm volatile("fence.mbarrier_init.release.cluster;" ::: "memory");
      fence_async_smem();
    }
  } else if (wid == 11) {
#pragma unroll
    for (int i = 0; i < 4; i++) sts4(sm + OFF_STATS + i * 512 + lane * 16, SENT, SENT, SENT, SENT);
    sts1(mb + B_ID, b);
    fence_async_smem();
  }
  __syncthreads();
  asm volatile("barrier.cluster.arrive.relaxed.aligned;\nbarrier.cluster.wait.aligned;" ::: "memory");

  if (wg == 2) {
    asm volatile("setmaxnreg.dec.sync.aligned.u32 56;");
    if (wid == 8) {
      if (elect_one()) {
#pragma unroll 1
        for (int kb = 1; kb < 15; kb++) {
          const uint32_t fb = mb + B_FULL + 8 * (kb & 3), st = sm + (kb & 3) * STAGE_B;
          const int kc = kcol(kb);
          if (kb < 4) while ((uint32_t)clock64() - tk < FD0 + kb * FD1) {}
          else mbar_wait(fb + B_EMPTY, ((kb >> 2) & 1) ^ 1);
          mbar_expect_tx(fb, STAGE_B);
          tma_2d_mc(st + rank * 16384, &T.m[M_X], kc, rb * 256 + rank * 128, fb, kb >= EFXK);
          load_w(st, kc, fb, EFW && kb >= EFWK);
          if (kb >= 8 && kb < 11) asm volatile("mbarrier.arrive.shared::cta.b64 _, [%0], %1;" :: "r"(fb + B_EMPTY), "r"(4) : "memory");
        }
        {
          const uint32_t st = sm + 3 * STAGE_B, fa = mb + B_FULL + 24, fb = mb + B_F15;
          const int kc = kcol(15);
          mbar_wait(fa, 0);
          mbar_expect_tx(fa, 32768); mbar_expect_tx(fb, 24576);
          if (rank) { mbar_wait(mb + B_EMPTY + 24, 0); tma_2d_mc(st + 16384, &T.m[M_X], kc, rb * 256 + 128, fa, EFXK < 16); }
          mbar_wait(mb + B_EMPTY, 1);
          tma_3d(st + 32768, &T.m[M_W], cg * 64, kc, 1, fa, EFW);
          if (!rank) { mbar_wait(mb + B_EMPTY + 24, 0); tma_2d_mc(st, &T.m[M_X], kc, rb * 256, fb, EFXK < 16); }
          tma_2d(st + 49152, &T.m[M_Q], cg * 64, kc, fb, EFW);
        }
        mbar_expect_tx(mb + B_KVP, 32768 + 2048);
      }
      __syncwarp();
      const uint4* kp = &P.s->kvp[cg * 8 * 256], *zq = &P.s->zp[cg * 8 * 16], *src = &P.s->obuf[(rb * 4 + rank * 2 + hf) * 64 * 128];
      asm volatile("" : "+l"(kp), "+l"(zq), "+l"(src));
      mbar_wait(mb + B_EVA, 0);
      meet(&P.s->when[cg * 32 + rb], (const uint4*)&P.s->when[cg * 32] + (lane & 1), MFIRST, MKV, mb + B_EVB);
      if (elect_one()) {
        bulk_load(sm + rank * (2 * STAGE_B) + STAGE_B, kp, 32768, mb + B_KVP);
        bulk_load(sm + rank * (2 * STAGE_B) + UNIT, zq, 2048, mb + B_KVP);
      }
      RTS(1);
      mbar_wait(mb + B_KVP, 0);
      RTS(2);
      meet(&P.s->when[(16 + rb * 2 + hf) * 32 + s3], (const uint4*)&P.s->when[(16 + (MWIDE == 2 ? lane >> 1 : (MWIDE ? (lane & 6) + (rb & 1) : rb) * 2 + (hf ^ 1))) * 32] + (lane & 1), MFIRST, MO, mb + B_E);
      RTS(3);
      if (elect_one()) {
        const uint32_t t0 = clock64();
        RTS(4);
#pragma unroll
        for (int p = 1; p < 5; p++) {
          if (p == 3) while ((uint32_t)clock64() - t0 < ADELAY2) {}
          bulk_load_mc(sm + ring_of(p, rank), src + (p - 1) * 512, UNIT, mb + B_BF + 8 * p);
        }
#pragma unroll 1
        for (int p = 5; p < 15; p++) {
          uint32_t dst = sm + ring_of(p, rank), bar = mb + B_BF + 8 * (p % 7);
          const uint4* q = src + frag_of(p);
          asm volatile("" : "+r"(dst), "+r"(bar), "+l"(q));
          mbar_wait(mb + B_E + 8 * ((p - 4) & 7), p >= 12);
          bulk_load_mc(dst, q, UNIT, bar);
        }
        asm volatile("mbarrier.arrive.shared::cta.b64 _, [%0], 8;" :: "r"(mb + B_GATE) : "memory");
        const uint4* s15 = &P.s->obuf[(rb * 4 + hf) * 64 * 128 + frag_of(15)];
        RTS_DUMP;
        mbar_wait(mb + B_E + 24, 1);
        bulk_load(sm + ring_of(15, 0), s15, UNIT, mb + B_BF + 8); bulk_load(sm + ring_of(15, 1), s15 + 2 * 64 * 128, UNIT, mb + B_BF + 8);
      }
    } else if (wid == 11) {
      IDS(get_b());
      if (fidx >= 0) {
        const uint32_t o = (rank * 32 + lane) * (F_ * 2) + (fidx >> 1) * 128;
        const char* q0 = (const char*)P.wg + o, *q1 = (const char*)P.wu + o;
        mbar_wait(mb + B_FULL + 24, 0);
        mbar_wait(mb + B_FULL + 8 * (PULL0 & 3), PULL0 >> 2);
#pragma unroll 1
        for (int r = 0; r < 16; r++, q0 += 64 * F_ * 2, q1 += 64 * F_ * 2) {
          if (mbar_test(mb + B_HOLD, 0)) { l2_prefetch(q0); l2_prefetch(q1); continue; }
          asm volatile("cp.async.ca.shared.global.L2::128B [%0], [%1], 4;\ncp.async.commit_group;\ncp.async.wait_group %3;\n"
                       "cp.async.ca.shared.global.L2::128B [%0], [%2], 4;\ncp.async.commit_group;\ncp.async.wait_group %3;" :: "r"(mb + B_DUMMY), "l"(q0), "l"(q1), "n"(PDEPTH) : "memory");
          if (lane == 0) g_dbgv(3, r + 1);
        }
        mbar_wait(mb + B_F15, 0);
        bar_sync(15, 288);
        if (lane == 0) PTS(1);
        q0 = (const char*)P.wd + fidx * 65536 + lane * 128;
        const uint32_t bar = mb + B_BF + 48;
        if (lane == 0) mbar_expect_tx(bar, 8192);
#pragma unroll 1
        for (int i = 0; i < 16 + PLAG; i++) {
          if (i < 16) l2_prefetch(q0 + i * 4096);
          if (i >= PLAG && elect_one()) tma_2d(sm + OFF_COLSUM, &T.m[M_L], 0, fidx * 512 + (i - PLAG) * 32, bar, false);
          const uint32_t t1 = clock64();
          while ((uint32_t)clock64() - t1 < PSTEP) {}
        }
        mbar_wait(bar, 0);
        __syncwarp();
        if (lane == 0) { mbar_arrive(bar); PTS(4); }
        asm volatile("cp.async.wait_all;" ::: "memory");
      } else bar_arrive(15, 288);
      bar_arrive(14, 64);
    } else {
      const uint32_t eb = (lane << 24) + bars + B_EMPTY;
      float c[6];
      if (wid == 10) {
        float sx[4] = {0.f, 0.f, 0.f, 0.f}, qx[4] = {0.f, 0.f, 0.f, 0.f};
        const uint32_t xa = sm + ((hf * 4 + (cg & 3)) * 32 + lane) * 128 + ((lane & 7) << 4);
#pragma unroll 1
        for (int kb = 0; kb < 8; kb++) {
          uint4 xv[8];
          const uint32_t so = xa + (kb & 3) * STAGE_B;
          mbar_wait(mb + B_FULL + 8 * (kb & 3), kb >> 2);
#pragma unroll
          for (int i = 0; i < 8; i++) xv[i] = lds4(so ^ (i << 4));
#pragma unroll
          for (int i = 0; i < 8; i++) {
            const uint32_t e[4] = {xv[i].x, xv[i].y, xv[i].z, xv[i].w};
#pragma unroll
            for (int j = 0; j < 4; j++) {
              const float d0 = bf_lo(e[j]), d1 = bf_hi(e[j]);
              sx[j] += d0 + d1; qx[j] = fmaf(d0, d0, fmaf(d1, d1, qx[j]));
            }
          }
          __syncwarp();
          if (lane < 2) mbar_arrive_rem(eb + 8 * (kb & 3));
          if (kb == RST2) {
        {
          const uint32_t ep = ld_rlx(&P.s->epoch);
          float s = 0.f;
#pragma unroll
          for (int i = 0; i < 4; i++) {
            const uint4 v = ld_cg4((const uint4*)P.wr + lane + i * 32);
            s += (bf_lo(v.x) + bf_hi(v.x)) + (bf_lo(v.y) + bf_hi(v.y)) + (bf_lo(v.z) + bf_hi(v.z)) + (bf_lo(v.w) + bf_hi(v.w));
          }
#pragma unroll
          for (int o = 16; o; o >>= 1) s += __shfl_xor_sync(~0u, s, o);
          if (lane == 0) sts1(mb + B_SW, (__float_as_uint(s) & ~255u) | ((ep + 1) & 255));
        }
        asm volatile("cp.async.bulk.wait_group 0;\nfence.proxy.async.global;" ::: "memory");
        fence_gpu();
        if (lane == 0) PTS(0);
          }
          if (kb == RST) {
        if (elect_one()) {
#pragma unroll 1
          for (int i = 0; i < 16; i++) bulk_store(&P.s->obuf[((rb * 4 + (i >> 2)) * 64 + (((i >> 2) & 1) == hf ? 32 + s3 * 4 + (i & 3) : (i & 3) * 8 + s3)) * 128], sm + OFF_STATS, 2048);
          bulk_store(&P.s->kvp[(cg * 8 + rb) * 256], sm + OFF_STATS, 2048); bulk_store(&P.s->kvp[(cg * 8 + rb) * 256 + 128], sm + OFF_STATS, 2048);
          bulk_store(&P.s->zp[(cg * 8 + rb) * 16], sm + OFF_STATS, 256);
          if (s3 == 0) bulk_store(&P.s->when[(16 + rb * 2 + hf) * 32], sm + OFF_STATS, 128);
          if (rb == 0) bulk_store(&P.s->when[cg * 32], sm + OFF_STATS, 128);
          asm volatile("cp.async.bulk.commit_group;" ::: "memory");
          #pragma unroll
          for (int i = M_O; i < M_N; i++) tmap_prefetch(&T.m[i]);
        }
        __syncwarp();
          }
        }
        c[0] = ((sx[0] + sx[1]) + (sx[2] + sx[3])) * (2.f / D_);
        c[1] = fmaxf(fmaf(-c[0], c[0], ((qx[0] + qx[1]) + (qx[2] + qx[3])) * (2.f / D_)), 0.f);
      } else {
        float a[12];
#pragma unroll
        for (int i = 0; i < 12; i++) a[i] = 0.f;
        const int r2 = lane >> 4, c16 = lane & 15;
        const uint32_t a0 = sm + 32768 + (rb >> 1) * 2048 + r2 * 128 + (((c16 >> 1) ^ r2) << 4) + (c16 & 1) * 8;
#pragma unroll 1
        for (int it = 0; it < 16; it++) {
          uint2 w[12];
          const int s = (it >> 1) & 3;
          const uint32_t so = a0 + s * STAGE_B + (it & 1) * 1024;
          if (!(it & 1)) { mbar_wait(mb + B_FULL + 8 * s, it >> 3); TSD(8 + (it >> 1)); }
          static_for<0, 12>([&](auto ic) { constexpr int i = decltype(ic)::value;
            const float2 v = lds2f_o<(i >> 2) * 8192 + (i & 3) * 256>(so ^ ((i & 3) << 5)); w[i] = make_uint2(__float_as_uint(v.x), __float_as_uint(v.y)); });
#pragma unroll
          for (int i = 0; i < 12; i++) { float* q = a + (i >> 2) * 4; q[0] += bf_lo(w[i].x); q[1] += bf_hi(w[i].x); q[2] += bf_lo(w[i].y); q[3] += bf_hi(w[i].y); }
          __syncwarp();
          if (lane < 2 && (it & 1)) mbar_arrive_rem(eb + 8 * s);
        }
#pragma unroll
        for (int i = 0; i < 6; i++) {
          const int o = (i >> 1) * 4 + (i & 1);
          c[i] = (r2 ? a[o + 2] : a[o]) + __shfl_xor_sync(~0u, r2 ? a[o] : a[o + 2], 16);
        }
      }
      TS(5);
      bar_sync(10, 64);
      TS(6);
      {
        const uint32_t tag = lds1(mb + B_SW) & 255;
        auto tagged = [&](float v) { return ((__float_as_uint(v) + 128) & ~255u) | tag; };
        if (wid == 9) {
#pragma unroll
          for (int sg = 0; sg < 3; sg++) {
            st_rlx2((uint2*)&P.s->csp[(cg * 8 + rb) * 48] + sg * 32 + (lane & 15) * 2 + (lane >> 4), tagged(c[sg * 2]), tagged(c[sg * 2 + 1]));
          }
        } else st_rlx2((uint2*)&P.s->st1[rb * 256 + (hf * 4 + (cg & 3)) * 32 + lane] + ((cg >> 2) & 1), tagged(c[0]), tagged(c[1]));
        { const uint32_t t0 = clock64(); while ((uint32_t)clock64() - t0 < GDELAY) {} }
#pragma unroll 1
        for (int h = wid - 9; h < 2; h++) {
          const int q = h * 24 + min(lane, 23), sd = wid == 10 ? 32 : 48;
          const uint4* gp = wid == 10 ? &P.s->st1[rb * 256 + lane] : &P.s->csp[cg * 8 * 48 + q];
          uint4 v[8];
#pragma unroll 1
          for (int it = 0;; it++) {
            uint32_t x = 0;
#pragma unroll
            for (int i = 0; i < 8; i++) v[i] = ld_rlx4(gp + i * sd);
#pragma unroll
            for (int i = 0; i < 8; i++) { v[i].x ^= tag; v[i].y ^= tag; v[i].z ^= tag; v[i].w ^= tag; x |= v[i].x | v[i].y | v[i].z | v[i].w; }
            if (!__any_sync(~0u, (x & 255) != 0)) break;
            SPINCHK(it, 3);
          }
          if (wid == 10) {
#pragma unroll
            for (int i = 0; i < 8; i++) {
              const float m0 = __uint_as_float(v[i].x), m1 = __uint_as_float(v[i].z), dm = 0.5f * (m0 - m1);
              sts2f(sm + OFF_STATS + (i * 32 + lane) * 8, -0.5f * (m0 + m1), rsq(fmaf(dm, dm, 0.5f * (__uint_as_float(v[i].y) + __uint_as_float(v[i].w))) + 1e-5f));
            }
          } else {
            float s4[4] = {0.f, 0.f, 0.f, 0.f};
#pragma unroll
            for (int i = 0; i < 8; i++) { s4[0] += __uint_as_float(v[i].x); s4[1] += __uint_as_float(v[i].y); s4[2] += __uint_as_float(v[i].z); s4[3] += __uint_as_float(v[i].w); }
            sts4(sm + OFF_COLSUM + q * 16, __float_as_uint(s4[0]), __float_as_uint(s4[1]), __float_as_uint(s4[2]), __float_as_uint(s4[3]));
          }
        }
        mbar_arrive(mb + B_AUX);
      }
      TS(2);
      IDS(get_b());
      const uint64_t btab = rank ? BT1 : BT0;
      if (wid == 9) {
        {
          const uint4 sv = make_uint4(SENT, SENT, SENT, SENT);
          uint4* y = &P.s->ybuf[b * NFFN * 2 + lane];
#pragma unroll
          for (int i = 0; i < 7; i++) y[i * 32] = sv;
          if (lane < 16) P.s->st2[b * 16 + lane] = make_uint4(0, 0, 0, 0); else P.s->hsel[b * 16 + lane - 16] = sv;
          if (b < 8) P.s->cand[b * 32 + lane] = SENT;
          fence_gpu();
          __syncwarp();
          if (lane == 0) mbar_arrive(mb + B_LATE);
        }
        TS(3);
        TS_DUMP(2);
        {
          const int p = lane & 15, sl = p % 7;
          const bool sliced = p > 0 && p < 9;
          const uint32_t c = sliced ? ((p - 1) >> 1) * 16 | ((hf ^ 1) * 8 + ((p - 1) & 1) * 4) << 8 | 128 << 16 : (hf * 8 + src_of(p)) << 8;
          const uint32_t ev = mb + (p < BHOLD ? B_EVA : p < 4 ? B_KVP : p < 6 ? B45 : B_E + 8 * ((p < 7 ? 1 : p - 4) & 7) + (p >= 12));
          mbar_wait(mb + B_EVA, 0);
          sts4(sm + OFF_COLSUM + 512 + p * 16, sm + unit_of(btab, sl), mb + B_BF + 8 * sl, c, ev);
          __syncwarp();
        }
        if (elect_one()) {
#pragma unroll 1
          for (int p = 0; p < 16; p++) {
            const uint4 e = lds4(sm + OFF_COLSUM + 512 + p * 16);
            if (p == 4) mbar_wait(mb + B_WR, 0);
            mbar_wait(e.w & ~1u, e.w & 1);
            mbar_expect_tx(e.y, p ? 4 * UNIT : 2 * UNIT);
            tma_4d(e.x, (const CUtensorMap*)((const char*)&T.m[M_O] + (e.z >> 16)), 0, e.z & 255, (e.z >> 8) & 255, c3 * 2, e.y, p >= EFB);
          }
          PTS(16);
        }
      } else {
        const uint2 w = ld_rlx2((const uint2*)(P.wr + c3 * 128) + lane);
#pragma unroll 1
        for (int i = 0; i < 4; i++) { l2_prefetch((const char*)P.wo + b * 16384 + i * 4096 + lane * 128); __nanosleep(300); }
        const int p = lane & 15, p2 = min(p + 2, 15);
        const uint32_t t0 = dlo(sb, 8192) + (unit_of(btab, p % 7) >> 4), t1 = ring_of(p + 1, lane >> 4), t2 = mb + B_BF + 8 * (p2 % 7);
        mbar_wait(mb + B_EVB, 0);
        bar_sync(14, 64);
        sts4(sm + OFF_COLSUM + lane * 16, w.x << 16, w.x & 0xFFFF0000u, w.y << 16, w.y & 0xFFFF0000u);
        sts4(sm + OFF_STATS + lane * 16, t0, t1, t2, (p2 / 7) & 1);
        __syncwarp();
        if (elect_one()) {
          mbar_arrive(mb + B_WR);
          if (fidx >= 0) {
            mbar_expect_tx(mb + B_FFN, 131072); mbar_expect_tx(mb + B_FFD, 32768);
            uint64_t gt = rank ? GT1 : GT0;
#pragma unroll 1
            for (int f = 0; f < 8; f++, gt >>= 5) {
              uint32_t d0 = sm + unit_of(gt, 0);
              asm volatile("" : "+r"(d0));
              if (f == 3) mbar_wait(mb + B_GATE, 1);
              mbar_wait(mb + (f < FEARLY ? B_KVB : B_E + (f < 3 ? 3 + 2 * f : (f + 5) >> 1) * 8), f < FEARLY || f >= 3);
              tma_3d(d0, &T.m[M_G], fidx * 32, f * 128, 0, mb + B_FFN, EFF);
              tma_3d(d0 + UNIT, &T.m[M_U], fidx * 32, f * 128, 0, mb + B_FFN, EFF);
            }
            PTS(17);
            mbar_expect_tx(mb + B_KVP, 32768);
#pragma unroll
            for (int w = 0; w < 8; w++) {
              if (w == 2) mbar_wait(mb + B_E + 56, 1);
              if (w == 6) mbar_wait(mb + B_E16, 1);
              if (w == DLATE) mbar_wait(mb + B_EVA, 1);
              tma_3d(sm + ((DT0 >> (5 * w)) & 31) * UNIT + (w < 4 ? 0 : w < 6 ? 14 * UNIT : -14 * UNIT) * rank, &T.m[M_D], 0, fidx * 32, 2 * w, mb + (w < 4 ? B_FFD : B_KVP), EFF);
            }
            PTS(18);
          }
        }
      }
    }
    __syncwarp();
    IDS(get_b());
    mbar_wait(mb + B_EVB, 0);
    mbar_wait(mb + B_OUT, 0);
    const float2 cf = lds2f(sm + OFF_STATS + 64);
    const int cand0 = 2047 - (__float_as_int(cf.x) & 2047), cand1 = 2047 - (__float_as_int(cf.y) & 2047), rr = lane >> 4;
    auto store_rows = [&](int tr, bool on) {
      const uint4 v = lds4(sm + 4 * UNIT + (tr >> 6) * STAGE_B + (tr & 63) * 256 + (((lane & 15) ^ (tr & 7)) << 4));
      const float2 pr = lds2f(sm + OFF_LNP + tr * 8);
      const float f = 1.f + pr.x, n = pr.y;
      if (on) st_out(P.out + (size_t)(rb * 256 + hf * 64 + tr + (tr & 64)) * D_ + c3 * 128 + (lane & 15) * 8,
          make_uint4(pack2(fmaf(bf_lo(v.x), f, n), fmaf(bf_hi(v.x), f, n)), pack2(fmaf(bf_lo(v.y), f, n), fmaf(bf_hi(v.y), f, n)),
                     pack2(fmaf(bf_lo(v.z), f, n), fmaf(bf_hi(v.z), f, n)), pack2(fmaf(bf_lo(v.w), f, n), fmaf(bf_hi(v.w), f, n))));
    };
    if (wid == 8) {
      mbar_wait(mb + B_SEL, 0);
      const float2 sel = lds2f(sm + OFF_STATS + 80);
      const uint32_t kc = __float_as_uint(rr ? cf.y : cf.x);
      const int c = rr ? cand1 : cand0;
      store_rows(((c >> 1) & 64) + (c & 63), kc != __float_as_uint(sel.x) && kc != __float_as_uint(sel.y) && (c >> 8) == rb && ((c >> 6) & 1) == hf);
    } else if (wid < 9 + NOUTW) {
      if (ODELAY) { const uint32_t t0 = clock64(); while ((uint32_t)clock64() - t0 < ODELAY) {} }
#pragma unroll OUNR
      for (int tr = (wid - 9) * 2 + rr; tr < 128; tr += 2 * NOUTW) {
        const int row = rb * 256 + hf * 64 + tr + (tr & 64);
        store_rows(tr, row != cand0 && row != cand1 && !NOOUT);
      }
      if (wid == 9 && lane == 0) { PTS(14); SPANS(2); }
    }
  } else {
    asm volatile("setmaxnreg.inc.sync.aligned.u32 224;");
    const int t128 = tid & 127, warp = wid & 3, g = lane >> 2, t = lane & 3;
    const uint32_t sk = rank * (2 * STAGE_B);
    uint4 ost[2][4];
    uint4* od1;
    int b1;
    const uint32_t eb = (lane << 24) + bars + B_E;
    float acc[64], wf[32];
    {
      float acc0[96], acc1[96];
#pragma unroll
      for (int i = 0; i < 96; i++) { acc0[i] = 0.f; acc1[i] = 0.f; }
      const uint32_t xo0 = dlo(sb, 16) + (wg * 2 + hf) * 512, xo1 = dlo(sb, 16) + (wg * 2 + (hf ^ 1)) * 512;
      constexpr uint32_t ST = STAGE_B >> 4, WD = dlo(sb + 49152, 8192), WV = dlo(sb + 32768, 8192);
      const uint32_t eb0 = (t128 << 24) + bars + B_EMPTY;
#pragma unroll 1
      for (int kb = 0; kb < 12; kb++) {
        const int s = kb & 3;
        mbar_wait(mb + B_FULL + 8 * s, (kb >> 2) & 1);
        if (kb == 0) TS(1);
        if (kb == 0 && !wg) bar_sync(2, 256);
        pin(acc0); pin(acc1);
        wg_fence();
#pragma unroll
        for (int k = 0; k < 4; k++) {
          const uint64_t db = dsc<1024, 1>(WV + s * ST + k * 128);
          wgmma_n192_ss<0, 1, 0>(acc0, dsc<1024, 1>(s * ST + xo0 + k * 2), db, 1);
          wgmma_n192_ss<0, 1, 0>(acc1, dsc<1024, 1>(s * ST + xo1 + k * 2), db, 1);
        }
        wg_commit();
        if (kb == 0 && wg) bar_arrive(2, 256);
        wg_wait<0>();
        pin(acc0); pin(acc1);
        if (t128 < 2 && kb < 11) mbar_arrive_rem(eb0 + 8 * s);
      }
      mbar_wait(mb + B_FULL, 1);
      if (t128 < 8) mbar_arrive_rem(t128 < 4 ? (wg << 24) + bars + B_EMPTY + 24 : mb + B_EMPTY);
      TS(2);
      mbar_wait(mb + B_AUX, 0);
      float rs[2][2], nm[2][2];
#pragma unroll
      for (int m = 0; m < 2; m++)
#pragma unroll
        for (int h = 0; h < 2; h++) { const float2 v = lds2f(sm + OFF_STATS + ((wg * 2 + (m ^ hf)) * 64 + warp * 16 + h * 8 + g) * 8); nm[m][h] = v.x; rs[m][h] = v.y; }
      auto center = [&](auto jc) {
        constexpr int j = decltype(jc)::value;
        const float2 cs = lds2f_o<sb + OFF_COLSUM + j * 32>(own + t * 8);
        acc1[j * 4] = fmaf(nm[1][0], cs.x, acc1[j * 4]); acc1[j * 4 + 1] = fmaf(nm[1][0], cs.y, acc1[j * 4 + 1]);
        acc1[j * 4 + 2] = fmaf(nm[1][1], cs.x, acc1[j * 4 + 2]); acc1[j * 4 + 3] = fmaf(nm[1][1], cs.y, acc1[j * 4 + 3]);
        acc0[j * 4] = fmaf(nm[0][0], cs.x, acc0[j * 4]); acc0[j * 4 + 1] = fmaf(nm[0][0], cs.y, acc0[j * 4 + 1]);
        acc0[j * 4 + 2] = fmaf(nm[0][1], cs.x, acc0[j * 4 + 2]); acc0[j * 4 + 3] = fmaf(nm[0][1], cs.y, acc0[j * 4 + 3]);
      };
      static_for<0, 16>(center);
      const float L2E = 1.4426950408889634f;
      uint32_t fa = sm + sk + (warp * 16 + (lane & 15)) * 128 + (((lane >> 4) ^ (lane & 7)) << 4);
      asm volatile("" : "+r"(fa));
      uint32_t xf0[32], xf1[32];
      auto pack_kv = [&](float (&a)[96], int i, float r0, float r1, uint32_t* o, uint32_t z = 0) {
        const float* p = a + i * 8;
        if (i < 4) {
          const float rl0 = __uint_as_float(__float_as_uint(r0 * L2E) | z), rl1 = __uint_as_float(__float_as_uint(r1 * L2E) | z);
          const uint32_t q0 = pack2(r0, r0), q1 = pack2(r1, r1);
          o[0] = phi2(p[0], p[1], rl0, q0); o[1] = phi2(p[2], p[3], rl1, q1); o[2] = phi2(p[4], p[5], rl0, q0); o[3] = phi2(p[6], p[7], rl1, q1);
        } else {
          r0 = __uint_as_float(__float_as_uint(r0) | z); r1 = __uint_as_float(__float_as_uint(r1) | z);
          o[0] = pack2(p[0] * r0, p[1] * r0); o[1] = pack2(p[2] * r1, p[3] * r1); o[2] = pack2(p[4] * r0, p[5] * r0); o[3] = pack2(p[6] * r1, p[7] * r1); }
      };
      auto swap_kv = [&](uint32_t (&xf)[32], uint32_t tile, int i, const uint32_t* o, uint32_t z = 0) {
        const uint32_t ad = (fa + tile * UNIT) ^ ((i & 3) << 5);
        if (i < 4) { ldsm4_o<0>(ad, xf[i * 4], xf[i * 4 + 1], xf[i * 4 + 2], xf[i * 4 + 3]); stsm4_o<0>(ad, o[0], o[1], o[2], o[3]); }
        else { ldsm4_o<STAGE_B>(ad | z, xf[i * 4], xf[i * 4 + 1], xf[i * 4 + 2], xf[i * 4 + 3]); stsm4_o<STAGE_B>(ad, o[0], o[1], o[2], o[3]); }
      };
      auto mma_q = [&](float (&a)[96], uint32_t (&xf)[32], uint32_t xo, bool ss) {
        const uint32_t r = __shfl_sync(~0u, sk >> 4, 0), o = 2 * ST - r;
#pragma unroll
        for (int j = 0; j < 8; j++) {
          if (ss) wgmma_n64_ss<0, 1, 64>(a, dsc<1024, 1>(o + (j >> 2) * ST + xo + (j & 3) * 2), dsc<1024, 1>(WD + o + (j >> 2) * ST + (j & 3) * 128), 1);
          else wgmma_n64_rs<1, 64>(a, xf[j * 4], xf[j * 4 + 1], xf[j * 4 + 2], xf[j * 4 + 3], dsc<1024, 1>(WD + r + (j >> 2) * ST + (j & 3) * 128), 1);
        }
      };
      auto epi_q = [&](float (&a)[96], float r0, float r1, uint32_t (&o)[16]) {
        const float rl0 = r0 * 1.44269511f, rl1 = r1 * 1.44269511f;
        const uint32_t q0 = dup2(r0), q1 = dup2(r1);
#pragma unroll
        for (int j = 0; j < 8; j++) { o[j * 2] = phi2(a[64 + j * 4], a[65 + j * 4], rl0, q0); o[j * 2 + 1] = phi2(a[66 + j * 4], a[67 + j * 4], rl1, q1); }
        pinu(o);
      };
      auto mma_kv1 = [&](float (&a)[96], uint32_t xo, int s) {
#pragma unroll
        for (int k = 0; k < 4; k++) wgmma_n128_ss<0, 1, 0>(a, dsc<1024, 1>(s * ST + xo + k * 2), dsc<1024, 1>(WV + s * ST + k * 128), 1);
      };
      auto epi_kv = [&](float (&a)[96], uint32_t (&xf)[32], uint32_t tile, float r0, float r1) {
        uint32_t o[8][4];
#pragma unroll
        for (int j = 3; j >= 0; j--) {
          const uint32_t z = j < 3 ? (xf[(j + 5) * 4] | (j < 2 ? o[j + 2][0] | o[j + 6][0] : 0)) & blockIdx.y : 0;
          pack_kv(a, j + 4, r0, r1, o[j + 4], z);
          swap_kv(xf, tile, j + 4, o[j + 4], (o[j + 4][2] | o[j + 4][3]) & blockIdx.y);
          pack_kv(a, j, r0, r1, o[j], z);
          swap_kv(xf, tile, j, o[j]);
        }
      };
      bar_arrive(15, 288);
      mbar_wait(mb + B_FULL + 8, 1);
      if (!wg) bar_sync(3, 256);
      pinr<0, 64>(acc0); pinr<0, 64>(acc1);
      wg_fence();
      mma_kv1(acc1, xo1, 0); mma_kv1(acc0, xo0, 0); mma_kv1(acc1, xo1, 1);
      if (GSPLIT == 2) mma_kv1(acc0, xo0, 1);
      mbar_wait(mb + B_FULL + 16, 1);
      wg_fence();
      mma_kv1(acc1, xo1, 2);
      mbar_wait(mb + (wg ? B_FULL + 24 : B_F15), wg);
      wg_fence();
      mma_kv1(acc1, xo1, 3);
      wg_commit();
      bar_arrive(4 - wg, 256);
      static_for<16, 24>(center);
      pinr<64, 96>(acc0); pinr<64, 96>(acc1);
      mbar_wait(mb + B_FULL + 8, 1);
      wg_wait<0>();
      pinr<0, 64>(acc0); pinr<0, 64>(acc1);
      epi_kv(acc1, xf1, wg * 2 + (hf ^ 1), rs[1][0], rs[1][1]);
      pinu(xf1);
      bar_sync(5 - wg, 256);
      wg_fence();
      if (GSPLIT == 1) mma_kv1(acc0, xo0, 1);
      mma_kv1(acc0, xo0, 2); mma_kv1(acc0, xo0, 3);
      wg_commit();
      mma_q(acc1, xf1, xo1, false);
      wg_commit();
      if (wg) bar_arrive(5, 256);
      else { fence_async_smem(); bar_arrive(6, 256); }
      if (tid >= 240) sts4(sm + OFF_STATS + (tid & 15) * 128 + ((tid & 7) << 4), 0x3F803F80u, 0x3F803F80u, 0x3F803F80u, 0x3F803F80u);
      wg_wait<1>();
      pinr<0, 64>(acc0);
      if (lane == 0) mbar_arrive(mb + B_EVA);
      TS(6);
      epi_kv(acc0, xf0, wg * 2 + hf, rs[0][0], rs[0][1]);
      fence_async_smem();
      pinu(xf0);
      if (!wg) bar_arrive(7, 256);
      const uint32_t kvb = 2 * STAGE_B + (2 + (hf ^ 1)) * UNIT - sk;
      b1 = get_b();
      od1 = &P.s->obuf[(((b1 >> 4) * 4 + wg * 2 + (hf ^ 1)) * 64 + (b1 & 7)) * 128 + t128];
      uint32_t ka0 = sm + kvb + wid * 1024 + (lane & 7) * 128 + (((lane >> 3) ^ (lane & 7)) << 4), ka1 = sm + kvb + wid * 1024 + (t * 2 + g) * 128 + ((4 ^ (t * 2 + g)) << 4);
      const uint8_t* g0 = smem_raw + sk + STAGE_B + tid * 16, *g1 = smem_raw + sk + UNIT + g * 256 + wid * 32 + t * 8;
      const uint8_t* h0 = (const uint8_t*)&P.s->kvp[(b1 & 15) * 8 * 256 + tid], *h1 = (const uint8_t*)&P.s->zp[((b1 & 15) * 8 + g) * 16] + wid * 32 + t * 8;
      asm volatile("" : "+r"(ka0), "+r"(ka1), "+l"(g0), "+l"(g1), "+l"(h0), "+l"(h1), "+l"(od1));
      if (wg) {
        float ka[36];
        auto mma_kv = [&](uint32_t tile, int i, int acc) {
          const uint32_t o = (sk >> 4) + tile * 512 + i * 128;
          wgmma_n72_ss<1, 1, 0>(ka, dsc<1024, 1>(dlo(sb, 8192) + o), dsc<1024, 1>(dlo(sb + STAGE_B, OFF_STATS - STAGE_B) + o * (1u - (1u << 16))), acc);
        };
#pragma unroll
        for (int i = 0; i < 36; i++) ka[i] = 0.f;
        bar_sync(6, 256);
        wg_fence();
#pragma unroll
        for (int i = 0; i < 4; i++) {
          mma_kv(2, i, i); mma_kv(3, i, 1); mma_kv(hf ^ 1, i, 1);
#pragma unroll
          for (int j = 2 * i; j < 2 * i + 2; j++)
            wgmma_n64_rs<1, 64>(acc0, xf0[j * 4], xf0[j * 4 + 1], xf0[j * 4 + 2], xf0[j * 4 + 3], dsc<1024, 1>(WD + (sk >> 4) + (j >> 2) * ST + (j & 3) * 128), 1);
        }
        const int kq = (b1 & 15) * 8 + (b1 >> 4);
        uint4* dst = &P.s->kvp[kq * 256 + warp * 64 + lane];
        uint32_t* dz = (uint32_t*)&P.s->zp[kq * 16] + warp * 16 + g + t * 8;
        asm volatile("" : "+l"(dst), "+l"(dz));
        mbar_wait(mb + B_LATE, 0);
        bar_sync(7, 256);
        wg_fence();
#pragma unroll
        for (int i = 0; i < 4; i++) mma_kv(hf, i, 1);
        wg_commit();
        bar_arrive(8, 256);
        wg_wait<0>();
        pin(ka); pinr<64, 96>(acc0);
        uint32_t kw[8];
#pragma unroll
        for (int i = 0; i < 8; i++) {
          const int j = (i & 3) * 4 + (i >> 2) * 2;
          asm("{\n.reg .pred p;\nsetp.ne.u32 p, %5, 0;\n@p cvt.rn.bf16x2.f32 %0, %4, %3;\n@!p cvt.rn.bf16x2.f32 %0, %2, %1;\n}"
              : "=r"(kw[i]) : "f"(ka[j]), "f"(ka[j + 1]), "f"(ka[16 + j]), "f"(ka[17 + j]), "r"(warp & 2));
        }
        st_rlx4(dst, make_uint4(kw[0], kw[1], kw[2], kw[3]));
        st_rlx4(dst + 32, make_uint4(kw[4], kw[5], kw[6], kw[7]));
        if (t < 2) st_rlx(dz, __float_as_uint(t ? ka[34] : ka[32]));
        if (lane == 0) mbar_arrive(mb + B_EVB);
        TS(8);
        const uint32_t t1 = clock64();
        while ((uint32_t)clock64() - t1 < SDELAY) {}
      } else {
        bar_sync(8, 256);
        wg_fence();
        mma_q(acc0, xf0, xo0, false);
      }
      if (!wg) bar_sync(9, 256);
      wg_fence();
      mma_q(acc1, xf1, xo1, true);
      wg_commit();
      if (wg) bar_arrive(9, 256);
      wg_wait<0>();
      pinr<64, 96>(acc1); pinr<64, 96>(acc0);
      TS(7);
      uint32_t pq[16];
      epi_q(acc1, rs[1][0], rs[1][1], pq);
      bar_sync(11 + wg + zero_after(pq), 128);
      wg_fence();
      mma_q(acc0, xf0, xo0, true);
      wg_commit();
      TS(5);
      {
        uint4 gv[8]; uint2 gz;
        uint32_t m[8], a[4];
        float z0, z1;
#pragma unroll
        for (int s = 0; s < 8; s++) { m[s] = ~blockIdx.y; asm volatile("" : "=r"(gv[s].x), "=r"(gv[s].y), "=r"(gv[s].z), "=r"(gv[s].w), "+r"(m[s])); }
        mbar_wait(mb + B_KVP, 0);
        TS(28);
#pragma unroll 1
        for (int it = 0; it < SPIN_LIMIT; it++) {
          gz = ld_gen2(g1);
#pragma unroll
          for (int s = 0; s < 8; s++) if (m[s] == SENT) gv[s] = ld_gen4(g0 + s * 4096);
          g0 = h0; g1 = h1;
          uint32_t mm = max(gz.x, gz.y);
          z0 = __uint_as_float(gz.x); z1 = __uint_as_float(gz.y);
#pragma unroll
          for (int o = 4; o < 32; o <<= 1) { z0 += __shfl_xor_sync(~0u, z0, o); z1 += __shfl_xor_sync(~0u, z1, o); }
#pragma unroll
          for (int s = 0; s < 8; s++) m[s] = max4(0, gv[s]);
#pragma unroll
          for (int s = 0; s < 8; s += 2) mm = __vimax3_u32(mm, m[s], m[s + 1]);
          a[0] = hadd2(hadd2(hadd2(gv[0].x, gv[1].x), hadd2(gv[2].x, gv[3].x)), hadd2(hadd2(gv[4].x, gv[5].x), hadd2(gv[6].x, gv[7].x)));
          a[1] = hadd2(hadd2(hadd2(gv[0].y, gv[1].y), hadd2(gv[2].y, gv[3].y)), hadd2(hadd2(gv[4].y, gv[5].y), hadd2(gv[6].y, gv[7].y)));
          a[2] = hadd2(hadd2(hadd2(gv[0].z, gv[1].z), hadd2(gv[2].z, gv[3].z)), hadd2(hadd2(gv[4].z, gv[5].z), hadd2(gv[6].z, gv[7].z)));
          a[3] = hadd2(hadd2(hadd2(gv[0].w, gv[1].w), hadd2(gv[2].w, gv[3].w)), hadd2(hadd2(gv[4].w, gv[5].w), hadd2(gv[6].w, gv[7].w)));
          pinu(a);
          if (!__any_sync(~0u, mm == SENT)) break;
          TSV(20, 1);
        }
        TS(23);
        wg_wait<0>();
        pinr<64, 96>(acc0);
        if (lane == 0) mbar_arrive(mb + B_KVB);
        stsm4(ka0, a[0], a[1], a[2], a[3]);
        const uint32_t zz = pack2(g ? z1 : z0, g ? z1 : z0);
        if (lane < 8) sts4(ka1, zz, zz, zz, zz);
        fence_async_smem();
        bar_sync(1, 256);
      }
      TS(21);
      auto make_o = [&](uint4 (&o)[4], auto first) {
        float oa[2][20];
        wg_fence();
#pragma unroll
        for (int ks = 0; ks < 4; ks++)
          wgmma_n40_rs<1, 0>(oa[ks >> 1], pq[ks * 4], pq[ks * 4 + 1], pq[ks * 4 + 2], pq[ks * 4 + 3], dsc<1024, 1>(dlo(sb, 8192) + (kvb >> 4) + ks * 128), ks & 1);
        wg_commit();
        if constexpr (!decltype(first)::value) {
          pinu(xf0);
#pragma unroll
          for (int q = 0; q < 32; q++) { acc[q * 2] = bf_lo(xf0[q]); acc[q * 2 + 1] = bf_hi(xf0[q]); }
          pin(acc);
          mbar_wait(mb + B_BF, 0);
        }
        wg_wait<0>();
        pin(oa[0]); pin(oa[1]);
        if (decltype(first)::value && lane < 2) mbar_arrive_rem(eb);
#pragma unroll
        for (int h = 0; h < 2; h++) {
          const float (&d)[20] = oa[h];
          const float i0 = rcp(d[16] + 1e-6f), i1 = rcp(d[18] + 1e-6f);
#pragma unroll
          for (int k2 = 0; k2 < 2; k2++) {
            o[h * 2 + k2] = make_uint4(pack2(d[k2 * 8] * i0, d[k2 * 8 + 1] * i0), pack2(d[k2 * 8 + 2] * i1, d[k2 * 8 + 3] * i1),
                                       pack2(d[k2 * 8 + 4] * i0, d[k2 * 8 + 5] * i0), pack2(d[k2 * 8 + 6] * i1, d[k2 * 8 + 7] * i1));
            if (decltype(first)::value && !h && k2 <= AFIRST) st_rlx4(od1 + k2 * 1024, o[k2]);
            if (decltype(first)::value && !h && k2 == AFIRST) { sched_fence(); TS(24); }
          }
        }
      };
      make_o(ost[1], std::true_type{});
      if (!AFIRST) { st_rlx4(od1 + 1024 + ((ost[1][2].x | ost[1][3].w) & blockIdx.y), ost[1][1]); sched_fence(); }
      epi_q(acc0, rs[0][0], rs[0][1], pq);
      if (AEARLY) { st_rlx4(od1 + 2048, ost[1][2]); st_rlx4(od1 + 3072, ost[1][3]); }
      make_o(ost[0], std::false_type{});
    }
   {
    IDS(b1);
    const int mb3 = rb * 4 + wg * 2 + hf;
    const int row0 = mb3 * 64 + warp * 16 + g;
    {
      uint4 abuf[3][4];
      const uint4* const ain = &P.s->obuf[mb3 * 64 * 128 + t128];
      uint4* const od0 = &P.s->obuf[(mb3 * 64 + 32 + s3 * 4) * 128 + t128];
#pragma unroll
      for (int i = 0; i < 4; i++) pin4(ost[0][i]);
      wg_fence();
#pragma unroll
      for (int k = 0; k < 4; k++) wgmma_n128_rs<1, 0>(acc, ost[0][k].x, ost[0][k].y, ost[0][k].z, ost[0][k].w, dsc<1024, 1>(dlo(sb + 4 * UNIT, 8192) + k * 128), 1);
      wg_commit();
      TS(29);
      if (!AEARLY) { st_rlx4(od1 + 2048, ost[1][2]); st_rlx4(od1 + 3072, ost[1][3]); }
      uint32_t la = sm + t128 * 16, ev = eb + 8;
      asm volatile("" : "+r"(la), "+r"(ev));
      auto fetch = [&](uint32_t off, uint4 (&a)[4]) { const uint32_t ra = la + off; a[0] = lds4_o<0>(ra); a[1] = lds4_o<2048>(ra); a[2] = lds4_o<4096>(ra); a[3] = lds4_o<6144>(ra); };
      auto check = [&](int p, uint4 (&a)[4]) {
        if (__any_sync(~0u, max(max4(max4(0, a[0]), a[1]), max4(max4(0, a[2]), a[3])) == SENT)) {
          int pl = p; asm volatile("" : "+r"(pl));
          const uint4* q = ain + frag_of(pl);
#pragma unroll 1
          for (int it = 0;; it++) {
            uint32_t mm = 0;
#pragma unroll
            for (int i = 0; i < 4; i++) { const uint32_t m = max4(0, a[i]); mm = max(mm, m); if (m == SENT) a[i] = ld_rlx4(q + i * 128); }
            if (!__any_sync(~0u, mm == SENT)) break;
            TSV(27, p < 3 ? 1 : p < 5 ? 100 : 10000);
            SPINCHK(it, 5);
          }
        }
        if (lane < 2) mbar_arrive_rem(ev);
        ev = (ev & ~0x38u) | ((ev + 8) & 0x38u);
      };
      auto mma = [&](int p, uint32_t bs, uint4 (&a)[4]) {
#pragma unroll
        for (int i = 0; i < 4; i++) pin4(a[i]);
        wg_fence();
#pragma unroll
        for (int k = 0; k < 4; k++) wgmma_n128_rs<1, 0>(acc, a[k].x, a[k].y, a[k].z, a[k].w, dsc<1024, 1>(bs + k * 128), 1);
        wg_commit();
      };
      uint32_t ta = sm + OFF_STATS + wg * 256 + 48;
      mbar_wait(mb + B_WR, 0);
      uint4 tp = lds4(ta);
      mbar_wait(mb + B_BF + 8, 0);
      TS(3);
      fetch(ring_of(1, wg), abuf[1]);
      check(1, abuf[1]);
      mbar_wait(mb + B_BF + 16, 0);
      fetch(ring_of(2, wg), abuf[2]);
      mma(1, dlo(sb + 11 * UNIT, 8192), abuf[1]);
      TS(25);
      st_rlx4(od0, ost[0][0]); st_rlx4(od0 + 128, ost[0][1]);
      check(2, abuf[2]);
      mbar_wait(mb + B_BF + 24, 0);
      fetch(ring_of(3, wg), abuf[0]);
      mma(2, dlo(sb + 18 * UNIT, 8192), abuf[2]);
      st_rlx4(od0 + 256, ost[0][2]); st_rlx4(od0 + 384, ost[0][3]);
      wg_wait<2>();
      check(3, abuf[0]);
      mbar_wait(mb + B_BF + 32, 0);
      TS(26);
#pragma unroll 1
      for (int p = 3; p < 15; p += 3) {
        static_for<0, 3>([&](auto jc) {
          constexpr int j = decltype(jc)::value;
          const uint4 tc = tp;
          const uint32_t bs = __shfl_sync(~0u, tc.x, 0);
          wg_wait<1>();
#pragma unroll
          for (int i = 0; i < 4; i++) pin4(abuf[(j + 1) % 3][i]);
          tp = lds4_o<16 * j + 16>(ta);
          fetch(tc.y, abuf[(j + 1) % 3]);
          mma(p + j, bs, abuf[j]);
          if (!CHKF) mbar_wait(tc.z, tc.w);
          check(p + j + 1, abuf[(j + 1) % 3]);
          if (CHKF) mbar_wait(tc.z, tc.w);
        });
        ta += 48;
      }
      mma(15, __shfl_sync(~0u, tp.x, 0), abuf[0]);
      wg_wait<2>();
      if (lane == 0) mbar_arrive(mb + B_E16);
      static_for<0, 16>([&](auto jc) { constexpr int j = decltype(jc)::value; const float2 v = lds2f_o<sb + OFF_COLSUM + j * 32>(own + t * 8); wf[j * 2] = v.x; wf[j * 2 + 1] = v.y; });
      pin(wf);
      wg_wait<0>();
      pin(acc);
#pragma unroll
      for (int i = 0; i < 4; i++) { pin4(abuf[0][i]); pin4(abuf[1][i]); pin4(abuf[2][i]); }
    }
    TS(10);
    {
      float s0 = 0.f, q0 = 0.f, e0 = 0.f, s1 = 0.f, q1 = 0.f, e1 = 0.f;
#pragma unroll
      for (int j = 0; j < 16; j++) {
        const float a = acc[j * 4], c = acc[j * 4 + 1], d = acc[j * 4 + 2], e = acc[j * 4 + 3];
        s0 += a + c; q0 = fmaf(a, a, fmaf(c, c, q0)); e0 = fmaf(a, wf[j * 2], fmaf(c, wf[j * 2 + 1], e0));
        s1 += d + e; q1 = fmaf(d, d, fmaf(e, e, q1)); e1 = fmaf(d, wf[j * 2], fmaf(e, wf[j * 2 + 1], e1));
      }
      const bool od = t & 1;
      float s = (od ? s1 : s0) + __shfl_xor_sync(~0u, od ? s0 : s1, 1);
      float q = (od ? q1 : q0) + __shfl_xor_sync(~0u, od ? q0 : q1, 1);
      float e = (od ? e1 : e0) + __shfl_xor_sync(~0u, od ? e0 : e1, 1);
      s += __shfl_xor_sync(~0u, s, 2); q += __shfl_xor_sync(~0u, q, 2); e += __shfl_xor_sync(~0u, e, 2);
      if (t < 2) red4(&P.s->st2[row0 + t * 8], s, q, e, 1.f);
    }
    TS(11);
    const uint32_t ts = clock64();
    const uint32_t msc = sm + OFF_STATS;
    const uint32_t hst = sm + 4 * UNIT + wg * STAGE_B + warp * 4096, gslot = sm + unit_of(rank ? GT1 : GT0, wid);
    bar_sync(1, 256);
#pragma unroll
    for (int j = 0; j < 8; j++)
      stsm4(hst + (lane & 15) * 256 + (((2 * j + (lane >> 4)) ^ (lane & 7)) << 4), pack2(acc[j * 8], acc[j * 8 + 1]), pack2(acc[j * 8 + 2], acc[j * 8 + 3]),
            pack2(acc[j * 8 + 4], acc[j * 8 + 5]), pack2(acc[j * 8 + 6], acc[j * 8 + 7]));
    uint32_t wa[8][4][4], wd[8][2][4];
    const uint32_t a0 = gslot + ((lane >> 4) * 8 + (lane & 7)) * 64 + ((((lane >> 3) & 1) ^ ((lane >> 1) & 3)) << 4);
    auto load_gu = [&](auto ic) { constexpr int i = decltype(ic)::value; ldsm4t_o<(i >> 2) * 1024 + ((i >> 1) & 1) * 8192>(a0 ^ ((i & 1) << 5), wa[i >> 2][i & 3]); };
    uint32_t tx;
    {
      const int row = rb * 256 + tid;
      const uint4* sp = &P.s->st2[row], *sq = &P.s->st2[row ^ 256];
      const float sw = __uint_as_float((lds1(mb + B_SW) & ~255u) | 128);
      uint4 v[2];
      if (fidx >= 0) mbar_wait(mb + B_FFN, 0);
      static_for<0, GU1>(load_gu);
      while ((uint32_t)clock64() - ts < SDEL2) {}
      v[0] = ld_rlx4(sp); v[1] = ld_rlx4(sq);
      TS(15);
      static_for<GU1, GU2>(load_gu);
#pragma unroll 1
      for (int it = 0; __any_sync(~0u, min(v[0].w, v[1].w) != 0x41000000u) && it < SPIN_LIMIT; it++) {
        if (v[0].w != 0x41000000u) v[0] = ld_rlx4(sp);
        if (v[1].w != 0x41000000u) v[1] = ld_rlx4(sq);
        TSV(22, 1);
      }
      if (lane == 0) mbar_arrive(mb + B_EVA);
      TS(12);
      uint32_t k[2];
#pragma unroll
      for (int i = 0; i < 2; i++) {
        const float mean = __uint_as_float(v[i].x) * (1.f / D_);
        const float rstd = rsq(fmaxf(fmaf(-mean, mean, __uint_as_float(v[i].y) * (1.f / D_)), 0.f) + 1e-5f);
        const uint32_t u = __float_as_uint(rstd * fmaf(-mean, sw, __uint_as_float(v[i].z)));
        k[i] = min(((u ^ ((uint32_t)((int)u >> 31) | 0x80000000u)) & ~2047u), 0xFFFFF000u) | (2047 - (row ^ (i << 8)));
        if (i == 0 && (warp >> 1) == hf) sts2f(sm + OFF_LNP + (wg * 64 + (tid & 63)) * 8, rstd, -mean * rstd);
      }
      const uint32_t hi = max(k[0], k[1]);
      uint32_t m1 = __reduce_max_sync(~0u, hi), m2 = __reduce_max_sync(~0u, hi == m1 ? min(k[0], k[1]) : hi);
      if (lane == 0) sts2f(msc + wid * 8, __uint_as_float(m1), __uint_as_float(m2));
      bar_sync(1, 256);
      const uint32_t kk = lds1(msc + (lane & 15) * 4);
      m1 = __reduce_max_sync(~0u, kk); m2 = __reduce_max_sync(~0u, kk == m1 ? 0 : kk);
      const int c0 = 2047 - (m1 & 2047), c1 = 2047 - (m2 & 2047);
      if ((c0 >> 4) == mb3 * 4 + warp || (c1 >> 4) == mb3 * 4 + warp) {
        const int ra = (lane & 4) ? c1 : c0, rd = (lane & 16) ? c1 : c0;
        uint32_t h0, h1, h2, h3;
        ldsm4_o<0>(hst + (ra & 15) * 256 + ((((lane & 3) * 4 + (lane >> 3)) ^ (ra & 7)) << 4), h0, h1, h2, h3);
        const float2 pr = lds2f(sm + OFF_LNP + (wid * 16 + (rd & 15)) * 8);
        if ((rd >> 4) == mb3 * 4 + warp) {
          const int slot = (rb & 6) + (lane >> 4);
          uint4* d = &P.s->hsel[c3 * 128 + (g & 3) * 32 + slot * 4 + t];
          st_rlx4(d, make_uint4(pack2(fmaf(bf_lo(h0), pr.x, pr.y), fmaf(bf_hi(h0), pr.x, pr.y)), pack2(fmaf(bf_lo(h1), pr.x, pr.y), fmaf(bf_hi(h1), pr.x, pr.y)),
                                pack2(fmaf(bf_lo(h2), pr.x, pr.y), fmaf(bf_hi(h2), pr.x, pr.y)), pack2(fmaf(bf_lo(h3), pr.x, pr.y), fmaf(bf_hi(h3), pr.x, pr.y))));
          if (!(lane & 15)) st_rlx(&P.s->cand[c3 * 32 + slot], (lane & 16) ? m2 : m1);
          st_rlx4(d + 1024, make_uint4(h0, h1, h2, h3));
        }
      }
      tx = clock64();
      if (tid == 0) { sts2f(msc + 64, __uint_as_float(m1), __uint_as_float(m2)); mbar_arrive(mb + B_OUT); }
    }
    TS(13);
    static_for<GU2, 32>(load_gu);
    const uint32_t dl = sm + (wid & 1) * 4096 + ((lane >> 4) * 8 + (lane & 7)) * 128 + ((((lane >> 3) & 1) ^ (lane & 7)) << 4);
    uint32_t da = dl + unit_of(DT0, wid >> 1), db = dl + unit_of(rank ? DT1 : DT0, 4 + (wid >> 1));
    uint32_t* yp = (uint32_t*)&P.s->ybuf[((wid * 8 + t * 2) * NFFN + fidx) * 2] + g;
    uint32_t k1, k2;
    uint2 key;
    {
      float gu[2][4][4];
      uint4 xb[4];
      uint32_t m[4];
      const uint4* xp = &P.s->hsel[wid * 128 + lane];
      const uint2* kp = (const uint2*)&P.s->cand[wid * 32] + t;
      uint32_t ps = gslot + g * 32;
      asm volatile("" : "+l"(xp), "+l"(kp), "+l"(yp), "+r"(db), "+r"(ps));
      if (fidx >= 0) mbar_wait(mb + B_FFD, 0);
      static_for<0, 8>([&](auto ic) { constexpr int i = decltype(ic)::value; ldsm4t_o<(i & 1) * 2048>(da ^ ((i >> 1) << 5), wd[i >> 1][i & 1]); });
      TS(9);
      while ((uint32_t)clock64() - tx < XDELAY) {}
      key = ld_rlx2(kp);
#pragma unroll
      for (int i = 0; i < 4; i++) xb[i] = ld_rlx4(xp + i * 32);
      if (fidx >= 0) mbar_wait(mb + B_KVP, 1);
#pragma unroll 1
      for (int it = 0; it < SPIN_LIMIT; it++) {
#pragma unroll
        for (int i = 0; i < 4; i++) m[i] = max4(0, xb[i]);
        if (!__any_sync(~0u, __vimax3_u32(__vimax3_u32(max(key.x, key.y), m[0], m[1]), m[2], m[3]) == SENT)) break;
        key = ld_rlx2(kp);
#pragma unroll
        for (int i = 0; i < 4; i++) if (m[i] == SENT) xb[i] = ld_rlx4(xp + i * 32);
        TSV(20, 100);
      }
      TS(14);
      const uint32_t hi = max(key.x, key.y);
      k1 = __reduce_max_sync(~0u, hi); k2 = __reduce_max_sync(~0u, hi == k1 ? min(key.x, key.y) : hi);
#pragma unroll
      for (int i = 0; i < 32; i++) gu[i >> 4][(i >> 2) & 3][i & 3] = 0.f;
#pragma unroll
      for (int ks = 0; ks < 8; ks++) {
#pragma unroll
        for (int i = 0; i < 4; i++) mma16816(gu[ks & 1][i], wa[ks][i], (ks & 1) ? xb[ks >> 1].z : xb[ks >> 1].x, (ks & 1) ? xb[ks >> 1].w : xb[ks >> 1].y);
        if (ks == 1) {
          const uint32_t dd = db | (__float_as_uint(gu[1][3][0]) & blockIdx.y);
          static_for<0, 8>([&](auto ic) { constexpr int i = decltype(ic)::value; ldsm4t_o<(i & 1) * 2048>(dd ^ ((i >> 1) << 5), wd[4 + (i >> 1)][i & 1]); });
        }
      }
#pragma unroll
      for (int c = 0; c < 2; c++) {
        const uint32_t kc = c ? key.y : key.x;
        float o[8];
#pragma unroll
        for (int j = 0; j < 8; j++) o[j] = gu[0][(j >> 2) + (j & 1) * 2][(j & 2) + c] + gu[1][(j >> 2) + (j & 1) * 2][(j & 2) + c];
        asm volatile("{\n.reg .pred p;\nsetp.ge.u32 p, %9, %10;\n@p st.shared.v4.f32 [%0], {%1,%2,%3,%4};\n@p st.shared.v4.f32 [%0+16], {%5,%6,%7,%8};\n}"
                     :: "r"(ps + (kc == k1 ? 0 : 256)), "f"(o[0]), "f"(o[1]), "f"(o[2]), "f"(o[3]), "f"(o[4]), "f"(o[5]), "f"(o[6]), "f"(o[7]), "r"(kc), "r"(k2) : "memory");
      }
    }
    TS(4);
    bar_sync(1, 256);
    {
      float g0 = 0.f, g1 = 0.f, u0 = 0.f, u1 = 0.f;
      static_for<0, 8>([&](auto wc) { constexpr int w = decltype(wc)::value;
        constexpr uint32_t o = sb + ((GT0 >> (5 * w)) & 31) * UNIT;
        const uint32_t ad = own + lane * 8 + (w == 0 || w == 7 ? sk : w < 3 ? -sk : 0);
        const float2 a = lds2f_o<o>(ad), c = lds2f_o<o + 256>(ad);
        g0 += a.x; u0 += a.y; g1 += c.x; u1 += c.y; });
      const uint32_t act = pack2(g0 * rcp(1.f + ex2(-1.4426950408889634f * g0)) * u0, g1 * rcp(1.f + ex2(-1.4426950408889634f * g1)) * u1);
      uint32_t bq[4];
#pragma unroll
      for (int i = 0; i < 4; i++) {
        const uint32_t lo = __shfl_sync(~0u, act, 8 * t + i), hi = __shfl_sync(~0u, act, 8 * t + 4 + i);
        bq[i] = __byte_perm(lo, hi, (g & 1) ? 0x7632 : 0x5410);
      }
      TS(16);
      float ya[8][4];
#pragma unroll
      for (int i = 0; i < 8; i++) { ya[i][0] = 0.f; ya[i][1] = 0.f; ya[i][2] = 0.f; ya[i][3] = 0.f; }
#pragma unroll
      for (int ks = 0; ks < 2; ks++)
#pragma unroll
        for (int i = 0; i < 8; i++) mma16816(ya[i], wd[i][ks], bq[ks * 2], bq[ks * 2 + 1]);
#pragma unroll
      for (int h = 0; h < 2; h++) {
        float o[4];
#pragma unroll
        for (int j = 0; j < 4; j++) o[j] = t == 0 ? ya[h * 4][j] : t == 1 ? ya[h * 4 + 1][j] : t == 2 ? ya[h * 4 + 2][j] : ya[h * 4 + 3][j];
        asm volatile("{\n.reg .pred p;\nsetp.ge.s32 p, %3, 0;\n@p st.relaxed.gpu.global.u32 [%0], %1;\n@p st.relaxed.gpu.global.u32 [%0+%4], %2;\n}"
                     :: "l"(yp + h * (64 * NFFN * 8)), "r"(pack2(o[0], o[1])), "r"(pack2(o[2], o[3])), "r"(fidx), "n"(NFFN * 32) : "memory");
      }
    }
    if (tid == 0) { sts2f(msc + 80, __uint_as_float(k1), __uint_as_float(k2)); mbar_arrive(mb + B_SEL); }
    TS(17);
    const uint32_t ty = clock64();
    if (wid < 7) {
      const uint4* yq = &P.s->ybuf[b * NFFN * 2 + tid];
      const uint32_t ks = (tid & 1) ? k2 : k1, grp = 3 - ((ks >> 9) & 3);
      const int fs = grp * 2 + (__shfl_sync(~0u, key.y, grp) == ks);
      const uint32_t* fq = (const uint32_t*)P.s->hsel + (((b >> 4) * 4 + ((b >> 2) & 3)) * 32 + fs * 4 + ((tid >> 2) & 3)) * 4 + (b & 3);
      float gate = rcp(1.f + ex2(-1.4426950408889634f * __uint_as_float(ks ^ (~(uint32_t)((int)ks >> 31) | 0x80000000u))));
      __nv_bfloat16* op = P.out + (size_t)(2047 - (ks & 2047)) * D_ + b * 8 + (tid >> 1);
      asm volatile("" : "+l"(yq), "+l"(fq), "+l"(op), "+f"(gate));
      while ((uint32_t)clock64() - ty < YDELAY) {}
      uint4 v;
      uint32_t fn = 0, fh = 0;
#pragma unroll 1
      for (int it = 0; it < SPIN_LIMIT; it++) {
        v = ld_rlx4(yq);
        if (wid == 0) { fn = ld_rlx(fq); fh = ld_rlx(fq + 4096); }
        TSV(22, 100);
        if (!__any_sync(~0u, max4(max(fn, fh), v) == SENT)) break;
      }
      const float base = (tid & 2) ? bf_hi(fh) + bf_hi(fn) : bf_lo(fh) + bf_lo(fn);
      TS(18);
      const bool p4 = lane & 16, p3 = lane & 8, p2 = lane & 4;
      const uint32_t w0 = __shfl_xor_sync(~0u, p4 ? v.x : v.z, 16), w1 = __shfl_xor_sync(~0u, p4 ? v.y : v.w, 16), o0 = p4 ? v.z : v.x, o1 = p4 ? v.w : v.y;
      const float y0 = bf_lo(o0) + bf_lo(w0), y1 = bf_hi(o0) + bf_hi(w0), y2 = bf_lo(o1) + bf_lo(w1), y3 = bf_hi(o1) + bf_hi(w1);
      const float z0 = (p3 ? y2 : y0) + __shfl_xor_sync(~0u, p3 ? y0 : y2, 8), z1 = (p3 ? y3 : y1) + __shfl_xor_sync(~0u, p3 ? y1 : y3, 8);
      float z = (p2 ? z1 : z0) + __shfl_xor_sync(~0u, p2 ? z0 : z1, 4);
      z += __shfl_xor_sync(~0u, z, 2);
      const uint32_t yx = msc + 128;
      if (!(lane & 2)) sts1(yx + wid * 64 + ((lane & 1) * 8 + (lane >> 2)) * 4, __float_as_uint(z));
      bar_sync(13, 224);
      if (tid < 16) {
        float y = 0.f;
#pragma unroll
        for (int w = 0; w < 7; w++) y += __uint_as_float(lds1(yx + w * 64 + tid * 4));
        *op = __float2bfloat16(fmaf(y, gate, base));
      }
      if (b == 0 && tid == 32) P.s->epoch = lds1(mb + B_SW) & 255;
    }
    if (tid == 0) SPANS(1);
    TS(19); TSG(31);
    if (warp == 0) TS_DUMP(wg);
   }
  }
}

typedef CUresult (*EncodeFn)(CUtensorMap*, CUtensorMapDataType, cuuint32_t, void*, const cuuint64_t*, const cuuint64_t*, const cuuint32_t*,
                             const cuuint32_t*, CUtensorMapInterleave, CUtensorMapSwizzle, CUtensorMapL2promotion, CUtensorMapFloatOOBfill);
void make_map(EncodeFn enc, CUtensorMap* m, const void* p, int rank, std::initializer_list<cuuint64_t> dims, std::initializer_list<cuuint64_t> str,
              std::initializer_list<cuuint32_t> box, CUtensorMapSwizzle sw) {
  const cuuint32_t es[4] = {1, 1, 1, 1};
  enc(m, CU_TENSOR_MAP_DATA_TYPE_BFLOAT16, rank, const_cast<void*>(p), dims.begin(), str.begin(), box.begin(), es, CU_TENSOR_MAP_INTERLEAVE_NONE, sw,
      CU_TENSOR_MAP_L2_PROMOTION_L2_128B, CU_TENSOR_MAP_FLOAT_OOB_FILL_NONE);
}

}

extern "C" void kernel_launch(void* const* d_in, const int* in_sizes, int n_in, void* d_out, int out_size) {
  (void)in_sizes; (void)n_in; (void)out_size;
  Ptrs P;
  P.x = (const __nv_bfloat16*)d_in[0]; P.wqkv = (const __nv_bfloat16*)d_in[1]; P.wo = (const __nv_bfloat16*)d_in[2];
  P.wr = (const __nv_bfloat16*)d_in[4]; P.wg = (const __nv_bfloat16*)d_in[5]; P.wu = (const __nv_bfloat16*)d_in[6];
  P.wd = (const __nv_bfloat16*)d_in[7]; P.out = (__nv_bfloat16*)d_out;
  cudaGetSymbolAddress((void**)&P.s, g_scratch);
  void* fn = nullptr;
  cudaDriverEntryPointQueryResult q;
  cudaGetDriverEntryPoint("cuTensorMapEncodeTiled", &fn, cudaEnableDefault, &q);
  EncodeFn enc = (EncodeFn)fn;
  Maps T;
  constexpr CUtensorMapSwizzle S128 = CU_TENSOR_MAP_SWIZZLE_128B, S64 = CU_TENSOR_MAP_SWIZZLE_64B;
  make_map(enc, &T.m[M_X], P.x, 2, {D_, S_}, {D_ * 2}, {64, 128}, S128);
  make_map(enc, &T.m[M_W], P.wqkv, 3, {D_, D_, 3}, {3 * D_ * 2, D_ * 2}, {64, 64, 2}, S128);
  make_map(enc, &T.m[M_Q], P.wqkv, 2, {3 * D_, D_}, {3 * D_ * 2}, {64, 64}, S128);
  make_map(enc, &T.m[M_O], P.wo, 4, {64, 64, 16, 16}, {D_ * 2, 64 * D_ * 2, 128}, {64, 64, 1, 2}, S128);
  make_map(enc, &T.m[M_S], P.wo, 4, {64, 64, 16, 16}, {D_ * 2, 64 * D_ * 2, 128}, {64, 16, 4, 2}, S128);
  make_map(enc, &T.m[M_G], P.wg, 3, {F_, D_, 1}, {F_ * 2, F_ * 2 * D_}, {32, 128, 1}, S64);
  make_map(enc, &T.m[M_U], P.wu, 3, {F_, D_, 1}, {F_ * 2, F_ * 2 * D_}, {32, 128, 1}, S64);
  make_map(enc, &T.m[M_D], P.wd, 3, {64, F_, 16}, {D_ * 2, 128}, {64, 32, 2}, S128);
  make_map(enc, &T.m[M_L], P.wd, 2, {64, F_ * 16}, {128}, {8, 32}, CU_TENSOR_MAP_SWIZZLE_NONE);
  cudaFuncSetAttribute(fused_kernel, cudaFuncAttributeMaxDynamicSharedMemorySize, SMEM_BYTES);
  fused_kernel<<<NCTA, 384, SMEM_BYTES>>>(P, T);
}
```

```cpp
#include <cuda_runtime.h>
#include <cuda.h>
#include <cuda_bf16.h>
#include <stdint.h>
#include <type_traits>
#include <initializer_list>

namespace {

constexpr int S_ = 2048, D_ = 1024, F_ = 3584;
constexpr int NCTA = 128, NFFN = 112;
constexpr uint32_t SENT = 0xFFFFFFFFu;
constexpr int SPIN_LIMIT = 1 << 20;

#define ADELAY 200
#define ADELAY2 600
#define PFA 6
#define PF0 8
#define WPF0 8
#define DPER 1200
#define PDEPTH 2
#define PSTART 4000
#define PPER 1700
#define PEARLY 5
#define PLEAD 0
#define RST 1
#define PSUB 2
#define HOLDP 1
#define QHOLD 1
#define NPULL 12
#define CDELAY 0
#define NOUTW 3
#define YDELAY 650
#define EFX 0
#define EFW 1
#define EFF 1
#define KLEAD 13
#define GDELAY 1000
#define NDIR 6
#define PULL0 3
#define FD0 600
#define FD1 800
#define SPF 1
#define MPF 1
#define TLBW 2
#define GORD 0
#define GSPLIT 2
#define EFW0 0
#define EFX0 0
#define EFWK 8
#define PSLEEP 20
#define P3PULL 1
#define RST2 4
#define KDELAY 450
#define AEARLY 0
#define BHOLD 4
#define SDELAY 100
#define FSTAG 150
#define OFL 0
#define CHKF 1
#define BEV 1
#define DLATE 4
#define P3GATE 3
#define ACCSW 0
#define B45 B_E
#define SDEL2 500
#define XDELAY 500
#define GU1 8
#define GU2 20
#define WD1 10
#define ODELAY 0
#define NOOUT 0
constexpr int OUNR =
  2;
#define P3N 2
#define HALFMAP 1
#define KWARP 7
#define FEARLY 1
#define MFIRST 350
#define MKV 900
#define MO 800
#define MST 1450
#define MSTE 13
#define AFIRST 0
#define MWIDE 0
#define PLAG 8
#define PSTEP 0
#define EFA 0
#define EFO 0
#define EFB 0
#define EFXK 12
#define P1F 1
#define R1MID 5
#define PSTOP 3
#define DMASK 0x5550
#define PFST 1
#define W0OFF 2
#define MAPM 2
#define XWPF 0
constexpr uint32_t STAGE_B = 57344;
constexpr uint32_t OFF_STATS = 229376;
constexpr uint32_t OFF_COLSUM = 231424;
constexpr uint32_t OFF_BARS = 232192;
constexpr uint32_t SMEM_BYTES = 232448;
constexpr uint32_t B_FULL = 0, B_EMPTY = 32, B_E = 64, B_AUX = 128, B_EVA = 136, B_EVB = 144, B_BF = 152, B_LATE = 232, B_FFN = 240, B_SW = 248;
constexpr uint32_t B_OUT = B_FULL, B_SEL = B_FULL + 8, B_WR = B_FULL + 16, B_FFD = B_FULL + 24, B_E16 = B_EMPTY + 16, B_KVB = B_EMPTY + 8, B_DUMMY = B_SW + 4,
                   B_GATE = B_EMPTY + 24, B_ID = B_BF + 56, B_KVP = B_BF + 64, B_F15 = B_BF + 72;
#define B_HOLD B_F15
#define HOLDPAR 0
constexpr uint32_t UNIT = 8192;
constexpr uint32_t sb = 1024;
constexpr uint32_t bars = sb + OFF_BARS;
constexpr uint64_t tab5(int a, int b, int c, int d, int e, int f, int g, int h, int i = 0, int j = 0) {
  return (uint64_t)a | (uint64_t)b << 5 | (uint64_t)c << 10 | (uint64_t)d << 15 | (uint64_t)e << 20 | (uint64_t)f << 25 | (uint64_t)g << 30 | (uint64_t)h << 35 |
         (uint64_t)i << 40 | (uint64_t)j << 45;
}
constexpr uint64_t BT0 = tab5(4, 11, 18, 25, 7, 9, 16, 0), BT1 = tab5(4, 11, 18, 25, 21, 23, 2, 0);
constexpr uint64_t GT0 = tab5(2, 21, 23, 18, 0, 25, 14, 7), GT1 = tab5(16, 7, 9, 18, 0, 25, 14, 21);
constexpr uint64_t DT0 = tab5(6, 13, 20, 27, 9, 10, 16, 17), DT1 = tab5(6, 13, 20, 27, 23, 24, 2, 3);
__device__ __forceinline__ uint32_t unit_of(uint64_t tab, int i) { return ((uint32_t)(tab >> (5 * i)) & 31) * UNIT; }
__device__ __forceinline__ uint32_t ring_of(int p, int w) { return (p & 1) * (2 * STAGE_B) + ((p & 2) ? 49152 + w * STAGE_B : w * UNIT); }
constexpr uint32_t OFF_LNP = OFF_STATS + 1024;

struct Scratch {
  uint4 obuf[32 * 64 * 128];
  uint4 kvp[16 * 8 * 256];
  uint4 zp[16 * 8 * 16];
  uint4 ybuf[NCTA * NFFN * 2];
  uint4 st1[64 * 48];
  uint4 csp[16 * 8 * 48];
  uint4 st2[S_];
  uint4 hsel[2 * 8 * 128];
  uint32_t cand[8 * 32];
  uint32_t when[32 * 32];
  unsigned epoch;
};
__device__ __align__(1024) Scratch g_scratch;
#define TS_DECL
#define TS(i)
#define TSG(i)
#define TSV(i, v)
#define TSD(i)
#define RTS_DECL
#define RTS(i)
#define RTS_DUMP
#define TS_DUMP(slot)
#define PTS(i)
#define g_dbgv(i, v)

#define SPANS(i)
__device__ __forceinline__ uint32_t smem_u32(const void* p) { return (uint32_t)__cvta_generic_to_shared(p); }
__device__ __forceinline__ void mbar_init(uint32_t bar, uint32_t cnt) { asm volatile("mbarrier.init.shared::cta.b64 [%0], %1;" :: "r"(bar), "r"(cnt) : "memory"); }
__device__ __forceinline__ void mbar_expect_tx(uint32_t bar, uint32_t bytes) { asm volatile("mbarrier.arrive.expect_tx.shared::cta.b64 _, [%0], %1;" :: "r"(bar), "r"(bytes) : "memory"); }
__device__ __forceinline__ void mbar_arrive(uint32_t bar) { asm volatile("mbarrier.arrive.shared::cta.b64 _, [%0];" :: "r"(bar) : "memory"); }
#define SPINCHK(it, code) if ((it) > SPIN_LIMIT) break
__device__ __forceinline__ void mbar_wait(uint32_t bar, uint32_t parity) {
  asm volatile("{\n.reg .pred p;\n.reg .u32 c;\nmov.u32 c, 0;\n"
               "WL:\nmbarrier.try_wait.parity.shared::cta.b64 p, [%0], %1;\n@p bra WD;\n"
               "add.u32 c, c, 1;\nsetp.lt.u32 p, c, 1048576;\n@p bra WL;\nWD:\n}" :: "r"(bar), "r"(parity) : "memory");
}
__device__ __forceinline__ bool mbar_test(uint32_t bar, uint32_t parity) {
  uint32_t ok;
  asm volatile("{\n.reg .pred p;\nmbarrier.test_wait.parity.shared::cta.b64 p, [%1], %2;\nselp.u32 %0, 1, 0, p;\n}" : "=r"(ok) : "r"(bar), "r"(parity) : "memory");
  return ok;
}
__device__ __forceinline__ uint64_t l2_stream() { uint64_t p; asm("createpolicy.fractional.L2::evict_first.b64 %0, 1.0;" : "=l"(p)); return p; }
__device__ __forceinline__ void tma_2d(uint32_t dst, const CUtensorMap* tm, int c0, int c1, uint32_t bar, bool stream) {
  if (stream) asm volatile("cp.async.bulk.tensor.2d.shared::cluster.global.mbarrier::complete_tx::bytes.L2::cache_hint [%0], [%1, {%3, %4}], [%2], %5;"
                           :: "r"(dst), "l"(tm), "r"(bar), "r"(c0), "r"(c1), "l"(l2_stream()) : "memory");
  else asm volatile("cp.async.bulk.tensor.2d.shared::cluster.global.mbarrier::complete_tx::bytes [%0], [%1, {%3, %4}], [%2];"
                    :: "r"(dst), "l"(tm), "r"(bar), "r"(c0), "r"(c1) : "memory");
}
__device__ __forceinline__ void tma_3d(uint32_t dst, const CUtensorMap* tm, int c0, int c1, int c2, uint32_t bar, bool stream) {
  if (stream) asm volatile("cp.async.bulk.tensor.3d.shared::cluster.global.mbarrier::complete_tx::bytes.L2::cache_hint [%0], [%1, {%3, %4, %5}], [%2], %6;"
                           :: "r"(dst), "l"(tm), "r"(bar), "r"(c0), "r"(c1), "r"(c2), "l"(l2_stream()) : "memory");
  else asm volatile("cp.async.bulk.tensor.3d.shared::cluster.global.mbarrier::complete_tx::bytes [%0], [%1, {%3, %4, %5}], [%2];"
                    :: "r"(dst), "l"(tm), "r"(bar), "r"(c0), "r"(c1), "r"(c2) : "memory");
}
__device__ __forceinline__ void tma_pf_3d(const CUtensorMap* tm, int c0, int c1, int c2) {
  asm volatile("cp.async.bulk.prefetch.tensor.3d.L2.global [%0, {%1, %2, %3}];" :: "l"(tm), "r"(c0), "r"(c1), "r"(c2) : "memory");
}
__device__ __forceinline__ void tma_4d(uint32_t dst, const CUtensorMap* tm, int c0, int c1, int c2, int c3, uint32_t bar, bool stream) {
  if (stream) asm volatile("cp.async.bulk.tensor.4d.shared::cluster.global.mbarrier::complete_tx::bytes.L2::cache_hint [%0], [%1, {%3, %4, %5, %6}], [%2], %7;"
                           :: "r"(dst), "l"(tm), "r"(bar), "r"(c0), "r"(c1), "r"(c2), "r"(c3), "l"(l2_stream()) : "memory");
  else asm volatile("cp.async.bulk.tensor.4d.shared::cluster.global.mbarrier::complete_tx::bytes [%0], [%1, {%3, %4, %5, %6}], [%2];"
                    :: "r"(dst), "l"(tm), "r"(bar), "r"(c0), "r"(c1), "r"(c2), "r"(c3) : "memory");
}
__device__ __forceinline__ void tma_2d_mc(uint32_t dst, const CUtensorMap* tm, int c0, int c1, uint32_t bar, bool stream) {
  if (stream) asm volatile("cp.async.bulk.tensor.2d.shared::cluster.global.mbarrier::complete_tx::bytes.multicast::cluster.L2::cache_hint [%0], [%1, {%3, %4}], [%2], %5, %6;"
                           :: "r"(dst), "l"(tm), "r"(bar), "r"(c0), "r"(c1), "h"((uint16_t)3), "l"(l2_stream()) : "memory");
  else asm volatile("cp.async.bulk.tensor.2d.shared::cluster.global.mbarrier::complete_tx::bytes.multicast::cluster [%0], [%1, {%3, %4}], [%2], %5;"
                    :: "r"(dst), "l"(tm), "r"(bar), "r"(c0), "r"(c1), "h"((uint16_t)3) : "memory");
}
__device__ __forceinline__ bool elect_one() {
  uint32_t p;
  asm volatile("{\n.reg .pred q;\nelect.sync _|q, 0xFFFFFFFF;\nselp.u32 %0, 1, 0, q;\n}" : "=r"(p));
  return p;
}
__device__ __forceinline__ void bulk_load_mc(uint32_t dst, const void* src, uint32_t bytes, uint32_t bar) {
  if (EFA) asm volatile("cp.async.bulk.shared::cluster.global.mbarrier::complete_tx::bytes.multicast::cluster.L2::cache_hint [%0], [%1], %2, [%3], %4, %5;"
                        :: "r"(dst), "l"(src), "r"(bytes), "r"(bar), "h"((uint16_t)3), "l"(l2_stream()) : "memory");
  else asm volatile("cp.async.bulk.shared::cluster.global.mbarrier::complete_tx::bytes.multicast::cluster [%0], [%1], %2, [%3], %4;"
                    :: "r"(dst), "l"(src), "r"(bytes), "r"(bar), "h"((uint16_t)3) : "memory");
}
__device__ __forceinline__ void bulk_load(uint32_t dst, const void* src, uint32_t bytes, uint32_t bar) {
  asm volatile("cp.async.bulk.shared::cluster.global.mbarrier::complete_tx::bytes [%0], [%1], %2, [%3];" :: "r"(dst), "l"(src), "r"(bytes), "r"(bar) : "memory");
}
__device__ __forceinline__ void st_out(void* p, uint4 v) {
  if (EFO == 1) asm volatile("st.global.L2::cache_hint.v4.u32 [%0], {%1,%2,%3,%4}, %5;" :: "l"(p), "r"(v.x), "r"(v.y), "r"(v.z), "r"(v.w), "l"(l2_stream()) : "memory");
  else if (EFO == 2) asm volatile("st.global.cs.v4.u32 [%0], {%1,%2,%3,%4};" :: "l"(p), "r"(v.x), "r"(v.y), "r"(v.z), "r"(v.w) : "memory");
  else asm volatile("st.global.v4.u32 [%0], {%1,%2,%3,%4};" :: "l"(p), "r"(v.x), "r"(v.y), "r"(v.z), "r"(v.w) : "memory");
}
__device__ __forceinline__ void bulk_store(void* dst, uint32_t src, uint32_t bytes) {
  asm volatile("cp.async.bulk.global.shared::cta.bulk_group [%0], [%1], %2;" :: "l"(dst), "r"(src), "r"(bytes) : "memory");
}
__device__ __forceinline__ void mbar_arrive_rem(uint32_t bar) { asm volatile("mbarrier.arrive.shared::cluster.b64 _, [%0];" :: "r"(bar) : "memory"); }
__device__ __forceinline__ void st_async4(uint32_t addr, const uint4& v, uint32_t bar) {
  asm volatile("st.async.shared::cluster.mbarrier::complete_tx::bytes.v4.b32 [%0], {%1,%2,%3,%4}, [%5];" :: "r"(addr), "r"(v.x), "r"(v.y), "r"(v.z), "r"(v.w), "r"(bar) : "memory");
}
template <uint32_t O> __device__ __forceinline__ void ldsm4_o(uint32_t addr, uint32_t& a, uint32_t& b, uint32_t& c, uint32_t& d) {
  asm volatile("ldmatrix.sync.aligned.m8n8.x4.shared.b16 {%0,%1,%2,%3}, [%4+%5];" : "=r"(a), "=r"(b), "=r"(c), "=r"(d) : "r"(addr), "n"(O) : "memory");
}
template <uint32_t O> __device__ __forceinline__ void ldsm4t_o(uint32_t addr, uint32_t (&r)[4]) {
  asm volatile("ldmatrix.sync.aligned.m8n8.x4.trans.shared.b16 {%0,%1,%2,%3}, [%4+%5];" : "=r"(r[0]), "=r"(r[1]), "=r"(r[2]), "=r"(r[3]) : "r"(addr), "n"(O) : "memory");
}
__device__ __forceinline__ void mma16816(float (&c)[4], const uint32_t (&a)[4], uint32_t b0, uint32_t b1) {
  asm("mma.sync.aligned.m16n8k16.row.col.f32.bf16.bf16.f32 {%0,%1,%2,%3}, {%4,%5,%6,%7}, {%8,%9}, {%0,%1,%2,%3};"
      : "+f"(c[0]), "+f"(c[1]), "+f"(c[2]), "+f"(c[3]) : "r"(a[0]), "r"(a[1]), "r"(a[2]), "r"(a[3]), "r"(b0), "r"(b1));
}
__device__ __forceinline__ void l2_prefetch(const void* p) { asm volatile("prefetch.global.L2 [%0];" :: "l"(p) : "memory"); }
__device__ __forceinline__ uint32_t ld_line(const void* p) { uint32_t v; asm volatile("ld.global.cg.L2::128B.u32 %0, [%1];" : "=r"(v) : "l"(p) : "memory"); return v; }
__device__ __forceinline__ void tmap_prefetch(const CUtensorMap* tm) { asm volatile("prefetch.tensormap [%0];" :: "l"(tm) : "memory"); }
__device__ __forceinline__ void wg_fence() { asm volatile("wgmma.fence.sync.aligned;" ::: "memory"); }
__device__ __forceinline__ void wg_commit() { asm volatile("wgmma.commit_group.sync.aligned;" ::: "memory"); }
template <int N> __device__ __forceinline__ void wg_wait() { asm volatile("wgmma.wait_group.sync.aligned %0;" :: "n"(N) : "memory"); }
template <int N> __device__ __forceinline__ void pin(float (&d)[N]) {
#pragma unroll
  for (int i = 0; i < N; i++) asm volatile("" : "+f"(d[i]) :: "memory");
}
__device__ __forceinline__ void pin4(uint4& v) { asm volatile("" : "+r"(v.x), "+r"(v.y), "+r"(v.z), "+r"(v.w) :: "memory"); }
template <uint32_t SBO, uint32_t SWZ> __device__ __forceinline__ uint64_t dsc(uint32_t lo) { return ((uint64_t)((SBO >> 4) | (SWZ << 30)) << 32) | lo; }
__host__ __device__ constexpr uint32_t dlo(uint32_t addr, uint32_t lbo) { return (addr >> 4) | ((lbo >> 4) << 16); }
__device__ __forceinline__ void bar_sync(int id, int n) { asm volatile("bar.sync %0, %1;" :: "r"(id), "r"(n) : "memory"); }
__device__ __forceinline__ void bar_arrive(int id, int n) { asm volatile("bar.arrive %0, %1;" :: "r"(id), "r"(n) : "memory"); }
__device__ __forceinline__ void fence_async_smem() { asm volatile("fence.proxy.async.shared::cta;" ::: "memory"); }
__device__ __forceinline__ void fence_gpu() { asm volatile("fence.acq_rel.gpu;" ::: "memory"); }
__device__ __forceinline__ uint4 ld_cg4(const void* p) { uint4 v; asm volatile("ld.global.cg.v4.u32 {%0,%1,%2,%3}, [%4];" : "=r"(v.x), "=r"(v.y), "=r"(v.z), "=r"(v.w) : "l"(p) : "memory"); return v; }
__device__ __forceinline__ uint4 ld_rlx4(const void* p) { uint4 v; asm volatile("ld.relaxed.gpu.global.v4.u32 {%0,%1,%2,%3}, [%4];" : "=r"(v.x), "=r"(v.y), "=r"(v.z), "=r"(v.w) : "l"(p) : "memory"); return v; }
__device__ __forceinline__ uint32_t ld_rlx(const void* p) { uint32_t v; asm volatile("ld.relaxed.gpu.global.u32 %0, [%1];" : "=r"(v) : "l"(p) : "memory"); return v; }
__device__ __forceinline__ void st_rlx4(void* p, uint4 v) { asm volatile("st.relaxed.gpu.global.v4.u32 [%0], {%1,%2,%3,%4};" :: "l"(p), "r"(v.x), "r"(v.y), "r"(v.z), "r"(v.w) : "memory"); }
__device__ __forceinline__ void st_rlx2(void* p, uint32_t a, uint32_t b) { asm volatile("st.relaxed.gpu.global.v2.u32 [%0], {%1,%2};" :: "l"(p), "r"(a), "r"(b) : "memory"); }
__device__ __forceinline__ void st_rlx(void* p, uint32_t a) { asm volatile("st.relaxed.gpu.global.u32 [%0], %1;" :: "l"(p), "r"(a) : "memory"); }
__device__ __forceinline__ void red4(void* p, float a, float b, float c, float d) { asm volatile("red.relaxed.gpu.global.add.v4.f32 [%0], {%1,%2,%3,%4};" :: "l"(p), "f"(a), "f"(b), "f"(c), "f"(d) : "memory"); }
__device__ __forceinline__ uint32_t pack2(float lo, float hi) { uint32_t r; asm("cvt.rn.bf16x2.f32 %0, %1, %2;" : "=r"(r) : "f"(hi), "f"(lo)); return r; }
__device__ __forceinline__ float bf_lo(uint32_t v) { return __uint_as_float(v << 16); }
__device__ __forceinline__ float bf_hi(uint32_t v) { return __uint_as_float(v & 0xFFFF0000u); }
__device__ __forceinline__ void stsm4(uint32_t addr, uint32_t a, uint32_t b, uint32_t c, uint32_t d) {
  asm volatile("stmatrix.sync.aligned.m8n8.x4.shared.b16 [%0], {%1,%2,%3,%4};" :: "r"(addr), "r"(a), "r"(b), "r"(c), "r"(d) : "memory");
}
template <uint32_t O> __device__ __forceinline__ void stsm4_o(uint32_t addr, uint32_t a, uint32_t b, uint32_t c, uint32_t d) {
  asm volatile("stmatrix.sync.aligned.m8n8.x4.shared.b16 [%0+%5], {%1,%2,%3,%4};" :: "r"(addr), "r"(a), "r"(b), "r"(c), "r"(d), "n"(O) : "memory");
}
__device__ __forceinline__ void sts4(uint32_t addr, uint32_t a, uint32_t b, uint32_t c, uint32_t d) { asm volatile("st.shared.v4.u32 [%0], {%1,%2,%3,%4};" :: "r"(addr), "r"(a), "r"(b), "r"(c), "r"(d) : "memory"); }
__device__ __forceinline__ void sts2f(uint32_t addr, float a, float b) { asm volatile("st.shared.v2.f32 [%0], {%1,%2};" :: "r"(addr), "f"(a), "f"(b) : "memory"); }
__device__ __forceinline__ void sts1(uint32_t addr, uint32_t a) { asm volatile("st.shared.u32 [%0], %1;" :: "r"(addr), "r"(a) : "memory"); }
__device__ __forceinline__ float2 lds2f(uint32_t addr) { float2 v; asm volatile("ld.shared.v2.f32 {%0,%1}, [%2];" : "=f"(v.x), "=f"(v.y) : "r"(addr) : "memory"); return v; }
template <uint32_t O> __device__ __forceinline__ float2 lds2f_o(uint32_t addr) { float2 v; asm volatile("ld.shared.v2.f32 {%0,%1}, [%2+%3];" : "=f"(v.x), "=f"(v.y) : "r"(addr), "n"(O) : "memory"); return v; }
template <int I, int N, class F> __device__ __forceinline__ void static_for(F&& f) { if constexpr (I < N) { f(std::integral_constant<int, I>{}); static_for<I + 1, N>(f); } }
__device__ __forceinline__ uint4 lds4(uint32_t addr) { uint4 v; asm volatile("ld.shared.v4.u32 {%0,%1,%2,%3}, [%4];" : "=r"(v.x), "=r"(v.y), "=r"(v.z), "=r"(v.w) : "r"(addr) : "memory"); return v; }
__device__ __forceinline__ uint32_t lds1(uint32_t addr) { uint32_t v; asm volatile("ld.shared.u32 %0, [%1];" : "=r"(v) : "r"(addr) : "memory"); return v; }
__device__ __forceinline__ float ex2(float x) { float y; asm("ex2.approx.ftz.f32 %0, %1;" : "=f"(y) : "f"(x)); return y; }
__device__ __forceinline__ uint32_t max4(uint32_t m, const uint4& v) { return __vimax3_u32(__vimax3_u32(m, v.x, v.y), v.z, v.w); }
__device__ __forceinline__ float rsq(float x) { float y; asm("rsqrt.approx.ftz.f32 %0, %1;" : "=f"(y) : "f"(x)); return y; }
__device__ __forceinline__ float rcp(float x) { float y; asm("rcp.approx.ftz.f32 %0, %1;" : "=f"(y) : "f"(x)); return y; }
__device__ __forceinline__ uint2 ld_rlx2(const void* p) { uint2 v; asm volatile("ld.relaxed.gpu.global.v2.u32 {%0,%1}, [%2];" : "=r"(v.x), "=r"(v.y) : "l"(p) : "memory"); return v; }
template <uint32_t O> __device__ __forceinline__ uint4 lds4_o(uint32_t addr) { uint4 v; asm volatile("ld.shared.v4.u32 {%0,%1,%2,%3}, [%4+%5];" : "=r"(v.x), "=r"(v.y), "=r"(v.z), "=r"(v.w) : "r"(addr), "n"(O) : "memory"); return v; }
__device__ __forceinline__ uint32_t phi2(float u0, float u1, float rl, uint32_t r2) {
  uint32_t pu, r;
  asm("cvt.rn.relu.bf16x2.f32 %0, %1, %2;" : "=r"(pu) : "f"(u1), "f"(u0));
  asm("fma.rn.bf16x2 %0, %1, %2, %3;" : "=r"(r) : "r"(pu), "r"(r2), "r"(pack2(__saturatef(ex2(u0 * rl) + 1e-6f), __saturatef(ex2(u1 * rl) + 1e-6f))));
  return r;
}
__device__ __forceinline__ uint32_t dup2(float r) { uint32_t v; asm("cvt.rn.relu.bf16x2.f32 %0, %1, %1;" : "=r"(v) : "f"(r)); return v; }
__device__ __forceinline__ uint32_t zero_after(const uint32_t (&v)[16]) {
  uint32_t z = 0;
#pragma unroll
  for (int i = 0; i < 16; i++) z |= v[i];
  return z & 0x80008000u;
}
__device__ __forceinline__ uint32_t hadd2(uint32_t a, uint32_t b) { uint32_t v; asm("add.rn.bf16x2 %0, %1, %2;" : "=r"(v) : "r"(a), "r"(b)); return v; }
__device__ __forceinline__ void sched_fence() { asm volatile("{\n.reg .pred p;\n.reg .u64 c;\nSF:\nmov.u64 c, %clock64;\nsetp.eq.u64 p, c, 0;\n@p bra SF;\n}" ::: "memory"); }
__device__ __forceinline__ uint4 ld_gen4(const void* p) { uint4 v; asm volatile("ld.relaxed.gpu.v4.u32 {%0,%1,%2,%3}, [%4];" : "=r"(v.x), "=r"(v.y), "=r"(v.z), "=r"(v.w) : "l"(p) : "memory"); return v; }
__device__ __forceinline__ uint2 ld_gen2(const void* p) { uint2 v; asm volatile("ld.relaxed.gpu.v2.u32 {%0,%1}, [%2];" : "=r"(v.x), "=r"(v.y) : "l"(p) : "memory"); return v; }
__device__ __forceinline__ uint32_t now_ns() { uint32_t v; asm volatile("mov.u32 %0, %%globaltimer_lo;" : "=r"(v) :: "memory"); return v; }
__device__ __forceinline__ void meet(uint32_t* mine, const uint4* all, int first, int after, uint32_t bar) {
  const uint32_t t0 = now_ns() & ~1u;
  if ((threadIdx.x & 31) == 0) st_rlx(mine, t0);
  while ((int)(now_ns() - t0) < first) {}
  uint4 v;
#pragma unroll 1
  for (int it = 0; it < SPIN_LIMIT; it++) { v = ld_rlx4(all); if (!__any_sync(~0u, max4(0, v) == SENT)) break; }
  const int d = min(__reduce_max_sync(~0u, max(max((int)(v.x - t0), (int)(v.y - t0)), max((int)(v.z - t0), (int)(v.w - t0)))), 100000) + after;
  mbar_wait(bar, 0);
  while ((int)(now_ns() - t0) < d) {}
}
__device__ __forceinline__ uint32_t lane_id() { uint32_t v; asm volatile("mov.u32 %0, %%laneid;" : "=r"(v)); return v; }
template <int A, int B, int N> __device__ __forceinline__ void pinr(float (&d)[N]) {
#pragma unroll
  for (int i = A; i < B; i++) asm volatile("" : "+f"(d[i]) :: "memory");
}
template <int N> __device__ __forceinline__ void pinu(uint32_t (&d)[N]) {
#pragma unroll
  for (int i = 0; i < N; i++) asm volatile("" : "+r"(d[i]) :: "memory");
}

template<int TA, int TB, int OFF, int SZ> __device__ __forceinline__ void wgmma_n192_ss(float (&d)[SZ], uint64_t da, uint64_t db, int scale_d) {
  asm volatile("{\n.reg .pred p;\nsetp.ne.b32 p, %98, 0;\n"
    "wgmma.mma_async.sync.aligned.m64n192k16.f32.bf16.bf16 {%0,%1,%2,%3,%4,%5,%6,%7,%8,%9,%10,%11,%12,%13,%14,%15,%16,%17,%18,%19,%20,%21,%22,%23,%24,%25,%26,%27,%28,%29,%30,%31,%32,%33,%34,%35,%36,%37,%38,%39,%40,%41,%42,%43,%44,%45,%46,%47,%48,%49,%50,%51,%52,%53,%54,%55,%56,%57,%58,%59,%60,%61,%62,%63,%64,%65,%66,%67,%68,%69,%70,%71,%72,%73,%74,%75,%76,%77,%78,%79,%80,%81,%82,%83,%84,%85,%86,%87,%88,%89,%90,%91,%92,%93,%94,%95}, %96, %97, p, 1, 1, %99, %100;\n}\n"
    : "+f"(d[OFF+0]), "+f"(d[OFF+1]), "+f"(d[OFF+2]), "+f"(d[OFF+3]), "+f"(d[OFF+4]), "+f"(d[OFF+5]), "+f"(d[OFF+6]), "+f"(d[OFF+7]),
      "+f"(d[OFF+8]), "+f"(d[OFF+9]), "+f"(d[OFF+10]), "+f"(d[OFF+11]), "+f"(d[OFF+12]), "+f"(d[OFF+13]), "+f"(d[OFF+14]), "+f"(d[OFF+15]),
      "+f"(d[OFF+16]), "+f"(d[OFF+17]), "+f"(d[OFF+18]), "+f"(d[OFF+19]), "+f"(d[OFF+20]), "+f"(d[OFF+21]), "+f"(d[OFF+22]), "+f"(d[OFF+23]),
      "+f"(d[OFF+24]), "+f"(d[OFF+25]), "+f"(d[OFF+26]), "+f"(d[OFF+27]), "+f"(d[OFF+28]), "+f"(d[OFF+29]), "+f"(d[OFF+30]), "+f"(d[OFF+31]),
      "+f"(d[OFF+32]), "+f"(d[OFF+33]), "+f"(d[OFF+34]), "+f"(d[OFF+35]), "+f"(d[OFF+36]), "+f"(d[OFF+37]), "+f"(d[OFF+38]), "+f"(d[OFF+39]),
      "+f"(d[OFF+40]), "+f"(d[OFF+41]), "+f"(d[OFF+42]), "+f"(d[OFF+43]), "+f"(d[OFF+44]), "+f"(d[OFF+45]), "+f"(d[OFF+46]), "+f"(d[OFF+47]),
      "+f"(d[OFF+48]), "+f"(d[OFF+49]), "+f"(d[OFF+50]), "+f"(d[OFF+51]), "+f"(d[OFF+52]), "+f"(d[OFF+53]), "+f"(d[OFF+54]), "+f"(d[OFF+55]),
      "+f"(d[OFF+56]), "+f"(d[OFF+57]), "+f"(d[OFF+58]), "+f"(d[OFF+59]), "+f"(d[OFF+60]), "+f"(d[OFF+61]), "+f"(d[OFF+62]), "+f"(d[OFF+63]),
      "+f"(d[OFF+64]), "+f"(d[OFF+65]), "+f"(d[OFF+66]), "+f"(d[OFF+67]), "+f"(d[OFF+68]), "+f"(d[OFF+69]), "+f"(d[OFF+70]), "+f"(d[OFF+71]),
      "+f"(d[OFF+72]), "+f"(d[OFF+73]), "+f"(d[OFF+74]), "+f"(d[OFF+75]), "+f"(d[OFF+76]), "+f"(d[OFF+77]), "+f"(d[OFF+78]), "+f"(d[OFF+79]),
      "+f"(d[OFF+80]), "+f"(d[OFF+81]), "+f"(d[OFF+82]), "+f"(d[OFF+83]), "+f"(d[OFF+84]), "+f"(d[OFF+85]), "+f"(d[OFF+86]), "+f"(d[OFF+87]),
      "+f"(d[OFF+88]), "+f"(d[OFF+89]), "+f"(d[OFF+90]), "+f"(d[OFF+91]), "+f"(d[OFF+92]), "+f"(d[OFF+93]), "+f"(d[OFF+94]), "+f"(d[OFF+95])
    : "l"(da), "l"(db), "r"(scale_d), "n"(TA), "n"(TB));
}
template<int TA, int TB, int OFF, int SZ> __device__ __forceinline__ void wgmma_n128_ss(float (&d)[SZ], uint64_t da, uint64_t db, int scale_d) {
  asm volatile("{\n.reg .pred p;\nsetp.ne.b32 p, %66, 0;\n"
    "wgmma.mma_async.sync.aligned.m64n128k16.f32.bf16.bf16 {%0,%1,%2,%3,%4,%5,%6,%7,%8,%9,%10,%11,%12,%13,%14,%15,%16,%17,%18,%19,%20,%21,%22,%23,%24,%25,%26,%27,%28,%29,%30,%31,%32,%33,%34,%35,%36,%37,%38,%39,%40,%41,%42,%43,%44,%45,%46,%47,%48,%49,%50,%51,%52,%53,%54,%55,%56,%57,%58,%59,%60,%61,%62,%63}, %64, %65, p, 1, 1, %67, %68;\n}\n"
    : "+f"(d[OFF+0]), "+f"(d[OFF+1]), "+f"(d[OFF+2]), "+f"(d[OFF+3]), "+f"(d[OFF+4]), "+f"(d[OFF+5]), "+f"(d[OFF+6]), "+f"(d[OFF+7]),
      "+f"(d[OFF+8]), "+f"(d[OFF+9]), "+f"(d[OFF+10]), "+f"(d[OFF+11]), "+f"(d[OFF+12]), "+f"(d[OFF+13]), "+f"(d[OFF+14]), "+f"(d[OFF+15]),
      "+f"(d[OFF+16]), "+f"(d[OFF+17]), "+f"(d[OFF+18]), "+f"(d[OFF+19]), "+f"(d[OFF+20]), "+f"(d[OFF+21]), "+f"(d[OFF+22]), "+f"(d[OFF+23]),
      "+f"(d[OFF+24]), "+f"(d[OFF+25]), "+f"(d[OFF+26]), "+f"(d[OFF+27]), "+f"(d[OFF+28]), "+f"(d[OFF+29]), "+f"(d[OFF+30]), "+f"(d[OFF+31]),
      "+f"(d[OFF+32]), "+f"(d[OFF+33]), "+f"(d[OFF+34]), "+f"(d[OFF+35]), "+f"(d[OFF+36]), "+f"(d[OFF+37]), "+f"(d[OFF+38]), "+f"(d[OFF+39]),
      "+f"(d[OFF+40]), "+f"(d[OFF+41]), "+f"(d[OFF+42]), "+f"(d[OFF+43]), "+f"(d[OFF+44]), "+f"(d[OFF+45]), "+f"(d[OFF+46]), "+f"(d[OFF+47]),
      "+f"(d[OFF+48]), "+f"(d[OFF+49]), "+f"(d[OFF+50]), "+f"(d[OFF+51]), "+f"(d[OFF+52]), "+f"(d[OFF+53]), "+f"(d[OFF+54]), "+f"(d[OFF+55]),
      "+f"(d[OFF+56]), "+f"(d[OFF+57]), "+f"(d[OFF+58]), "+f"(d[OFF+59]), "+f"(d[OFF+60]), "+f"(d[OFF+61]), "+f"(d[OFF+62]), "+f"(d[OFF+63])
    : "l"(da), "l"(db), "r"(scale_d), "n"(TA), "n"(TB));
}
template<int TA, int TB, int OFF, int SZ> __device__ __forceinline__ void wgmma_n64_ss(float (&d)[SZ], uint64_t da, uint64_t db, int scale_d) {
  asm volatile("{\n.reg .pred p;\nsetp.ne.b32 p, %34, 0;\n"
    "wgmma.mma_async.sync.aligned.m64n64k16.f32.bf16.bf16 {%0,%1,%2,%3,%4,%5,%6,%7,%8,%9,%10,%11,%12,%13,%14,%15,%16,%17,%18,%19,%20,%21,%22,%23,%24,%25,%26,%27,%28,%29,%30,%31}, %32, %33, p, 1, 1, %35, %36;\n}\n"
    : "+f"(d[OFF+0]), "+f"(d[OFF+1]), "+f"(d[OFF+2]), "+f"(d[OFF+3]), "+f"(d[OFF+4]), "+f"(d[OFF+5]), "+f"(d[OFF+6]), "+f"(d[OFF+7]),
      "+f"(d[OFF+8]), "+f"(d[OFF+9]), "+f"(d[OFF+10]), "+f"(d[OFF+11]), "+f"(d[OFF+12]), "+f"(d[OFF+13]), "+f"(d[OFF+14]), "+f"(d[OFF+15]),
      "+f"(d[OFF+16]), "+f"(d[OFF+17]), "+f"(d[OFF+18]), "+f"(d[OFF+19]), "+f"(d[OFF+20]), "+f"(d[OFF+21]), "+f"(d[OFF+22]), "+f"(d[OFF+23]),
      "+f"(d[OFF+24]), "+f"(d[OFF+25]), "+f"(d[OFF+26]), "+f"(d[OFF+27]), "+f"(d[OFF+28]), "+f"(d[OFF+29]), "+f"(d[OFF+30]), "+f"(d[OFF+31])
    : "l"(da), "l"(db), "r"(scale_d), "n"(TA), "n"(TB));
}
template<int TA, int TB, int OFF, int SZ> __device__ __forceinline__ void wgmma_n72_ss(float (&d)[SZ], uint64_t da, uint64_t db, int scale_d) {
  asm volatile("{\n.reg .pred p;\nsetp.ne.b32 p, %38, 0;\n"
    "wgmma.mma_async.sync.aligned.m64n72k16.f32.bf16.bf16 {%0,%1,%2,%3,%4,%5,%6,%7,%8,%9,%10,%11,%12,%13,%14,%15,%16,%17,%18,%19,%20,%21,%22,%23,%24,%25,%26,%27,%28,%29,%30,%31,%32,%33,%34,%35}, %36, %37, p, 1, 1, %39, %40;\n}\n"
    : "+f"(d[OFF+0]), "+f"(d[OFF+1]), "+f"(d[OFF+2]), "+f"(d[OFF+3]), "+f"(d[OFF+4]), "+f"(d[OFF+5]), "+f"(d[OFF+6]), "+f"(d[OFF+7]),
      "+f"(d[OFF+8]), "+f"(d[OFF+9]), "+f"(d[OFF+10]), "+f"(d[OFF+11]), "+f"(d[OFF+12]), "+f"(d[OFF+13]), "+f"(d[OFF+14]), "+f"(d[OFF+15]),
      "+f"(d[OFF+16]), "+f"(d[OFF+17]), "+f"(d[OFF+18]), "+f"(d[OFF+19]), "+f"(d[OFF+20]), "+f"(d[OFF+21]), "+f"(d[OFF+22]), "+f"(d[OFF+23]),
      "+f"(d[OFF+24]), "+f"(d[OFF+25]), "+f"(d[OFF+26]), "+f"(d[OFF+27]), "+f"(d[OFF+28]), "+f"(d[OFF+29]), "+f"(d[OFF+30]), "+f"(d[OFF+31]),
      "+f"(d[OFF+32]), "+f"(d[OFF+33]), "+f"(d[OFF+34]), "+f"(d[OFF+35])
    : "l"(da), "l"(db), "r"(scale_d), "n"(TA), "n"(TB));
}
template<int TB, int OFF, int SZ> __device__ __forceinline__ void wgmma_n64_rs(float (&d)[SZ], uint32_t a0, uint32_t a1, uint32_t a2, uint32_t a3, uint64_t db, int scale_d) {
  asm volatile("{\n.reg .pred p;\nsetp.ne.b32 p, %37, 0;\n"
    "wgmma.mma_async.sync.aligned.m64n64k16.f32.bf16.bf16 {%0,%1,%2,%3,%4,%5,%6,%7,%8,%9,%10,%11,%12,%13,%14,%15,%16,%17,%18,%19,%20,%21,%22,%23,%24,%25,%26,%27,%28,%29,%30,%31}, {%32,%33,%34,%35}, %36, p, 1, 1, %38;\n}\n"
    : "+f"(d[OFF+0]), "+f"(d[OFF+1]), "+f"(d[OFF+2]), "+f"(d[OFF+3]), "+f"(d[OFF+4]), "+f"(d[OFF+5]), "+f"(d[OFF+6]), "+f"(d[OFF+7]),
      "+f"(d[OFF+8]), "+f"(d[OFF+9]), "+f"(d[OFF+10]), "+f"(d[OFF+11]), "+f"(d[OFF+12]), "+f"(d[OFF+13]), "+f"(d[OFF+14]), "+f"(d[OFF+15]),
      "+f"(d[OFF+16]), "+f"(d[OFF+17]), "+f"(d[OFF+18]), "+f"(d[OFF+19]), "+f"(d[OFF+20]), "+f"(d[OFF+21]), "+f"(d[OFF+22]), "+f"(d[OFF+23]),
      "+f"(d[OFF+24]), "+f"(d[OFF+25]), "+f"(d[OFF+26]), "+f"(d[OFF+27]), "+f"(d[OFF+28]), "+f"(d[OFF+29]), "+f"(d[OFF+30]), "+f"(d[OFF+31])
    : "r"(a0), "r"(a1), "r"(a2), "r"(a3), "l"(db), "r"(scale_d), "n"(TB));
}
template<int TB, int OFF, int SZ> __device__ __forceinline__ void wgmma_n40_rs(float (&d)[SZ], uint32_t a0, uint32_t a1, uint32_t a2, uint32_t a3, uint64_t db, int scale_d) {
  asm volatile("{\n.reg .pred p;\nsetp.ne.b32 p, %25, 0;\n"
    "wgmma.mma_async.sync.aligned.m64n40k16.f32.bf16.bf16 {%0,%1,%2,%3,%4,%5,%6,%7,%8,%9,%10,%11,%12,%13,%14,%15,%16,%17,%18,%19}, {%20,%21,%22,%23}, %24, p, 1, 1, %26;\n}\n"
    : "+f"(d[OFF+0]), "+f"(d[OFF+1]), "+f"(d[OFF+2]), "+f"(d[OFF+3]), "+f"(d[OFF+4]), "+f"(d[OFF+5]), "+f"(d[OFF+6]), "+f"(d[OFF+7]),
      "+f"(d[OFF+8]), "+f"(d[OFF+9]), "+f"(d[OFF+10]), "+f"(d[OFF+11]), "+f"(d[OFF+12]), "+f"(d[OFF+13]), "+f"(d[OFF+14]), "+f"(d[OFF+15]),
      "+f"(d[OFF+16]), "+f"(d[OFF+17]), "+f"(d[OFF+18]), "+f"(d[OFF+19])
    : "r"(a0), "r"(a1), "r"(a2), "r"(a3), "l"(db), "r"(scale_d), "n"(TB));
}
template<int TB, int OFF, int SZ> __device__ __forceinline__ void wgmma_n128_rs(float (&d)[SZ], uint32_t a0, uint32_t a1, uint32_t a2, uint32_t a3, uint64_t db, int scale_d) {
  asm volatile("{\n.reg .pred p;\nsetp.ne.b32 p, %69, 0;\n"
    "wgmma.mma_async.sync.aligned.m64n128k16.f32.bf16.bf16 {%0,%1,%2,%3,%4,%5,%6,%7,%8,%9,%10,%11,%12,%13,%14,%15,%16,%17,%18,%19,%20,%21,%22,%23,%24,%25,%26,%27,%28,%29,%30,%31,%32,%33,%34,%35,%36,%37,%38,%39,%40,%41,%42,%43,%44,%45,%46,%47,%48,%49,%50,%51,%52,%53,%54,%55,%56,%57,%58,%59,%60,%61,%62,%63}, {%64,%65,%66,%67}, %68, p, 1, 1, %70;\n}\n"
    : "+f"(d[OFF+0]), "+f"(d[OFF+1]), "+f"(d[OFF+2]), "+f"(d[OFF+3]), "+f"(d[OFF+4]), "+f"(d[OFF+5]), "+f"(d[OFF+6]), "+f"(d[OFF+7]),
      "+f"(d[OFF+8]), "+f"(d[OFF+9]), "+f"(d[OFF+10]), "+f"(d[OFF+11]), "+f"(d[OFF+12]), "+f"(d[OFF+13]), "+f"(d[OFF+14]), "+f"(d[OFF+15]),
      "+f"(d[OFF+16]), "+f"(d[OFF+17]), "+f"(d[OFF+18]), "+f"(d[OFF+19]), "+f"(d[OFF+20]), "+f"(d[OFF+21]), "+f"(d[OFF+22]), "+f"(d[OFF+23]),
      "+f"(d[OFF+24]), "+f"(d[OFF+25]), "+f"(d[OFF+26]), "+f"(d[OFF+27]), "+f"(d[OFF+28]), "+f"(d[OFF+29]), "+f"(d[OFF+30]), "+f"(d[OFF+31]),
      "+f"(d[OFF+32]), "+f"(d[OFF+33]), "+f"(d[OFF+34]), "+f"(d[OFF+35]), "+f"(d[OFF+36]), "+f"(d[OFF+37]), "+f"(d[OFF+38]), "+f"(d[OFF+39]),
      "+f"(d[OFF+40]), "+f"(d[OFF+41]), "+f"(d[OFF+42]), "+f"(d[OFF+43]), "+f"(d[OFF+44]), "+f"(d[OFF+45]), "+f"(d[OFF+46]), "+f"(d[OFF+47]),
      "+f"(d[OFF+48]), "+f"(d[OFF+49]), "+f"(d[OFF+50]), "+f"(d[OFF+51]), "+f"(d[OFF+52]), "+f"(d[OFF+53]), "+f"(d[OFF+54]), "+f"(d[OFF+55]),
      "+f"(d[OFF+56]), "+f"(d[OFF+57]), "+f"(d[OFF+58]), "+f"(d[OFF+59]), "+f"(d[OFF+60]), "+f"(d[OFF+61]), "+f"(d[OFF+62]), "+f"(d[OFF+63])
    : "r"(a0), "r"(a1), "r"(a2), "r"(a3), "l"(db), "r"(scale_d), "n"(TB));
}

struct Ptrs { const __nv_bfloat16 *x, *wqkv, *wo, *wr, *wg, *wu, *wd; __nv_bfloat16* out; Scratch* s; };

enum { M_X, M_W, M_Q, M_O, M_S, M_G, M_U, M_D, M_L, M_N };
struct Maps { CUtensorMap m[M_N]; };

__global__ void __cluster_dims__(2, 1, 1) __launch_bounds__(384, 1) fused_kernel(const Ptrs P, const __grid_constant__ Maps T) {
  extern __shared__ __align__(1024) uint8_t smem_raw[];
  TS_DECL; TS(0); TSG(30);
  if (threadIdx.x == 320) SPANS(0);
  const uint32_t rank = blockIdx.x & 1, own = rank << 24;
  const uint32_t sm = own + sb, mb = own + bars;
  int b0;
  { const int j = blockIdx.x >> 1, u = j - 36, v = j * 2 - 8 + (max(u * 37 + 256, 0) >> 8) * (u < 0 ? 0 : 2), w = j < 4 ? j * 16 + 64 : v;
    b0 = ((w & 15) | (w & 48) << 1 | (w & 64) >> 2) + rank; }
#define IDS(B) \
  const int b = (B), rb = b >> 4, cg = b & 15, hf = cg >> 3, s3 = cg & 7, c3 = s3 ^ ((rb & 1) << 2), jp = cg >> 1, km = (~c3 & 6) << 1; \
  const int fidx = jp == rb ? -1 : b - 2 * rb - (jp > rb ? 2 : 0); \
  auto kcol = [&](int kb) { return (kb ^ (kb < 8 ? km & 8 : km)) * 64; }; \
  auto src_of = [&](int p) { return p == 0 ? s3 : p == 15 ? s3 ^ 1 : (((jp & 3) ^ ((p - 7) >> 1)) << 1) + ((p - 1) & 1); }; \
  auto frag_of = [&](int p) { return p < 9 ? (p - 1) * 512 : 4096 + src_of(p) * 512; }; \
  (void)hf; (void)fidx; (void)kcol; (void)frag_of
  auto get_b = [&]() { return __shfl_sync(~0u, (int)lds1(mb + B_ID), 0); };
  IDS(b0);
  auto load_w = [&](uint32_t st, int kc, uint32_t bar, bool last) { tma_3d(st + 32768, &T.m[M_W], cg * 64, kc, 1, bar, last); tma_2d(st + 49152, &T.m[M_Q], cg * 64, kc, bar, last); };
  RTS_DECL;
  if (threadIdx.x < 32 && elect_one()) {
    mbar_init(mb + B_FULL, 1);
    asm volatile("fence.mbarrier_init.release.cluster;" ::: "memory");
    mbar_expect_tx(mb + B_FULL, STAGE_B);
    load_w(sm, kcol(0), mb + B_FULL, false);
    tma_2d(sm + 16384, &T.m[M_X], kcol(0), rb * 256 + 128, mb + B_FULL, false);
    tma_2d(sm, &T.m[M_X], kcol(0), rb * 256, mb + B_FULL, false);
  }
  TS(15);
  const int tid = threadIdx.x, wid = __shfl_sync(~0u, tid >> 5, 0), wg = wid >> 2, lane = lane_id();
  const uint32_t tk = clock64();
  if (wid < 4) {
    const int i = tid - 64;
    if (SPF && tid >= 32 && tid < 112)
      l2_prefetch(i < 0 ? P.x + (rb * 256 + (hf * 4 + (cg & 3)) * 32 + lane) * D_ + kcol(0) : P.wqkv + (kcol(0) + (rb >> 1) * 16 + (i & 15)) * 3072 + (i >> 4) * 1024 + cg * 64);
  } else if (wid == 9) {
    if (elect_one()) {
#pragma unroll
      for (int i = 1; i < 31; i++) if (8 * i != B_ID) mbar_init(mb + 8 * i, i < 4 ? 1 : i < 8 ? 8 : i < 16 ? 16 : i == 16 ? 64 : i == 17 ? 8 : i == 18 ? 4 : 1);
      asm volatile("fence.mbarrier_init.release.cluster;" ::: "memory");
      fence_async_smem();
    }
  } else if (wid == 11) {
#pragma unroll
    for (int i = 0; i < 4; i++) sts4(sm + OFF_STATS + i * 512 + lane * 16, SENT, SENT, SENT, SENT);
    sts1(mb + B_ID, b);
    if (smem_u32(smem_raw) != sm) asm volatile("trap;");
    fence_async_smem();
  }
  __syncthreads();
  asm volatile("barrier.cluster.arrive.relaxed.aligned;\nbarrier.cluster.wait.aligned;" ::: "memory");

  if (wg == 2) {
    asm volatile("setmaxnreg.dec.sync.aligned.u32 56;");
    if (wid == 8) {
      if (elect_one()) {
#pragma unroll 1
        for (int kb = 1; kb < 15; kb++) {
          const uint32_t fb = mb + B_FULL + 8 * (kb & 3), st = sm + (kb & 3) * STAGE_B;
          const int kc = kcol(kb);
          if (kb < 4) while ((uint32_t)clock64() - tk < FD0 + kb * FD1) {}
          else mbar_wait(fb + B_EMPTY, ((kb >> 2) & 1) ^ 1);
          mbar_expect_tx(fb, STAGE_B);
          tma_2d_mc(st + rank * 16384, &T.m[M_X], kc, rb * 256 + rank * 128, fb, kb >= EFXK);
          load_w(st, kc, fb, EFW && kb >= EFWK);
          if (kb >= 8 && kb < 11) asm volatile("mbarrier.arrive.shared::cta.b64 _, [%0], %1;" :: "r"(fb + B_EMPTY), "r"(4) : "memory");
        }
        {
          const uint32_t st = sm + 3 * STAGE_B, fa = mb + B_FULL + 24, fb = mb + B_F15;
          const int kc = kcol(15);
          mbar_wait(fa, 0);
          mbar_expect_tx(fa, 32768); mbar_expect_tx(fb, 24576);
          if (rank) { mbar_wait(mb + B_EMPTY + 24, 0); tma_2d_mc(st + 16384, &T.m[M_X], kc, rb * 256 + 128, fa, EFXK < 16); }
          mbar_wait(mb + B_EMPTY, 1);
          tma_3d(st + 32768, &T.m[M_W], cg * 64, kc, 1, fa, EFW);
          if (!rank) { mbar_wait(mb + B_EMPTY + 24, 0); tma_2d_mc(st, &T.m[M_X], kc, rb * 256, fb, EFXK < 16); }
          tma_2d(st + 49152, &T.m[M_Q], cg * 64, kc, fb, EFW);
        }
        mbar_expect_tx(mb + B_KVP, 32768 + 2048);
      }
      __syncwarp();
      const uint4* kp = &P.s->kvp[cg * 8 * 256], *zq = &P.s->zp[cg * 8 * 16], *src = &P.s->obuf[(rb * 4 + rank * 2 + hf) * 64 * 128];
      asm volatile("" : "+l"(kp), "+l"(zq), "+l"(src));
      mbar_wait(mb + B_EVA, 0);
      meet(&P.s->when[cg * 32 + rb], (const uint4*)&P.s->when[cg * 32] + (lane & 1), MFIRST, MKV, mb + B_EVB);
      if (elect_one()) {
        bulk_load(sm + rank * (2 * STAGE_B) + STAGE_B, kp, 32768, mb + B_KVP);
        bulk_load(sm + rank * (2 * STAGE_B) + UNIT, zq, 2048, mb + B_KVP);
      }
      RTS(1);
      mbar_wait(mb + B_KVP, 0);
      RTS(2);
      meet(&P.s->when[(16 + rb * 2 + hf) * 32 + s3], (const uint4*)&P.s->when[(16 + (MWIDE == 2 ? lane >> 1 : (MWIDE ? (lane & 6) + (rb & 1) : rb) * 2 + (hf ^ 1))) * 32] + (lane & 1), MFIRST, MO, mb + B_E);
      RTS(3);
      if (elect_one()) {
        const uint32_t t0 = clock64();
        mbar_arrive(mb + B_F15);
        RTS(4);
#pragma unroll
        for (int p = 2; p < 5; p++) {
          if (p < 4) while ((uint32_t)clock64() - t0 < (p == 2 ? ADELAY : ADELAY2)) {}
          bulk_load_mc(sm + ring_of(p, rank), src + (p - 1) * 512, UNIT, mb + B_BF + 8 * p);
        }
#pragma unroll 1
        for (int p = 5; p < 15; p++) {
          uint32_t dst = sm + ring_of(p, rank), bar = mb + B_BF + 8 * (p % 7);
          const uint4* q = src + frag_of(p);
          asm volatile("" : "+r"(dst), "+r"(bar), "+l"(q));
          mbar_wait(mb + B_E + 8 * ((p - 4) & 7), p >= 12);
          bulk_load_mc(dst, q, UNIT, bar);
        }
        asm volatile("mbarrier.arrive.shared::cta.b64 _, [%0], 8;" :: "r"(mb + B_GATE) : "memory");
        const uint4* s15 = &P.s->obuf[(rb * 4 + hf) * 64 * 128 + frag_of(15)];
        RTS_DUMP;
        mbar_wait(mb + B_E + 24, 1);
        bulk_load(sm + ring_of(15, 0), s15, UNIT, mb + B_BF + 8); bulk_load(sm + ring_of(15, 1), s15 + 2 * 64 * 128, UNIT, mb + B_BF + 8);
      }
    } else if (wid == 11) {
      IDS(get_b());
      if (fidx >= 0) {
        const uint32_t o = (rank * 32 + lane) * (F_ * 2) + (fidx >> 1) * 128;
        const char* q0 = (const char*)P.wg + o, *q1 = (const char*)P.wu + o;
        mbar_wait(mb + B_FULL + 24, 0);
        mbar_wait(mb + B_FULL + 8 * (PULL0 & 3), PULL0 >> 2);
#pragma unroll 1
        for (int r = 0; r < 16; r++, q0 += 64 * F_ * 2, q1 += 64 * F_ * 2) {
          if (mbar_test(mb + B_HOLD, 0)) { l2_prefetch(q0); l2_prefetch(q1); continue; }
          asm volatile("cp.async.ca.shared.global.L2::128B [%0], [%1], 4;\ncp.async.commit_group;\ncp.async.wait_group %3;\n"
                       "cp.async.ca.shared.global.L2::128B [%0], [%2], 4;\ncp.async.commit_group;\ncp.async.wait_group %3;" :: "r"(mb + B_DUMMY), "l"(q0), "l"(q1), "n"(PDEPTH) : "memory");
          if (lane == 0) g_dbgv(3, r + 1);
        }
        mbar_wait(mb + B_F15, 0);
        bar_sync(15, 288);
        if (lane == 0) PTS(1);
        q0 = (const char*)P.wd + fidx * 65536 + lane * 128;
        const uint32_t bar = mb + B_BF + 48;
        if (lane == 0) mbar_expect_tx(bar, 8192);
#pragma unroll 1
        for (int i = 0; i < 16 + PLAG; i++) {
          if (i < 16) l2_prefetch(q0 + i * 4096);
          if (i >= PLAG && elect_one()) tma_2d(sm + OFF_COLSUM, &T.m[M_L], 0, fidx * 512 + (i - PLAG) * 32, bar, false);
          const uint32_t t1 = clock64();
          while ((uint32_t)clock64() - t1 < PSTEP) {}
        }
        mbar_wait(bar, 0);
        __syncwarp();
        if (lane == 0) { mbar_arrive(bar); PTS(4); }
        asm volatile("cp.async.wait_all;" ::: "memory");
      } else bar_arrive(15, 288);
      bar_arrive(14, 64);
    } else {
      const uint32_t eb = (lane << 24) + bars + B_EMPTY;
      float c[6];
      if (wid == 10) {
        float sx[4] = {0.f, 0.f, 0.f, 0.f}, qx[4] = {0.f, 0.f, 0.f, 0.f};
        const uint32_t xa = sm + ((hf * 4 + (cg & 3)) * 32 + lane) * 128 + ((lane & 7) << 4);
#pragma unroll 1
        for (int kb = 0; kb < 8; kb++) {
          uint4 xv[8];
          const uint32_t so = xa + (kb & 3) * STAGE_B;
          mbar_wait(mb + B_FULL + 8 * (kb & 3), kb >> 2);
#pragma unroll
          for (int i = 0; i < 8; i++) xv[i] = lds4(so ^ (i << 4));
#pragma unroll
          for (int i = 0; i < 8; i++) {
            const uint32_t e[4] = {xv[i].x, xv[i].y, xv[i].z, xv[i].w};
#pragma unroll
            for (int j = 0; j < 4; j++) {
              const float d0 = bf_lo(e[j]), d1 = bf_hi(e[j]);
              sx[j] += d0 + d1; qx[j] = fmaf(d0, d0, fmaf(d1, d1, qx[j]));
            }
          }
          __syncwarp();
          if (lane < 2) mbar_arrive_rem(eb + 8 * (kb & 3));
          if (kb == RST2) {
        {
          const uint32_t ep = ld_rlx(&P.s->epoch);
          float s = 0.f;
#pragma unroll
          for (int i = 0; i < 4; i++) {
            const uint4 v = ld_cg4((const uint4*)P.wr + lane + i * 32);
            s += (bf_lo(v.x) + bf_hi(v.x)) + (bf_lo(v.y) + bf_hi(v.y)) + (bf_lo(v.z) + bf_hi(v.z)) + (bf_lo(v.w) + bf_hi(v.w));
          }
#pragma unroll
          for (int o = 16; o; o >>= 1) s += __shfl_xor_sync(~0u, s, o);
          if (lane == 0) sts1(mb + B_SW, (__float_as_uint(s) & ~255u) | ((ep + 1) & 255));
        }
        asm volatile("cp.async.bulk.wait_group 0;\nfence.proxy.async.global;" ::: "memory");
        fence_gpu();
        if (lane == 0) PTS(0);
          }
          if (kb == RST) {
        if (elect_one()) {
#pragma unroll 1
          for (int i = 0; i < 16; i++) bulk_store(&P.s->obuf[((rb * 4 + (i >> 2)) * 64 + (((i >> 2) & 1) == hf ? 32 + s3 * 4 + (i & 3) : (i & 3) * 8 + s3)) * 128], sm + OFF_STATS, 2048);
          bulk_store(&P.s->kvp[(cg * 8 + rb) * 256], sm + OFF_STATS, 2048); bulk_store(&P.s->kvp[(cg * 8 + rb) * 256 + 128], sm + OFF_STATS, 2048);
          bulk_store(&P.s->zp[(cg * 8 + rb) * 16], sm + OFF_STATS, 256);
          if (s3 == 0) bulk_store(&P.s->when[(16 + rb * 2 + hf) * 32], sm + OFF_STATS, 128);
          if (rb == 0) bulk_store(&P.s->when[cg * 32], sm + OFF_STATS, 128);
          asm volatile("cp.async.bulk.commit_group;" ::: "memory");
          #pragma unroll
          for (int i = M_O; i < M_N; i++) tmap_prefetch(&T.m[i]);
        }
        __syncwarp();
          }
        }
        c[0] = ((sx[0] + sx[1]) + (sx[2] + sx[3])) * (2.f / D_);
        c[1] = fmaxf(fmaf(-c[0], c[0], ((qx[0] + qx[1]) + (qx[2] + qx[3])) * (2.f / D_)), 0.f);
      } else {
        float a[12];
#pragma unroll
        for (int i = 0; i < 12; i++) a[i] = 0.f;
        const int r2 = lane >> 4, c16 = lane & 15;
        const uint32_t a0 = sm + 32768 + (rb >> 1) * 2048 + r2 * 128 + (((c16 >> 1) ^ r2) << 4) + (c16 & 1) * 8;
#pragma unroll 1
        for (int it = 0; it < 16; it++) {
          uint2 w[12];
          const int s = (it >> 1) & 3;
          const uint32_t so = a0 + s * STAGE_B + (it & 1) * 1024;
          if (!(it & 1)) { mbar_wait(mb + B_FULL + 8 * s, it >> 3); TSD(8 + (it >> 1)); }
          static_for<0, 12>([&](auto ic) { constexpr int i = decltype(ic)::value;
            const float2 v = lds2f_o<(i >> 2) * 8192 + (i & 3) * 256>(so ^ ((i & 3) << 5)); w[i] = make_uint2(__float_as_uint(v.x), __float_as_uint(v.y)); });
#pragma unroll
          for (int i = 0; i < 12; i++) { float* q = a + (i >> 2) * 4; q[0] += bf_lo(w[i].x); q[1] += bf_hi(w[i].x); q[2] += bf_lo(w[i].y); q[3] += bf_hi(w[i].y); }
          __syncwarp();
          if (lane < 2 && (it & 1)) mbar_arrive_rem(eb + 8 * s);
        }
#pragma unroll
        for (int i = 0; i < 6; i++) {
          const int o = (i >> 1) * 4 + (i & 1);
          c[i] = (r2 ? a[o + 2] : a[o]) + __shfl_xor_sync(~0u, r2 ? a[o] : a[o + 2], 16);
        }
      }
      TS(5);
      bar_sync(10, 64);
      TS(6);
      {
        const uint32_t tag = lds1(mb + B_SW) & 255;
        auto tagged = [&](float v) { return ((__float_as_uint(v) + 128) & ~255u) | tag; };
        if (wid == 9) {
#pragma unroll
          for (int sg = 0; sg < 3; sg++) {
            st_rlx2((uint2*)&P.s->csp[(cg * 8 + rb) * 48] + sg * 32 + (lane & 15) * 2 + (lane >> 4), tagged(c[sg * 2]), tagged(c[sg * 2 + 1]));
          }
        } else st_rlx2((uint2*)&P.s->st1[(rb * 8 + hf * 4 + (cg & 3)) * 48 + lane] + ((cg >> 2) & 1), tagged(c[0]), tagged(c[1]));
        { const uint32_t t0 = clock64(); while ((uint32_t)clock64() - t0 < GDELAY) {} }
#pragma unroll 1
        for (int h = wid - 9; h < 2; h++) {
          const int q = h * 24 + min(lane, 23);
          const uint4* gp = wid == 10 ? &P.s->st1[rb * 8 * 48 + lane] : &P.s->csp[cg * 8 * 48 + q];
          uint4 v[8];
#pragma unroll 1
          for (int it = 0;; it++) {
            uint32_t x = 0;
#pragma unroll
            for (int i = 0; i < 8; i++) v[i] = ld_rlx4(gp + i * 48);
#pragma unroll
            for (int i = 0; i < 8; i++) { v[i].x ^= tag; v[i].y ^= tag; v[i].z ^= tag; v[i].w ^= tag; x |= v[i].x | v[i].y | v[i].z | v[i].w; }
            if (!__any_sync(~0u, (x & 255) != 0)) break;
            SPINCHK(it, 3);
          }
          if (wid == 10) {
#pragma unroll
            for (int i = 0; i < 8; i++) {
              const float m0 = __uint_as_float(v[i].x), m1 = __uint_as_float(v[i].z), dm = 0.5f * (m0 - m1);
              sts2f(sm + OFF_STATS + (i * 32 + lane) * 8, -0.5f * (m0 + m1), rsq(fmaf(dm, dm, 0.5f * (__uint_as_float(v[i].y) + __uint_as_float(v[i].w))) + 1e-5f));
            }
          } else {
            float s4[4] = {0.f, 0.f, 0.f, 0.f};
#pragma unroll
            for (int i = 0; i < 8; i++) { s4[0] += __uint_as_float(v[i].x); s4[1] += __uint_as_float(v[i].y); s4[2] += __uint_as_float(v[i].z); s4[3] += __uint_as_float(v[i].w); }
            sts4(sm + OFF_COLSUM + q * 16, __float_as_uint(s4[0]), __float_as_uint(s4[1]), __float_as_uint(s4[2]), __float_as_uint(s4[3]));
          }
        }
        mbar_arrive(mb + B_AUX);
      }
      TS(2);
      IDS(get_b());
      const uint64_t btab = rank ? BT1 : BT0;
      if (wid == 9) {
        {
          const uint4 sv = make_uint4(SENT, SENT, SENT, SENT);
          uint4* y = &P.s->ybuf[b * NFFN * 2 + lane];
#pragma unroll
          for (int i = 0; i < 7; i++) y[i * 32] = sv;
          if (lane < 16) P.s->st2[b * 16 + lane] = make_uint4(0, 0, 0, 0); else P.s->hsel[b * 16 + lane - 16] = sv;
          if (b < 8) P.s->cand[b * 32 + lane] = SENT;
          fence_gpu();
          __syncwarp();
          if (lane == 0) mbar_arrive(mb + B_LATE);
        }
        TS(3);
        TS_DUMP(2);
        {
          const int p = lane & 15, sl = p % 7;
          const bool sliced = p > 0 && p < 9;
          const uint32_t c = sliced ? ((p - 1) >> 1) * 16 | ((hf ^ 1) * 8 + ((p - 1) & 1) * 4) << 8 | 128 << 16 : (hf * 8 + src_of(p)) << 8;
          const uint32_t ev = mb + (p < BHOLD ? B_EVA : p < 4 ? B_KVP : p < 6 ? B45 : B_E + 8 * ((p < 7 ? 1 : p - 4) & 7) + (p >= 12));
          mbar_wait(mb + B_EVA, 0);
          sts4(sm + OFF_COLSUM + 512 + p * 16, sm + unit_of(btab, sl), mb + B_BF + 8 * sl, c, ev);
          __syncwarp();
        }
        if (elect_one()) {
#pragma unroll 1
          for (int p = 0; p < 16; p++) {
            const uint4 e = lds4(sm + OFF_COLSUM + 512 + p * 16);
            if (p == 4) mbar_wait(mb + B_WR, 0);
            mbar_wait(e.w & ~1u, e.w & 1);
            mbar_expect_tx(e.y, p > 1 ? 4 * UNIT : 2 * UNIT);
            tma_4d(e.x, (const CUtensorMap*)((const char*)&T.m[M_O] + (e.z >> 16)), 0, e.z & 255, (e.z >> 8) & 255, c3 * 2, e.y, p >= EFB);
          }
          PTS(16);
        }
      } else {
        const uint2 w = ld_rlx2((const uint2*)(P.wr + c3 * 128) + lane);
#pragma unroll 1
        for (int i = 0; i < 4; i++) { l2_prefetch((const char*)P.wo + b * 16384 + i * 4096 + lane * 128); __nanosleep(300); }
        const int p = lane & 15, p2 = min(p + 2, 15);
        const uint32_t t0 = dlo(sb, 8192) + (unit_of(btab, p % 7) >> 4), t1 = ring_of(p + 1, lane >> 4), t2 = mb + B_BF + 8 * (p2 % 7);
        mbar_wait(mb + B_EVB, 0);
        bar_sync(14, 64);
        sts4(sm + OFF_COLSUM + lane * 16, w.x << 16, w.x & 0xFFFF0000u, w.y << 16, w.y & 0xFFFF0000u);
        sts4(sm + OFF_STATS + lane * 16, t0, t1, t2, (p2 / 7) & 1);
        __syncwarp();
        if (elect_one()) {
          mbar_arrive(mb + B_WR);
          if (fidx >= 0) {
            mbar_expect_tx(mb + B_FFN, 131072); mbar_expect_tx(mb + B_FFD, 32768);
            uint64_t gt = rank ? GT1 : GT0;
#pragma unroll 1
            for (int f = 0; f < 8; f++, gt >>= 5) {
              uint32_t d0 = sm + unit_of(gt, 0);
              asm volatile("" : "+r"(d0));
              if (f == 3) mbar_wait(mb + B_GATE, 1);
              mbar_wait(mb + (f < FEARLY ? B_KVB : B_E + (f < 3 ? 3 + 2 * f : (f + 5) >> 1) * 8), f < FEARLY || f >= 3);
              tma_3d(d0, &T.m[M_G], fidx * 32, f * 128, 0, mb + B_FFN, EFF);
              tma_3d(d0 + UNIT, &T.m[M_U], fidx * 32, f * 128, 0, mb + B_FFN, EFF);
            }
            PTS(17);
            mbar_expect_tx(mb + B_KVP, 32768);
#pragma unroll
            for (int w = 0; w < 8; w++) {
              if (w == 2) mbar_wait(mb + B_E + 56, 1);
              if (w == 6) mbar_wait(mb + B_E16, 1);
              if (w == DLATE) mbar_wait(mb + B_EVA, 1);
              tma_3d(sm + ((DT0 >> (5 * w)) & 31) * UNIT + (w < 4 ? 0 : w < 6 ? 14 * UNIT : -14 * UNIT) * rank, &T.m[M_D], 0, fidx * 32, 2 * w, mb + (w < 4 ? B_FFD : B_KVP), EFF);
            }
            PTS(18);
          }
        }
      }
    }
    __syncwarp();
    IDS(get_b());
    mbar_wait(mb + B_EVB, 0);
    mbar_wait(mb + B_OUT, 0);
    const float2 cf = lds2f(sm + OFF_STATS + 64);
    const int cand0 = 2047 - (__float_as_int(cf.x) & 2047), cand1 = 2047 - (__float_as_int(cf.y) & 2047), rr = lane >> 4;
    auto store_rows = [&](int tr, bool on) {
      const uint4 v = lds4(sm + 4 * UNIT + (tr >> 6) * STAGE_B + (tr & 63) * 256 + (((lane & 15) ^ (tr & 7)) << 4));
      const float2 pr = lds2f(sm + OFF_LNP + tr * 8);
      const float f = 1.f + pr.x, n = pr.y;
      if (on) st_out(P.out + (size_t)(rb * 256 + hf * 64 + tr + (tr & 64)) * D_ + c3 * 128 + (lane & 15) * 8,
          make_uint4(pack2(fmaf(bf_lo(v.x), f, n), fmaf(bf_hi(v.x), f, n)), pack2(fmaf(bf_lo(v.y), f, n), fmaf(bf_hi(v.y), f, n)),
                     pack2(fmaf(bf_lo(v.z), f, n), fmaf(bf_hi(v.z), f, n)), pack2(fmaf(bf_lo(v.w), f, n), fmaf(bf_hi(v.w), f, n))));
    };
    if (wid == 8) {
      mbar_wait(mb + B_SEL, 0);
      const float2 sel = lds2f(sm + OFF_STATS + 80);
      const uint32_t kc = __float_as_uint(rr ? cf.y : cf.x);
      const int c = rr ? cand1 : cand0;
      store_rows(((c >> 1) & 64) + (c & 63), kc != __float_as_uint(sel.x) && kc != __float_as_uint(sel.y) && (c >> 8) == rb && ((c >> 6) & 1) == hf);
    } else if (wid < 9 + NOUTW) {
      if (ODELAY) { const uint32_t t0 = clock64(); while ((uint32_t)clock64() - t0 < ODELAY) {} }
#pragma unroll OUNR
      for (int tr = (wid - 9) * 2 + rr; tr < 128; tr += 2 * NOUTW) {
        const int row = rb * 256 + hf * 64 + tr + (tr & 64);
        store_rows(tr, row != cand0 && row != cand1 && !NOOUT);
      }
      if (wid == 9 && lane == 0) { PTS(14); SPANS(2); }
    }
  } else {
    asm volatile("setmaxnreg.inc.sync.aligned.u32 224;");
    const int t128 = tid & 127, warp = wid & 3, g = lane >> 2, t = lane & 3;
    const uint32_t sk = rank * (2 * STAGE_B);
    uint4 ost[2][4];
    uint4 abuf[3][4];
    uint4* od1;
    const uint4* ain;
    int b1;
    const uint32_t eb = (lane << 24) + bars + B_E;
    float acc[64], wf[32];
    {
      float acc1[96], acc0[96];
#pragma unroll
      for (int i = 0; i < 96; i++) { acc0[i] = 0.f; acc1[i] = 0.f; }
      const uint32_t xo0 = dlo(sb, 16) + (wg * 2 + hf) * 512, xo1 = dlo(sb, 16) + (wg * 2 + (hf ^ 1)) * 512;
      constexpr uint32_t ST = STAGE_B >> 4, WD = dlo(sb + 49152, 8192), WV = dlo(sb + 32768, 8192);
      const uint32_t eb0 = (t128 << 24) + bars + B_EMPTY;
#pragma unroll 1
      for (int kb = 0; kb < 12; kb++) {
        const int s = kb & 3;
        mbar_wait(mb + B_FULL + 8 * s, (kb >> 2) & 1);
        if (kb == 0) TS(1);
        if (kb == 0 && !wg) bar_sync(2, 256);
        pin(acc0); pin(acc1);
        wg_fence();
#pragma unroll
        for (int k = 0; k < 4; k++) {
          const uint64_t db = dsc<1024, 1>(WV + s * ST + k * 128);
          wgmma_n192_ss<0, 1, 0>(acc0, dsc<1024, 1>(s * ST + xo0 + k * 2), db, 1);
          wgmma_n192_ss<0, 1, 0>(acc1, dsc<1024, 1>(s * ST + xo1 + k * 2), db, 1);
        }
        wg_commit();
        if (kb == 0 && wg) bar_arrive(2, 256);
        wg_wait<0>();
        pin(acc0); pin(acc1);
        if (t128 < 2 && kb < 11) mbar_arrive_rem(eb0 + 8 * s);
      }
      mbar_wait(mb + B_FULL, 1);
      if (t128 < 8) mbar_arrive_rem(t128 < 4 ? (wg << 24) + bars + B_EMPTY + 24 : mb + B_EMPTY);
      TS(2);
      mbar_wait(mb + B_AUX, 0);
      float rs[2][2], nm[2][2];
#pragma unroll
      for (int m = 0; m < 2; m++)
#pragma unroll
        for (int h = 0; h < 2; h++) { const float2 v = lds2f(sm + OFF_STATS + ((wg * 2 + (m ^ hf)) * 64 + warp * 16 + h * 8 + g) * 8); nm[m][h] = v.x; rs[m][h] = v.y; }
      auto center = [&](auto jc) {
        constexpr int j = decltype(jc)::value;
        const float2 cs = lds2f_o<sb + OFF_COLSUM + j * 32>(own + t * 8);
        acc1[j * 4] = fmaf(nm[1][0], cs.x, acc1[j * 4]); acc1[j * 4 + 1] = fmaf(nm[1][0], cs.y, acc1[j * 4 + 1]);
        acc1[j * 4 + 2] = fmaf(nm[1][1], cs.x, acc1[j * 4 + 2]); acc1[j * 4 + 3] = fmaf(nm[1][1], cs.y, acc1[j * 4 + 3]);
        acc0[j * 4] = fmaf(nm[0][0], cs.x, acc0[j * 4]); acc0[j * 4 + 1] = fmaf(nm[0][0], cs.y, acc0[j * 4 + 1]);
        acc0[j * 4 + 2] = fmaf(nm[0][1], cs.x, acc0[j * 4 + 2]); acc0[j * 4 + 3] = fmaf(nm[0][1], cs.y, acc0[j * 4 + 3]);
      };
      static_for<0, 16>(center);
      const float L2E = 1.4426950408889634f;
      uint32_t fa = sm + sk + (warp * 16 + (lane & 15)) * 128 + (((lane >> 4) ^ (lane & 7)) << 4);
      asm volatile("" : "+r"(fa));
      uint32_t xf0[32], xf1[32];
      auto pack_kv = [&](float (&a)[96], int i, float r0, float r1, uint32_t* o, uint32_t z = 0) {
        const float* p = a + i * 8;
        if (i < 4) {
          const float rl0 = __uint_as_float(__float_as_uint(r0 * L2E) | z), rl1 = __uint_as_float(__float_as_uint(r1 * L2E) | z);
          const uint32_t q0 = pack2(r0, r0), q1 = pack2(r1, r1);
          o[0] = phi2(p[0], p[1], rl0, q0); o[1] = phi2(p[2], p[3], rl1, q1); o[2] = phi2(p[4], p[5], rl0, q0); o[3] = phi2(p[6], p[7], rl1, q1);
        } else {
          r0 = __uint_as_float(__float_as_uint(r0) | z); r1 = __uint_as_float(__float_as_uint(r1) | z);
          o[0] = pack2(p[0] * r0, p[1] * r0); o[1] = pack2(p[2] * r1, p[3] * r1); o[2] = pack2(p[4] * r0, p[5] * r0); o[3] = pack2(p[6] * r1, p[7] * r1); }
      };
      auto swap_kv = [&](uint32_t (&xf)[32], uint32_t tile, int i, const uint32_t* o, uint32_t z = 0) {
        const uint32_t ad = (fa + tile * UNIT) ^ ((i & 3) << 5);
        if (i < 4) { ldsm4_o<0>(ad, xf[i * 4], xf[i * 4 + 1], xf[i * 4 + 2], xf[i * 4 + 3]); stsm4_o<0>(ad, o[0], o[1], o[2], o[3]); }
        else { ldsm4_o<STAGE_B>(ad | z, xf[i * 4], xf[i * 4 + 1], xf[i * 4 + 2], xf[i * 4 + 3]); stsm4_o<STAGE_B>(ad, o[0], o[1], o[2], o[3]); }
      };
      auto mma_q = [&](float (&a)[96], uint32_t (&xf)[32], uint32_t xo, bool ss) {
        const uint32_t r = __shfl_sync(~0u, sk >> 4, 0), o = 2 * ST - r;
#pragma unroll
        for (int j = 0; j < 8; j++) {
          if (ss) wgmma_n64_ss<0, 1, 64>(a, dsc<1024, 1>(o + (j >> 2) * ST + xo + (j & 3) * 2), dsc<1024, 1>(WD + o + (j >> 2) * ST + (j & 3) * 128), 1);
          else wgmma_n64_rs<1, 64>(a, xf[j * 4], xf[j * 4 + 1], xf[j * 4 + 2], xf[j * 4 + 3], dsc<1024, 1>(WD + r + (j >> 2) * ST + (j & 3) * 128), 1);
        }
      };
      auto epi_q = [&](float (&a)[96], float r0, float r1, uint32_t (&o)[16]) {
        const float rl0 = r0 * 1.44269511f, rl1 = r1 * 1.44269511f;
        const uint32_t q0 = dup2(r0), q1 = dup2(r1);
#pragma unroll
        for (int j = 0; j < 8; j++) { o[j * 2] = phi2(a[64 + j * 4], a[65 + j * 4], rl0, q0); o[j * 2 + 1] = phi2(a[66 + j * 4], a[67 + j * 4], rl1, q1); }
        pinu(o);
      };
      auto mma_kv1 = [&](float (&a)[96], uint32_t xo, int s) {
#pragma unroll
        for (int k = 0; k < 4; k++) wgmma_n128_ss<0, 1, 0>(a, dsc<1024, 1>(s * ST + xo + k * 2), dsc<1024, 1>(WV + s * ST + k * 128), 1);
      };
      auto epi_kv = [&](float (&a)[96], uint32_t (&xf)[32], uint32_t tile, float r0, float r1) {
        uint32_t o[8][4];
#pragma unroll
        for (int j = 3; j >= 0; j--) {
          const uint32_t z = j < 3 ? (xf[(j + 5) * 4] | (j < 2 ? o[j + 2][0] | o[j + 6][0] : 0)) & blockIdx.y : 0;
          pack_kv(a, j + 4, r0, r1, o[j + 4], z);
          swap_kv(xf, tile, j + 4, o[j + 4], (o[j + 4][2] | o[j + 4][3]) & blockIdx.y);
          pack_kv(a, j, r0, r1, o[j], z);
          swap_kv(xf, tile, j, o[j]);
        }
      };
      bar_arrive(15, 288);
      mbar_wait(mb + B_FULL + 8, 1);
      if (!wg) bar_sync(3, 256);
      pinr<0, 64>(acc0); pinr<0, 64>(acc1);
      wg_fence();
      mma_kv1(acc1, xo1, 0); mma_kv1(acc0, xo0, 0); mma_kv1(acc1, xo1, 1);
      if (GSPLIT == 2) mma_kv1(acc0, xo0, 1);
      mbar_wait(mb + B_FULL + 16, 1);
      wg_fence();
      mma_kv1(acc1, xo1, 2);
      mbar_wait(mb + (wg ? B_FULL + 24 : B_F15), wg);
      wg_fence();
      mma_kv1(acc1, xo1, 3);
      wg_commit();
      bar_arrive(4 - wg, 256);
      static_for<16, 24>(center);
      pinr<64, 96>(acc0); pinr<64, 96>(acc1);
      mbar_wait(mb + B_FULL + 8, 1);
      wg_wait<0>();
      pinr<0, 64>(acc0); pinr<0, 64>(acc1);
      epi_kv(acc1, xf1, wg * 2 + (hf ^ 1), rs[1][0], rs[1][1]);
      pinu(xf1);
      bar_sync(5 - wg, 256);
      wg_fence();
      if (GSPLIT == 1) mma_kv1(acc0, xo0, 1);
      mma_kv1(acc0, xo0, 2); mma_kv1(acc0, xo0, 3);
      wg_commit();
      mma_q(acc1, xf1, xo1, false);
      wg_commit();
      if (wg) bar_arrive(5, 256);
      else { fence_async_smem(); bar_arrive(6, 256); }
      if (tid >= 240) sts4(sm + OFF_STATS + (tid & 15) * 128 + ((tid & 7) << 4), 0x3F803F80u, 0x3F803F80u, 0x3F803F80u, 0x3F803F80u);
      wg_wait<1>();
      pinr<0, 64>(acc0);
      if (lane == 0) mbar_arrive(mb + B_EVA);
      TS(6);
      epi_kv(acc0, xf0, wg * 2 + hf, rs[0][0], rs[0][1]);
      fence_async_smem();
      pinu(xf0);
      if (!wg) bar_arrive(7, 256);
      const uint32_t kvb = 2 * STAGE_B + (2 + (hf ^ 1)) * UNIT - sk;
      b1 = get_b();
      od1 = &P.s->obuf[(((b1 >> 4) * 4 + wg * 2 + (hf ^ 1)) * 64 + (b1 & 7)) * 128 + t128];
      ain = &P.s->obuf[((b1 >> 4) * 4 + wg * 2 + hf) * 64 * 128 + t128];
      uint32_t ka0 = sm + kvb + wid * 1024 + (lane & 7) * 128 + (((lane >> 3) ^ (lane & 7)) << 4), ka1 = sm + kvb + wid * 1024 + (t * 2 + g) * 128 + ((4 ^ (t * 2 + g)) << 4);
      const uint8_t* g0 = smem_raw + sk + STAGE_B + tid * 16, *g1 = smem_raw + sk + UNIT + g * 256 + wid * 32 + t * 8;
      const uint8_t* h0 = (const uint8_t*)&P.s->kvp[(b1 & 15) * 8 * 256 + tid], *h1 = (const uint8_t*)&P.s->zp[((b1 & 15) * 8 + g) * 16] + wid * 32 + t * 8;
      asm volatile("" : "+r"(ka0), "+r"(ka1), "+l"(g0), "+l"(g1), "+l"(h0), "+l"(h1), "+l"(od1));
      if (wg) {
        float ka[36];
        auto mma_kv = [&](uint32_t tile, int i, int acc) {
          const uint32_t o = (sk >> 4) + tile * 512 + i * 128;
          wgmma_n72_ss<1, 1, 0>(ka, dsc<1024, 1>(dlo(sb, 8192) + o), dsc<1024, 1>(dlo(sb + STAGE_B, OFF_STATS - STAGE_B) + o * (1u - (1u << 16))), acc);
        };
#pragma unroll
        for (int i = 0; i < 36; i++) ka[i] = 0.f;
        bar_sync(6, 256);
        wg_fence();
#pragma unroll
        for (int i = 0; i < 4; i++) {
          mma_kv(2, i, i); mma_kv(3, i, 1); mma_kv(hf ^ 1, i, 1);
#pragma unroll
          for (int j = 2 * i; j < 2 * i + 2; j++)
            wgmma_n64_rs<1, 64>(acc0, xf0[j * 4], xf0[j * 4 + 1], xf0[j * 4 + 2], xf0[j * 4 + 3], dsc<1024, 1>(WD + (sk >> 4) + (j >> 2) * ST + (j & 3) * 128), 1);
        }
        const int kq = (b1 & 15) * 8 + (b1 >> 4);
        uint4* dst = &P.s->kvp[kq * 256 + warp * 64 + lane];
        uint32_t* dz = (uint32_t*)&P.s->zp[kq * 16] + warp * 16 + g + t * 8;
        asm volatile("" : "+l"(dst), "+l"(dz));
        mbar_wait(mb + B_LATE, 0);
        bar_sync(7, 256);
        wg_fence();
#pragma unroll
        for (int i = 0; i < 4; i++) mma_kv(hf, i, 1);
        wg_commit();
        bar_arrive(8, 256);
        wg_wait<0>();
        pin(ka); pinr<64, 96>(acc0);
        uint32_t kw[8];
#pragma unroll
        for (int i = 0; i < 8; i++) {
          const int j = (i & 3) * 4 + (i >> 2) * 2;
          asm("{\n.reg .pred p;\nsetp.ne.u32 p, %5, 0;\n@p cvt.rn.bf16x2.f32 %0, %4, %3;\n@!p cvt.rn.bf16x2.f32 %0, %2, %1;\n}"
              : "=r"(kw[i]) : "f"(ka[j]), "f"(ka[j + 1]), "f"(ka[16 + j]), "f"(ka[17 + j]), "r"(warp & 2));
        }
        st_rlx4(dst, make_uint4(kw[0], kw[1], kw[2], kw[3]));
        st_rlx4(dst + 32, make_uint4(kw[4], kw[5], kw[6], kw[7]));
        if (t < 2) st_rlx(dz, __float_as_uint(t ? ka[34] : ka[32]));
        if (lane == 0) mbar_arrive(mb + B_EVB);
        TS(8);
        const uint32_t t1 = clock64();
        while ((uint32_t)clock64() - t1 < SDELAY) {}
      } else {
        bar_sync(8, 256);
        wg_fence();
        mma_q(acc0, xf0, xo0, false);
      }
      if (!wg) bar_sync(9, 256);
      wg_fence();
      mma_q(acc1, xf1, xo1, true);
      wg_commit();
      if (wg) bar_arrive(9, 256); else mma_q(acc0, xf0, xo0, true);
      wg_commit();
      wg_wait<1>();
      pinr<64, 96>(acc1);
      TS(7);
      uint32_t pq[16];
      epi_q(acc1, rs[1][0], rs[1][1], pq);
      bar_sync(11 + wg + zero_after(pq), 128);
      if (wg) {
        wg_fence();
        mma_q(acc0, xf0, xo0, true);
        wg_commit();
      }
      TS(5);
      {
        uint4 gv[8]; uint2 gz;
        uint32_t m[8], a[4];
        float z0, z1;
#pragma unroll
        for (int s = 0; s < 8; s++) { m[s] = ~blockIdx.y; asm volatile("" : "=r"(gv[s].x), "=r"(gv[s].y), "=r"(gv[s].z), "=r"(gv[s].w), "+r"(m[s])); }
        mbar_wait(mb + B_KVP, 0);
        TS(28);
#pragma unroll 1
        for (int it = 0; it < SPIN_LIMIT; it++) {
          gz = ld_gen2(g1);
#pragma unroll
          for (int s = 0; s < 8; s++) if (m[s] == SENT) gv[s] = ld_gen4(g0 + s * 4096);
          g0 = h0; g1 = h1;
          uint32_t mm = max(gz.x, gz.y);
          z0 = __uint_as_float(gz.x); z1 = __uint_as_float(gz.y);
#pragma unroll
          for (int o = 4; o < 32; o <<= 1) { z0 += __shfl_xor_sync(~0u, z0, o); z1 += __shfl_xor_sync(~0u, z1, o); }
#pragma unroll
          for (int s = 0; s < 8; s++) m[s] = max4(0, gv[s]);
#pragma unroll
          for (int s = 0; s < 8; s += 2) mm = __vimax3_u32(mm, m[s], m[s + 1]);
          a[0] = hadd2(hadd2(hadd2(gv[0].x, gv[1].x), hadd2(gv[2].x, gv[3].x)), hadd2(hadd2(gv[4].x, gv[5].x), hadd2(gv[6].x, gv[7].x)));
          a[1] = hadd2(hadd2(hadd2(gv[0].y, gv[1].y), hadd2(gv[2].y, gv[3].y)), hadd2(hadd2(gv[4].y, gv[5].y), hadd2(gv[6].y, gv[7].y)));
          a[2] = hadd2(hadd2(hadd2(gv[0].z, gv[1].z), hadd2(gv[2].z, gv[3].z)), hadd2(hadd2(gv[4].z, gv[5].z), hadd2(gv[6].z, gv[7].z)));
          a[3] = hadd2(hadd2(hadd2(gv[0].w, gv[1].w), hadd2(gv[2].w, gv[3].w)), hadd2(hadd2(gv[4].w, gv[5].w), hadd2(gv[6].w, gv[7].w)));
          pinu(a);
          if (!__any_sync(~0u, mm == SENT)) break;
          TSV(20, 1);
        }
        TS(23);
        wg_wait<0>();
        pinr<64, 96>(acc0);
        if (lane == 0) mbar_arrive(mb + B_KVB);
        stsm4(ka0, a[0], a[1], a[2], a[3]);
        const uint32_t zz = pack2(g ? z1 : z0, g ? z1 : z0);
        if (lane < 8) sts4(ka1, zz, zz, zz, zz);
        fence_async_smem();
        bar_sync(1, 256);
      }
      TS(21);
      auto make_o = [&](uint4 (&o)[4], auto first) {
        float oa[2][20];
        wg_fence();
#pragma unroll
        for (int ks = 0; ks < 4; ks++)
          wgmma_n40_rs<1, 0>(oa[ks >> 1], pq[ks * 4], pq[ks * 4 + 1], pq[ks * 4 + 2], pq[ks * 4 + 3], dsc<1024, 1>(dlo(sb, 8192) + (kvb >> 4) + ks * 128), ks & 1);
        wg_commit();
        if constexpr (!decltype(first)::value) {
          pinu(xf0);
#pragma unroll
          for (int q = 0; q < 32; q++) { acc[q * 2] = bf_lo(xf0[q]); acc[q * 2 + 1] = bf_hi(xf0[q]); }
          pin(acc);
          if (!R1MID) {
            mbar_wait(mb + B_F15, 1);
#pragma unroll
            for (int i = 0; i < 4; i++) abuf[1][i] = ld_rlx4(ain + i * 128);
            TS(3);
          }
          mbar_wait(mb + B_BF, 0);
        }
        wg_wait<0>();
        pin(oa[0]); pin(oa[1]);
        if (decltype(first)::value && lane < 2) mbar_arrive_rem(eb);
#pragma unroll
        for (int h = 0; h < 2; h++) {
          const float (&d)[20] = oa[h];
          const float i0 = rcp(d[16] + 1e-6f), i1 = rcp(d[18] + 1e-6f);
#pragma unroll
          for (int k2 = 0; k2 < 2; k2++) {
            o[h * 2 + k2] = make_uint4(pack2(d[k2 * 8] * i0, d[k2 * 8 + 1] * i0), pack2(d[k2 * 8 + 2] * i1, d[k2 * 8 + 3] * i1),
                                       pack2(d[k2 * 8 + 4] * i0, d[k2 * 8 + 5] * i0), pack2(d[k2 * 8 + 6] * i1, d[k2 * 8 + 7] * i1));
            if (decltype(first)::value && !h && k2 <= AFIRST) st_rlx4(od1 + k2 * 1024, o[k2]);
            if (decltype(first)::value && !h && k2 == AFIRST) { sched_fence(); TS(24); }
          }
        }
      };
      make_o(ost[1], std::true_type{});
      if (!AFIRST) { st_rlx4(od1 + 1024 + ((ost[1][2].x | ost[1][3].w) & blockIdx.y), ost[1][1]); sched_fence(); }
      auto read1 = [&](uint32_t z) {
        mbar_wait(mb + B_F15 + z, 1);
#pragma unroll
        for (int i = 0; i < 4; i++) abuf[1][i] = ld_rlx4(ain + i * 128);
        TS(3);
      };
      if (R1MID) {
        const float rl0 = rs[0][0] * 1.44269511f, rl1 = rs[0][1] * 1.44269511f;
        const uint32_t q0 = dup2(rs[0][0]), q1 = dup2(rs[0][1]);
        uint32_t z = 0;
#pragma unroll
        for (int j = 0; j < 8; j++) {
          pq[j * 2] = phi2(acc0[64 + j * 4], acc0[65 + j * 4], rl0, q0); pq[j * 2 + 1] = phi2(acc0[66 + j * 4], acc0[67 + j * 4], rl1, q1);
          if (j < R1MID) z |= pq[j * 2] | pq[j * 2 + 1];
          if (j == R1MID - 1) read1(z & 0x80008000u);
        }
      } else epi_q(acc0, rs[0][0], rs[0][1], pq);
      if (AEARLY == 1) { st_rlx4(od1 + 2048, ost[1][2]); st_rlx4(od1 + 3072, ost[1][3]); }
      make_o(ost[0], std::false_type{});
    }
   {
    IDS(b1);
    const int mb3 = rb * 4 + wg * 2 + hf;
    const int row0 = mb3 * 64 + warp * 16 + g;
    {
      uint4* const od0 = &P.s->obuf[(mb3 * 64 + 32 + s3 * 4) * 128 + t128];
#pragma unroll
      for (int i = 0; i < 4; i++) pin4(ost[0][i]);
      wg_fence();
#pragma unroll
      for (int k = 0; k < 4; k++) wgmma_n128_rs<1, 0>(acc, ost[0][k].x, ost[0][k].y, ost[0][k].z, ost[0][k].w, dsc<1024, 1>(dlo(sb + 4 * UNIT, 8192) + k * 128), 1);
      wg_commit();
      TS(29);
      if (AEARLY == 0) { st_rlx4(od1 + 2048, ost[1][2]); st_rlx4(od1 + 3072, ost[1][3]); }
      if (AEARLY == 2) st_rlx4(od1 + 2048, ost[1][2]);
      uint32_t la = sm + t128 * 16, ev = eb + 8;
      asm volatile("" : "+r"(la), "+r"(ev));
      auto fetch = [&](uint32_t off, uint4 (&a)[4]) { const uint32_t ra = la + off; a[0] = lds4_o<0>(ra); a[1] = lds4_o<2048>(ra); a[2] = lds4_o<4096>(ra); a[3] = lds4_o<6144>(ra); };
      auto check = [&](int p, uint4 (&a)[4]) {
        if (__any_sync(~0u, max(max4(max4(0, a[0]), a[1]), max4(max4(0, a[2]), a[3])) == SENT)) {
          int pl = p; asm volatile("" : "+r"(pl));
          const uint4* q = ain + frag_of(pl);
#pragma unroll 1
          for (int it = 0;; it++) {
            uint32_t mm = 0;
#pragma unroll
            for (int i = 0; i < 4; i++) { const uint32_t m = max4(0, a[i]); mm = max(mm, m); if (m == SENT) a[i] = ld_rlx4(q + i * 128); }
            if (!__any_sync(~0u, mm == SENT)) break;
            TSV(27, p < 3 ? 1 : p < 5 ? 100 : 10000);
            SPINCHK(it, 5);
          }
        }
        if (lane < 2) mbar_arrive_rem(ev);
        ev = (ev & ~0x38u) | ((ev + 8) & 0x38u);
      };
      auto mma = [&](int p, uint32_t bs, uint4 (&a)[4]) {
#pragma unroll
        for (int i = 0; i < 4; i++) pin4(a[i]);
        wg_fence();
#pragma unroll
        for (int k = 0; k < 4; k++) wgmma_n128_rs<1, 0>(acc, a[k].x, a[k].y, a[k].z, a[k].w, dsc<1024, 1>(bs + k * 128), 1);
        wg_commit();
      };
      uint32_t ta = sm + OFF_STATS + wg * 256 + 48;
      mbar_wait(mb + B_WR, 0);
      uint4 tp = lds4(ta);
      mbar_wait(mb + B_BF + 8, 0);
      check(1, abuf[1]);
      if (P1F) { mbar_wait(mb + B_BF + 16, 0); fetch(ring_of(2, wg), abuf[2]); }
      mma(1, dlo(sb + 11 * UNIT, 8192), abuf[1]);
      if (!P1F) { mbar_wait(mb + B_BF + 16, 0); fetch(ring_of(2, wg), abuf[2]); }
      TS(25);
      if (AEARLY == 2) st_rlx4(od1 + 3072, ost[1][3]);
      st_rlx4(od0, ost[0][0]); st_rlx4(od0 + 128, ost[0][1]);
      check(2, abuf[2]);
      mbar_wait(mb + B_BF + 24, 0);
      fetch(ring_of(3, wg), abuf[0]);
      mma(2, dlo(sb + 18 * UNIT, 8192), abuf[2]);
      st_rlx4(od0 + 256, ost[0][2]); st_rlx4(od0 + 384, ost[0][3]);
      wg_wait<2>();
      check(3, abuf[0]);
      mbar_wait(mb + B_BF + 32, 0);
      TS(26);
#pragma unroll 1
      for (int p = 3; p < 15; p += 3) {
        static_for<0, 3>([&](auto jc) {
          constexpr int j = decltype(jc)::value;
          const uint4 tc = tp;
          const uint32_t bs = __shfl_sync(~0u, tc.x, 0);
          wg_wait<1>();
#pragma unroll
          for (int i = 0; i < 4; i++) pin4(abuf[(j + 1) % 3][i]);
          tp = lds4_o<16 * j + 16>(ta);
          fetch(tc.y, abuf[(j + 1) % 3]);
          mma(p + j, bs, abuf[j]);
          if (!CHKF) mbar_wait(tc.z, tc.w);
          check(p + j + 1, abuf[(j + 1) % 3]);
          if (CHKF) mbar_wait(tc.z, tc.w);
        });
        ta += 48;
      }
      mma(15, __shfl_sync(~0u, tp.x, 0), abuf[0]);
      wg_wait<2>();
      if (lane == 0) mbar_arrive(mb + B_E16);
      static_for<0, 16>([&](auto jc) { constexpr int j = decltype(jc)::value; const float2 v = lds2f_o<sb + OFF_COLSUM + j * 32>(own + t * 8); wf[j * 2] = v.x; wf[j * 2 + 1] = v.y; });
      pin(wf);
      wg_wait<0>();
      pin(acc);
#pragma unroll
      for (int i = 0; i < 4; i++) { pin4(abuf[0][i]); pin4(abuf[1][i]); pin4(abuf[2][i]); }
    }
    TS(10);
    {
      float s0 = 0.f, q0 = 0.f, e0 = 0.f, s1 = 0.f, q1 = 0.f, e1 = 0.f;
#pragma unroll
      for (int j = 0; j < 16; j++) {
        const float a = acc[j * 4], c = acc[j * 4 + 1], d = acc[j * 4 + 2], e = acc[j * 4 + 3];
        s0 += a + c; q0 = fmaf(a, a, fmaf(c, c, q0)); e0 = fmaf(a, wf[j * 2], fmaf(c, wf[j * 2 + 1], e0));
        s1 += d + e; q1 = fmaf(d, d, fmaf(e, e, q1)); e1 = fmaf(d, wf[j * 2], fmaf(e, wf[j * 2 + 1], e1));
      }
      const bool od = t & 1;
      float s = (od ? s1 : s0) + __shfl_xor_sync(~0u, od ? s0 : s1, 1);
      float q = (od ? q1 : q0) + __shfl_xor_sync(~0u, od ? q0 : q1, 1);
      float e = (od ? e1 : e0) + __shfl_xor_sync(~0u, od ? e0 : e1, 1);
      s += __shfl_xor_sync(~0u, s, 2); q += __shfl_xor_sync(~0u, q, 2); e += __shfl_xor_sync(~0u, e, 2);
      if (t < 2) red4(&P.s->st2[row0 + t * 8], s, q, e, 1.f);
    }
    TS(11);
    const uint32_t ts = clock64();
    const uint32_t msc = sm + OFF_STATS;
    const uint32_t hst = sm + 4 * UNIT + wg * STAGE_B + warp * 4096, gslot = sm + unit_of(rank ? GT1 : GT0, wid);
    bar_sync(1, 256);
#pragma unroll
    for (int j = 0; j < 8; j++)
      stsm4(hst + (lane & 15) * 256 + (((2 * j + (lane >> 4)) ^ (lane & 7)) << 4), pack2(acc[j * 8], acc[j * 8 + 1]), pack2(acc[j * 8 + 2], acc[j * 8 + 3]),
            pack2(acc[j * 8 + 4], acc[j * 8 + 5]), pack2(acc[j * 8 + 6], acc[j * 8 + 7]));
    uint32_t wa[8][4][4], wd[8][2][4];
    const uint32_t a0 = gslot + ((lane >> 4) * 8 + (lane & 7)) * 64 + ((((lane >> 3) & 1) ^ ((lane >> 1) & 3)) << 4);
    auto load_gu = [&](auto ic) { constexpr int i = decltype(ic)::value; ldsm4t_o<(i >> 2) * 1024 + ((i >> 1) & 1) * 8192>(a0 ^ ((i & 1) << 5), wa[i >> 2][i & 3]); };
    uint32_t tx;
    {
      const int row = rb * 256 + tid;
      const uint4* sp = &P.s->st2[row], *sq = &P.s->st2[row ^ 256];
      const float sw = __uint_as_float((lds1(mb + B_SW) & ~255u) | 128);
      uint4 v[2];
      if (fidx >= 0) mbar_wait(mb + B_FFN, 0);
      static_for<0, GU1>(load_gu);
      while ((uint32_t)clock64() - ts < SDEL2) {}
      v[0] = ld_rlx4(sp); v[1] = ld_rlx4(sq);
      static_for<GU1, GU2>(load_gu);
#pragma unroll 1
      for (int it = 0; __any_sync(~0u, min(v[0].w, v[1].w) != 0x41000000u) && it < SPIN_LIMIT; it++) {
        if (v[0].w != 0x41000000u) v[0] = ld_rlx4(sp);
        if (v[1].w != 0x41000000u) v[1] = ld_rlx4(sq);
        TSV(22, 1);
      }
      if (lane == 0) mbar_arrive(mb + B_EVA);
      TS(12);
      uint32_t k[2];
#pragma unroll
      for (int i = 0; i < 2; i++) {
        const float mean = __uint_as_float(v[i].x) * (1.f / D_);
        const float rstd = rsq(fmaxf(fmaf(-mean, mean, __uint_as_float(v[i].y) * (1.f / D_)), 0.f) + 1e-5f);
        const uint32_t u = __float_as_uint(rstd * fmaf(-mean, sw, __uint_as_float(v[i].z)));
        k[i] = min(((u ^ ((uint32_t)((int)u >> 31) | 0x80000000u)) & ~2047u), 0xFFFFF000u) | (2047 - (row ^ (i << 8)));
        if (i == 0 && (warp >> 1) == hf) sts2f(sm + OFF_LNP + (wg * 64 + (tid & 63)) * 8, rstd, -mean * rstd);
      }
      const uint32_t hi = max(k[0], k[1]);
      uint32_t m1 = __reduce_max_sync(~0u, hi), m2 = __reduce_max_sync(~0u, hi == m1 ? min(k[0], k[1]) : hi);
      if (lane == 0) sts2f(msc + wid * 8, __uint_as_float(m1), __uint_as_float(m2));
      bar_sync(1, 256);
      const uint32_t kk = lds1(msc + (lane & 15) * 4);
      m1 = __reduce_max_sync(~0u, kk); m2 = __reduce_max_sync(~0u, kk == m1 ? 0 : kk);
      const int c0 = 2047 - (m1 & 2047), c1 = 2047 - (m2 & 2047);
      if ((c0 >> 4) == mb3 * 4 + warp || (c1 >> 4) == mb3 * 4 + warp) {
        const int ra = (lane & 4) ? c1 : c0, rd = (lane & 16) ? c1 : c0;
        uint32_t h0, h1, h2, h3;
        ldsm4_o<0>(hst + (ra & 15) * 256 + ((((lane & 3) * 4 + (lane >> 3)) ^ (ra & 7)) << 4), h0, h1, h2, h3);
        const float2 pr = lds2f(sm + OFF_LNP + (wid * 16 + (rd & 15)) * 8);
        if ((rd >> 4) == mb3 * 4 + warp) {
          const int slot = (rb & 6) + (lane >> 4);
          uint4* d = &P.s->hsel[c3 * 128 + (g & 3) * 32 + slot * 4 + t];
          st_rlx4(d, make_uint4(pack2(fmaf(bf_lo(h0), pr.x, pr.y), fmaf(bf_hi(h0), pr.x, pr.y)), pack2(fmaf(bf_lo(h1), pr.x, pr.y), fmaf(bf_hi(h1), pr.x, pr.y)),
                                pack2(fmaf(bf_lo(h2), pr.x, pr.y), fmaf(bf_hi(h2), pr.x, pr.y)), pack2(fmaf(bf_lo(h3), pr.x, pr.y), fmaf(bf_hi(h3), pr.x, pr.y))));
          if (!(lane & 15)) st_rlx(&P.s->cand[c3 * 32 + slot], (lane & 16) ? m2 : m1);
          st_rlx4(d + 1024, make_uint4(h0, h1, h2, h3));
        }
      }
      tx = clock64();
      if (tid == 0) { sts2f(msc + 64, __uint_as_float(m1), __uint_as_float(m2)); mbar_arrive(mb + B_OUT); }
    }
    TS(13);
    static_for<GU2, 32>(load_gu);
    const uint32_t dl = sm + (wid & 1) * 4096 + ((lane >> 4) * 8 + (lane & 7)) * 128 + ((((lane >> 3) & 1) ^ (lane & 7)) << 4);
    uint32_t da = dl + unit_of(DT0, wid >> 1), db = dl + unit_of(rank ? DT1 : DT0, 4 + (wid >> 1));
    uint32_t* yp = (uint32_t*)&P.s->ybuf[((wid * 8 + t * 2) * NFFN + fidx) * 2] + g;
    uint32_t k1, k2;
    uint2 key;
    {
      float gu[2][4][4];
      uint4 xb[4];
      uint32_t m[4];
      const uint4* xp = &P.s->hsel[wid * 128 + lane];
      const uint2* kp = (const uint2*)&P.s->cand[wid * 32] + t;
      uint32_t ps = gslot + g * 32;
      asm volatile("" : "+l"(xp), "+l"(kp), "+l"(yp), "+r"(db), "+r"(ps));
      if (fidx >= 0) mbar_wait(mb + B_FFD, 0);
      static_for<0, 8>([&](auto ic) { constexpr int i = decltype(ic)::value; ldsm4t_o<(i & 1) * 2048>(da ^ ((i >> 1) << 5), wd[i >> 1][i & 1]); });
      TS(9);
      while ((uint32_t)clock64() - tx < XDELAY) {}
      key = ld_rlx2(kp);
#pragma unroll
      for (int i = 0; i < 4; i++) xb[i] = ld_rlx4(xp + i * 32);
      if (fidx >= 0) mbar_wait(mb + B_KVP, 1);
#pragma unroll 1
      for (int it = 0; it < SPIN_LIMIT; it++) {
#pragma unroll
        for (int i = 0; i < 4; i++) m[i] = max4(0, xb[i]);
        if (!__any_sync(~0u, __vimax3_u32(__vimax3_u32(max(key.x, key.y), m[0], m[1]), m[2], m[3]) == SENT)) break;
        key = ld_rlx2(kp);
#pragma unroll
        for (int i = 0; i < 4; i++) if (m[i] == SENT) xb[i] = ld_rlx4(xp + i * 32);
        TSV(20, 100);
      }
      TS(14);
      const uint32_t hi = max(key.x, key.y);
      k1 = __reduce_max_sync(~0u, hi); k2 = __reduce_max_sync(~0u, hi == k1 ? min(key.x, key.y) : hi);
#pragma unroll
      for (int i = 0; i < 32; i++) gu[i >> 4][(i >> 2) & 3][i & 3] = 0.f;
#pragma unroll
      for (int ks = 0; ks < 8; ks++) {
#pragma unroll
        for (int i = 0; i < 4; i++) mma16816(gu[ks & 1][i], wa[ks][i], (ks & 1) ? xb[ks >> 1].z : xb[ks >> 1].x, (ks & 1) ? xb[ks >> 1].w : xb[ks >> 1].y);
        if (ks == 1) {
          const uint32_t dd = db | (__float_as_uint(gu[1][3][0]) & blockIdx.y);
          static_for<0, 8>([&](auto ic) { constexpr int i = decltype(ic)::value; ldsm4t_o<(i & 1) * 2048>(dd ^ ((i >> 1) << 5), wd[4 + (i >> 1)][i & 1]); });
        }
      }
#pragma unroll
      for (int c = 0; c < 2; c++) {
        const uint32_t kc = c ? key.y : key.x;
        float o[8];
#pragma unroll
        for (int j = 0; j < 8; j++) o[j] = gu[0][(j >> 2) + (j & 1) * 2][(j & 2) + c] + gu[1][(j >> 2) + (j & 1) * 2][(j & 2) + c];
        asm volatile("{\n.reg .pred p;\nsetp.ge.u32 p, %9, %10;\n@p st.shared.v4.f32 [%0], {%1,%2,%3,%4};\n@p st.shared.v4.f32 [%0+16], {%5,%6,%7,%8};\n}"
                     :: "r"(ps + (kc == k1 ? 0 : 256)), "f"(o[0]), "f"(o[1]), "f"(o[2]), "f"(o[3]), "f"(o[4]), "f"(o[5]), "f"(o[6]), "f"(o[7]), "r"(kc), "r"(k2) : "memory");
      }
    }
    TS(4);
    bar_sync(1, 256);
    {
      float g0 = 0.f, g1 = 0.f, u0 = 0.f, u1 = 0.f;
      static_for<0, 8>([&](auto wc) { constexpr int w = decltype(wc)::value;
        constexpr uint32_t o = sb + ((GT0 >> (5 * w)) & 31) * UNIT;
        const uint32_t ad = own + lane * 8 + (w == 0 || w == 7 ? sk : w < 3 ? -sk : 0);
        const float2 a = lds2f_o<o>(ad), c = lds2f_o<o + 256>(ad);
        g0 += a.x; u0 += a.y; g1 += c.x; u1 += c.y; });
      const uint32_t act = pack2(g0 * rcp(1.f + ex2(-1.4426950408889634f * g0)) * u0, g1 * rcp(1.f + ex2(-1.4426950408889634f * g1)) * u1);
      uint32_t bq[4];
#pragma unroll
      for (int i = 0; i < 4; i++) {
        const uint32_t lo = __shfl_sync(~0u, act, 8 * t + i), hi = __shfl_sync(~0u, act, 8 * t + 4 + i);
        bq[i] = __byte_perm(lo, hi, (g & 1) ? 0x7632 : 0x5410);
      }
      TS(16);
      float ya[8][4];
#pragma unroll
      for (int i = 0; i < 8; i++) { ya[i][0] = 0.f; ya[i][1] = 0.f; ya[i][2] = 0.f; ya[i][3] = 0.f; }
#pragma unroll
      for (int ks = 0; ks < 2; ks++)
#pragma unroll
        for (int i = 0; i < 8; i++) mma16816(ya[i], wd[i][ks], bq[ks * 2], bq[ks * 2 + 1]);
#pragma unroll
      for (int h = 0; h < 2; h++) {
        float o[4];
#pragma unroll
        for (int j = 0; j < 4; j++) o[j] = t == 0 ? ya[h * 4][j] : t == 1 ? ya[h * 4 + 1][j] : t == 2 ? ya[h * 4 + 2][j] : ya[h * 4 + 3][j];
        asm volatile("{\n.reg .pred p;\nsetp.ge.s32 p, %3, 0;\n@p st.relaxed.gpu.global.u32 [%0], %1;\n@p st.relaxed.gpu.global.u32 [%0+%4], %2;\n}"
                     :: "l"(yp + h * (64 * NFFN * 8)), "r"(pack2(o[0], o[1])), "r"(pack2(o[2], o[3])), "r"(fidx), "n"(NFFN * 32) : "memory");
      }
    }
    if (tid == 0) { sts2f(msc + 80, __uint_as_float(k1), __uint_as_float(k2)); mbar_arrive(mb + B_SEL); }
    TS(17);
    const uint32_t ty = clock64();
    if (wid < 7) {
      const uint4* yq = &P.s->ybuf[b * NFFN * 2 + tid];
      const uint32_t ks = (tid & 1) ? k2 : k1, grp = 3 - ((ks >> 9) & 3);
      const int fs = grp * 2 + (__shfl_sync(~0u, key.y, grp) == ks);
      const uint32_t* fq = (const uint32_t*)P.s->hsel + (((b >> 4) * 4 + ((b >> 2) & 3)) * 32 + fs * 4 + ((tid >> 2) & 3)) * 4 + (b & 3);
      float gate = rcp(1.f + ex2(-1.4426950408889634f * __uint_as_float(ks ^ (~(uint32_t)((int)ks >> 31) | 0x80000000u))));
      __nv_bfloat16* op = P.out + (size_t)(2047 - (ks & 2047)) * D_ + b * 8 + (tid >> 1);
      asm volatile("" : "+l"(yq), "+l"(fq), "+l"(op), "+f"(gate));
      while ((uint32_t)clock64() - ty < YDELAY) {}
      uint4 v;
      uint32_t fn = 0, fh = 0;
#pragma unroll 1
      for (int it = 0; it < SPIN_LIMIT; it++) {
        v = ld_rlx4(yq);
        if (wid == 0) { fn = ld_rlx(fq); fh = ld_rlx(fq + 4096); }
        TSV(22, 100);
        if (!__any_sync(~0u, max4(max(fn, fh), v) == SENT)) break;
      }
      const float base = (tid & 2) ? bf_hi(fh) + bf_hi(fn) : bf_lo(fh) + bf_lo(fn);
      TS(18);
      const bool p4 = lane & 16, p3 = lane & 8, p2 = lane & 4;
      const uint32_t w0 = __shfl_xor_sync(~0u, p4 ? v.x : v.z, 16), w1 = __shfl_xor_sync(~0u, p4 ? v.y : v.w, 16), o0 = p4 ? v.z : v.x, o1 = p4 ? v.w : v.y;
      const float y0 = bf_lo(o0) + bf_lo(w0), y1 = bf_hi(o0) + bf_hi(w0), y2 = bf_lo(o1) + bf_lo(w1), y3 = bf_hi(o1) + bf_hi(w1);
      const float z0 = (p3 ? y2 : y0) + __shfl_xor_sync(~0u, p3 ? y0 : y2, 8), z1 = (p3 ? y3 : y1) + __shfl_xor_sync(~0u, p3 ? y1 : y3, 8);
      float z = (p2 ? z1 : z0) + __shfl_xor_sync(~0u, p2 ? z0 : z1, 4);
      z += __shfl_xor_sync(~0u, z, 2);
      const uint32_t yx = msc + 128;
      if (!(lane & 2)) sts1(yx + wid * 64 + ((lane & 1) * 8 + (lane >> 2)) * 4, __float_as_uint(z));
      bar_sync(13, 224);
      if (tid < 16) {
        float y = 0.f;
#pragma unroll
        for (int w = 0; w < 7; w++) y += __uint_as_float(lds1(yx + w * 64 + tid * 4));
        *op = __float2bfloat16(fmaf(y, gate, base));
      }
      if (b == 0 && tid == 32) P.s->epoch = lds1(mb + B_SW) & 255;
    }
    if (tid == 0) SPANS(1);
    TS(19); TSG(31);
    if (warp == 0) TS_DUMP(wg);
   }
  }
}

typedef CUresult (*EncodeFn)(CUtensorMap*, CUtensorMapDataType, cuuint32_t, void*, const cuuint64_t*, const cuuint64_t*, const cuuint32_t*,
                             const cuuint32_t*, CUtensorMapInterleave, CUtensorMapSwizzle, CUtensorMapL2promotion, CUtensorMapFloatOOBfill);
void make_map(EncodeFn enc, CUtensorMap* m, const void* p, int rank, std::initializer_list<cuuint64_t> dims, std::initializer_list<cuuint64_t> str,
              std::initializer_list<cuuint32_t> box, CUtensorMapSwizzle sw) {
  const cuuint32_t es[4] = {1, 1, 1, 1};
  enc(m, CU_TENSOR_MAP_DATA_TYPE_BFLOAT16, rank, const_cast<void*>(p), dims.begin(), str.begin(), box.begin(), es, CU_TENSOR_MAP_INTERLEAVE_NONE, sw,
      CU_TENSOR_MAP_L2_PROMOTION_L2_128B, CU_TENSOR_MAP_FLOAT_OOB_FILL_NONE);
}

}

extern "C" void kernel_launch(void* const* d_in, const int* in_sizes, int n_in, void* d_out, int out_size) {
  (void)in_sizes; (void)n_in; (void)out_size;
  Ptrs P;
  P.x = (const __nv_bfloat16*)d_in[0]; P.wqkv = (const __nv_bfloat16*)d_in[1]; P.wo = (const __nv_bfloat16*)d_in[2];
  P.wr = (const __nv_bfloat16*)d_in[4]; P.wg = (const __nv_bfloat16*)d_in[5]; P.wu = (const __nv_bfloat16*)d_in[6];
  P.wd = (const __nv_bfloat16*)d_in[7]; P.out = (__nv_bfloat16*)d_out;
  cudaGetSymbolAddress((void**)&P.s, g_scratch);
  void* fn = nullptr;
  cudaDriverEntryPointQueryResult q;
  cudaGetDriverEntryPoint("cuTensorMapEncodeTiled", &fn, cudaEnableDefault, &q);
  EncodeFn enc = (EncodeFn)fn;
  Maps T;
  constexpr CUtensorMapSwizzle S128 = CU_TENSOR_MAP_SWIZZLE_128B, S64 = CU_TENSOR_MAP_SWIZZLE_64B;
  make_map(enc, &T.m[M_X], P.x, 2, {D_, S_}, {D_ * 2}, {64, 128}, S128);
  make_map(enc, &T.m[M_W], P.wqkv, 3, {D_, D_, 3}, {3 * D_ * 2, D_ * 2}, {64, 64, 2}, S128);
  make_map(enc, &T.m[M_Q], P.wqkv, 2, {3 * D_, D_}, {3 * D_ * 2}, {64, 64}, S128);
  make_map(enc, &T.m[M_O], P.wo, 4, {64, 64, 16, 16}, {D_ * 2, 64 * D_ * 2, 128}, {64, 64, 1, 2}, S128);
  make_map(enc, &T.m[M_S], P.wo, 4, {64, 64, 16, 16}, {D_ * 2, 64 * D_ * 2, 128}, {64, 16, 4, 2}, S128);
  make_map(enc, &T.m[M_G], P.wg, 3, {F_, D_, 1}, {F_ * 2, F_ * 2 * D_}, {32, 128, 1}, S64);
  make_map(enc, &T.m[M_U], P.wu, 3, {F_, D_, 1}, {F_ * 2, F_ * 2 * D_}, {32, 128, 1}, S64);
  make_map(enc, &T.m[M_D], P.wd, 3, {64, F_, 16}, {D_ * 2, 128}, {64, 32, 2}, S128);
  make_map(enc, &T.m[M_L], P.wd, 2, {64, F_ * 16}, {128}, {8, 32}, CU_TENSOR_MAP_SWIZZLE_NONE);
  cudaFuncSetAttribute(fused_kernel, cudaFuncAttributeMaxDynamicSharedMemorySize, SMEM_BYTES);
  fused_kernel<<<NCTA, 384, SMEM_BYTES>>>(P, T);
}
```

```cpp
#include <cuda_runtime.h>
#include <cuda.h>
#include <cuda_bf16.h>
#include <stdint.h>
#include <type_traits>
#include <initializer_list>

namespace {

constexpr int S_ = 2048, D_ = 1024, F_ = 3584;
constexpr int NCTA = 128, NFFN = 112;
constexpr uint32_t SENT = 0xFFFFFFFFu;
constexpr int SPIN_LIMIT = 1 << 20;

#define ADELAY 200
#define ADELAY2 600
#define PFA 6
#define PF0 8
#define WPF0 8
#define DPER 1200
#define PDEPTH 2
#define PSTART 4000
#define PPER 1700
#define PEARLY 5
#define PLEAD 0
#define RST 1
#define PSUB 2
#define HOLDP 1
#define QHOLD 1
#define NPULL 12
#define CDELAY 0
#define NOUTW 3
#define YDELAY 650
#define EFX 0
#define EFW 1
#define EFF 1
#define KLEAD 13
#define GDELAY 1000
#define NDIR 6
#define PULL0 3
#define FD0 600
#define FD1 800
#define SPF 1
#define MPF 1
#define TLBW 2
#define GORD 0
#define GSPLIT 2
#define EFW0 0
#define EFX0 0
#define EFWK 8
#define PSLEEP 20
#define P3PULL 1
#define RST2 4
#define KDELAY 450
#define AEARLY 0
#define BHOLD 4
#define SDELAY 100
#define FSTAG 150
#define OFL 0
#define CHKF 1
#define BEV 1
#define DLATE 4
#define P3GATE 3
#define ACCSW 0
#define B45 B_E
#define SDEL2 500
#define XDELAY 500
#define GU1 8
#define GU2 20
#define WD1 10
#define ODELAY 0
#define NOOUT 0
constexpr int OUNR =
  2;
#define P3N 2
#define HALFMAP 1
#define KWARP 7
#define FEARLY 1
#define MFIRST 350
#define MKV 900
#define MO 800
#define MST 1450
#define MSTE 13
#define AFIRST 0
#define MWIDE 0
#define PLAG 8
#define PSTEP 0
#define EFA 0
#define EFO 0
#define EFB 0
#define EFXK 12
#define P1F 1
#define R1MID 5
#define PSTOP 3
#define DMASK 0x5550
#define PFST 1
#define W0OFF 2
#define MAPM 2
#define XWPF 0
constexpr uint32_t STAGE_B = 57344;
constexpr uint32_t OFF_STATS = 229376;
constexpr uint32_t OFF_COLSUM = 231424;
constexpr uint32_t OFF_BARS = 232192;
constexpr uint32_t SMEM_BYTES = 232448;
constexpr uint32_t B_FULL = 0, B_EMPTY = 32, B_E = 64, B_AUX = 128, B_EVA = 136, B_EVB = 144, B_BF = 152, B_LATE = 232, B_FFN = 240, B_SW = 248;
constexpr uint32_t B_OUT = B_FULL, B_SEL = B_FULL + 8, B_WR = B_FULL + 16, B_FFD = B_FULL + 24, B_E16 = B_EMPTY + 16, B_KVB = B_EMPTY + 8, B_DUMMY = B_SW + 4,
                   B_GATE = B_EMPTY + 24, B_ID = B_BF + 56, B_KVP = B_BF + 64, B_F15 = B_BF + 72;
#define B_HOLD B_F15
#define HOLDPAR 0
constexpr uint32_t UNIT = 8192;
constexpr uint32_t sb = 1024;
constexpr uint32_t bars = sb + OFF_BARS;
constexpr uint64_t tab5(int a, int b, int c, int d, int e, int f, int g, int h, int i = 0, int j = 0) {
  return (uint64_t)a | (uint64_t)b << 5 | (uint64_t)c << 10 | (uint64_t)d << 15 | (uint64_t)e << 20 | (uint64_t)f << 25 | (uint64_t)g << 30 | (uint64_t)h << 35 |
         (uint64_t)i << 40 | (uint64_t)j << 45;
}
constexpr uint64_t BT0 = tab5(4, 11, 18, 25, 7, 9, 16, 0), BT1 = tab5(4, 11, 18, 25, 21, 23, 2, 0);
constexpr uint64_t GT0 = tab5(2, 21, 23, 18, 0, 25, 14, 7), GT1 = tab5(16, 7, 9, 18, 0, 25, 14, 21);
constexpr uint64_t DT0 = tab5(6, 13, 20, 27, 9, 10, 16, 17), DT1 = tab5(6, 13, 20, 27, 23, 24, 2, 3);
__device__ __forceinline__ uint32_t unit_of(uint64_t tab, int i) { return ((uint32_t)(tab >> (5 * i)) & 31) * UNIT; }
__device__ __forceinline__ uint32_t ring_of(int p, int w) { return (p & 1) * (2 * STAGE_B) + ((p & 2) ? 49152 + w * STAGE_B : w * UNIT); }
constexpr uint32_t OFF_LNP = OFF_STATS + 1024;

struct Scratch {
  uint4 obuf[32 * 64 * 128];
  uint4 kvp[16 * 8 * 256];
  uint4 zp[16 * 8 * 16];
  uint4 ybuf[NCTA * NFFN * 2];
  uint4 st1[64 * 48];
  uint4 csp[16 * 8 * 48];
  uint4 st2[S_];
  uint4 hsel[2 * 8 * 128];
  uint32_t cand[8 * 32];
  uint32_t when[32 * 32];
  unsigned epoch;
};
__device__ __align__(1024) Scratch g_scratch;
#define TS_DECL
#define TS(i)
#define TSG(i)
#define TSV(i, v)
#define TSD(i)
#define RTS_DECL
#define RTS(i)
#define RTS_DUMP
#define TS_DUMP(slot)
#define PTS(i)
#define g_dbgv(i, v)

#define SPANS(i)
__device__ __forceinline__ uint32_t smem_u32(const void* p) { return (uint32_t)__cvta_generic_to_shared(p); }
__device__ __forceinline__ void mbar_init(uint32_t bar, uint32_t cnt) { asm volatile("mbarrier.init.shared::cta.b64 [%0], %1;" :: "r"(bar), "r"(cnt) : "memory"); }
__device__ __forceinline__ void mbar_expect_tx(uint32_t bar, uint32_t bytes) { asm volatile("mbarrier.arrive.expect_tx.shared::cta.b64 _, [%0], %1;" :: "r"(bar), "r"(bytes) : "memory"); }
__device__ __forceinline__ void mbar_arrive(uint32_t bar) { asm volatile("mbarrier.arrive.shared::cta.b64 _, [%0];" :: "r"(bar) : "memory"); }
#define SPINCHK(it, code) if ((it) > SPIN_LIMIT) break
__device__ __forceinline__ void mbar_wait(uint32_t bar, uint32_t parity) {
  asm volatile("{\n.reg .pred p;\n.reg .u32 c;\nmov.u32 c, 0;\n"
               "WL:\nmbarrier.try_wait.parity.shared::cta.b64 p, [%0], %1;\n@p bra WD;\n"
               "add.u32 c, c, 1;\nsetp.lt.u32 p, c, 1048576;\n@p bra WL;\nWD:\n}" :: "r"(bar), "r"(parity) : "memory");
}
__device__ __forceinline__ bool mbar_test(uint32_t bar, uint32_t parity) {
  uint32_t ok;
  asm volatile("{\n.reg .pred p;\nmbarrier.test_wait.parity.shared::cta.b64 p, [%1], %2;\nselp.u32 %0, 1, 0, p;\n}" : "=r"(ok) : "r"(bar), "r"(parity) : "memory");
  return ok;
}
__device__ __forceinline__ uint64_t l2_stream() { uint64_t p; asm("createpolicy.fractional.L2::evict_first.b64 %0, 1.0;" : "=l"(p)); return p; }
__device__ __forceinline__ void tma_2d(uint32_t dst, const CUtensorMap* tm, int c0, int c1, uint32_t bar, bool stream) {
  if (stream) asm volatile("cp.async.bulk.tensor.2d.shared::cluster.global.mbarrier::complete_tx::bytes.L2::cache_hint [%0], [%1, {%3, %4}], [%2], %5;"
                           :: "r"(dst), "l"(tm), "r"(bar), "r"(c0), "r"(c1), "l"(l2_stream()) : "memory");
  else asm volatile("cp.async.bulk.tensor.2d.shared::cluster.global.mbarrier::complete_tx::bytes [%0], [%1, {%3, %4}], [%2];"
                    :: "r"(dst), "l"(tm), "r"(bar), "r"(c0), "r"(c1) : "memory");
}
__device__ __forceinline__ void tma_3d(uint32_t dst, const CUtensorMap* tm, int c0, int c1, int c2, uint32_t bar, bool stream) {
  if (stream) asm volatile("cp.async.bulk.tensor.3d.shared::cluster.global.mbarrier::complete_tx::bytes.L2::cache_hint [%0], [%1, {%3, %4, %5}], [%2], %6;"
                           :: "r"(dst), "l"(tm), "r"(bar), "r"(c0), "r"(c1), "r"(c2), "l"(l2_stream()) : "memory");
  else asm volatile("cp.async.bulk.tensor.3d.shared::cluster.global.mbarrier::complete_tx::bytes [%0], [%1, {%3, %4, %5}], [%2];"
                    :: "r"(dst), "l"(tm), "r"(bar), "r"(c0), "r"(c1), "r"(c2) : "memory");
}
__device__ __forceinline__ void tma_pf_3d(const CUtensorMap* tm, int c0, int c1, int c2) {
  asm volatile("cp.async.bulk.prefetch.tensor.3d.L2.global [%0, {%1, %2, %3}];" :: "l"(tm), "r"(c0), "r"(c1), "r"(c2) : "memory");
}
__device__ __forceinline__ void tma_4d(uint32_t dst, const CUtensorMap* tm, int c0, int c1, int c2, int c3, uint32_t bar, bool stream) {
  if (stream) asm volatile("cp.async.bulk.tensor.4d.shared::cluster.global.mbarrier::complete_tx::bytes.L2::cache_hint [%0], [%1, {%3, %4, %5, %6}], [%2], %7;"
                           :: "r"(dst), "l"(tm), "r"(bar), "r"(c0), "r"(c1), "r"(c2), "r"(c3), "l"(l2_stream()) : "memory");
  else asm volatile("cp.async.bulk.tensor.4d.shared::cluster.global.mbarrier::complete_tx::bytes [%0], [%1, {%3, %4, %5, %6}], [%2];"
                    :: "r"(dst), "l"(tm), "r"(bar), "r"(c0), "r"(c1), "r"(c2), "r"(c3) : "memory");
}
__device__ __forceinline__ void tma_2d_mc(uint32_t dst, const CUtensorMap* tm, int c0, int c1, uint32_t bar, bool stream) {
  if (stream) asm volatile("cp.async.bulk.tensor.2d.shared::cluster.global.mbarrier::complete_tx::bytes.multicast::cluster.L2::cache_hint [%0], [%1, {%3, %4}], [%2], %5, %6;"
                           :: "r"(dst), "l"(tm), "r"(bar), "r"(c0), "r"(c1), "h"((uint16_t)3), "l"(l2_stream()) : "memory");
  else asm volatile("cp.async.bulk.tensor.2d.shared::cluster.global.mbarrier::complete_tx::bytes.multicast::cluster [%0], [%1, {%3, %4}], [%2], %5;"
                    :: "r"(dst), "l"(tm), "r"(bar), "r"(c0), "r"(c1), "h"((uint16_t)3) : "memory");
}
__device__ __forceinline__ bool elect_one() {
  uint32_t p;
  asm volatile("{\n.reg .pred q;\nelect.sync _|q, 0xFFFFFFFF;\nselp.u32 %0, 1, 0, q;\n}" : "=r"(p));
  return p;
}
__device__ __forceinline__ void bulk_load_mc(uint32_t dst, const void* src, uint32_t bytes, uint32_t bar) {
  if (EFA) asm volatile("cp.async.bulk.shared::cluster.global.mbarrier::complete_tx::bytes.multicast::cluster.L2::cache_hint [%0], [%1], %2, [%3], %4, %5;"
                        :: "r"(dst), "l"(src), "r"(bytes), "r"(bar), "h"((uint16_t)3), "l"(l2_stream()) : "memory");
  else asm volatile("cp.async.bulk.shared::cluster.global.mbarrier::complete_tx::bytes.multicast::cluster [%0], [%1], %2, [%3], %4;"
                    :: "r"(dst), "l"(src), "r"(bytes), "r"(bar), "h"((uint16_t)3) : "memory");
}
__device__ __forceinline__ void bulk_load(uint32_t dst, const void* src, uint32_t bytes, uint32_t bar) {
  asm volatile("cp.async.bulk.shared::cluster.global.mbarrier::complete_tx::bytes [%0], [%1], %2, [%3];" :: "r"(dst), "l"(src), "r"(bytes), "r"(bar) : "memory");
}
__device__ __forceinline__ void st_out(void* p, uint4 v) {
  if (EFO == 1) asm volatile("st.global.L2::cache_hint.v4.u32 [%0], {%1,%2,%3,%4}, %5;" :: "l"(p), "r"(v.x), "r"(v.y), "r"(v.z), "r"(v.w), "l"(l2_stream()) : "memory");
  else if (EFO == 2) asm volatile("st.global.cs.v4.u32 [%0], {%1,%2,%3,%4};" :: "l"(p), "r"(v.x), "r"(v.y), "r"(v.z), "r"(v.w) : "memory");
  else asm volatile("st.global.v4.u32 [%0], {%1,%2,%3,%4};" :: "l"(p), "r"(v.x), "r"(v.y), "r"(v.z), "r"(v.w) : "memory");
}
__device__ __forceinline__ void bulk_store(void* dst, uint32_t src, uint32_t bytes) {
  asm volatile("cp.async.bulk.global.shared::cta.bulk_group [%0], [%1], %2;" :: "l"(dst), "r"(src), "r"(bytes) : "memory");
}
__device__ __forceinline__ void mbar_arrive_rem(uint32_t bar) { asm volatile("mbarrier.arrive.shared::cluster.b64 _, [%0];" :: "r"(bar) : "memory"); }
__device__ __forceinline__ void st_async4(uint32_t addr, const uint4& v, uint32_t bar) {
  asm volatile("st.async.shared::cluster.mbarrier::complete_tx::bytes.v4.b32 [%0], {%1,%2,%3,%4}, [%5];" :: "r"(addr), "r"(v.x), "r"(v.y), "r"(v.z), "r"(v.w), "r"(bar) : "memory");
}
template <uint32_t O> __device__ __forceinline__ void ldsm4_o(uint32_t addr, uint32_t& a, uint32_t& b, uint32_t& c, uint32_t& d) {
  asm volatile("ldmatrix.sync.aligned.m8n8.x4.shared.b16 {%0,%1,%2,%3}, [%4+%5];" : "=r"(a), "=r"(b), "=r"(c), "=r"(d) : "r"(addr), "n"(O) : "memory");
}
template <uint32_t O> __device__ __forceinline__ void ldsm4t_o(uint32_t addr, uint32_t (&r)[4]) {
  asm volatile("ldmatrix.sync.aligned.m8n8.x4.trans.shared.b16 {%0,%1,%2,%3}, [%4+%5];" : "=r"(r[0]), "=r"(r[1]), "=r"(r[2]), "=r"(r[3]) : "r"(addr), "n"(O) : "memory");
}
__device__ __forceinline__ void mma16816(float (&c)[4], const uint32_t (&a)[4], uint32_t b0, uint32_t b1) {
  asm("mma.sync.aligned.m16n8k16.row.col.f32.bf16.bf16.f32 {%0,%1,%2,%3}, {%4,%5,%6,%7}, {%8,%9}, {%0,%1,%2,%3};"
      : "+f"(c[0]), "+f"(c[1]), "+f"(c[2]), "+f"(c[3]) : "r"(a[0]), "r"(a[1]), "r"(a[2]), "r"(a[3]), "r"(b0), "r"(b1));
}
__device__ __forceinline__ void l2_prefetch(const void* p) { asm volatile("prefetch.global.L2 [%0];" :: "l"(p) : "memory"); }
__device__ __forceinline__ uint32_t ld_line(const void* p) { uint32_t v; asm volatile("ld.global.cg.L2::128B.u32 %0, [%1];" : "=r"(v) : "l"(p) : "memory"); return v; }
__device__ __forceinline__ void tmap_prefetch(const CUtensorMap* tm) { asm volatile("prefetch.tensormap [%0];" :: "l"(tm) : "memory"); }
__device__ __forceinline__ void wg_fence() { asm volatile("wgmma.fence.sync.aligned;" ::: "memory"); }
__device__ __forceinline__ void wg_commit() { asm volatile("wgmma.commit_group.sync.aligned;" ::: "memory"); }
template <int N> __device__ __forceinline__ void wg_wait() { asm volatile("wgmma.wait_group.sync.aligned %0;" :: "n"(N) : "memory"); }
template <int N> __device__ __forceinline__ void pin(float (&d)[N]) {
#pragma unroll
  for (int i = 0; i < N; i++) asm volatile("" : "+f"(d[i]) :: "memory");
}
__device__ __forceinline__ void pin4(uint4& v) { asm volatile("" : "+r"(v.x), "+r"(v.y), "+r"(v.z), "+r"(v.w) :: "memory"); }
template <uint32_t SBO, uint32_t SWZ> __device__ __forceinline__ uint64_t dsc(uint32_t lo) { return ((uint64_t)((SBO >> 4) | (SWZ << 30)) << 32) | lo; }
__host__ __device__ constexpr uint32_t dlo(uint32_t addr, uint32_t lbo) { return (addr >> 4) | ((lbo >> 4) << 16); }
__device__ __forceinline__ void bar_sync(int id, int n) { asm volatile("bar.sync %0, %1;" :: "r"(id), "r"(n) : "memory"); }
__device__ __forceinline__ void bar_arrive(int id, int n) { asm volatile("bar.arrive %0, %1;" :: "r"(id), "r"(n) : "memory"); }
__device__ __forceinline__ void fence_async_smem() { asm volatile("fence.proxy.async.shared::cta;" ::: "memory"); }
__device__ __forceinline__ void fence_gpu() { asm volatile("fence.acq_rel.gpu;" ::: "memory"); }
__device__ __forceinline__ uint4 ld_cg4(const void* p) { uint4 v; asm volatile("ld.global.cg.v4.u32 {%0,%1,%2,%3}, [%4];" : "=r"(v.x), "=r"(v.y), "=r"(v.z), "=r"(v.w) : "l"(p) : "memory"); return v; }
__device__ __forceinline__ uint4 ld_rlx4(const void* p) { uint4 v; asm volatile("ld.relaxed.gpu.global.v4.u32 {%0,%1,%2,%3}, [%4];" : "=r"(v.x), "=r"(v.y), "=r"(v.z), "=r"(v.w) : "l"(p) : "memory"); return v; }
__device__ __forceinline__ uint32_t ld_rlx(const void* p) { uint32_t v; asm volatile("ld.relaxed.gpu.global.u32 %0, [%1];" : "=r"(v) : "l"(p) : "memory"); return v; }
__device__ __forceinline__ void st_rlx4(void* p, uint4 v) { asm volatile("st.relaxed.gpu.global.v4.u32 [%0], {%1,%2,%3,%4};" :: "l"(p), "r"(v.x), "r"(v.y), "r"(v.z), "r"(v.w) : "memory"); }
__device__ __forceinline__ void st_rlx2(void* p, uint32_t a, uint32_t b) { asm volatile("st.relaxed.gpu.global.v2.u32 [%0], {%1,%2};" :: "l"(p), "r"(a), "r"(b) : "memory"); }
__device__ __forceinline__ void st_rlx(void* p, uint32_t a) { asm volatile("st.relaxed.gpu.global.u32 [%0], %1;" :: "l"(p), "r"(a) : "memory"); }
__device__ __forceinline__ void red4(void* p, float a, float b, float c, float d) { asm volatile("red.relaxed.gpu.global.add.v4.f32 [%0], {%1,%2,%3,%4};" :: "l"(p), "f"(a), "f"(b), "f"(c), "f"(d) : "memory"); }
__device__ __forceinline__ uint32_t pack2(float lo, float hi) { uint32_t r; asm("cvt.rn.bf16x2.f32 %0, %1, %2;" : "=r"(r) : "f"(hi), "f"(lo)); return r; }
__device__ __forceinline__ float bf_lo(uint32_t v) { return __uint_as_float(v << 16); }
__device__ __forceinline__ float bf_hi(uint32_t v) { return __uint_as_float(v & 0xFFFF0000u); }
__device__ __forceinline__ void stsm4(uint32_t addr, uint32_t a, uint32_t b, uint32_t c, uint32_t d) {
  asm volatile("stmatrix.sync.aligned.m8n8.x4.shared.b16 [%0], {%1,%2,%3,%4};" :: "r"(addr), "r"(a), "r"(b), "r"(c), "r"(d) : "memory");
}
template <uint32_t O> __device__ __forceinline__ void stsm4_o(uint32_t addr, uint32_t a, uint32_t b, uint32_t c, uint32_t d) {
  asm volatile("stmatrix.sync.aligned.m8n8.x4.shared.b16 [%0+%5], {%1,%2,%3,%4};" :: "r"(addr), "r"(a), "r"(b), "r"(c), "r"(d), "n"(O) : "memory");
}
__device__ __forceinline__ void sts4(uint32_t addr, uint32_t a, uint32_t b, uint32_t c, uint32_t d) { asm volatile("st.shared.v4.u32 [%0], {%1,%2,%3,%4};" :: "r"(addr), "r"(a), "r"(b), "r"(c), "r"(d) : "memory"); }
__device__ __forceinline__ void sts2f(uint32_t addr, float a, float b) { asm volatile("st.shared.v2.f32 [%0], {%1,%2};" :: "r"(addr), "f"(a), "f"(b) : "memory"); }
__device__ __forceinline__ void sts1(uint32_t addr, uint32_t a) { asm volatile("st.shared.u32 [%0], %1;" :: "r"(addr), "r"(a) : "memory"); }
__device__ __forceinline__ float2 lds2f(uint32_t addr) { float2 v; asm volatile("ld.shared.v2.f32 {%0,%1}, [%2];" : "=f"(v.x), "=f"(v.y) : "r"(addr) : "memory"); return v; }
template <uint32_t O> __device__ __forceinline__ float2 lds2f_o(uint32_t addr) { float2 v; asm volatile("ld.shared.v2.f32 {%0,%1}, [%2+%3];" : "=f"(v.x), "=f"(v.y) : "r"(addr), "n"(O) : "memory"); return v; }
template <int I, int N, class F> __device__ __forceinline__ void static_for(F&& f) { if constexpr (I < N) { f(std::integral_constant<int, I>{}); static_for<I + 1, N>(f); } }
__device__ __forceinline__ uint4 lds4(uint32_t addr) { uint4 v; asm volatile("ld.shared.v4.u32 {%0,%1,%2,%3}, [%4];" : "=r"(v.x), "=r"(v.y), "=r"(v.z), "=r"(v.w) : "r"(addr) : "memory"); return v; }
__device__ __forceinline__ uint32_t lds1(uint32_t addr) { uint32_t v; asm volatile("ld.shared.u32 %0, [%1];" : "=r"(v) : "r"(addr) : "memory"); return v; }
__device__ __forceinline__ float ex2(float x) { float y; asm("ex2.approx.ftz.f32 %0, %1;" : "=f"(y) : "f"(x)); return y; }
__device__ __forceinline__ uint32_t max4(uint32_t m, const uint4& v) { return __vimax3_u32(__vimax3_u32(m, v.x, v.y), v.z, v.w); }
__device__ __forceinline__ float rsq(float x) { float y; asm("rsqrt.approx.ftz.f32 %0, %1;" : "=f"(y) : "f"(x)); return y; }
__device__ __forceinline__ float rcp(float x) { float y; asm("rcp.approx.ftz.f32 %0, %1;" : "=f"(y) : "f"(x)); return y; }
__device__ __forceinline__ uint2 ld_rlx2(const void* p) { uint2 v; asm volatile("ld.relaxed.gpu.global.v2.u32 {%0,%1}, [%2];" : "=r"(v.x), "=r"(v.y) : "l"(p) : "memory"); return v; }
template <uint32_t O> __device__ __forceinline__ uint4 lds4_o(uint32_t addr) { uint4 v; asm volatile("ld.shared.v4.u32 {%0,%1,%2,%3}, [%4+%5];" : "=r"(v.x), "=r"(v.y), "=r"(v.z), "=r"(v.w) : "r"(addr), "n"(O) : "memory"); return v; }
__device__ __forceinline__ uint32_t phi2(float u0, float u1, float rl, uint32_t r2) {
  uint32_t pu, r;
  asm("cvt.rn.relu.bf16x2.f32 %0, %1, %2;" : "=r"(pu) : "f"(u1), "f"(u0));
  asm("fma.rn.bf16x2 %0, %1, %2, %3;" : "=r"(r) : "r"(pu), "r"(r2), "r"(pack2(__saturatef(ex2(u0 * rl) + 1e-6f), __saturatef(ex2(u1 * rl) + 1e-6f))));
  return r;
}
__device__ __forceinline__ uint32_t dup2(float r) { uint32_t v; asm("cvt.rn.relu.bf16x2.f32 %0, %1, %1;" : "=r"(v) : "f"(r)); return v; }
__device__ __forceinline__ uint32_t zero_after(const uint32_t (&v)[16]) {
  uint32_t z = 0;
#pragma unroll
  for (int i = 0; i < 16; i++) z |= v[i];
  return z & 0x80008000u;
}
__device__ __forceinline__ uint32_t hadd2(uint32_t a, uint32_t b) { uint32_t v; asm("add.rn.bf16x2 %0, %1, %2;" : "=r"(v) : "r"(a), "r"(b)); return v; }
__device__ __forceinline__ void sched_fence() { asm volatile("{\n.reg .pred p;\n.reg .u64 c;\nSF:\nmov.u64 c, %clock64;\nsetp.eq.u64 p, c, 0;\n@p bra SF;\n}" ::: "memory"); }
__device__ __forceinline__ uint4 ld_gen4(const void* p) { uint4 v; asm volatile("ld.relaxed.gpu.v4.u32 {%0,%1,%2,%3}, [%4];" : "=r"(v.x), "=r"(v.y), "=r"(v.z), "=r"(v.w) : "l"(p) : "memory"); return v; }
__device__ __forceinline__ uint2 ld_gen2(const void* p) { uint2 v; asm volatile("ld.relaxed.gpu.v2.u32 {%0,%1}, [%2];" : "=r"(v.x), "=r"(v.y) : "l"(p) : "memory"); return v; }
__device__ __forceinline__ uint32_t now_ns() { uint32_t v; asm volatile("mov.u32 %0, %%globaltimer_lo;" : "=r"(v) :: "memory"); return v; }
__device__ __forceinline__ void meet(uint32_t* mine, const uint4* all, int first, int after, uint32_t bar) {
  const uint32_t t0 = now_ns() & ~1u;
  if ((threadIdx.x & 31) == 0) st_rlx(mine, t0);
  while ((int)(now_ns() - t0) < first) {}
  uint4 v;
#pragma unroll 1
  for (int it = 0; it < SPIN_LIMIT; it++) { v = ld_rlx4(all); if (!__any_sync(~0u, max4(0, v) == SENT)) break; }
  const int d = min(__reduce_max_sync(~0u, max(max((int)(v.x - t0), (int)(v.y - t0)), max((int)(v.z - t0), (int)(v.w - t0)))), 100000) + after;
  mbar_wait(bar, 0);
  while ((int)(now_ns() - t0) < d) {}
}
__device__ __forceinline__ uint32_t lane_id() { uint32_t v; asm volatile("mov.u32 %0, %%laneid;" : "=r"(v)); return v; }
template <int A, int B, int N> __device__ __forceinline__ void pinr(float (&d)[N]) {
#pragma unroll
  for (int i = A; i < B; i++) asm volatile("" : "+f"(d[i]) :: "memory");
}
template <int N> __device__ __forceinline__ void pinu(uint32_t (&d)[N]) {
#pragma unroll
  for (int i = 0; i < N; i++) asm volatile("" : "+r"(d[i]) :: "memory");
}

template<int TA, int TB, int OFF, int SZ> __device__ __forceinline__ void wgmma_n192_ss(float (&d)[SZ], uint64_t da, uint64_t db, int scale_d) {
  asm volatile("{\n.reg .pred p;\nsetp.ne.b32 p, %98, 0;\n"
    "wgmma.mma_async.sync.aligned.m64n192k16.f32.bf16.bf16 {%0,%1,%2,%3,%4,%5,%6,%7,%8,%9,%10,%11,%12,%13,%14,%15,%16,%17,%18,%19,%20,%21,%22,%23,%24,%25,%26,%27,%28,%29,%30,%31,%32,%33,%34,%35,%36,%37,%38,%39,%40,%41,%42,%43,%44,%45,%46,%47,%48,%49,%50,%51,%52,%53,%54,%55,%56,%57,%58,%59,%60,%61,%62,%63,%64,%65,%66,%67,%68,%69,%70,%71,%72,%73,%74,%75,%76,%77,%78,%79,%80,%81,%82,%83,%84,%85,%86,%87,%88,%89,%90,%91,%92,%93,%94,%95}, %96, %97, p, 1, 1, %99, %100;\n}\n"
    : "+f"(d[OFF+0]), "+f"(d[OFF+1]), "+f"(d[OFF+2]), "+f"(d[OFF+3]), "+f"(d[OFF+4]), "+f"(d[OFF+5]), "+f"(d[OFF+6]), "+f"(d[OFF+7]),
      "+f"(d[OFF+8]), "+f"(d[OFF+9]), "+f"(d[OFF+10]), "+f"(d[OFF+11]), "+f"(d[OFF+12]), "+f"(d[OFF+13]), "+f"(d[OFF+14]), "+f"(d[OFF+15]),
      "+f"(d[OFF+16]), "+f"(d[OFF+17]), "+f"(d[OFF+18]), "+f"(d[OFF+19]), "+f"(d[OFF+20]), "+f"(d[OFF+21]), "+f"(d[OFF+22]), "+f"(d[OFF+23]),
      "+f"(d[OFF+24]), "+f"(d[OFF+25]), "+f"(d[OFF+26]), "+f"(d[OFF+27]), "+f"(d[OFF+28]), "+f"(d[OFF+29]), "+f"(d[OFF+30]), "+f"(d[OFF+31]),
      "+f"(d[OFF+32]), "+f"(d[OFF+33]), "+f"(d[OFF+34]), "+f"(d[OFF+35]), "+f"(d[OFF+36]), "+f"(d[OFF+37]), "+f"(d[OFF+38]), "+f"(d[OFF+39]),
      "+f"(d[OFF+40]), "+f"(d[OFF+41]), "+f"(d[OFF+42]), "+f"(d[OFF+43]), "+f"(d[OFF+44]), "+f"(d[OFF+45]), "+f"(d[OFF+46]), "+f"(d[OFF+47]),
      "+f"(d[OFF+48]), "+f"(d[OFF+49]), "+f"(d[OFF+50]), "+f"(d[OFF+51]), "+f"(d[OFF+52]), "+f"(d[OFF+53]), "+f"(d[OFF+54]), "+f"(d[OFF+55]),
      "+f"(d[OFF+56]), "+f"(d[OFF+57]), "+f"(d[OFF+58]), "+f"(d[OFF+59]), "+f"(d[OFF+60]), "+f"(d[OFF+61]), "+f"(d[OFF+62]), "+f"(d[OFF+63]),
      "+f"(d[OFF+64]), "+f"(d[OFF+65]), "+f"(d[OFF+66]), "+f"(d[OFF+67]), "+f"(d[OFF+68]), "+f"(d[OFF+69]), "+f"(d[OFF+70]), "+f"(d[OFF+71]),
      "+f"(d[OFF+72]), "+f"(d[OFF+73]), "+f"(d[OFF+74]), "+f"(d[OFF+75]), "+f"(d[OFF+76]), "+f"(d[OFF+77]), "+f"(d[OFF+78]), "+f"(d[OFF+79]),
      "+f"(d[OFF+80]), "+f"(d[OFF+81]), "+f"(d[OFF+82]), "+f"(d[OFF+83]), "+f"(d[OFF+84]), "+f"(d[OFF+85]), "+f"(d[OFF+86]), "+f"(d[OFF+87]),
      "+f"(d[OFF+88]), "+f"(d[OFF+89]), "+f"(d[OFF+90]), "+f"(d[OFF+91]), "+f"(d[OFF+92]), "+f"(d[OFF+93]), "+f"(d[OFF+94]), "+f"(d[OFF+95])
    : "l"(da), "l"(db), "r"(scale_d), "n"(TA), "n"(TB));
}
template<int TA, int TB, int OFF, int SZ> __device__ __forceinline__ void wgmma_n128_ss(float (&d)[SZ], uint64_t da, uint64_t db, int scale_d) {
  asm volatile("{\n.reg .pred p;\nsetp.ne.b32 p, %66, 0;\n"
    "wgmma.mma_async.sync.aligned.m64n128k16.f32.bf16.bf16 {%0,%1,%2,%3,%4,%5,%6,%7,%8,%9,%10,%11,%12,%13,%14,%15,%16,%17,%18,%19,%20,%21,%22,%23,%24,%25,%26,%27,%28,%29,%30,%31,%32,%33,%34,%35,%36,%37,%38,%39,%40,%41,%42,%43,%44,%45,%46,%47,%48,%49,%50,%51,%52,%53,%54,%55,%56,%57,%58,%59,%60,%61,%62,%63}, %64, %65, p, 1, 1, %67, %68;\n}\n"
    : "+f"(d[OFF+0]), "+f"(d[OFF+1]), "+f"(d[OFF+2]), "+f"(d[OFF+3]), "+f"(d[OFF+4]), "+f"(d[OFF+5]), "+f"(d[OFF+6]), "+f"(d[OFF+7]),
      "+f"(d[OFF+8]), "+f"(d[OFF+9]), "+f"(d[OFF+10]), "+f"(d[OFF+11]), "+f"(d[OFF+12]), "+f"(d[OFF+13]), "+f"(d[OFF+14]), "+f"(d[OFF+15]),
      "+f"(d[OFF+16]), "+f"(d[OFF+17]), "+f"(d[OFF+18]), "+f"(d[OFF+19]), "+f"(d[OFF+20]), "+f"(d[OFF+21]), "+f"(d[OFF+22]), "+f"(d[OFF+23]),
      "+f"(d[OFF+24]), "+f"(d[OFF+25]), "+f"(d[OFF+26]), "+f"(d[OFF+27]), "+f"(d[OFF+28]), "+f"(d[OFF+29]), "+f"(d[OFF+30]), "+f"(d[OFF+31]),
      "+f"(d[OFF+32]), "+f"(d[OFF+33]), "+f"(d[OFF+34]), "+f"(d[OFF+35]), "+f"(d[OFF+36]), "+f"(d[OFF+37]), "+f"(d[OFF+38]), "+f"(d[OFF+39]),
      "+f"(d[OFF+40]), "+f"(d[OFF+41]), "+f"(d[OFF+42]), "+f"(d[OFF+43]), "+f"(d[OFF+44]), "+f"(d[OFF+45]), "+f"(d[OFF+46]), "+f"(d[OFF+47]),
      "+f"(d[OFF+48]), "+f"(d[OFF+49]), "+f"(d[OFF+50]), "+f"(d[OFF+51]), "+f"(d[OFF+52]), "+f"(d[OFF+53]), "+f"(d[OFF+54]), "+f"(d[OFF+55]),
      "+f"(d[OFF+56]), "+f"(d[OFF+57]), "+f"(d[OFF+58]), "+f"(d[OFF+59]), "+f"(d[OFF+60]), "+f"(d[OFF+61]), "+f"(d[OFF+62]), "+f"(d[OFF+63])
    : "l"(da), "l"(db), "r"(scale_d), "n"(TA), "n"(TB));
}
template<int TA, int TB, int OFF, int SZ> __device__ __forceinline__ void wgmma_n64_ss(float (&d)[SZ], uint64_t da, uint64_t db, int scale_d) {
  asm volatile("{\n.reg .pred p;\nsetp.ne.b32 p, %34, 0;\n"
    "wgmma.mma_async.sync.aligned.m64n64k16.f32.bf16.bf16 {%0,%1,%2,%3,%4,%5,%6,%7,%8,%9,%10,%11,%12,%13,%14,%15,%16,%17,%18,%19,%20,%21,%22,%23,%24,%25,%26,%27,%28,%29,%30,%31}, %32, %33, p, 1, 1, %35, %36;\n}\n"
    : "+f"(d[OFF+0]), "+f"(d[OFF+1]), "+f"(d[OFF+2]), "+f"(d[OFF+3]), "+f"(d[OFF+4]), "+f"(d[OFF+5]), "+f"(d[OFF+6]), "+f"(d[OFF+7]),
      "+f"(d[OFF+8]), "+f"(d[OFF+9]), "+f"(d[OFF+10]), "+f"(d[OFF+11]), "+f"(d[OFF+12]), "+f"(d[OFF+13]), "+f"(d[OFF+14]), "+f"(d[OFF+15]),
      "+f"(d[OFF+16]), "+f"(d[OFF+17]), "+f"(d[OFF+18]), "+f"(d[OFF+19]), "+f"(d[OFF+20]), "+f"(d[OFF+21]), "+f"(d[OFF+22]), "+f"(d[OFF+23]),
      "+f"(d[OFF+24]), "+f"(d[OFF+25]), "+f"(d[OFF+26]), "+f"(d[OFF+27]), "+f"(d[OFF+28]), "+f"(d[OFF+29]), "+f"(d[OFF+30]), "+f"(d[OFF+31])
    : "l"(da), "l"(db), "r"(scale_d), "n"(TA), "n"(TB));
}
template<int TA, int TB, int OFF, int SZ> __device__ __forceinline__ void wgmma_n72_ss(float (&d)[SZ], uint64_t da, uint64_t db, int scale_d) {
  asm volatile("{\n.reg .pred p;\nsetp.ne.b32 p, %38, 0;\n"
    "wgmma.mma_async.sync.aligned.m64n72k16.f32.bf16.bf16 {%0,%1,%2,%3,%4,%5,%6,%7,%8,%9,%10,%11,%12,%13,%14,%15,%16,%17,%18,%19,%20,%21,%22,%23,%24,%25,%26,%27,%28,%29,%30,%31,%32,%33,%34,%35}, %36, %37, p, 1, 1, %39, %40;\n}\n"
    : "+f"(d[OFF+0]), "+f"(d[OFF+1]), "+f"(d[OFF+2]), "+f"(d[OFF+3]), "+f"(d[OFF+4]), "+f"(d[OFF+5]), "+f"(d[OFF+6]), "+f"(d[OFF+7]),
      "+f"(d[OFF+8]), "+f"(d[OFF+9]), "+f"(d[OFF+10]), "+f"(d[OFF+11]), "+f"(d[OFF+12]), "+f"(d[OFF+13]), "+f"(d[OFF+14]), "+f"(d[OFF+15]),
      "+f"(d[OFF+16]), "+f"(d[OFF+17]), "+f"(d[OFF+18]), "+f"(d[OFF+19]), "+f"(d[OFF+20]), "+f"(d[OFF+21]), "+f"(d[OFF+22]), "+f"(d[OFF+23]),
      "+f"(d[OFF+24]), "+f"(d[OFF+25]), "+f"(d[OFF+26]), "+f"(d[OFF+27]), "+f"(d[OFF+28]), "+f"(d[OFF+29]), "+f"(d[OFF+30]), "+f"(d[OFF+31]),
      "+f"(d[OFF+32]), "+f"(d[OFF+33]), "+f"(d[OFF+34]), "+f"(d[OFF+35])
    : "l"(da), "l"(db), "r"(scale_d), "n"(TA), "n"(TB));
}
template<int TB, int OFF, int SZ> __device__ __forceinline__ void wgmma_n64_rs(float (&d)[SZ], uint32_t a0, uint32_t a1, uint32_t a2, uint32_t a3, uint64_t db, int scale_d) {
  asm volatile("{\n.reg .pred p;\nsetp.ne.b32 p, %37, 0;\n"
    "wgmma.mma_async.sync.aligned.m64n64k16.f32.bf16.bf16 {%0,%1,%2,%3,%4,%5,%6,%7,%8,%9,%10,%11,%12,%13,%14,%15,%16,%17,%18,%19,%20,%21,%22,%23,%24,%25,%26,%27,%28,%29,%30,%31}, {%32,%33,%34,%35}, %36, p, 1, 1, %38;\n}\n"
    : "+f"(d[OFF+0]), "+f"(d[OFF+1]), "+f"(d[OFF+2]), "+f"(d[OFF+3]), "+f"(d[OFF+4]), "+f"(d[OFF+5]), "+f"(d[OFF+6]), "+f"(d[OFF+7]),
      "+f"(d[OFF+8]), "+f"(d[OFF+9]), "+f"(d[OFF+10]), "+f"(d[OFF+11]), "+f"(d[OFF+12]), "+f"(d[OFF+13]), "+f"(d[OFF+14]), "+f"(d[OFF+15]),
      "+f"(d[OFF+16]), "+f"(d[OFF+17]), "+f"(d[OFF+18]), "+f"(d[OFF+19]), "+f"(d[OFF+20]), "+f"(d[OFF+21]), "+f"(d[OFF+22]), "+f"(d[OFF+23]),
      "+f"(d[OFF+24]), "+f"(d[OFF+25]), "+f"(d[OFF+26]), "+f"(d[OFF+27]), "+f"(d[OFF+28]), "+f"(d[OFF+29]), "+f"(d[OFF+30]), "+f"(d[OFF+31])
    : "r"(a0), "r"(a1), "r"(a2), "r"(a3), "l"(db), "r"(scale_d), "n"(TB));
}
template<int TB, int OFF, int SZ> __device__ __forceinline__ void wgmma_n40_rs(float (&d)[SZ], uint32_t a0, uint32_t a1, uint32_t a2, uint32_t a3, uint64_t db, int scale_d) {
  asm volatile("{\n.reg .pred p;\nsetp.ne.b32 p, %25, 0;\n"
    "wgmma.mma_async.sync.aligned.m64n40k16.f32.bf16.bf16 {%0,%1,%2,%3,%4,%5,%6,%7,%8,%9,%10,%11,%12,%13,%14,%15,%16,%17,%18,%19}, {%20,%21,%22,%23}, %24, p, 1, 1, %26;\n}\n"
    : "+f"(d[OFF+0]), "+f"(d[OFF+1]), "+f"(d[OFF+2]), "+f"(d[OFF+3]), "+f"(d[OFF+4]), "+f"(d[OFF+5]), "+f"(d[OFF+6]), "+f"(d[OFF+7]),
      "+f"(d[OFF+8]), "+f"(d[OFF+9]), "+f"(d[OFF+10]), "+f"(d[OFF+11]), "+f"(d[OFF+12]), "+f"(d[OFF+13]), "+f"(d[OFF+14]), "+f"(d[OFF+15]),
      "+f"(d[OFF+16]), "+f"(d[OFF+17]), "+f"(d[OFF+18]), "+f"(d[OFF+19])
    : "r"(a0), "r"(a1), "r"(a2), "r"(a3), "l"(db), "r"(scale_d), "n"(TB));
}
template<int TB, int OFF, int SZ> __device__ __forceinline__ void wgmma_n128_rs(float (&d)[SZ], uint32_t a0, uint32_t a1, uint32_t a2, uint32_t a3, uint64_t db, int scale_d) {
  asm volatile("{\n.reg .pred p;\nsetp.ne.b32 p, %69, 0;\n"
    "wgmma.mma_async.sync.aligned.m64n128k16.f32.bf16.bf16 {%0,%1,%2,%3,%4,%5,%6,%7,%8,%9,%10,%11,%12,%13,%14,%15,%16,%17,%18,%19,%20,%21,%22,%23,%24,%25,%26,%27,%28,%29,%30,%31,%32,%33,%34,%35,%36,%37,%38,%39,%40,%41,%42,%43,%44,%45,%46,%47,%48,%49,%50,%51,%52,%53,%54,%55,%56,%57,%58,%59,%60,%61,%62,%63}, {%64,%65,%66,%67}, %68, p, 1, 1, %70;\n}\n"
    : "+f"(d[OFF+0]), "+f"(d[OFF+1]), "+f"(d[OFF+2]), "+f"(d[OFF+3]), "+f"(d[OFF+4]), "+f"(d[OFF+5]), "+f"(d[OFF+6]), "+f"(d[OFF+7]),
      "+f"(d[OFF+8]), "+f"(d[OFF+9]), "+f"(d[OFF+10]), "+f"(d[OFF+11]), "+f"(d[OFF+12]), "+f"(d[OFF+13]), "+f"(d[OFF+14]), "+f"(d[OFF+15]),
      "+f"(d[OFF+16]), "+f"(d[OFF+17]), "+f"(d[OFF+18]), "+f"(d[OFF+19]), "+f"(d[OFF+20]), "+f"(d[OFF+21]), "+f"(d[OFF+22]), "+f"(d[OFF+23]),
      "+f"(d[OFF+24]), "+f"(d[OFF+25]), "+f"(d[OFF+26]), "+f"(d[OFF+27]), "+f"(d[OFF+28]), "+f"(d[OFF+29]), "+f"(d[OFF+30]), "+f"(d[OFF+31]),
      "+f"(d[OFF+32]), "+f"(d[OFF+33]), "+f"(d[OFF+34]), "+f"(d[OFF+35]), "+f"(d[OFF+36]), "+f"(d[OFF+37]), "+f"(d[OFF+38]), "+f"(d[OFF+39]),
      "+f"(d[OFF+40]), "+f"(d[OFF+41]), "+f"(d[OFF+42]), "+f"(d[OFF+43]), "+f"(d[OFF+44]), "+f"(d[OFF+45]), "+f"(d[OFF+46]), "+f"(d[OFF+47]),
      "+f"(d[OFF+48]), "+f"(d[OFF+49]), "+f"(d[OFF+50]), "+f"(d[OFF+51]), "+f"(d[OFF+52]), "+f"(d[OFF+53]), "+f"(d[OFF+54]), "+f"(d[OFF+55]),
      "+f"(d[OFF+56]), "+f"(d[OFF+57]), "+f"(d[OFF+58]), "+f"(d[OFF+59]), "+f"(d[OFF+60]), "+f"(d[OFF+61]), "+f"(d[OFF+62]), "+f"(d[OFF+63])
    : "r"(a0), "r"(a1), "r"(a2), "r"(a3), "l"(db), "r"(scale_d), "n"(TB));
}

struct Ptrs { const __nv_bfloat16 *x, *wqkv, *wo, *wr, *wg, *wu, *wd; __nv_bfloat16* out; Scratch* s; };

enum { M_X, M_W, M_Q, M_O, M_S, M_G, M_U, M_D, M_L, M_N };
struct Maps { CUtensorMap m[M_N]; };

__global__ void __cluster_dims__(2, 1, 1) __launch_bounds__(384, 1) fused_kernel(const Ptrs P, const __grid_constant__ Maps T) {
  extern __shared__ __align__(1024) uint8_t smem_raw[];
  TS_DECL; TS(0); TSG(30);
  if (threadIdx.x == 320) SPANS(0);
  const uint32_t rank = blockIdx.x & 1;
  uint32_t own = rank << 24;
  asm("" : "+r"(own));
  const uint32_t sm = own + sb, mb = own + bars;
  int b0;
  { const int j = blockIdx.x >> 1, u = j - 36, v = j * 2 - 8 + (max(u * 37 + 256, 0) >> 8) * (u < 0 ? 0 : 2), w = j < 4 ? j * 16 + 64 : v;
    b0 = ((w & 15) | (w & 48) << 1 | (w & 64) >> 2) + rank; }
#define IDS(B) \
  const int b = (B), rb = b >> 4, cg = b & 15, hf = cg >> 3, s3 = cg & 7, c3 = s3 ^ ((rb & 1) << 2), jp = cg >> 1, km = (~c3 & 6) << 1; \
  const int fidx = jp == rb ? -1 : b - 2 * rb - (jp > rb ? 2 : 0); \
  auto kcol = [&](int kb) { return (kb ^ (kb < 8 ? km & 8 : km)) * 64; }; \
  auto src_of = [&](int p) { return p == 0 ? s3 : p == 15 ? s3 ^ 1 : (((jp & 3) ^ ((p - 7) >> 1)) << 1) + ((p - 1) & 1); }; \
  auto frag_of = [&](int p) { return p < 9 ? (p - 1) * 512 : 4096 + src_of(p) * 512; }; \
  (void)hf; (void)fidx; (void)kcol; (void)frag_of
  auto get_b = [&]() { return __shfl_sync(~0u, (int)lds1(mb + B_ID), 0); };
  IDS(b0);
  auto load_w = [&](uint32_t st, int kc, uint32_t bar, bool last) { tma_3d(st + 32768, &T.m[M_W], cg * 64, kc, 1, bar, last); tma_2d(st + 49152, &T.m[M_Q], cg * 64, kc, bar, last); };
  RTS_DECL;
  if (threadIdx.x < 32 && elect_one()) {
    mbar_init(mb + B_FULL, 1);
    asm volatile("fence.mbarrier_init.release.cluster;" ::: "memory");
    mbar_expect_tx(mb + B_FULL, STAGE_B);
    load_w(sm, kcol(0), mb + B_FULL, false);
    tma_2d(sm + 16384, &T.m[M_X], kcol(0), rb * 256 + 128, mb + B_FULL, false);
    tma_2d(sm, &T.m[M_X], kcol(0), rb * 256, mb + B_FULL, false);
  }
  TS(15);
  const int tid = threadIdx.x, wid = __shfl_sync(~0u, tid >> 5, 0), wg = wid >> 2, lane = lane_id();
  const uint32_t tk = clock64();
  if (wid < 4) {
    const int i = tid - 64;
    if (SPF && tid >= 32 && tid < 112)
      l2_prefetch(i < 0 ? P.x + (rb * 256 + (hf * 4 + (cg & 3)) * 32 + lane) * D_ + kcol(0) : P.wqkv + (kcol(0) + (rb >> 1) * 16 + (i & 15)) * 3072 + (i >> 4) * 1024 + cg * 64);
  } else if (wid == 9) {
    if (elect_one()) {
#pragma unroll
      for (int i = 1; i < 31; i++) if (8 * i != B_ID) mbar_init(mb + 8 * i, i < 4 ? 1 : i < 8 ? 8 : i < 16 ? 16 : i == 16 ? 64 : i == 17 ? 8 : i == 18 ? 4 : 1);
      asm volatile("fence.mbarrier_init.release.cluster;" ::: "memory");
      fence_async_smem();
    }
  } else if (wid == 11) {
#pragma unroll
    for (int i = 0; i < 4; i++) sts4(sm + OFF_STATS + i * 512 + lane * 16, SENT, SENT, SENT, SENT);
    sts1(mb + B_ID, b);
    if (smem_u32(smem_raw) != sm) asm volatile("trap;");
    fence_async_smem();
  }
  __syncthreads();
  asm volatile("barrier.cluster.arrive.relaxed.aligned;\nbarrier.cluster.wait.aligned;" ::: "memory");

  if (wg == 2) {
    asm volatile("setmaxnreg.dec.sync.aligned.u32 56;");
    if (wid == 8) {
      if (elect_one()) {
#pragma unroll 1
        for (int kb = 1; kb < 15; kb++) {
          const uint32_t fb = mb + B_FULL + 8 * (kb & 3), st = sm + (kb & 3) * STAGE_B;
          const int kc = kcol(kb);
          if (kb < 4) while ((uint32_t)clock64() - tk < FD0 + kb * FD1) {}
          else mbar_wait(fb + B_EMPTY, ((kb >> 2) & 1) ^ 1);
          mbar_expect_tx(fb, STAGE_B);
          tma_2d_mc(st + rank * 16384, &T.m[M_X], kc, rb * 256 + rank * 128, fb, kb >= EFXK);
          load_w(st, kc, fb, EFW && kb >= EFWK);
          if (kb >= 8 && kb < 11) asm volatile("mbarrier.arrive.shared::cta.b64 _, [%0], %1;" :: "r"(fb + B_EMPTY), "r"(4) : "memory");
        }
        {
          const uint32_t st = sm + 3 * STAGE_B, fa = mb + B_FULL + 24, fb = mb + B_F15;
          const int kc = kcol(15);
          mbar_wait(fa, 0);
          mbar_expect_tx(fa, 32768); mbar_expect_tx(fb, 24576);
          if (rank) { mbar_wait(mb + B_EMPTY + 24, 0); tma_2d_mc(st + 16384, &T.m[M_X], kc, rb * 256 + 128, fa, EFXK < 16); }
          mbar_wait(mb + B_EMPTY, 1);
          tma_3d(st + 32768, &T.m[M_W], cg * 64, kc, 1, fa, EFW);
          if (!rank) { mbar_wait(mb + B_EMPTY + 24, 0); tma_2d_mc(st, &T.m[M_X], kc, rb * 256, fb, EFXK < 16); }
          tma_2d(st + 49152, &T.m[M_Q], cg * 64, kc, fb, EFW);
        }
        mbar_expect_tx(mb + B_KVP, 32768 + 2048);
      }
      __syncwarp();
      const uint4* kp = &P.s->kvp[cg * 8 * 256], *zq = &P.s->zp[cg * 8 * 16], *src = &P.s->obuf[(rb * 4 + rank * 2 + hf) * 64 * 128];
      asm volatile("" : "+l"(kp), "+l"(zq), "+l"(src));
      mbar_wait(mb + B_EVA, 0);
      meet(&P.s->when[cg * 32 + rb], (const uint4*)&P.s->when[cg * 32] + (lane & 1), MFIRST, MKV, mb + B_EVB);
      if (elect_one()) {
        bulk_load(sm + rank * (2 * STAGE_B) + STAGE_B, kp, 32768, mb + B_KVP);
        bulk_load(sm + rank * (2 * STAGE_B) + UNIT, zq, 2048, mb + B_KVP);
      }
      RTS(1);
      mbar_wait(mb + B_KVP, 0);
      RTS(2);
      meet(&P.s->when[(16 + rb * 2 + hf) * 32 + s3], (const uint4*)&P.s->when[(16 + (MWIDE == 2 ? lane >> 1 : (MWIDE ? (lane & 6) + (rb & 1) : rb) * 2 + (hf ^ 1))) * 32] + (lane & 1), MFIRST, MO, mb + B_E);
      RTS(3);
      if (elect_one()) {
        const uint32_t t0 = clock64();
        mbar_arrive(mb + B_F15);
        RTS(4);
#pragma unroll
        for (int p = 2; p < 5; p++) {
          if (p < 4) while ((uint32_t)clock64() - t0 < (p == 2 ? ADELAY : ADELAY2)) {}
          bulk_load_mc(sm + ring_of(p, rank), src + (p - 1) * 512, UNIT, mb + B_BF + 8 * p);
        }
#pragma unroll 1
        for (int p = 5; p < 15; p++) {
          uint32_t dst = sm + ring_of(p, rank), bar = mb + B_BF + 8 * (p % 7);
          const uint4* q = src + frag_of(p);
          asm volatile("" : "+r"(dst), "+r"(bar), "+l"(q));
          mbar_wait(mb + B_E + 8 * ((p - 4) & 7), p >= 12);
          bulk_load_mc(dst, q, UNIT, bar);
        }
        asm volatile("mbarrier.arrive.shared::cta.b64 _, [%0], 8;" :: "r"(mb + B_GATE) : "memory");
        const uint4* s15 = &P.s->obuf[(rb * 4 + hf) * 64 * 128 + frag_of(15)];
        RTS_DUMP;
        mbar_wait(mb + B_E + 24, 1);
        bulk_load(sm + ring_of(15, 0), s15, UNIT, mb + B_BF + 8); bulk_load(sm + ring_of(15, 1), s15 + 2 * 64 * 128, UNIT, mb + B_BF + 8);
      }
    } else if (wid == 11) {
      IDS(get_b());
      if (fidx >= 0) {
        const uint32_t o = (rank * 32 + lane) * (F_ * 2) + (fidx >> 1) * 128;
        const char* q0 = (const char*)P.wg + o, *q1 = (const char*)P.wu + o;
        mbar_wait(mb + B_FULL + 24, 0);
        mbar_wait(mb + B_FULL + 8 * (PULL0 & 3), PULL0 >> 2);
#pragma unroll 1
        for (int r = 0; r < 16; r++, q0 += 64 * F_ * 2, q1 += 64 * F_ * 2) {
          if (mbar_test(mb + B_HOLD, 0)) { l2_prefetch(q0); l2_prefetch(q1); continue; }
          asm volatile("cp.async.ca.shared.global.L2::128B [%0], [%1], 4;\ncp.async.commit_group;\ncp.async.wait_group %3;\n"
                       "cp.async.ca.shared.global.L2::128B [%0], [%2], 4;\ncp.async.commit_group;\ncp.async.wait_group %3;" :: "r"(mb + B_DUMMY), "l"(q0), "l"(q1), "n"(PDEPTH) : "memory");
          if (lane == 0) g_dbgv(3, r + 1);
        }
        mbar_wait(mb + B_F15, 0);
        bar_sync(15, 288);
        if (lane == 0) PTS(1);
        q0 = (const char*)P.wd + fidx * 65536 + lane * 128;
        const uint32_t bar = mb + B_BF + 48;
        if (lane == 0) mbar_expect_tx(bar, 8192);
#pragma unroll 1
        for (int i = 0; i < 16 + PLAG; i++) {
          if (i < 16) l2_prefetch(q0 + i * 4096);
          if (i >= PLAG && elect_one()) tma_2d(sm + OFF_COLSUM, &T.m[M_L], 0, fidx * 512 + (i - PLAG) * 32, bar, false);
          const uint32_t t1 = clock64();
          while ((uint32_t)clock64() - t1 < PSTEP) {}
        }
        mbar_wait(bar, 0);
        __syncwarp();
        if (lane == 0) { mbar_arrive(bar); PTS(4); }
        asm volatile("cp.async.wait_all;" ::: "memory");
      } else bar_arrive(15, 288);
      bar_arrive(14, 64);
    } else {
      const uint32_t eb = (lane << 24) + bars + B_EMPTY;
      float c[6];
      if (wid == 10) {
        float sx[4] = {0.f, 0.f, 0.f, 0.f}, qx[4] = {0.f, 0.f, 0.f, 0.f};
        const uint32_t xa = sm + ((hf * 4 + (cg & 3)) * 32 + lane) * 128 + ((lane & 7) << 4);
#pragma unroll 1
        for (int kb = 0; kb < 8; kb++) {
          uint4 xv[8];
          const uint32_t so = xa + (kb & 3) * STAGE_B;
          mbar_wait(mb + B_FULL + 8 * (kb & 3), kb >> 2);
#pragma unroll
          for (int i = 0; i < 8; i++) xv[i] = lds4(so ^ (i << 4));
#pragma unroll
          for (int i = 0; i < 8; i++) {
            const uint32_t e[4] = {xv[i].x, xv[i].y, xv[i].z, xv[i].w};
#pragma unroll
            for (int j = 0; j < 4; j++) {
              const float d0 = bf_lo(e[j]), d1 = bf_hi(e[j]);
              sx[j] += d0 + d1; qx[j] = fmaf(d0, d0, fmaf(d1, d1, qx[j]));
            }
          }
          __syncwarp();
          if (lane < 2) mbar_arrive_rem(eb + 8 * (kb & 3));
          if (kb == RST2) {
        {
          const uint32_t ep = ld_rlx(&P.s->epoch);
          float s = 0.f;
#pragma unroll
          for (int i = 0; i < 4; i++) {
            const uint4 v = ld_cg4((const uint4*)P.wr + lane + i * 32);
            s += (bf_lo(v.x) + bf_hi(v.x)) + (bf_lo(v.y) + bf_hi(v.y)) + (bf_lo(v.z) + bf_hi(v.z)) + (bf_lo(v.w) + bf_hi(v.w));
          }
#pragma unroll
          for (int o = 16; o; o >>= 1) s += __shfl_xor_sync(~0u, s, o);
          if (lane == 0) sts1(mb + B_SW, (__float_as_uint(s) & ~255u) | ((ep + 1) & 255));
        }
        asm volatile("cp.async.bulk.wait_group 0;\nfence.proxy.async.global;" ::: "memory");
        fence_gpu();
        if (lane == 0) PTS(0);
          }
          if (kb == RST) {
        if (elect_one()) {
#pragma unroll 1
          for (int i = 0; i < 16; i++) bulk_store(&P.s->obuf[((rb * 4 + (i >> 2)) * 64 + (((i >> 2) & 1) == hf ? 32 + s3 * 4 + (i & 3) : (i & 3) * 8 + s3)) * 128], sm + OFF_STATS, 2048);
          bulk_store(&P.s->kvp[(cg * 8 + rb) * 256], sm + OFF_STATS, 2048); bulk_store(&P.s->kvp[(cg * 8 + rb) * 256 + 128], sm + OFF_STATS, 2048);
          bulk_store(&P.s->zp[(cg * 8 + rb) * 16], sm + OFF_STATS, 256);
          if (s3 == 0) bulk_store(&P.s->when[(16 + rb * 2 + hf) * 32], sm + OFF_STATS, 128);
          if (rb == 0) bulk_store(&P.s->when[cg * 32], sm + OFF_STATS, 128);
          asm volatile("cp.async.bulk.commit_group;" ::: "memory");
          #pragma unroll
          for (int i = M_O; i < M_N; i++) tmap_prefetch(&T.m[i]);
        }
        __syncwarp();
          }
        }
        c[0] = ((sx[0] + sx[1]) + (sx[2] + sx[3])) * (2.f / D_);
        c[1] = fmaxf(fmaf(-c[0], c[0], ((qx[0] + qx[1]) + (qx[2] + qx[3])) * (2.f / D_)), 0.f);
      } else {
        float a[12];
#pragma unroll
        for (int i = 0; i < 12; i++) a[i] = 0.f;
        const int r2 = lane >> 4, c16 = lane & 15;
        const uint32_t a0 = sm + 32768 + (rb >> 1) * 2048 + r2 * 128 + (((c16 >> 1) ^ r2) << 4) + (c16 & 1) * 8;
#pragma unroll 1
        for (int it = 0; it < 16; it++) {
          uint2 w[12];
          const int s = (it >> 1) & 3;
          const uint32_t so = a0 + s * STAGE_B + (it & 1) * 1024;
          if (!(it & 1)) { mbar_wait(mb + B_FULL + 8 * s, it >> 3); TSD(8 + (it >> 1)); }
          static_for<0, 12>([&](auto ic) { constexpr int i = decltype(ic)::value;
            const float2 v = lds2f_o<(i >> 2) * 8192 + (i & 3) * 256>(so ^ ((i & 3) << 5)); w[i] = make_uint2(__float_as_uint(v.x), __float_as_uint(v.y)); });
#pragma unroll
          for (int i = 0; i < 12; i++) { float* q = a + (i >> 2) * 4; q[0] += bf_lo(w[i].x); q[1] += bf_hi(w[i].x); q[2] += bf_lo(w[i].y); q[3] += bf_hi(w[i].y); }
          __syncwarp();
          if (lane < 2 && (it & 1)) mbar_arrive_rem(eb + 8 * s);
        }
#pragma unroll
        for (int i = 0; i < 6; i++) {
          const int o = (i >> 1) * 4 + (i & 1);
          c[i] = (r2 ? a[o + 2] : a[o]) + __shfl_xor_sync(~0u, r2 ? a[o] : a[o + 2], 16);
        }
      }
      TS(5);
      bar_sync(10, 64);
      TS(6);
      {
        const uint32_t tag = lds1(mb + B_SW) & 255;
        auto tagged = [&](float v) { return ((__float_as_uint(v) + 128) & ~255u) | tag; };
        if (wid == 9) {
#pragma unroll
          for (int sg = 0; sg < 3; sg++) {
            st_rlx2((uint2*)&P.s->csp[(cg * 8 + rb) * 48] + sg * 32 + (lane & 15) * 2 + (lane >> 4), tagged(c[sg * 2]), tagged(c[sg * 2 + 1]));
          }
        } else st_rlx2((uint2*)&P.s->st1[(rb * 8 + hf * 4 + (cg & 3)) * 48 + lane] + ((cg >> 2) & 1), tagged(c[0]), tagged(c[1]));
        { const uint32_t t0 = clock64(); while ((uint32_t)clock64() - t0 < GDELAY) {} }
#pragma unroll 1
        for (int h = wid - 9; h < 2; h++) {
          const int q = h * 24 + min(lane, 23);
          const uint4* gp = wid == 10 ? &P.s->st1[rb * 8 * 48 + lane] : &P.s->csp[cg * 8 * 48 + q];
          uint4 v[8];
#pragma unroll 1
          for (int it = 0;; it++) {
            uint32_t x = 0;
#pragma unroll
            for (int i = 0; i < 8; i++) v[i] = ld_rlx4(gp + i * 48);
#pragma unroll
            for (int i = 0; i < 8; i++) { v[i].x ^= tag; v[i].y ^= tag; v[i].z ^= tag; v[i].w ^= tag; x |= v[i].x | v[i].y | v[i].z | v[i].w; }
            if (!__any_sync(~0u, (x & 255) != 0)) break;
            SPINCHK(it, 3);
          }
          if (wid == 10) {
#pragma unroll
            for (int i = 0; i < 8; i++) {
              const float m0 = __uint_as_float(v[i].x), m1 = __uint_as_float(v[i].z), dm = 0.5f * (m0 - m1);
              sts2f(sm + OFF_STATS + (i * 32 + lane) * 8, -0.5f * (m0 + m1), rsq(fmaf(dm, dm, 0.5f * (__uint_as_float(v[i].y) + __uint_as_float(v[i].w))) + 1e-5f));
            }
          } else {
            float s4[4] = {0.f, 0.f, 0.f, 0.f};
#pragma unroll
            for (int i = 0; i < 8; i++) { s4[0] += __uint_as_float(v[i].x); s4[1] += __uint_as_float(v[i].y); s4[2] += __uint_as_float(v[i].z); s4[3] += __uint_as_float(v[i].w); }
            sts4(sm + OFF_COLSUM + q * 16, __float_as_uint(s4[0]), __float_as_uint(s4[1]), __float_as_uint(s4[2]), __float_as_uint(s4[3]));
          }
        }
        mbar_arrive(mb + B_AUX);
      }
      TS(2);
      IDS(get_b());
      const uint64_t btab = rank ? BT1 : BT0;
      if (wid == 9) {
        {
          const uint4 sv = make_uint4(SENT, SENT, SENT, SENT);
          uint4* y = &P.s->ybuf[b * NFFN * 2 + lane];
#pragma unroll
          for (int i = 0; i < 7; i++) y[i * 32] = sv;
          if (lane < 16) P.s->st2[b * 16 + lane] = make_uint4(0, 0, 0, 0); else P.s->hsel[b * 16 + lane - 16] = sv;
          if (b < 8) P.s->cand[b * 32 + lane] = SENT;
          fence_gpu();
          __syncwarp();
          if (lane == 0) mbar_arrive(mb + B_LATE);
        }
        TS(3);
        TS_DUMP(2);
        {
          const int p = lane & 15, sl = p % 7;
          const bool sliced = p > 0 && p < 9;
          const uint32_t c = sliced ? ((p - 1) >> 1) * 16 | ((hf ^ 1) * 8 + ((p - 1) & 1) * 4) << 8 | 128 << 16 : (hf * 8 + src_of(p)) << 8;
          const uint32_t ev = mb + (p < BHOLD ? B_EVA : p < 4 ? B_KVP : p < 6 ? B45 : B_E + 8 * ((p < 7 ? 1 : p - 4) & 7) + (p >= 12));
          mbar_wait(mb + B_EVA, 0);
          sts4(sm + OFF_COLSUM + 512 + p * 16, sm + unit_of(btab, sl), mb + B_BF + 8 * sl, c, ev);
          __syncwarp();
        }
        if (elect_one()) {
#pragma unroll 1
          for (int p = 0; p < 16; p++) {
            const uint4 e = lds4(sm + OFF_COLSUM + 512 + p * 16);
            if (p == 4) mbar_wait(mb + B_WR, 0);
            mbar_wait(e.w & ~1u, e.w & 1);
            mbar_expect_tx(e.y, p > 1 ? 4 * UNIT : 2 * UNIT);
            tma_4d(e.x, (const CUtensorMap*)((const char*)&T.m[M_O] + (e.z >> 16)), 0, e.z & 255, (e.z >> 8) & 255, c3 * 2, e.y, p >= EFB);
          }
          PTS(16);
        }
      } else {
        const uint32_t* wp = (const uint32_t*)(P.wr + c3 * 128) + (lane & 7) * 8 + (lane >> 3);
        const uint32_t w0 = ld_rlx(wp), w1 = ld_rlx(wp + 4);
#pragma unroll 1
        for (int i = 0; i < 4; i++) { l2_prefetch((const char*)P.wo + b * 16384 + i * 4096 + lane * 128); __nanosleep(300); }
        const int p = lane & 15, p2 = min(p + 2, 15);
        const uint32_t t0 = dlo(sb, 8192) + (unit_of(btab, p % 7) >> 4), t1 = ring_of(p + 1, lane >> 4), t2 = mb + B_BF + 8 * (p2 % 7);
        mbar_wait(mb + B_EVB, 0);
        bar_sync(14, 64);
        sts2f(sm + OFF_COLSUM + lane * 8, __uint_as_float(w0), __uint_as_float(w1));
        sts1(sm + OFF_COLSUM + 256 + lane * 4, 0x3F803F80u);
        sts4(sm + OFF_STATS + lane * 16, t0, t1, t2, (p2 / 7) & 1);
        __syncwarp();
        if (elect_one()) {
          mbar_arrive(mb + B_WR);
          if (fidx >= 0) {
            mbar_expect_tx(mb + B_FFN, 131072); mbar_expect_tx(mb + B_FFD, 32768);
            uint64_t gt = rank ? GT1 : GT0;
#pragma unroll 1
            for (int f = 0; f < 8; f++, gt >>= 5) {
              uint32_t d0 = sm + unit_of(gt, 0);
              asm volatile("" : "+r"(d0));
              if (f == 3) mbar_wait(mb + B_GATE, 1);
              mbar_wait(mb + (f < FEARLY ? B_KVB : B_E + (f < 3 ? 3 + 2 * f : (f + 5) >> 1) * 8), f < FEARLY || f >= 3);
              tma_3d(d0, &T.m[M_G], fidx * 32, f * 128, 0, mb + B_FFN, EFF);
              tma_3d(d0 + UNIT, &T.m[M_U], fidx * 32, f * 128, 0, mb + B_FFN, EFF);
            }
            PTS(17);
            mbar_expect_tx(mb + B_KVP, 32768);
#pragma unroll
            for (int w = 0; w < 8; w++) {
              if (w == 2) mbar_wait(mb + B_E + 56, 1);
              if (w == 6) mbar_wait(mb + B_E16, 1);
              if (w == DLATE) mbar_wait(mb + B_EVA, 1);
              tma_3d(sm + ((DT0 >> (5 * w)) & 31) * UNIT + (w < 4 ? 0 : w < 6 ? 14 * UNIT : -14 * UNIT) * rank, &T.m[M_D], 0, fidx * 32, 2 * w, mb + (w < 4 ? B_FFD : B_KVP), EFF);
            }
            PTS(18);
          }
        }
      }
    }
    __syncwarp();
    IDS(get_b());
    mbar_wait(mb + B_EVB, 0);
    mbar_wait(mb + B_OUT, 0);
    const float2 cf = lds2f(sm + OFF_STATS + 64);
    const int cand0 = 2047 - (__float_as_int(cf.x) & 2047), cand1 = 2047 - (__float_as_int(cf.y) & 2047), rr = lane >> 4;
    auto store_rows = [&](int tr, bool on) {
      const uint4 v = lds4(sm + 4 * UNIT + (tr >> 6) * STAGE_B + (tr & 63) * 256 + (((lane & 15) ^ (tr & 7)) << 4));
      const float2 pr = lds2f(sm + OFF_LNP + tr * 8);
      const float f = 1.f + pr.x, n = pr.y;
      if (on) st_out(P.out + (size_t)(rb * 256 + hf * 64 + tr + (tr & 64)) * D_ + c3 * 128 + (lane & 15) * 8,
          make_uint4(pack2(fmaf(bf_lo(v.x), f, n), fmaf(bf_hi(v.x), f, n)), pack2(fmaf(bf_lo(v.y), f, n), fmaf(bf_hi(v.y), f, n)),
                     pack2(fmaf(bf_lo(v.z), f, n), fmaf(bf_hi(v.z), f, n)), pack2(fmaf(bf_lo(v.w), f, n), fmaf(bf_hi(v.w), f, n))));
    };
    if (wid == 8) {
      mbar_wait(mb + B_SEL, 0);
      const float2 sel = lds2f(sm + OFF_STATS + 80);
      const uint32_t kc = __float_as_uint(rr ? cf.y : cf.x);
      const int c = rr ? cand1 : cand0;
      store_rows(((c >> 1) & 64) + (c & 63), kc != __float_as_uint(sel.x) && kc != __float_as_uint(sel.y) && (c >> 8) == rb && ((c >> 6) & 1) == hf);
    } else if (wid < 9 + NOUTW) {
      if (ODELAY) { const uint32_t t0 = clock64(); while ((uint32_t)clock64() - t0 < ODELAY) {} }
#pragma unroll OUNR
      for (int tr = (wid - 9) * 2 + rr; tr < 128; tr += 2 * NOUTW) {
        const int row = rb * 256 + hf * 64 + tr + (tr & 64);
        store_rows(tr, row != cand0 && row != cand1 && !NOOUT);
      }
      if (wid == 9 && lane == 0) { PTS(14); SPANS(2); }
    }
  } else {
    asm volatile("setmaxnreg.inc.sync.aligned.u32 224;");
    const int t128 = tid & 127, warp = wid & 3, g = lane >> 2, t = lane & 3;
    const uint32_t sk = rank * (2 * STAGE_B);
    uint4 ost[2][4];
    uint4 abuf[3][4];
    uint4* od1;
    const uint4* ain;
    int b1;
    const uint32_t eb = (lane << 24) + bars + B_E;
    float acc[64];
    uint4 wb[4];
    uint32_t hp[32];
    {
      float acc1[96], acc0[96];
#pragma unroll
      for (int i = 0; i < 96; i++) { acc0[i] = 0.f; acc1[i] = 0.f; }
      const uint32_t xo0 = dlo(sb, 16) + (wg * 2 + hf) * 512, xo1 = dlo(sb, 16) + (wg * 2 + (hf ^ 1)) * 512;
      constexpr uint32_t ST = STAGE_B >> 4, WD = dlo(sb + 49152, 8192), WV = dlo(sb + 32768, 8192);
      const uint32_t eb0 = (t128 << 24) + bars + B_EMPTY;
#pragma unroll 1
      for (int kb = 0; kb < 12; kb++) {
        const int s = kb & 3;
        mbar_wait(mb + B_FULL + 8 * s, (kb >> 2) & 1);
        if (kb == 0) TS(1);
        if (kb == 0 && !wg) bar_sync(2, 256);
        pin(acc0); pin(acc1);
        wg_fence();
#pragma unroll
        for (int k = 0; k < 4; k++) {
          const uint64_t db = dsc<1024, 1>(WV + s * ST + k * 128);
          wgmma_n192_ss<0, 1, 0>(acc0, dsc<1024, 1>(s * ST + xo0 + k * 2), db, 1);
          wgmma_n192_ss<0, 1, 0>(acc1, dsc<1024, 1>(s * ST + xo1 + k * 2), db, 1);
        }
        wg_commit();
        if (kb == 0 && wg) bar_arrive(2, 256);
        wg_wait<0>();
        pin(acc0); pin(acc1);
        if (t128 < 2 && kb < 11) mbar_arrive_rem(eb0 + 8 * s);
      }
      mbar_wait(mb + B_FULL, 1);
      if (t128 < 8) mbar_arrive_rem(t128 < 4 ? (wg << 24) + bars + B_EMPTY + 24 : mb + B_EMPTY);
      TS(2);
      mbar_wait(mb + B_AUX, 0);
      float rs[2][2], nm[2][2];
#pragma unroll
      for (int m = 0; m < 2; m++)
#pragma unroll
        for (int h = 0; h < 2; h++) { const float2 v = lds2f(sm + OFF_STATS + ((wg * 2 + (m ^ hf)) * 64 + warp * 16 + h * 8 + g) * 8); nm[m][h] = v.x; rs[m][h] = v.y; }
      auto center = [&](auto jc) {
        constexpr int j = decltype(jc)::value;
        const float2 cs = lds2f_o<sb + OFF_COLSUM + j * 32>(own + t * 8);
        acc1[j * 4] = fmaf(nm[1][0], cs.x, acc1[j * 4]); acc1[j * 4 + 1] = fmaf(nm[1][0], cs.y, acc1[j * 4 + 1]);
        acc1[j * 4 + 2] = fmaf(nm[1][1], cs.x, acc1[j * 4 + 2]); acc1[j * 4 + 3] = fmaf(nm[1][1], cs.y, acc1[j * 4 + 3]);
        acc0[j * 4] = fmaf(nm[0][0], cs.x, acc0[j * 4]); acc0[j * 4 + 1] = fmaf(nm[0][0], cs.y, acc0[j * 4 + 1]);
        acc0[j * 4 + 2] = fmaf(nm[0][1], cs.x, acc0[j * 4 + 2]); acc0[j * 4 + 3] = fmaf(nm[0][1], cs.y, acc0[j * 4 + 3]);
      };
      static_for<0, 16>(center);
      const float L2E = 1.4426950408889634f;
      uint32_t fa = sm + sk + (warp * 16 + (lane & 15)) * 128 + (((lane >> 4) ^ (lane & 7)) << 4);
      asm volatile("" : "+r"(fa));
      uint32_t xf0[32], xf1[32];
      auto pack_kv = [&](float (&a)[96], int i, float r0, float r1, uint32_t* o, uint32_t z = 0) {
        const float* p = a + i * 8;
        if (i < 4) {
          const float rl0 = __uint_as_float(__float_as_uint(r0 * L2E) | z), rl1 = __uint_as_float(__float_as_uint(r1 * L2E) | z);
          const uint32_t q0 = pack2(r0, r0), q1 = pack2(r1, r1);
          o[0] = phi2(p[0], p[1], rl0, q0); o[1] = phi2(p[2], p[3], rl1, q1); o[2] = phi2(p[4], p[5], rl0, q0); o[3] = phi2(p[6], p[7], rl1, q1);
        } else {
          r0 = __uint_as_float(__float_as_uint(r0) | z); r1 = __uint_as_float(__float_as_uint(r1) | z);
          o[0] = pack2(p[0] * r0, p[1] * r0); o[1] = pack2(p[2] * r1, p[3] * r1); o[2] = pack2(p[4] * r0, p[5] * r0); o[3] = pack2(p[6] * r1, p[7] * r1); }
      };
      auto swap_kv = [&](uint32_t (&xf)[32], uint32_t tile, int i, const uint32_t* o, uint32_t z = 0) {
        const uint32_t ad = (fa + tile * UNIT) ^ ((i & 3) << 5);
        if (i < 4) { ldsm4_o<0>(ad, xf[i * 4], xf[i * 4 + 1], xf[i * 4 + 2], xf[i * 4 + 3]); stsm4_o<0>(ad, o[0], o[1], o[2], o[3]); }
        else { ldsm4_o<STAGE_B>(ad | z, xf[i * 4], xf[i * 4 + 1], xf[i * 4 + 2], xf[i * 4 + 3]); stsm4_o<STAGE_B>(ad, o[0], o[1], o[2], o[3]); }
      };
      auto mma_q = [&](float (&a)[96], uint32_t (&xf)[32], uint32_t xo, bool ss) {
        const uint32_t r = __shfl_sync(~0u, sk >> 4, 0), o = 2 * ST - r;
#pragma unroll
        for (int j = 0; j < 8; j++) {
          if (ss) wgmma_n64_ss<0, 1, 64>(a, dsc<1024, 1>(o + (j >> 2) * ST + xo + (j & 3) * 2), dsc<1024, 1>(WD + o + (j >> 2) * ST + (j & 3) * 128), 1);
          else wgmma_n64_rs<1, 64>(a, xf[j * 4], xf[j * 4 + 1], xf[j * 4 + 2], xf[j * 4 + 3], dsc<1024, 1>(WD + r + (j >> 2) * ST + (j & 3) * 128), 1);
        }
      };
      auto epi_q = [&](float (&a)[96], float r0, float r1, uint32_t (&o)[16]) {
        const float rl0 = r0 * 1.44269511f, rl1 = r1 * 1.44269511f;
        const uint32_t q0 = dup2(r0), q1 = dup2(r1);
#pragma unroll
        for (int j = 0; j < 8; j++) { o[j * 2] = phi2(a[64 + j * 4], a[65 + j * 4], rl0, q0); o[j * 2 + 1] = phi2(a[66 + j * 4], a[67 + j * 4], rl1, q1); }
        pinu(o);
      };
      auto mma_kv1 = [&](float (&a)[96], uint32_t xo, int s) {
#pragma unroll
        for (int k = 0; k < 4; k++) wgmma_n128_ss<0, 1, 0>(a, dsc<1024, 1>(s * ST + xo + k * 2), dsc<1024, 1>(WV + s * ST + k * 128), 1);
      };
      auto epi_kv = [&](float (&a)[96], uint32_t (&xf)[32], uint32_t tile, float r0, float r1) {
        uint32_t o[8][4];
#pragma unroll
        for (int j = 3; j >= 0; j--) {
          const uint32_t z = j < 3 ? (xf[(j + 5) * 4] | (j < 2 ? o[j + 2][0] | o[j + 6][0] : 0)) & blockIdx.y : 0;
          pack_kv(a, j + 4, r0, r1, o[j + 4], z);
          swap_kv(xf, tile, j + 4, o[j + 4], (o[j + 4][2] | o[j + 4][3]) & blockIdx.y);
          pack_kv(a, j, r0, r1, o[j], z);
          swap_kv(xf, tile, j, o[j]);
        }
      };
      bar_arrive(15, 288);
      mbar_wait(mb + B_FULL + 8, 1);
      if (!wg) bar_sync(3, 256);
      pinr<0, 64>(acc0); pinr<0, 64>(acc1);
      wg_fence();
      mma_kv1(acc1, xo1, 0); mma_kv1(acc0, xo0, 0); mma_kv1(acc1, xo1, 1);
      if (GSPLIT == 2) mma_kv1(acc0, xo0, 1);
      mbar_wait(mb + B_FULL + 16, 1);
      wg_fence();
      mma_kv1(acc1, xo1, 2);
      mbar_wait(mb + (wg ? B_FULL + 24 : B_F15), wg);
      wg_fence();
      mma_kv1(acc1, xo1, 3);
      wg_commit();
      bar_arrive(4 - wg, 256);
      static_for<16, 24>(center);
      pinr<64, 96>(acc0); pinr<64, 96>(acc1);
      mbar_wait(mb + B_FULL + 8, 1);
      wg_wait<0>();
      pinr<0, 64>(acc0); pinr<0, 64>(acc1);
      epi_kv(acc1, xf1, wg * 2 + (hf ^ 1), rs[1][0], rs[1][1]);
      pinu(xf1);
      bar_sync(5 - wg, 256);
      wg_fence();
      if (GSPLIT == 1) mma_kv1(acc0, xo0, 1);
      mma_kv1(acc0, xo0, 2); mma_kv1(acc0, xo0, 3);
      wg_commit();
      mma_q(acc1, xf1, xo1, false);
      wg_commit();
      if (wg) bar_arrive(5, 256);
      else { fence_async_smem(); bar_arrive(6, 256); }
      if (tid >= 240) sts4(sm + OFF_STATS + (tid & 15) * 128 + ((tid & 7) << 4), 0x3F803F80u, 0x3F803F80u, 0x3F803F80u, 0x3F803F80u);
      wg_wait<1>();
      pinr<0, 64>(acc0);
      if (lane == 0) mbar_arrive(mb + B_EVA);
      TS(6);
      epi_kv(acc0, xf0, wg * 2 + hf, rs[0][0], rs[0][1]);
      fence_async_smem();
      pinu(xf0);
      if (!wg) bar_arrive(7, 256);
      const uint32_t kvb = 2 * STAGE_B + (2 + (hf ^ 1)) * UNIT - sk;
      b1 = get_b();
      od1 = &P.s->obuf[(((b1 >> 4) * 4 + wg * 2 + (hf ^ 1)) * 64 + (b1 & 7)) * 128 + t128];
      ain = &P.s->obuf[((b1 >> 4) * 4 + wg * 2 + hf) * 64 * 128 + t128];
      uint32_t ka0 = sm + kvb + wid * 1024 + (lane & 7) * 128 + (((lane >> 3) ^ (lane & 7)) << 4), ka1 = sm + kvb + wid * 1024 + (t * 2 + g) * 128 + ((4 ^ (t * 2 + g)) << 4);
      const uint8_t* g0 = smem_raw + sk + STAGE_B + tid * 16, *g1 = smem_raw + sk + UNIT + g * 256 + wid * 32 + t * 8;
      const uint8_t* h0 = (const uint8_t*)&P.s->kvp[(b1 & 15) * 8 * 256 + tid], *h1 = (const uint8_t*)&P.s->zp[((b1 & 15) * 8 + g) * 16] + wid * 32 + t * 8;
      asm volatile("" : "+r"(ka0), "+r"(ka1), "+l"(g0), "+l"(g1), "+l"(h0), "+l"(h1), "+l"(od1));
      if (wg) {
        float ka[36];
        auto mma_kv = [&](uint32_t tile, int i, int acc) {
          const uint32_t o = (sk >> 4) + tile * 512 + i * 128;
          wgmma_n72_ss<1, 1, 0>(ka, dsc<1024, 1>(dlo(sb, 8192) + o), dsc<1024, 1>(dlo(sb + STAGE_B, OFF_STATS - STAGE_B) + o * (1u - (1u << 16))), acc);
        };
#pragma unroll
        for (int i = 0; i < 36; i++) ka[i] = 0.f;
        bar_sync(6, 256);
        wg_fence();
#pragma unroll
        for (int i = 0; i < 4; i++) {
          mma_kv(2, i, i); mma_kv(3, i, 1); mma_kv(hf ^ 1, i, 1);
#pragma unroll
          for (int j = 2 * i; j < 2 * i + 2; j++)
            wgmma_n64_rs<1, 64>(acc0, xf0[j * 4], xf0[j * 4 + 1], xf0[j * 4 + 2], xf0[j * 4 + 3], dsc<1024, 1>(WD + (sk >> 4) + (j >> 2) * ST + (j & 3) * 128), 1);
        }
        const int kq = (b1 & 15) * 8 + (b1 >> 4);
        uint4* dst = &P.s->kvp[kq * 256 + warp * 64 + lane];
        uint32_t* dz = (uint32_t*)&P.s->zp[kq * 16] + warp * 16 + g + t * 8;
        asm volatile("" : "+l"(dst), "+l"(dz));
        mbar_wait(mb + B_LATE, 0);
        bar_sync(7, 256);
        wg_fence();
#pragma unroll
        for (int i = 0; i < 4; i++) mma_kv(hf, i, 1);
        wg_commit();
        bar_arrive(8, 256);
        wg_wait<0>();
        pin(ka); pinr<64, 96>(acc0);
        uint32_t kw[8];
#pragma unroll
        for (int i = 0; i < 8; i++) {
          const int j = (i & 3) * 4 + (i >> 2) * 2;
          asm("{\n.reg .pred p;\nsetp.ne.u32 p, %5, 0;\n@p cvt.rn.bf16x2.f32 %0, %4, %3;\n@!p cvt.rn.bf16x2.f32 %0, %2, %1;\n}"
              : "=r"(kw[i]) : "f"(ka[j]), "f"(ka[j + 1]), "f"(ka[16 + j]), "f"(ka[17 + j]), "r"(warp & 2));
        }
        st_rlx4(dst, make_uint4(kw[0], kw[1], kw[2], kw[3]));
        st_rlx4(dst + 32, make_uint4(kw[4], kw[5], kw[6], kw[7]));
        if (t < 2) st_rlx(dz, __float_as_uint(t ? ka[34] : ka[32]));
        if (lane == 0) mbar_arrive(mb + B_EVB);
        TS(8);
        const uint32_t t1 = clock64();
        while ((uint32_t)clock64() - t1 < SDELAY) {}
      } else {
        bar_sync(8, 256);
        wg_fence();
        mma_q(acc0, xf0, xo0, false);
      }
      if (!wg) bar_sync(9, 256);
      wg_fence();
      mma_q(acc1, xf1, xo1, true);
      wg_commit();
      if (wg) bar_arrive(9, 256); else mma_q(acc0, xf0, xo0, true);
      wg_commit();
      wg_wait<1>();
      pinr<64, 96>(acc1);
      TS(7);
      uint32_t pq[16];
      epi_q(acc1, rs[1][0], rs[1][1], pq);
      bar_sync(11 + wg + zero_after(pq), 128);
      if (wg) {
        wg_fence();
        mma_q(acc0, xf0, xo0, true);
        wg_commit();
      }
      TS(5);
      {
        uint4 gv[8]; uint2 gz;
        uint32_t m[8], a[4];
        float z0, z1;
#pragma unroll
        for (int s = 0; s < 8; s++) { m[s] = ~blockIdx.y; asm volatile("" : "=r"(gv[s].x), "=r"(gv[s].y), "=r"(gv[s].z), "=r"(gv[s].w), "+r"(m[s])); }
        mbar_wait(mb + B_KVP, 0);
        TS(28);
#pragma unroll 1
        for (int it = 0; it < SPIN_LIMIT; it++) {
          gz = ld_gen2(g1);
#pragma unroll
          for (int s = 0; s < 8; s++) if (m[s] == SENT) gv[s] = ld_gen4(g0 + s * 4096);
          g0 = h0; g1 = h1;
          uint32_t mm = max(gz.x, gz.y);
          z0 = __uint_as_float(gz.x); z1 = __uint_as_float(gz.y);
#pragma unroll
          for (int o = 4; o < 32; o <<= 1) { z0 += __shfl_xor_sync(~0u, z0, o); z1 += __shfl_xor_sync(~0u, z1, o); }
#pragma unroll
          for (int s = 0; s < 8; s++) m[s] = max4(0, gv[s]);
#pragma unroll
          for (int s = 0; s < 8; s += 2) mm = __vimax3_u32(mm, m[s], m[s + 1]);
          a[0] = hadd2(hadd2(hadd2(gv[0].x, gv[1].x), hadd2(gv[2].x, gv[3].x)), hadd2(hadd2(gv[4].x, gv[5].x), hadd2(gv[6].x, gv[7].x)));
          a[1] = hadd2(hadd2(hadd2(gv[0].y, gv[1].y), hadd2(gv[2].y, gv[3].y)), hadd2(hadd2(gv[4].y, gv[5].y), hadd2(gv[6].y, gv[7].y)));
          a[2] = hadd2(hadd2(hadd2(gv[0].z, gv[1].z), hadd2(gv[2].z, gv[3].z)), hadd2(hadd2(gv[4].z, gv[5].z), hadd2(gv[6].z, gv[7].z)));
          a[3] = hadd2(hadd2(hadd2(gv[0].w, gv[1].w), hadd2(gv[2].w, gv[3].w)), hadd2(hadd2(gv[4].w, gv[5].w), hadd2(gv[6].w, gv[7].w)));
          pinu(a);
          if (!__any_sync(~0u, mm == SENT)) break;
          TSV(20, 1);
        }
        TS(23);
        wg_wait<0>();
        pinr<64, 96>(acc0);
        if (lane == 0) mbar_arrive(mb + B_KVB);
        stsm4(ka0, a[0], a[1], a[2], a[3]);
        const uint32_t zz = pack2(g ? z1 : z0, g ? z1 : z0);
        if (lane < 8) sts4(ka1, zz, zz, zz, zz);
        fence_async_smem();
        bar_sync(1, 256);
      }
      TS(21);
      auto make_o = [&](uint4 (&o)[4], auto first) {
        float oa[2][20];
        wg_fence();
#pragma unroll
        for (int ks = 0; ks < 4; ks++)
          wgmma_n40_rs<1, 0>(oa[ks >> 1], pq[ks * 4], pq[ks * 4 + 1], pq[ks * 4 + 2], pq[ks * 4 + 3], dsc<1024, 1>(dlo(sb, 8192) + (kvb >> 4) + ks * 128), ks & 1);
        wg_commit();
        if constexpr (!decltype(first)::value) {
          pinu(xf0);
#pragma unroll
          for (int q = 0; q < 32; q++) { acc[q * 2] = bf_lo(xf0[q]); acc[q * 2 + 1] = bf_hi(xf0[q]); }
          pin(acc);
          if (!R1MID) {
            mbar_wait(mb + B_F15, 1);
#pragma unroll
            for (int i = 0; i < 4; i++) abuf[1][i] = ld_rlx4(ain + i * 128);
            TS(3);
          }
          mbar_wait(mb + B_BF, 0);
        }
        wg_wait<0>();
        pin(oa[0]); pin(oa[1]);
        if (decltype(first)::value && lane < 2) mbar_arrive_rem(eb);
#pragma unroll
        for (int h = 0; h < 2; h++) {
          const float (&d)[20] = oa[h];
          const float i0 = rcp(d[16] + 1e-6f), i1 = rcp(d[18] + 1e-6f);
#pragma unroll
          for (int k2 = 0; k2 < 2; k2++) {
            o[h * 2 + k2] = make_uint4(pack2(d[k2 * 8] * i0, d[k2 * 8 + 1] * i0), pack2(d[k2 * 8 + 2] * i1, d[k2 * 8 + 3] * i1),
                                       pack2(d[k2 * 8 + 4] * i0, d[k2 * 8 + 5] * i0), pack2(d[k2 * 8 + 6] * i1, d[k2 * 8 + 7] * i1));
            if (decltype(first)::value && !h && k2 <= AFIRST) st_rlx4(od1 + k2 * 1024, o[k2]);
            if (decltype(first)::value && !h && k2 == AFIRST) { sched_fence(); TS(24); }
          }
        }
      };
      make_o(ost[1], std::true_type{});
      if (!AFIRST) { st_rlx4(od1 + 1024 + ((ost[1][2].x | ost[1][3].w) & blockIdx.y), ost[1][1]); sched_fence(); }
      auto read1 = [&](uint32_t z) {
        mbar_wait(mb + B_F15 + z, 1);
#pragma unroll
        for (int i = 0; i < 4; i++) abuf[1][i] = ld_rlx4(ain + i * 128);
        TS(3);
      };
      if (R1MID) {
        const float rl0 = rs[0][0] * 1.44269511f, rl1 = rs[0][1] * 1.44269511f;
        const uint32_t q0 = dup2(rs[0][0]), q1 = dup2(rs[0][1]);
        uint32_t z = 0;
#pragma unroll
        for (int j = 0; j < 8; j++) {
          pq[j * 2] = phi2(acc0[64 + j * 4], acc0[65 + j * 4], rl0, q0); pq[j * 2 + 1] = phi2(acc0[66 + j * 4], acc0[67 + j * 4], rl1, q1);
          if (j < R1MID) z |= pq[j * 2] | pq[j * 2 + 1];
          if (j == R1MID - 1) read1(z & 0x80008000u);
        }
      } else epi_q(acc0, rs[0][0], rs[0][1], pq);
      if (AEARLY == 1) { st_rlx4(od1 + 2048, ost[1][2]); st_rlx4(od1 + 3072, ost[1][3]); }
      make_o(ost[0], std::false_type{});
    }
   {
    IDS(b1);
    const int mb3 = rb * 4 + wg * 2 + hf;
    uint4* rp = &P.s->st2[mb3 * 64 + warp * 16 + g + t * 8];
    {
      uint4* const od0 = &P.s->obuf[(mb3 * 64 + 32 + s3 * 4) * 128 + t128];
#pragma unroll
      for (int i = 0; i < 4; i++) pin4(ost[0][i]);
      wg_fence();
#pragma unroll
      for (int k = 0; k < 4; k++) wgmma_n128_rs<1, 0>(acc, ost[0][k].x, ost[0][k].y, ost[0][k].z, ost[0][k].w, dsc<1024, 1>(dlo(sb + 4 * UNIT, 8192) + k * 128), 1);
      wg_commit();
      TS(29);
      if (AEARLY == 0) { st_rlx4(od1 + 2048, ost[1][2]); st_rlx4(od1 + 3072, ost[1][3]); }
      if (AEARLY == 2) st_rlx4(od1 + 2048, ost[1][2]);
      uint32_t la = sm + t128 * 16, ev = eb + 8;
      asm volatile("" : "+r"(la), "+r"(ev));
      auto fetch = [&](uint32_t off, uint4 (&a)[4]) { const uint32_t ra = la + off; a[0] = lds4_o<0>(ra); a[1] = lds4_o<2048>(ra); a[2] = lds4_o<4096>(ra); a[3] = lds4_o<6144>(ra); };
      auto check = [&](int p, uint4 (&a)[4]) {
        if (__any_sync(~0u, max(max4(max4(0, a[0]), a[1]), max4(max4(0, a[2]), a[3])) == SENT)) {
          int pl = p; asm volatile("" : "+r"(pl));
          const uint4* q = ain + frag_of(pl);
#pragma unroll 1
          for (int it = 0;; it++) {
            uint32_t mm = 0;
#pragma unroll
            for (int i = 0; i < 4; i++) { const uint32_t m = max4(0, a[i]); mm = max(mm, m); if (m == SENT) a[i] = ld_rlx4(q + i * 128); }
            if (!__any_sync(~0u, mm == SENT)) break;
            TSV(27, p < 3 ? 1 : p < 5 ? 100 : 10000);
            SPINCHK(it, 5);
          }
        }
        if (lane < 2) mbar_arrive_rem(ev);
        ev = (ev & ~0x38u) | ((ev + 8) & 0x38u);
      };
      auto mma = [&](int p, uint32_t bs, uint4 (&a)[4]) {
#pragma unroll
        for (int i = 0; i < 4; i++) pin4(a[i]);
        wg_fence();
#pragma unroll
        for (int k = 0; k < 4; k++) wgmma_n128_rs<1, 0>(acc, a[k].x, a[k].y, a[k].z, a[k].w, dsc<1024, 1>(bs + k * 128), 1);
        wg_commit();
      };
      uint32_t ta = sm + OFF_STATS + wg * 256 + 48;
      mbar_wait(mb + B_WR, 0);
      uint4 tp = lds4(ta);
      mbar_wait(mb + B_BF + 8, 0);
      check(1, abuf[1]);
      if (P1F) { mbar_wait(mb + B_BF + 16, 0); fetch(ring_of(2, wg), abuf[2]); }
      mma(1, dlo(sb + 11 * UNIT, 8192), abuf[1]);
      if (!P1F) { mbar_wait(mb + B_BF + 16, 0); fetch(ring_of(2, wg), abuf[2]); }
      TS(25);
      if (AEARLY == 2) st_rlx4(od1 + 3072, ost[1][3]);
      st_rlx4(od0, ost[0][0]); st_rlx4(od0 + 128, ost[0][1]);
      check(2, abuf[2]);
      mbar_wait(mb + B_BF + 24, 0);
      fetch(ring_of(3, wg), abuf[0]);
      mma(2, dlo(sb + 18 * UNIT, 8192), abuf[2]);
      st_rlx4(od0 + 256, ost[0][2]); st_rlx4(od0 + 384, ost[0][3]);
      wg_wait<2>();
      check(3, abuf[0]);
      mbar_wait(mb + B_BF + 32, 0);
      TS(26);
#pragma unroll 1
      for (int p = 3; p < 15; p += 3) {
        static_for<0, 3>([&](auto jc) {
          constexpr int j = decltype(jc)::value;
          const uint4 tc = tp;
          const uint32_t bs = __shfl_sync(~0u, tc.x, 0);
          wg_wait<1>();
#pragma unroll
          for (int i = 0; i < 4; i++) pin4(abuf[(j + 1) % 3][i]);
          tp = lds4_o<16 * j + 16>(ta);
          fetch(tc.y, abuf[(j + 1) % 3]);
          mma(p + j, bs, abuf[j]);
          if (!CHKF) mbar_wait(tc.z, tc.w);
          check(p + j + 1, abuf[(j + 1) % 3]);
          if (CHKF) mbar_wait(tc.z, tc.w);
        });
        ta += 48;
      }
      {
        const uint32_t wa0 = sm + OFF_COLSUM + ((g & 1) ? t * 64 : 256);
        wb[0] = lds4_o<0>(wa0); wb[1] = lds4_o<16>(wa0); wb[2] = lds4_o<32>(wa0); wb[3] = lds4_o<48>(wa0);
      }
      mma(15, __shfl_sync(~0u, tp.x, 0), abuf[0]);
      wg_wait<2>();
      if (lane == 0) mbar_arrive(mb + B_E16);
      asm volatile("" : "+l"(rp));
      sched_fence();
      wg_wait<0>();
      pin(acc);
#pragma unroll
      for (int i = 0; i < 4; i++) { pin4(abuf[0][i]); pin4(abuf[1][i]); pin4(abuf[2][i]); }
    }
    TS(10);
    {
      float q0[2] = {0.f, 0.f}, q1[2] = {0.f, 0.f}, c[2][4] = {};
#pragma unroll
      for (int j = 0; j < 16; j++) {
        hp[j * 2] = pack2(acc[j * 4], acc[j * 4 + 1]); hp[j * 2 + 1] = pack2(acc[j * 4 + 2], acc[j * 4 + 3]);
        q0[j & 1] = fmaf(acc[j * 4], acc[j * 4], fmaf(acc[j * 4 + 1], acc[j * 4 + 1], q0[j & 1]));
        q1[j & 1] = fmaf(acc[j * 4 + 2], acc[j * 4 + 2], fmaf(acc[j * 4 + 3], acc[j * 4 + 3], q1[j & 1]));
        if (j & 1) {
          const uint32_t a[4] = {hp[j * 2 - 2], hp[j * 2 - 1], hp[j * 2], hp[j * 2 + 1]};
          mma16816(c[(j >> 1) & 1], a, (j & 2) ? wb[j >> 2].z : wb[j >> 2].x, (j & 2) ? wb[j >> 2].w : wb[j >> 2].y);
        }
      }
      const bool od = t & 1;
      float q = (od ? q1[0] + q1[1] : q0[0] + q0[1]) + __shfl_xor_sync(~0u, od ? q0[0] + q0[1] : q1[0] + q1[1], 1);
      q += __shfl_xor_sync(~0u, q, 2);
      asm volatile("{\n.reg .pred p;\nsetp.lt.u32 p, %5, 2;\n@p red.relaxed.gpu.global.add.v4.f32 [%0], {%1,%2,%3,%4};\n}"
                   :: "l"(rp), "f"(od ? c[0][2] + c[1][2] : c[0][0] + c[1][0]), "f"(q), "f"(od ? c[0][3] + c[1][3] : c[0][1] + c[1][1]), "f"(1.f), "r"(t) : "memory");
    }
    TS(11);
    const uint32_t ts = clock64();
    const uint32_t msc = sm + OFF_STATS;
    const uint32_t hst = sm + 4 * UNIT + wg * STAGE_B + warp * 4096, gslot = sm + unit_of(rank ? GT1 : GT0, wid);
    bar_sync(1, 256);
#pragma unroll
    for (int j = 0; j < 8; j++)
      stsm4(hst + (lane & 15) * 256 + (((2 * j + (lane >> 4)) ^ (lane & 7)) << 4), hp[j * 4], hp[j * 4 + 1], hp[j * 4 + 2], hp[j * 4 + 3]);
    uint32_t wa[8][4][4], wd[8][2][4];
    const uint32_t a0 = gslot + ((lane >> 4) * 8 + (lane & 7)) * 64 + ((((lane >> 3) & 1) ^ ((lane >> 1) & 3)) << 4);
    auto load_gu = [&](auto ic) { constexpr int i = decltype(ic)::value; ldsm4t_o<(i >> 2) * 1024 + ((i >> 1) & 1) * 8192>(a0 ^ ((i & 1) << 5), wa[i >> 2][i & 3]); };
    uint32_t tx;
    {
      const int row = rb * 256 + tid;
      const uint4* sp = &P.s->st2[row], *sq = &P.s->st2[row ^ 256];
      const float sw = __uint_as_float((lds1(mb + B_SW) & ~255u) | 128);
      uint4 v[2];
      uint4* d = &P.s->hsel[c3 * 128 + (g & 3) * 32 + ((rb & 6) + (lane >> 4)) * 4 + t];
      uint32_t* dk = &P.s->cand[c3 * 32 + (rb & 6) + (lane >> 4)];
      asm volatile("" : "+l"(d), "+l"(dk));
      if (fidx >= 0) mbar_wait(mb + B_FFN, 0);
      static_for<0, GU1>(load_gu);
      while ((uint32_t)clock64() - ts < SDEL2) {}
      v[0] = ld_rlx4(sp); v[1] = ld_rlx4(sq);
      static_for<GU1, GU2>(load_gu);
#pragma unroll 1
      for (int it = 0; __any_sync(~0u, min(v[0].w, v[1].w) != 0x41000000u) && it < SPIN_LIMIT; it++) {
        if (v[0].w != 0x41000000u) v[0] = ld_rlx4(sp);
        if (v[1].w != 0x41000000u) v[1] = ld_rlx4(sq);
        TSV(22, 1);
      }
      if (lane == 0) mbar_arrive(mb + B_EVA);
      TS(12);
      uint32_t k[2];
#pragma unroll
      for (int i = 0; i < 2; i++) {
        const float mean = __uint_as_float(v[i].x) * (1.f / D_);
        const float rstd = rsq(fmaxf(fmaf(-mean, mean, __uint_as_float(v[i].y) * (1.f / D_)), 0.f) + 1e-5f);
        const uint32_t u = __float_as_uint(rstd * fmaf(-mean, sw, __uint_as_float(v[i].z)));
        k[i] = min(((u ^ ((uint32_t)((int)u >> 31) | 0x80000000u)) & ~2047u), 0xFFFFF000u) | (2047 - (row ^ (i << 8)));
        if (i == 0 && (warp >> 1) == hf) sts2f(sm + OFF_LNP + (wg * 64 + (tid & 63)) * 8, rstd, -mean * rstd);
      }
      const uint32_t hi = max(k[0], k[1]);
      uint32_t m1 = __reduce_max_sync(~0u, hi), m2 = __reduce_max_sync(~0u, hi == m1 ? min(k[0], k[1]) : hi);
      if (lane == 0) sts2f(msc + wid * 8, __uint_as_float(m1), __uint_as_float(m2));
      bar_sync(1, 256);
      const uint32_t kk = lds1(msc + (lane & 15) * 4);
      m1 = __reduce_max_sync(~0u, kk); m2 = __reduce_max_sync(~0u, kk == m1 ? 0 : kk);
      const int c0 = 2047 - (m1 & 2047), c1 = 2047 - (m2 & 2047);
      if ((c0 >> 4) == mb3 * 4 + warp || (c1 >> 4) == mb3 * 4 + warp) {
        const int ra = (lane & 4) ? c1 : c0, rd = (lane & 16) ? c1 : c0;
        uint32_t h0, h1, h2, h3;
        ldsm4_o<0>(hst + (ra & 15) * 256 + ((((lane & 3) * 4 + (lane >> 3)) ^ (ra & 7)) << 4), h0, h1, h2, h3);
        const float2 pr = lds2f(sm + OFF_LNP + (wid * 16 + (rd & 15)) * 8);
        if ((rd >> 4) == mb3 * 4 + warp) {
          st_rlx4(d, make_uint4(pack2(fmaf(bf_lo(h0), pr.x, pr.y), fmaf(bf_hi(h0), pr.x, pr.y)), pack2(fmaf(bf_lo(h1), pr.x, pr.y), fmaf(bf_hi(h1), pr.x, pr.y)),
                                pack2(fmaf(bf_lo(h2), pr.x, pr.y), fmaf(bf_hi(h2), pr.x, pr.y)), pack2(fmaf(bf_lo(h3), pr.x, pr.y), fmaf(bf_hi(h3), pr.x, pr.y))));
          if (!(lane & 15)) st_rlx(dk, (lane & 16) ? m2 : m1);
          st_rlx4(d + 1024, make_uint4(h0, h1, h2, h3));
        }
      }
      tx = clock64();
      if (tid == 0) { sts2f(msc + 64, __uint_as_float(m1), __uint_as_float(m2)); mbar_arrive(mb + B_OUT); }
    }
    TS(13);
    static_for<GU2, 32>(load_gu);
    const uint32_t dl = sm + (wid & 1) * 4096 + ((lane >> 4) * 8 + (lane & 7)) * 128 + ((((lane >> 3) & 1) ^ (lane & 7)) << 4);
    uint32_t da = dl + unit_of(DT0, wid >> 1), db = dl + unit_of(rank ? DT1 : DT0, 4 + (wid >> 1));
    uint32_t* yp = (uint32_t*)&P.s->ybuf[((wid * 8 + t * 2) * NFFN + fidx) * 2] + g;
    uint32_t k1, k2;
    uint2 key;
    {
      float gu[2][4][4];
      uint4 xb[4];
      uint32_t m[4];
      const uint4* xp = &P.s->hsel[wid * 128 + lane];
      const uint2* kp = (const uint2*)&P.s->cand[wid * 32] + t;
      uint32_t ps = gslot + g * 32;
      asm volatile("" : "+l"(xp), "+l"(kp), "+l"(yp), "+r"(db), "+r"(ps));
      if (fidx >= 0) mbar_wait(mb + B_FFD, 0);
      static_for<0, 8>([&](auto ic) { constexpr int i = decltype(ic)::value; ldsm4t_o<(i & 1) * 2048>(da ^ ((i >> 1) << 5), wd[i >> 1][i & 1]); });
      TS(9);
      while ((uint32_t)clock64() - tx < XDELAY) {}
      key = ld_rlx2(kp);
#pragma unroll
      for (int i = 0; i < 4; i++) xb[i] = ld_rlx4(xp + i * 32);
      if (fidx >= 0) mbar_wait(mb + B_KVP, 1);
#pragma unroll 1
      for (int it = 0; it < SPIN_LIMIT; it++) {
#pragma unroll
        for (int i = 0; i < 4; i++) m[i] = max4(0, xb[i]);
        if (!__any_sync(~0u, __vimax3_u32(__vimax3_u32(max(key.x, key.y), m[0], m[1]), m[2], m[3]) == SENT)) break;
        key = ld_rlx2(kp);
#pragma unroll
        for (int i = 0; i < 4; i++) if (m[i] == SENT) xb[i] = ld_rlx4(xp + i * 32);
        TSV(20, 100);
      }
      TS(14);
      const uint32_t hi = max(key.x, key.y);
      k1 = __reduce_max_sync(~0u, hi); k2 = __reduce_max_sync(~0u, hi == k1 ? min(key.x, key.y) : hi);
#pragma unroll
      for (int i = 0; i < 32; i++) gu[i >> 4][(i >> 2) & 3][i & 3] = 0.f;
#pragma unroll
      for (int ks = 0; ks < 8; ks++) {
#pragma unroll
        for (int i = 0; i < 4; i++) mma16816(gu[ks & 1][i], wa[ks][i], (ks & 1) ? xb[ks >> 1].z : xb[ks >> 1].x, (ks & 1) ? xb[ks >> 1].w : xb[ks >> 1].y);
        if (ks == 1) {
          const uint32_t dd = db | (__float_as_uint(gu[1][3][0]) & blockIdx.y);
          static_for<0, 8>([&](auto ic) { constexpr int i = decltype(ic)::value; ldsm4t_o<(i & 1) * 2048>(dd ^ ((i >> 1) << 5), wd[4 + (i >> 1)][i & 1]); });
        }
      }
#pragma unroll
      for (int c = 0; c < 2; c++) {
        const uint32_t kc = c ? key.y : key.x;
        float o[8];
#pragma unroll
        for (int j = 0; j < 8; j++) o[j] = gu[0][(j >> 2) + (j & 1) * 2][(j & 2) + c] + gu[1][(j >> 2) + (j & 1) * 2][(j & 2) + c];
        asm volatile("{\n.reg .pred p;\nsetp.ge.u32 p, %9, %10;\n@p st.shared.v4.f32 [%0], {%1,%2,%3,%4};\n@p st.shared.v4.f32 [%0+16], {%5,%6,%7,%8};\n}"
                     :: "r"(ps + (kc == k1 ? 0 : 256)), "f"(o[0]), "f"(o[1]), "f"(o[2]), "f"(o[3]), "f"(o[4]), "f"(o[5]), "f"(o[6]), "f"(o[7]), "r"(kc), "r"(k2) : "memory");
      }
    }
    TS(4);
    bar_sync(1, 256);
    {
      float g0 = 0.f, g1 = 0.f, u0 = 0.f, u1 = 0.f;
      static_for<0, 8>([&](auto wc) { constexpr int w = decltype(wc)::value;
        constexpr uint32_t o = sb + ((GT0 >> (5 * w)) & 31) * UNIT;
        const uint32_t ad = own + lane * 8 + (w == 0 || w == 7 ? sk : w < 3 ? -sk : 0);
        const float2 a = lds2f_o<o>(ad), c = lds2f_o<o + 256>(ad);
        g0 += a.x; u0 += a.y; g1 += c.x; u1 += c.y; });
      const uint32_t act = pack2(g0 * rcp(1.f + ex2(-1.4426950408889634f * g0)) * u0, g1 * rcp(1.f + ex2(-1.4426950408889634f * g1)) * u1);
      uint32_t bq[4];
#pragma unroll
      for (int i = 0; i < 4; i++) {
        const uint32_t lo = __shfl_sync(~0u, act, 8 * t + i), hi = __shfl_sync(~0u, act, 8 * t + 4 + i);
        bq[i] = __byte_perm(lo, hi, (g & 1) ? 0x7632 : 0x5410);
      }
      TS(16);
      float ya[8][4];
#pragma unroll
      for (int i = 0; i < 8; i++) { ya[i][0] = 0.f; ya[i][1] = 0.f; ya[i][2] = 0.f; ya[i][3] = 0.f; }
#pragma unroll
      for (int ks = 0; ks < 2; ks++)
#pragma unroll
        for (int i = 0; i < 8; i++) mma16816(ya[i], wd[i][ks], bq[ks * 2], bq[ks * 2 + 1]);
#pragma unroll
      for (int h = 0; h < 2; h++) {
        float o[4];
#pragma unroll
        for (int j = 0; j < 4; j++) o[j] = t == 0 ? ya[h * 4][j] : t == 1 ? ya[h * 4 + 1][j] : t == 2 ? ya[h * 4 + 2][j] : ya[h * 4 + 3][j];
        asm volatile("{\n.reg .pred p;\nsetp.ge.s32 p, %3, 0;\n@p st.relaxed.gpu.global.u32 [%0], %1;\n@p st.relaxed.gpu.global.u32 [%0+%4], %2;\n}"
                     :: "l"(yp + h * (64 * NFFN * 8)), "r"(pack2(o[0], o[1])), "r"(pack2(o[2], o[3])), "r"(fidx), "n"(NFFN * 32) : "memory");
      }
    }
    if (tid == 0) { sts2f(msc + 80, __uint_as_float(k1), __uint_as_float(k2)); mbar_arrive(mb + B_SEL); }
    TS(17);
    const uint32_t ty = clock64();
    if (wid < 7) {
      const uint4* yq = &P.s->ybuf[b * NFFN * 2 + tid];
      const uint32_t ks = (tid & 1) ? k2 : k1, grp = 3 - ((ks >> 9) & 3);
      const int fs = grp * 2 + (__shfl_sync(~0u, key.y, grp) == ks);
      const uint32_t* fq = (const uint32_t*)P.s->hsel + (((b >> 4) * 4 + ((b >> 2) & 3)) * 32 + fs * 4 + ((tid >> 2) & 3)) * 4 + (b & 3);
      float gate = rcp(1.f + ex2(-1.4426950408889634f * __uint_as_float(ks ^ (~(uint32_t)((int)ks >> 31) | 0x80000000u))));
      __nv_bfloat16* op = P.out + (size_t)(2047 - (ks & 2047)) * D_ + b * 8 + (tid >> 1);
      asm volatile("" : "+l"(yq), "+l"(fq), "+l"(op), "+f"(gate));
      while ((uint32_t)clock64() - ty < YDELAY) {}
      uint4 v;
      uint32_t fn = 0, fh = 0;
#pragma unroll 1
      for (int it = 0; it < SPIN_LIMIT; it++) {
        v = ld_rlx4(yq);
        if (wid == 0) { fn = ld_rlx(fq); fh = ld_rlx(fq + 4096); }
        TSV(22, 100);
        if (!__any_sync(~0u, max4(max(fn, fh), v) == SENT)) break;
      }
      const float base = (tid & 2) ? bf_hi(fh) + bf_hi(fn) : bf_lo(fh) + bf_lo(fn);
      TS(18);
      const bool p4 = lane & 16, p3 = lane & 8, p2 = lane & 4;
      const uint32_t w0 = __shfl_xor_sync(~0u, p4 ? v.x : v.z, 16), w1 = __shfl_xor_sync(~0u, p4 ? v.y : v.w, 16), o0 = p4 ? v.z : v.x, o1 = p4 ? v.w : v.y;
      const float y0 = bf_lo(o0) + bf_lo(w0), y1 = bf_hi(o0) + bf_hi(w0), y2 = bf_lo(o1) + bf_lo(w1), y3 = bf_hi(o1) + bf_hi(w1);
      const float z0 = (p3 ? y2 : y0) + __shfl_xor_sync(~0u, p3 ? y0 : y2, 8), z1 = (p3 ? y3 : y1) + __shfl_xor_sync(~0u, p3 ? y1 : y3, 8);
      float z = (p2 ? z1 : z0) + __shfl_xor_sync(~0u, p2 ? z0 : z1, 4);
      z += __shfl_xor_sync(~0u, z, 2);
      const uint32_t yx = msc + 128;
      if (!(lane & 2)) sts1(yx + wid * 64 + ((lane & 1) * 8 + (lane >> 2)) * 4, __float_as_uint(z));
      bar_sync(13, 224);
      if (tid < 16) {
        float y = 0.f;
#pragma unroll
        for (int w = 0; w < 7; w++) y += __uint_as_float(lds1(yx + w * 64 + tid * 4));
        *op = __float2bfloat16(fmaf(y, gate, base));
      }
      if (b == 0 && tid == 32) P.s->epoch = lds1(mb + B_SW) & 255;
    }
    if (tid == 0) SPANS(1);
    TS(19); TSG(31);
    if (warp == 0) TS_DUMP(wg);
   }
  }
}

typedef CUresult (*EncodeFn)(CUtensorMap*, CUtensorMapDataType, cuuint32_t, void*, const cuuint64_t*, const cuuint64_t*, const cuuint32_t*,
                             const cuuint32_t*, CUtensorMapInterleave, CUtensorMapSwizzle, CUtensorMapL2promotion, CUtensorMapFloatOOBfill);
void make_map(EncodeFn enc, CUtensorMap* m, const void* p, int rank, std::initializer_list<cuuint64_t> dims, std::initializer_list<cuuint64_t> str,
              std::initializer_list<cuuint32_t> box, CUtensorMapSwizzle sw) {
  const cuuint32_t es[4] = {1, 1, 1, 1};
  enc(m, CU_TENSOR_MAP_DATA_TYPE_BFLOAT16, rank, const_cast<void*>(p), dims.begin(), str.begin(), box.begin(), es, CU_TENSOR_MAP_INTERLEAVE_NONE, sw,
      CU_TENSOR_MAP_L2_PROMOTION_L2_128B, CU_TENSOR_MAP_FLOAT_OOB_FILL_NONE);
}

}

extern "C" void kernel_launch(void* const* d_in, const int* in_sizes, int n_in, void* d_out, int out_size) {
  (void)in_sizes; (void)n_in; (void)out_size;
  Ptrs P;
  P.x = (const __nv_bfloat16*)d_in[0]; P.wqkv = (const __nv_bfloat16*)d_in[1]; P.wo = (const __nv_bfloat16*)d_in[2];
  P.wr = (const __nv_bfloat16*)d_in[4]; P.wg = (const __nv_bfloat16*)d_in[5]; P.wu = (const __nv_bfloat16*)d_in[6];
  P.wd = (const __nv_bfloat16*)d_in[7]; P.out = (__nv_bfloat16*)d_out;
  cudaGetSymbolAddress((void**)&P.s, g_scratch);
  void* fn = nullptr;
  cudaDriverEntryPointQueryResult q;
  cudaGetDriverEntryPoint("cuTensorMapEncodeTiled", &fn, cudaEnableDefault, &q);
  EncodeFn enc = (EncodeFn)fn;
  Maps T;
  constexpr CUtensorMapSwizzle S128 = CU_TENSOR_MAP_SWIZZLE_128B, S64 = CU_TENSOR_MAP_SWIZZLE_64B;
  make_map(enc, &T.m[M_X], P.x, 2, {D_, S_}, {D_ * 2}, {64, 128}, S128);
  make_map(enc, &T.m[M_W], P.wqkv, 3, {D_, D_, 3}, {3 * D_ * 2, D_ * 2}, {64, 64, 2}, S128);
  make_map(enc, &T.m[M_Q], P.wqkv, 2, {3 * D_, D_}, {3 * D_ * 2}, {64, 64}, S128);
  make_map(enc, &T.m[M_O], P.wo, 4, {64, 64, 16, 16}, {D_ * 2, 64 * D_ * 2, 128}, {64, 64, 1, 2}, S128);
  make_map(enc, &T.m[M_S], P.wo, 4, {64, 64, 16, 16}, {D_ * 2, 64 * D_ * 2, 128}, {64, 16, 4, 2}, S128);
  make_map(enc, &T.m[M_G], P.wg, 3, {F_, D_, 1}, {F_ * 2, F_ * 2 * D_}, {32, 128, 1}, S64);
  make_map(enc, &T.m[M_U], P.wu, 3, {F_, D_, 1}, {F_ * 2, F_ * 2 * D_}, {32, 128, 1}, S64);
  make_map(enc, &T.m[M_D], P.wd, 3, {64, F_, 16}, {D_ * 2, 128}, {64, 32, 2}, S128);
  make_map(enc, &T.m[M_L], P.wd, 2, {64, F_ * 16}, {128}, {8, 32}, CU_TENSOR_MAP_SWIZZLE_NONE);
  cudaFuncSetAttribute(fused_kernel, cudaFuncAttributeMaxDynamicSharedMemorySize, SMEM_BYTES);
  fused_kernel<<<NCTA, 384, SMEM_BYTES>>>(P, T);
}
```

```cpp
#include <cuda_runtime.h>
#include <cuda.h>
#include <cuda_bf16.h>
#include <stdint.h>
#include <type_traits>
#include <initializer_list>

namespace {

constexpr int S_ = 2048, D_ = 1024, F_ = 3584;
constexpr int NCTA = 128, NFFN = 112;
constexpr uint32_t SENT = 0xFFFFFFFFu;
constexpr int SPIN_LIMIT = 1 << 20;

#define ADELAY 200
#define ADELAY2 600
#define PFA 6
#define PF0 8
#define WPF0 8
#define DPER 1200
#define PDEPTH 2
#define PSTART 4000
#define PPER 1700
#define PEARLY 5
#define PLEAD 0
#define RST 1
#define PSUB 2
#define HOLDP 1
#define QHOLD 1
#define NPULL 12
#define CDELAY 0
#define NOUTW 4
#define YDELAY 650
#define EFX 0
#define EFW 1
#define EFF 1
#define KLEAD 13
#define GDELAY 400
#define NDIR 6
#define PULL0 3
#define FD0 600
#define FD1 800
#define SPF 1
#define MPF 1
#define TLBW 2
#define GORD 0
#define GSPLIT 2
#define EFW0 0
#define EFX0 0
#define EFWK 8
#define PSLEEP 20
#define P3PULL 1
#define RST2 4
#define KDELAY 450
#define AEARLY 0
#define BHOLD 4
#define SDELAY 100
#define FSTAG 150
#define OFL 0
#define CHKF 1
#define BEV 1
#define DLATE 4
#define P3GATE 3
#define ACCSW 0
#define B45 B_E
#define SDEL2 500
#define XDELAY 500
#define GU1 8
#define GU2 20
#define WD1 10
#define ODELAY 0
#define NOOUT 0
constexpr int OUNR =
  2;
#define P3N 2
#define HALFMAP 1
#define KWARP 7
#define FEARLY 1
#define MFIRST 350
#define MKV 850
#define MO 800
#define MST 1450
#define MSTE 13
#define AFIRST 0
#define MWIDE 0
#define PLAG 8
#define PSTEP 0
#define EFA 0
#define EFO 0
#define EFB 0
#define EFXK 12
#define P1F 1
#define R1MID 5
#define OPACE 450
#define VH 1
#define VZ 0
#define FPOS 1
#define NOHELP 0
#define NAPNS 20
#define NAP do { if (NAPNS) __nanosleep(NAPNS); } while (0)
#define SMASK 3
#define YPRED 1
#define PSTOP 3
#define DMASK 0x5550
#define PFST 1
#define W0OFF 2
#define MAPM 2
#define XWPF 0
constexpr uint32_t STAGE_B = 57344;
constexpr uint32_t OFF_STATS = 229376;
constexpr uint32_t OFF_COLSUM = 231424;
constexpr uint32_t OFF_BARS = 232192;
constexpr uint32_t SMEM_BYTES = 232448;
constexpr uint32_t B_FULL = 0, B_EMPTY = 32, B_E = 64, B_AUX = 128, B_EVA = 136, B_EVB = 144, B_BF = 152, B_LATE = 232, B_FFN = 240, B_SW = 248;
constexpr uint32_t B_OUT = B_FULL, B_SEL = B_FULL + 8, B_WR = B_FULL + 16, B_FFD = B_FULL + 24, B_E16 = B_EMPTY + 16, B_KVB = B_EMPTY + 8, B_DUMMY = B_SW + 4,
                   B_GATE = B_EMPTY + 24, B_ID = B_BF + 56, B_KVP = B_BF + 64, B_F15 = B_BF + 72;
#define B_HOLD B_F15
#define HOLDPAR 0
constexpr uint32_t UNIT = 8192;
constexpr uint32_t sb = 1024;
constexpr uint32_t bars = sb + OFF_BARS;
constexpr uint64_t tab5(int a, int b, int c, int d, int e, int f, int g, int h, int i = 0, int j = 0) {
  return (uint64_t)a | (uint64_t)b << 5 | (uint64_t)c << 10 | (uint64_t)d << 15 | (uint64_t)e << 20 | (uint64_t)f << 25 | (uint64_t)g << 30 | (uint64_t)h << 35 |
         (uint64_t)i << 40 | (uint64_t)j << 45;
}
constexpr uint64_t BT0 = tab5(4, 11, 18, 25, 7, 9, 16, 0), BT1 = tab5(4, 11, 18, 25, 21, 23, 2, 0);
constexpr uint64_t GT0 = tab5(2, 21, 23, 18, 0, 25, 14, 7), GT1 = tab5(16, 7, 9, 18, 0, 25, 14, 21);
constexpr uint64_t DT0 = tab5(6, 13, 20, 27, 9, 10, 16, 17), DT1 = tab5(6, 13, 20, 27, 23, 24, 2, 3);
__device__ __forceinline__ uint32_t unit_of(uint64_t tab, int i) { return ((uint32_t)(tab >> (5 * i)) & 31) * UNIT; }
__device__ __forceinline__ uint32_t ring_of(int p, int w) { return (p & 1) * (2 * STAGE_B) + ((p & 2) ? 49152 + w * STAGE_B : w * UNIT); }
constexpr uint32_t OFF_LNP = OFF_STATS + 1024;

struct Scratch {
  uint4 obuf[32 * 64 * 128];
  uint4 kvp[16 * 8 * 256];
  uint4 zp[16 * 8 * 16];
  uint4 ybuf[NCTA * NFFN * 2];
  uint4 st1[64 * 48];
  uint4 csp[16 * 8 * 48];
  uint4 st2[S_];
  uint4 hsel[2 * 8 * 128];
  uint32_t cand[8 * 32];
  uint32_t when[32 * 32];
  unsigned epoch;
};
__device__ __align__(1024) Scratch g_scratch;
#define TS_DECL
#define TS(i)
#define TSG(i)
#define TSV(i, v)
#define TSD(i)
#define RTS_DECL
#define RTS(i)
#define RTS_DUMP
#define TS_DUMP(slot)
#define PTS(i)
#define g_dbgv(i, v)

#define SPANS(i)
__device__ __forceinline__ uint32_t smem_u32(const void* p) { return (uint32_t)__cvta_generic_to_shared(p); }
__device__ __forceinline__ void mbar_init(uint32_t bar, uint32_t cnt) { asm volatile("mbarrier.init.shared::cta.b64 [%0], %1;" :: "r"(bar), "r"(cnt) : "memory"); }
__device__ __forceinline__ void mbar_expect_tx(uint32_t bar, uint32_t bytes) { asm volatile("mbarrier.arrive.expect_tx.shared::cta.b64 _, [%0], %1;" :: "r"(bar), "r"(bytes) : "memory"); }
__device__ __forceinline__ void mbar_arrive(uint32_t bar) { asm volatile("mbarrier.arrive.shared::cta.b64 _, [%0];" :: "r"(bar) : "memory"); }
#define SPINCHK(it, code) if ((it) > SPIN_LIMIT) break
__device__ __forceinline__ void mbar_wait(uint32_t bar, uint32_t parity) {
  asm volatile("{\n.reg .pred p;\n.reg .u32 c;\nmov.u32 c, 0;\n"
               "WL:\nmbarrier.try_wait.parity.shared::cta.b64 p, [%0], %1;\n@p bra WD;\n"
               "add.u32 c, c, 1;\nsetp.lt.u32 p, c, 1048576;\n@p bra WL;\nWD:\n}" :: "r"(bar), "r"(parity) : "memory");
}
__device__ __forceinline__ bool mbar_test(uint32_t bar, uint32_t parity) {
  uint32_t ok;
  asm volatile("{\n.reg .pred p;\nmbarrier.test_wait.parity.shared::cta.b64 p, [%1], %2;\nselp.u32 %0, 1, 0, p;\n}" : "=r"(ok) : "r"(bar), "r"(parity) : "memory");
  return ok;
}
__device__ __forceinline__ uint64_t l2_stream() { uint64_t p; asm("createpolicy.fractional.L2::evict_first.b64 %0, 1.0;" : "=l"(p)); return p; }
__device__ __forceinline__ void tma_2d(uint32_t dst, const CUtensorMap* tm, int c0, int c1, uint32_t bar, bool stream) {
  if (stream) asm volatile("cp.async.bulk.tensor.2d.shared::cluster.global.mbarrier::complete_tx::bytes.L2::cache_hint [%0], [%1, {%3, %4}], [%2], %5;"
                           :: "r"(dst), "l"(tm), "r"(bar), "r"(c0), "r"(c1), "l"(l2_stream()) : "memory");
  else asm volatile("cp.async.bulk.tensor.2d.shared::cluster.global.mbarrier::complete_tx::bytes [%0], [%1, {%3, %4}], [%2];"
                    :: "r"(dst), "l"(tm), "r"(bar), "r"(c0), "r"(c1) : "memory");
}
__device__ __forceinline__ void tma_3d(uint32_t dst, const CUtensorMap* tm, int c0, int c1, int c2, uint32_t bar, bool stream) {
  if (stream) asm volatile("cp.async.bulk.tensor.3d.shared::cluster.global.mbarrier::complete_tx::bytes.L2::cache_hint [%0], [%1, {%3, %4, %5}], [%2], %6;"
                           :: "r"(dst), "l"(tm), "r"(bar), "r"(c0), "r"(c1), "r"(c2), "l"(l2_stream()) : "memory");
  else asm volatile("cp.async.bulk.tensor.3d.shared::cluster.global.mbarrier::complete_tx::bytes [%0], [%1, {%3, %4, %5}], [%2];"
                    :: "r"(dst), "l"(tm), "r"(bar), "r"(c0), "r"(c1), "r"(c2) : "memory");
}
__device__ __forceinline__ void tma_pf_3d(const CUtensorMap* tm, int c0, int c1, int c2) {
  asm volatile("cp.async.bulk.prefetch.tensor.3d.L2.global [%0, {%1, %2, %3}];" :: "l"(tm), "r"(c0), "r"(c1), "r"(c2) : "memory");
}
__device__ __forceinline__ void tma_4d(uint32_t dst, const CUtensorMap* tm, int c0, int c1, int c2, int c3, uint32_t bar, bool stream) {
  if (stream) asm volatile("cp.async.bulk.tensor.4d.shared::cluster.global.mbarrier::complete_tx::bytes.L2::cache_hint [%0], [%1, {%3, %4, %5, %6}], [%2], %7;"
                           :: "r"(dst), "l"(tm), "r"(bar), "r"(c0), "r"(c1), "r"(c2), "r"(c3), "l"(l2_stream()) : "memory");
  else asm volatile("cp.async.bulk.tensor.4d.shared::cluster.global.mbarrier::complete_tx::bytes [%0], [%1, {%3, %4, %5, %6}], [%2];"
                    :: "r"(dst), "l"(tm), "r"(bar), "r"(c0), "r"(c1), "r"(c2), "r"(c3) : "memory");
}
__device__ __forceinline__ void tma_2d_mc(uint32_t dst, const CUtensorMap* tm, int c0, int c1, uint32_t bar, bool stream) {
  if (stream) asm volatile("cp.async.bulk.tensor.2d.shared::cluster.global.mbarrier::complete_tx::bytes.multicast::cluster.L2::cache_hint [%0], [%1, {%3, %4}], [%2], %5, %6;"
                           :: "r"(dst), "l"(tm), "r"(bar), "r"(c0), "r"(c1), "h"((uint16_t)3), "l"(l2_stream()) : "memory");
  else asm volatile("cp.async.bulk.tensor.2d.shared::cluster.global.mbarrier::complete_tx::bytes.multicast::cluster [%0], [%1, {%3, %4}], [%2], %5;"
                    :: "r"(dst), "l"(tm), "r"(bar), "r"(c0), "r"(c1), "h"((uint16_t)3) : "memory");
}
__device__ __forceinline__ bool elect_one() {
  uint32_t p;
  asm volatile("{\n.reg .pred q;\nelect.sync _|q, 0xFFFFFFFF;\nselp.u32 %0, 1, 0, q;\n}" : "=r"(p));
  return p;
}
__device__ __forceinline__ void bulk_load_mc(uint32_t dst, const void* src, uint32_t bytes, uint32_t bar) {
  if (EFA) asm volatile("cp.async.bulk.shared::cluster.global.mbarrier::complete_tx::bytes.multicast::cluster.L2::cache_hint [%0], [%1], %2, [%3], %4, %5;"
                        :: "r"(dst), "l"(src), "r"(bytes), "r"(bar), "h"((uint16_t)3), "l"(l2_stream()) : "memory");
  else asm volatile("cp.async.bulk.shared::cluster.global.mbarrier::complete_tx::bytes.multicast::cluster [%0], [%1], %2, [%3], %4;"
                    :: "r"(dst), "l"(src), "r"(bytes), "r"(bar), "h"((uint16_t)3) : "memory");
}
__device__ __forceinline__ void bulk_load(uint32_t dst, const void* src, uint32_t bytes, uint32_t bar) {
  asm volatile("cp.async.bulk.shared::cluster.global.mbarrier::complete_tx::bytes [%0], [%1], %2, [%3];" :: "r"(dst), "l"(src), "r"(bytes), "r"(bar) : "memory");
}
__device__ __forceinline__ void st_out(void* p, uint4 v) {
  if (EFO == 1) asm volatile("st.global.L2::cache_hint.v4.u32 [%0], {%1,%2,%3,%4}, %5;" :: "l"(p), "r"(v.x), "r"(v.y), "r"(v.z), "r"(v.w), "l"(l2_stream()) : "memory");
  else if (EFO == 2) asm volatile("st.global.cs.v4.u32 [%0], {%1,%2,%3,%4};" :: "l"(p), "r"(v.x), "r"(v.y), "r"(v.z), "r"(v.w) : "memory");
  else asm volatile("st.global.v4.u32 [%0], {%1,%2,%3,%4};" :: "l"(p), "r"(v.x), "r"(v.y), "r"(v.z), "r"(v.w) : "memory");
}
__device__ __forceinline__ void bulk_store(void* dst, uint32_t src, uint32_t bytes) {
  asm volatile("cp.async.bulk.global.shared::cta.bulk_group [%0], [%1], %2;" :: "l"(dst), "r"(src), "r"(bytes) : "memory");
}
__device__ __forceinline__ void mbar_arrive_rem(uint32_t bar) { asm volatile("mbarrier.arrive.shared::cluster.b64 _, [%0];" :: "r"(bar) : "memory"); }
__device__ __forceinline__ void st_async4(uint32_t addr, const uint4& v, uint32_t bar) {
  asm volatile("st.async.shared::cluster.mbarrier::complete_tx::bytes.v4.b32 [%0], {%1,%2,%3,%4}, [%5];" :: "r"(addr), "r"(v.x), "r"(v.y), "r"(v.z), "r"(v.w), "r"(bar) : "memory");
}
template <uint32_t O> __device__ __forceinline__ void ldsm4_o(uint32_t addr, uint32_t& a, uint32_t& b, uint32_t& c, uint32_t& d) {
  asm volatile("ldmatrix.sync.aligned.m8n8.x4.shared.b16 {%0,%1,%2,%3}, [%4+%5];" : "=r"(a), "=r"(b), "=r"(c), "=r"(d) : "r"(addr), "n"(O) : "memory");
}
template <uint32_t O> __device__ __forceinline__ void ldsm4t_o(uint32_t addr, uint32_t (&r)[4]) {
  asm volatile("ldmatrix.sync.aligned.m8n8.x4.trans.shared.b16 {%0,%1,%2,%3}, [%4+%5];" : "=r"(r[0]), "=r"(r[1]), "=r"(r[2]), "=r"(r[3]) : "r"(addr), "n"(O) : "memory");
}
__device__ __forceinline__ void mma16816(float (&c)[4], const uint32_t (&a)[4], uint32_t b0, uint32_t b1) {
  asm("mma.sync.aligned.m16n8k16.row.col.f32.bf16.bf16.f32 {%0,%1,%2,%3}, {%4,%5,%6,%7}, {%8,%9}, {%0,%1,%2,%3};"
      : "+f"(c[0]), "+f"(c[1]), "+f"(c[2]), "+f"(c[3]) : "r"(a[0]), "r"(a[1]), "r"(a[2]), "r"(a[3]), "r"(b0), "r"(b1));
}
__device__ __forceinline__ void l2_prefetch(const void* p) { asm volatile("prefetch.global.L2 [%0];" :: "l"(p) : "memory"); }
__device__ __forceinline__ uint32_t ld_line(const void* p) { uint32_t v; asm volatile("ld.global.cg.L2::128B.u32 %0, [%1];" : "=r"(v) : "l"(p) : "memory"); return v; }
__device__ __forceinline__ void tmap_prefetch(const CUtensorMap* tm) { asm volatile("prefetch.tensormap [%0];" :: "l"(tm) : "memory"); }
__device__ __forceinline__ void wg_fence() { asm volatile("wgmma.fence.sync.aligned;" ::: "memory"); }
__device__ __forceinline__ void wg_commit() { asm volatile("wgmma.commit_group.sync.aligned;" ::: "memory"); }
template <int N> __device__ __forceinline__ void wg_wait() { asm volatile("wgmma.wait_group.sync.aligned %0;" :: "n"(N) : "memory"); }
template <int N> __device__ __forceinline__ void pin(float (&d)[N]) {
#pragma unroll
  for (int i = 0; i < N; i++) asm volatile("" : "+f"(d[i]) :: "memory");
}
__device__ __forceinline__ void pin4(uint4& v) { asm volatile("" : "+r"(v.x), "+r"(v.y), "+r"(v.z), "+r"(v.w) :: "memory"); }
template <uint32_t SBO, uint32_t SWZ> __device__ __forceinline__ uint64_t dsc(uint32_t lo) { return ((uint64_t)((SBO >> 4) | (SWZ << 30)) << 32) | lo; }
__host__ __device__ constexpr uint32_t dlo(uint32_t addr, uint32_t lbo) { return (addr >> 4) | ((lbo >> 4) << 16); }
__device__ __forceinline__ void bar_sync(int id, int n) { asm volatile("bar.sync %0, %1;" :: "r"(id), "r"(n) : "memory"); }
__device__ __forceinline__ void bar_arrive(int id, int n) { asm volatile("bar.arrive %0, %1;" :: "r"(id), "r"(n) : "memory"); }
__device__ __forceinline__ void fence_async_smem() { asm volatile("fence.proxy.async.shared::cta;" ::: "memory"); }
__device__ __forceinline__ void fence_gpu() { asm volatile("fence.acq_rel.gpu;" ::: "memory"); }
__device__ __forceinline__ uint4 ld_cg4(const void* p) { uint4 v; asm volatile("ld.global.cg.v4.u32 {%0,%1,%2,%3}, [%4];" : "=r"(v.x), "=r"(v.y), "=r"(v.z), "=r"(v.w) : "l"(p) : "memory"); return v; }
__device__ __forceinline__ uint4 ld_rlx4(const void* p) { uint4 v; asm volatile("ld.relaxed.gpu.global.v4.u32 {%0,%1,%2,%3}, [%4];" : "=r"(v.x), "=r"(v.y), "=r"(v.z), "=r"(v.w) : "l"(p) : "memory"); return v; }
__device__ __forceinline__ uint32_t ld_rlx(const void* p) { uint32_t v; asm volatile("ld.relaxed.gpu.global.u32 %0, [%1];" : "=r"(v) : "l"(p) : "memory"); return v; }
__device__ __forceinline__ void st_rlx4(void* p, uint4 v) { asm volatile("st.relaxed.gpu.global.v4.u32 [%0], {%1,%2,%3,%4};" :: "l"(p), "r"(v.x), "r"(v.y), "r"(v.z), "r"(v.w) : "memory"); }
__device__ __forceinline__ void st_rlx2(void* p, uint32_t a, uint32_t b) { asm volatile("st.relaxed.gpu.global.v2.u32 [%0], {%1,%2};" :: "l"(p), "r"(a), "r"(b) : "memory"); }
__device__ __forceinline__ void st_rlx(void* p, uint32_t a) { asm volatile("st.relaxed.gpu.global.u32 [%0], %1;" :: "l"(p), "r"(a) : "memory"); }
__device__ __forceinline__ void red4(void* p, float a, float b, float c, float d) { asm volatile("red.relaxed.gpu.global.add.v4.f32 [%0], {%1,%2,%3,%4};" :: "l"(p), "f"(a), "f"(b), "f"(c), "f"(d) : "memory"); }
__device__ __forceinline__ uint32_t pack2(float lo, float hi) { uint32_t r; asm("cvt.rn.bf16x2.f32 %0, %1, %2;" : "=r"(r) : "f"(hi), "f"(lo)); return r; }
__device__ __forceinline__ float bf_lo(uint32_t v) { return __uint_as_float(v << 16); }
__device__ __forceinline__ float bf_hi(uint32_t v) { return __uint_as_float(v & 0xFFFF0000u); }
__device__ __forceinline__ void stsm4(uint32_t addr, uint32_t a, uint32_t b, uint32_t c, uint32_t d) {
  asm volatile("stmatrix.sync.aligned.m8n8.x4.shared.b16 [%0], {%1,%2,%3,%4};" :: "r"(addr), "r"(a), "r"(b), "r"(c), "r"(d) : "memory");
}
template <uint32_t O> __device__ __forceinline__ void stsm4_o(uint32_t addr, uint32_t a, uint32_t b, uint32_t c, uint32_t d) {
  asm volatile("stmatrix.sync.aligned.m8n8.x4.shared.b16 [%0+%5], {%1,%2,%3,%4};" :: "r"(addr), "r"(a), "r"(b), "r"(c), "r"(d), "n"(O) : "memory");
}
__device__ __forceinline__ void sts4(uint32_t addr, uint32_t a, uint32_t b, uint32_t c, uint32_t d) { asm volatile("st.shared.v4.u32 [%0], {%1,%2,%3,%4};" :: "r"(addr), "r"(a), "r"(b), "r"(c), "r"(d) : "memory"); }
__device__ __forceinline__ void sts2f(uint32_t addr, float a, float b) { asm volatile("st.shared.v2.f32 [%0], {%1,%2};" :: "r"(addr), "f"(a), "f"(b) : "memory"); }
__device__ __forceinline__ void sts1(uint32_t addr, uint32_t a) { asm volatile("st.shared.u32 [%0], %1;" :: "r"(addr), "r"(a) : "memory"); }
__device__ __forceinline__ float2 lds2f(uint32_t addr) { float2 v; asm volatile("ld.shared.v2.f32 {%0,%1}, [%2];" : "=f"(v.x), "=f"(v.y) : "r"(addr) : "memory"); return v; }
template <uint32_t O> __device__ __forceinline__ float2 lds2f_o(uint32_t addr) { float2 v; asm volatile("ld.shared.v2.f32 {%0,%1}, [%2+%3];" : "=f"(v.x), "=f"(v.y) : "r"(addr), "n"(O) : "memory"); return v; }
template <int I, int N, class F> __device__ __forceinline__ void static_for(F&& f) { if constexpr (I < N) { f(std::integral_constant<int, I>{}); static_for<I + 1, N>(f); } }
__device__ __forceinline__ uint4 lds4(uint32_t addr) { uint4 v; asm volatile("ld.shared.v4.u32 {%0,%1,%2,%3}, [%4];" : "=r"(v.x), "=r"(v.y), "=r"(v.z), "=r"(v.w) : "r"(addr) : "memory"); return v; }
__device__ __forceinline__ uint32_t lds1(uint32_t addr) { uint32_t v; asm volatile("ld.shared.u32 %0, [%1];" : "=r"(v) : "r"(addr) : "memory"); return v; }
__device__ __forceinline__ float ex2(float x) { float y; asm("ex2.approx.ftz.f32 %0, %1;" : "=f"(y) : "f"(x)); return y; }
__device__ __forceinline__ uint32_t max4(uint32_t m, const uint4& v) { return __vimax3_u32(__vimax3_u32(m, v.x, v.y), v.z, v.w); }
__device__ __forceinline__ float rsq(float x) { float y; asm("rsqrt.approx.ftz.f32 %0, %1;" : "=f"(y) : "f"(x)); return y; }
__device__ __forceinline__ float rcp(float x) { float y; asm("rcp.approx.ftz.f32 %0, %1;" : "=f"(y) : "f"(x)); return y; }
__device__ __forceinline__ uint2 ld_rlx2(const void* p) { uint2 v; asm volatile("ld.relaxed.gpu.global.v2.u32 {%0,%1}, [%2];" : "=r"(v.x), "=r"(v.y) : "l"(p) : "memory"); return v; }
template <uint32_t O> __device__ __forceinline__ uint4 lds4_o(uint32_t addr) { uint4 v; asm volatile("ld.shared.v4.u32 {%0,%1,%2,%3}, [%4+%5];" : "=r"(v.x), "=r"(v.y), "=r"(v.z), "=r"(v.w) : "r"(addr), "n"(O) : "memory"); return v; }
__device__ __forceinline__ uint32_t phi2(float u0, float u1, float rl, uint32_t r2) {
  uint32_t pu, r;
  asm("cvt.rn.relu.bf16x2.f32 %0, %1, %2;" : "=r"(pu) : "f"(u1), "f"(u0));
  asm("fma.rn.bf16x2 %0, %1, %2, %3;" : "=r"(r) : "r"(pu), "r"(r2), "r"(pack2(__saturatef(ex2(u0 * rl) + 1e-6f), __saturatef(ex2(u1 * rl) + 1e-6f))));
  return r;
}
__device__ __forceinline__ uint32_t dup2(float r) { uint32_t v; asm("cvt.rn.relu.bf16x2.f32 %0, %1, %1;" : "=r"(v) : "f"(r)); return v; }
__device__ __forceinline__ uint32_t zero_after(const uint32_t (&v)[16]) {
  uint32_t z = 0;
#pragma unroll
  for (int i = 0; i < 16; i++) z |= v[i];
  return z & 0x80008000u;
}
__device__ __forceinline__ uint32_t hadd2(uint32_t a, uint32_t b) { uint32_t v; asm("add.rn.bf16x2 %0, %1, %2;" : "=r"(v) : "r"(a), "r"(b)); return v; }
__device__ __forceinline__ void sched_fence() { asm volatile("{\n.reg .pred p;\n.reg .u64 c;\nSF:\nmov.u64 c, %clock64;\nsetp.eq.u64 p, c, 0;\n@p bra SF;\n}" ::: "memory"); }
__device__ __forceinline__ uint4 ld_gen4(const void* p) { uint4 v; asm volatile("ld.relaxed.gpu.v4.u32 {%0,%1,%2,%3}, [%4];" : "=r"(v.x), "=r"(v.y), "=r"(v.z), "=r"(v.w) : "l"(p) : "memory"); return v; }
__device__ __forceinline__ uint2 ld_gen2(const void* p) { uint2 v; asm volatile("ld.relaxed.gpu.v2.u32 {%0,%1}, [%2];" : "=r"(v.x), "=r"(v.y) : "l"(p) : "memory"); return v; }
__device__ __forceinline__ uint32_t now_ns() { uint32_t v; asm volatile("mov.u32 %0, %%globaltimer_lo;" : "=r"(v) :: "memory"); return v; }
__device__ __forceinline__ void meet(uint32_t* mine, const uint4* all, int first, int after, uint32_t bar) {
  const uint32_t t0 = now_ns() & ~1u;
  if ((threadIdx.x & 31) == 0) st_rlx(mine, t0);
  while ((int)(now_ns() - t0) < first) NAP;
  uint4 v;
#pragma unroll 1
  for (int it = 0; it < SPIN_LIMIT; it++) { v = ld_rlx4(all); if (!__any_sync(~0u, max4(0, v) == SENT)) break; }
  const int d = min(__reduce_max_sync(~0u, max(max((int)(v.x - t0), (int)(v.y - t0)), max((int)(v.z - t0), (int)(v.w - t0)))), 100000) + after;
  mbar_wait(bar, 0);
  while ((int)(now_ns() - t0) < d) NAP;
}
__device__ __forceinline__ uint32_t hmul2(uint32_t a, uint32_t b) { uint32_t v; asm("mul.rn.bf16x2 %0, %1, %2;" : "=r"(v) : "r"(a), "r"(b)); return v; }
__device__ __forceinline__ uint32_t lane_id() { uint32_t v; asm volatile("mov.u32 %0, %%laneid;" : "=r"(v)); return v; }
template <int A, int B, int N> __device__ __forceinline__ void pinr(float (&d)[N]) {
#pragma unroll
  for (int i = A; i < B; i++) asm volatile("" : "+f"(d[i]) :: "memory");
}
template <int N> __device__ __forceinline__ void pinu(uint32_t (&d)[N]) {
#pragma unroll
  for (int i = 0; i < N; i++) asm volatile("" : "+r"(d[i]) :: "memory");
}

template<int TA, int TB, int OFF, int SZ> __device__ __forceinline__ void wgmma_n192_ss(float (&d)[SZ], uint64_t da, uint64_t db, int scale_d) {
  asm volatile("{\n.reg .pred p;\nsetp.ne.b32 p, %98, 0;\n"
    "wgmma.mma_async.sync.aligned.m64n192k16.f32.bf16.bf16 {%0,%1,%2,%3,%4,%5,%6,%7,%8,%9,%10,%11,%12,%13,%14,%15,%16,%17,%18,%19,%20,%21,%22,%23,%24,%25,%26,%27,%28,%29,%30,%31,%32,%33,%34,%35,%36,%37,%38,%39,%40,%41,%42,%43,%44,%45,%46,%47,%48,%49,%50,%51,%52,%53,%54,%55,%56,%57,%58,%59,%60,%61,%62,%63,%64,%65,%66,%67,%68,%69,%70,%71,%72,%73,%74,%75,%76,%77,%78,%79,%80,%81,%82,%83,%84,%85,%86,%87,%88,%89,%90,%91,%92,%93,%94,%95}, %96, %97, p, 1, 1, %99, %100;\n}\n"
    : "+f"(d[OFF+0]), "+f"(d[OFF+1]), "+f"(d[OFF+2]), "+f"(d[OFF+3]), "+f"(d[OFF+4]), "+f"(d[OFF+5]), "+f"(d[OFF+6]), "+f"(d[OFF+7]),
      "+f"(d[OFF+8]), "+f"(d[OFF+9]), "+f"(d[OFF+10]), "+f"(d[OFF+11]), "+f"(d[OFF+12]), "+f"(d[OFF+13]), "+f"(d[OFF+14]), "+f"(d[OFF+15]),
      "+f"(d[OFF+16]), "+f"(d[OFF+17]), "+f"(d[OFF+18]), "+f"(d[OFF+19]), "+f"(d[OFF+20]), "+f"(d[OFF+21]), "+f"(d[OFF+22]), "+f"(d[OFF+23]),
      "+f"(d[OFF+24]), "+f"(d[OFF+25]), "+f"(d[OFF+26]), "+f"(d[OFF+27]), "+f"(d[OFF+28]), "+f"(d[OFF+29]), "+f"(d[OFF+30]), "+f"(d[OFF+31]),
      "+f"(d[OFF+32]), "+f"(d[OFF+33]), "+f"(d[OFF+34]), "+f"(d[OFF+35]), "+f"(d[OFF+36]), "+f"(d[OFF+37]), "+f"(d[OFF+38]), "+f"(d[OFF+39]),
      "+f"(d[OFF+40]), "+f"(d[OFF+41]), "+f"(d[OFF+42]), "+f"(d[OFF+43]), "+f"(d[OFF+44]), "+f"(d[OFF+45]), "+f"(d[OFF+46]), "+f"(d[OFF+47]),
      "+f"(d[OFF+48]), "+f"(d[OFF+49]), "+f"(d[OFF+50]), "+f"(d[OFF+51]), "+f"(d[OFF+52]), "+f"(d[OFF+53]), "+f"(d[OFF+54]), "+f"(d[OFF+55]),
      "+f"(d[OFF+56]), "+f"(d[OFF+57]), "+f"(d[OFF+58]), "+f"(d[OFF+59]), "+f"(d[OFF+60]), "+f"(d[OFF+61]), "+f"(d[OFF+62]), "+f"(d[OFF+63]),
      "+f"(d[OFF+64]), "+f"(d[OFF+65]), "+f"(d[OFF+66]), "+f"(d[OFF+67]), "+f"(d[OFF+68]), "+f"(d[OFF+69]), "+f"(d[OFF+70]), "+f"(d[OFF+71]),
      "+f"(d[OFF+72]), "+f"(d[OFF+73]), "+f"(d[OFF+74]), "+f"(d[OFF+75]), "+f"(d[OFF+76]), "+f"(d[OFF+77]), "+f"(d[OFF+78]), "+f"(d[OFF+79]),
      "+f"(d[OFF+80]), "+f"(d[OFF+81]), "+f"(d[OFF+82]), "+f"(d[OFF+83]), "+f"(d[OFF+84]), "+f"(d[OFF+85]), "+f"(d[OFF+86]), "+f"(d[OFF+87]),
      "+f"(d[OFF+88]), "+f"(d[OFF+89]), "+f"(d[OFF+90]), "+f"(d[OFF+91]), "+f"(d[OFF+92]), "+f"(d[OFF+93]), "+f"(d[OFF+94]), "+f"(d[OFF+95])
    : "l"(da), "l"(db), "r"(scale_d), "n"(TA), "n"(TB));
}
template<int TA, int TB, int OFF, int SZ> __device__ __forceinline__ void wgmma_n128_ss(float (&d)[SZ], uint64_t da, uint64_t db, int scale_d) {
  asm volatile("{\n.reg .pred p;\nsetp.ne.b32 p, %66, 0;\n"
    "wgmma.mma_async.sync.aligned.m64n128k16.f32.bf16.bf16 {%0,%1,%2,%3,%4,%5,%6,%7,%8,%9,%10,%11,%12,%13,%14,%15,%16,%17,%18,%19,%20,%21,%22,%23,%24,%25,%26,%27,%28,%29,%30,%31,%32,%33,%34,%35,%36,%37,%38,%39,%40,%41,%42,%43,%44,%45,%46,%47,%48,%49,%50,%51,%52,%53,%54,%55,%56,%57,%58,%59,%60,%61,%62,%63}, %64, %65, p, 1, 1, %67, %68;\n}\n"
    : "+f"(d[OFF+0]), "+f"(d[OFF+1]), "+f"(d[OFF+2]), "+f"(d[OFF+3]), "+f"(d[OFF+4]), "+f"(d[OFF+5]), "+f"(d[OFF+6]), "+f"(d[OFF+7]),
      "+f"(d[OFF+8]), "+f"(d[OFF+9]), "+f"(d[OFF+10]), "+f"(d[OFF+11]), "+f"(d[OFF+12]), "+f"(d[OFF+13]), "+f"(d[OFF+14]), "+f"(d[OFF+15]),
      "+f"(d[OFF+16]), "+f"(d[OFF+17]), "+f"(d[OFF+18]), "+f"(d[OFF+19]), "+f"(d[OFF+20]), "+f"(d[OFF+21]), "+f"(d[OFF+22]), "+f"(d[OFF+23]),
      "+f"(d[OFF+24]), "+f"(d[OFF+25]), "+f"(d[OFF+26]), "+f"(d[OFF+27]), "+f"(d[OFF+28]), "+f"(d[OFF+29]), "+f"(d[OFF+30]), "+f"(d[OFF+31]),
      "+f"(d[OFF+32]), "+f"(d[OFF+33]), "+f"(d[OFF+34]), "+f"(d[OFF+35]), "+f"(d[OFF+36]), "+f"(d[OFF+37]), "+f"(d[OFF+38]), "+f"(d[OFF+39]),
      "+f"(d[OFF+40]), "+f"(d[OFF+41]), "+f"(d[OFF+42]), "+f"(d[OFF+43]), "+f"(d[OFF+44]), "+f"(d[OFF+45]), "+f"(d[OFF+46]), "+f"(d[OFF+47]),
      "+f"(d[OFF+48]), "+f"(d[OFF+49]), "+f"(d[OFF+50]), "+f"(d[OFF+51]), "+f"(d[OFF+52]), "+f"(d[OFF+53]), "+f"(d[OFF+54]), "+f"(d[OFF+55]),
      "+f"(d[OFF+56]), "+f"(d[OFF+57]), "+f"(d[OFF+58]), "+f"(d[OFF+59]), "+f"(d[OFF+60]), "+f"(d[OFF+61]), "+f"(d[OFF+62]), "+f"(d[OFF+63])
    : "l"(da), "l"(db), "r"(scale_d), "n"(TA), "n"(TB));
}
template<int TA, int TB, int OFF, int SZ> __device__ __forceinline__ void wgmma_n64_ss(float (&d)[SZ], uint64_t da, uint64_t db, int scale_d) {
  asm volatile("{\n.reg .pred p;\nsetp.ne.b32 p, %34, 0;\n"
    "wgmma.mma_async.sync.aligned.m64n64k16.f32.bf16.bf16 {%0,%1,%2,%3,%4,%5,%6,%7,%8,%9,%10,%11,%12,%13,%14,%15,%16,%17,%18,%19,%20,%21,%22,%23,%24,%25,%26,%27,%28,%29,%30,%31}, %32, %33, p, 1, 1, %35, %36;\n}\n"
    : "+f"(d[OFF+0]), "+f"(d[OFF+1]), "+f"(d[OFF+2]), "+f"(d[OFF+3]), "+f"(d[OFF+4]), "+f"(d[OFF+5]), "+f"(d[OFF+6]), "+f"(d[OFF+7]),
      "+f"(d[OFF+8]), "+f"(d[OFF+9]), "+f"(d[OFF+10]), "+f"(d[OFF+11]), "+f"(d[OFF+12]), "+f"(d[OFF+13]), "+f"(d[OFF+14]), "+f"(d[OFF+15]),
      "+f"(d[OFF+16]), "+f"(d[OFF+17]), "+f"(d[OFF+18]), "+f"(d[OFF+19]), "+f"(d[OFF+20]), "+f"(d[OFF+21]), "+f"(d[OFF+22]), "+f"(d[OFF+23]),
      "+f"(d[OFF+24]), "+f"(d[OFF+25]), "+f"(d[OFF+26]), "+f"(d[OFF+27]), "+f"(d[OFF+28]), "+f"(d[OFF+29]), "+f"(d[OFF+30]), "+f"(d[OFF+31])
    : "l"(da), "l"(db), "r"(scale_d), "n"(TA), "n"(TB));
}
template<int TA, int TB, int OFF, int SZ> __device__ __forceinline__ void wgmma_n72_ss(float (&d)[SZ], uint64_t da, uint64_t db, int scale_d) {
  asm volatile("{\n.reg .pred p;\nsetp.ne.b32 p, %38, 0;\n"
    "wgmma.mma_async.sync.aligned.m64n72k16.f32.bf16.bf16 {%0,%1,%2,%3,%4,%5,%6,%7,%8,%9,%10,%11,%12,%13,%14,%15,%16,%17,%18,%19,%20,%21,%22,%23,%24,%25,%26,%27,%28,%29,%30,%31,%32,%33,%34,%35}, %36, %37, p, 1, 1, %39, %40;\n}\n"
    : "+f"(d[OFF+0]), "+f"(d[OFF+1]), "+f"(d[OFF+2]), "+f"(d[OFF+3]), "+f"(d[OFF+4]), "+f"(d[OFF+5]), "+f"(d[OFF+6]), "+f"(d[OFF+7]),
      "+f"(d[OFF+8]), "+f"(d[OFF+9]), "+f"(d[OFF+10]), "+f"(d[OFF+11]), "+f"(d[OFF+12]), "+f"(d[OFF+13]), "+f"(d[OFF+14]), "+f"(d[OFF+15]),
      "+f"(d[OFF+16]), "+f"(d[OFF+17]), "+f"(d[OFF+18]), "+f"(d[OFF+19]), "+f"(d[OFF+20]), "+f"(d[OFF+21]), "+f"(d[OFF+22]), "+f"(d[OFF+23]),
      "+f"(d[OFF+24]), "+f"(d[OFF+25]), "+f"(d[OFF+26]), "+f"(d[OFF+27]), "+f"(d[OFF+28]), "+f"(d[OFF+29]), "+f"(d[OFF+30]), "+f"(d[OFF+31]),
      "+f"(d[OFF+32]), "+f"(d[OFF+33]), "+f"(d[OFF+34]), "+f"(d[OFF+35])
    : "l"(da), "l"(db), "r"(scale_d), "n"(TA), "n"(TB));
}
template<int TB, int OFF, int SZ> __device__ __forceinline__ void wgmma_n64_rs(float (&d)[SZ], uint32_t a0, uint32_t a1, uint32_t a2, uint32_t a3, uint64_t db, int scale_d) {
  asm volatile("{\n.reg .pred p;\nsetp.ne.b32 p, %37, 0;\n"
    "wgmma.mma_async.sync.aligned.m64n64k16.f32.bf16.bf16 {%0,%1,%2,%3,%4,%5,%6,%7,%8,%9,%10,%11,%12,%13,%14,%15,%16,%17,%18,%19,%20,%21,%22,%23,%24,%25,%26,%27,%28,%29,%30,%31}, {%32,%33,%34,%35}, %36, p, 1, 1, %38;\n}\n"
    : "+f"(d[OFF+0]), "+f"(d[OFF+1]), "+f"(d[OFF+2]), "+f"(d[OFF+3]), "+f"(d[OFF+4]), "+f"(d[OFF+5]), "+f"(d[OFF+6]), "+f"(d[OFF+7]),
      "+f"(d[OFF+8]), "+f"(d[OFF+9]), "+f"(d[OFF+10]), "+f"(d[OFF+11]), "+f"(d[OFF+12]), "+f"(d[OFF+13]), "+f"(d[OFF+14]), "+f"(d[OFF+15]),
      "+f"(d[OFF+16]), "+f"(d[OFF+17]), "+f"(d[OFF+18]), "+f"(d[OFF+19]), "+f"(d[OFF+20]), "+f"(d[OFF+21]), "+f"(d[OFF+22]), "+f"(d[OFF+23]),
      "+f"(d[OFF+24]), "+f"(d[OFF+25]), "+f"(d[OFF+26]), "+f"(d[OFF+27]), "+f"(d[OFF+28]), "+f"(d[OFF+29]), "+f"(d[OFF+30]), "+f"(d[OFF+31])
    : "r"(a0), "r"(a1), "r"(a2), "r"(a3), "l"(db), "r"(scale_d), "n"(TB));
}
template<int TB, int OFF, int SZ> __device__ __forceinline__ void wgmma_n40_rs(float (&d)[SZ], uint32_t a0, uint32_t a1, uint32_t a2, uint32_t a3, uint64_t db, int scale_d) {
  asm volatile("{\n.reg .pred p;\nsetp.ne.b32 p, %25, 0;\n"
    "wgmma.mma_async.sync.aligned.m64n40k16.f32.bf16.bf16 {%0,%1,%2,%3,%4,%5,%6,%7,%8,%9,%10,%11,%12,%13,%14,%15,%16,%17,%18,%19}, {%20,%21,%22,%23}, %24, p, 1, 1, %26;\n}\n"
    : "+f"(d[OFF+0]), "+f"(d[OFF+1]), "+f"(d[OFF+2]), "+f"(d[OFF+3]), "+f"(d[OFF+4]), "+f"(d[OFF+5]), "+f"(d[OFF+6]), "+f"(d[OFF+7]),
      "+f"(d[OFF+8]), "+f"(d[OFF+9]), "+f"(d[OFF+10]), "+f"(d[OFF+11]), "+f"(d[OFF+12]), "+f"(d[OFF+13]), "+f"(d[OFF+14]), "+f"(d[OFF+15]),
      "+f"(d[OFF+16]), "+f"(d[OFF+17]), "+f"(d[OFF+18]), "+f"(d[OFF+19])
    : "r"(a0), "r"(a1), "r"(a2), "r"(a3), "l"(db), "r"(scale_d), "n"(TB));
}
template<int TB, int OFF, int SZ> __device__ __forceinline__ void wgmma_n128_rs(float (&d)[SZ], uint32_t a0, uint32_t a1, uint32_t a2, uint32_t a3, uint64_t db, int scale_d) {
  asm volatile("{\n.reg .pred p;\nsetp.ne.b32 p, %69, 0;\n"
    "wgmma.mma_async.sync.aligned.m64n128k16.f32.bf16.bf16 {%0,%1,%2,%3,%4,%5,%6,%7,%8,%9,%10,%11,%12,%13,%14,%15,%16,%17,%18,%19,%20,%21,%22,%23,%24,%25,%26,%27,%28,%29,%30,%31,%32,%33,%34,%35,%36,%37,%38,%39,%40,%41,%42,%43,%44,%45,%46,%47,%48,%49,%50,%51,%52,%53,%54,%55,%56,%57,%58,%59,%60,%61,%62,%63}, {%64,%65,%66,%67}, %68, p, 1, 1, %70;\n}\n"
    : "+f"(d[OFF+0]), "+f"(d[OFF+1]), "+f"(d[OFF+2]), "+f"(d[OFF+3]), "+f"(d[OFF+4]), "+f"(d[OFF+5]), "+f"(d[OFF+6]), "+f"(d[OFF+7]),
      "+f"(d[OFF+8]), "+f"(d[OFF+9]), "+f"(d[OFF+10]), "+f"(d[OFF+11]), "+f"(d[OFF+12]), "+f"(d[OFF+13]), "+f"(d[OFF+14]), "+f"(d[OFF+15]),
      "+f"(d[OFF+16]), "+f"(d[OFF+17]), "+f"(d[OFF+18]), "+f"(d[OFF+19]), "+f"(d[OFF+20]), "+f"(d[OFF+21]), "+f"(d[OFF+22]), "+f"(d[OFF+23]),
      "+f"(d[OFF+24]), "+f"(d[OFF+25]), "+f"(d[OFF+26]), "+f"(d[OFF+27]), "+f"(d[OFF+28]), "+f"(d[OFF+29]), "+f"(d[OFF+30]), "+f"(d[OFF+31]),
      "+f"(d[OFF+32]), "+f"(d[OFF+33]), "+f"(d[OFF+34]), "+f"(d[OFF+35]), "+f"(d[OFF+36]), "+f"(d[OFF+37]), "+f"(d[OFF+38]), "+f"(d[OFF+39]),
      "+f"(d[OFF+40]), "+f"(d[OFF+41]), "+f"(d[OFF+42]), "+f"(d[OFF+43]), "+f"(d[OFF+44]), "+f"(d[OFF+45]), "+f"(d[OFF+46]), "+f"(d[OFF+47]),
      "+f"(d[OFF+48]), "+f"(d[OFF+49]), "+f"(d[OFF+50]), "+f"(d[OFF+51]), "+f"(d[OFF+52]), "+f"(d[OFF+53]), "+f"(d[OFF+54]), "+f"(d[OFF+55]),
      "+f"(d[OFF+56]), "+f"(d[OFF+57]), "+f"(d[OFF+58]), "+f"(d[OFF+59]), "+f"(d[OFF+60]), "+f"(d[OFF+61]), "+f"(d[OFF+62]), "+f"(d[OFF+63])
    : "r"(a0), "r"(a1), "r"(a2), "r"(a3), "l"(db), "r"(scale_d), "n"(TB));
}

struct Ptrs { const __nv_bfloat16 *x, *wqkv, *wo, *wr, *wg, *wu, *wd; __nv_bfloat16* out; Scratch* s; };

enum { M_X, M_W, M_Q, M_O, M_S, M_G, M_U, M_D, M_L, M_N };
struct Maps { CUtensorMap m[M_N]; };

__global__ void __cluster_dims__(2, 1, 1) __launch_bounds__(384, 1) fused_kernel(const Ptrs P, const __grid_constant__ Maps T) {
  extern __shared__ __align__(1024) uint8_t smem_raw[];
  TS_DECL; TS(0); TSG(30);
  if (threadIdx.x == 320) SPANS(0);
  const uint32_t rank = blockIdx.x & 1;
  uint32_t own = rank << 24;
  asm("" : "+r"(own));
  const uint32_t sm = own + sb, mb = own + bars;
  int b0;
  { const int j = blockIdx.x >> 1, u = j - 36, v = j * 2 - 8 + (max(u * 37 + 256, 0) >> 8) * (u < 0 ? 0 : 2), w = j < 4 ? j * 16 + 64 : v;
    b0 = ((w & 15) | (w & 48) << 1 | (w & 64) >> 2) + rank; }
#define IDS(B) \
  const int b = (B), rb = b >> 4, cg = b & 15, hf = cg >> 3, s3 = cg & 7, c3 = s3 ^ ((rb & 1) << 2), jp = cg >> 1, km = (~c3 & 6) << 1; \
  const int fidx = jp == rb ? -1 : b - 2 * rb - (jp > rb ? 2 : 0); \
  auto kcol = [&](int kb) { return (kb ^ (kb < 8 ? km & 8 : km)) * 64; }; \
  auto src_of = [&](int p) { return p == 0 ? s3 : p == 15 ? s3 ^ 1 : (((jp & 3) ^ ((p - 7) >> 1)) << 1) + ((p - 1) & 1); }; \
  auto frag_of = [&](int p) { return p < 9 ? (p - 1) * 512 : 4096 + src_of(p) * 512; }; \
  (void)hf; (void)fidx; (void)kcol; (void)frag_of
  auto get_b = [&]() { return __shfl_sync(~0u, (int)lds1(mb + B_ID), 0); };
  IDS(b0);
  auto load_w = [&](uint32_t st, int kc, uint32_t bar, bool last) { tma_3d(st + 32768, &T.m[M_W], cg * 64, kc, 1, bar, last); tma_2d(st + 49152, &T.m[M_Q], cg * 64, kc, bar, last); };
  RTS_DECL;
  if (threadIdx.x < 32 && elect_one()) {
    mbar_init(mb + B_FULL, 1);
    asm volatile("fence.mbarrier_init.release.cluster;" ::: "memory");
    mbar_expect_tx(mb + B_FULL, STAGE_B);
    load_w(sm, kcol(0), mb + B_FULL, false);
    tma_2d(sm + 16384, &T.m[M_X], kcol(0), rb * 256 + 128, mb + B_FULL, false);
    tma_2d(sm, &T.m[M_X], kcol(0), rb * 256, mb + B_FULL, false);
  }
  const int tid = threadIdx.x, wid = __shfl_sync(~0u, tid >> 5, 0), wg = wid >> 2, lane = lane_id();
  const uint32_t tk = clock64();
  if (wid < 4) {
    const int i = tid - 64;
    if (SPF && tid >= 32 && tid < 112)
      l2_prefetch(i < 0 ? P.x + (rb * 256 + (hf * 4 + (cg & 3)) * 32 + lane) * D_ + kcol(0) : P.wqkv + (kcol(0) + (rb >> 1) * 16 + (i & 15)) * 3072 + (i >> 4) * 1024 + cg * 64);
  } else if (wid == 9) {
    if (elect_one()) {
#pragma unroll
      for (int i = 1; i < 31; i++) if (8 * i != B_ID) mbar_init(mb + 8 * i, i < 4 ? 1 : i < 8 ? 8 : i < 16 ? 16 : i == 16 ? 64 : i == 17 ? 8 : i == 18 ? 4 : 1);
      asm volatile("fence.mbarrier_init.release.cluster;" ::: "memory");
      fence_async_smem();
    }
  } else if (wid == 11) {
#pragma unroll
    for (int i = 0; i < 4; i++) sts4(sm + OFF_STATS + i * 512 + lane * 16, SENT, SENT, SENT, SENT);
    sts1(mb + B_ID, b);
    if (smem_u32(smem_raw) != sm) asm volatile("trap;");
    fence_async_smem();
  }
  __syncthreads();
  asm volatile("barrier.cluster.arrive.relaxed.aligned;\nbarrier.cluster.wait.aligned;" ::: "memory");

  if (wg == 2) {
    asm volatile("setmaxnreg.dec.sync.aligned.u32 56;");
    if (wid == 8) {
      if (elect_one()) {
#pragma unroll 1
        for (int kb = 1; kb < 15; kb++) {
          const uint32_t fb = mb + B_FULL + 8 * (kb & 3), st = sm + (kb & 3) * STAGE_B;
          const int kc = kcol(kb);
          if (kb < 4) while ((uint32_t)clock64() - tk < FD0 + kb * FD1) {}
          else mbar_wait(fb + B_EMPTY, ((kb >> 2) & 1) ^ 1);
          mbar_expect_tx(fb, STAGE_B);
          tma_2d_mc(st + rank * 16384, &T.m[M_X], kc, rb * 256 + rank * 128, fb, kb >= EFXK);
          load_w(st, kc, fb, EFW && kb >= EFWK);
          if (kb >= 8 && kb < 11) asm volatile("mbarrier.arrive.shared::cta.b64 _, [%0], %1;" :: "r"(fb + B_EMPTY), "r"(4) : "memory");
        }
        {
          const uint32_t st = sm + 3 * STAGE_B, fa = mb + B_FULL + 24, fb = mb + B_F15;
          const int kc = kcol(15);
          mbar_wait(fa, 0);
          mbar_expect_tx(fa, 32768); mbar_expect_tx(fb, 24576);
          if (rank) { mbar_wait(mb + B_EMPTY + 24, 0); tma_2d_mc(st + 16384, &T.m[M_X], kc, rb * 256 + 128, fa, EFXK < 16); }
          mbar_wait(mb + B_EMPTY, 1);
          tma_3d(st + 32768, &T.m[M_W], cg * 64, kc, 1, fa, EFW);
          if (!rank) { mbar_wait(mb + B_EMPTY + 24, 0); tma_2d_mc(st, &T.m[M_X], kc, rb * 256, fb, EFXK < 16); }
          tma_2d(st + 49152, &T.m[M_Q], cg * 64, kc, fb, EFW);
        }
        mbar_expect_tx(mb + B_KVP, 32768 + 2048);
      }
      __syncwarp();
      const uint4* kp = &P.s->kvp[cg * 8 * 256], *zq = &P.s->zp[cg * 8 * 16], *src = &P.s->obuf[(rb * 4 + rank * 2 + hf) * 64 * 128];
      asm volatile("" : "+l"(kp), "+l"(zq), "+l"(src));
      mbar_wait(mb + B_EVA, 0);
      meet(&P.s->when[cg * 32 + rb], (const uint4*)&P.s->when[cg * 32] + (lane & 1), MFIRST, MKV, mb + B_EVB);
      if (elect_one()) {
        bulk_load(sm + rank * (2 * STAGE_B) + STAGE_B, kp, 32768, mb + B_KVP);
        bulk_load(sm + rank * (2 * STAGE_B) + UNIT, zq, 2048, mb + B_KVP);
      }
      RTS(1);
      mbar_wait(mb + B_KVP, 0);
      RTS(2);
      meet(&P.s->when[(16 + rb * 2 + hf) * 32 + s3], (const uint4*)&P.s->when[(16 + (MWIDE == 2 ? lane >> 1 : (MWIDE ? (lane & 6) + (rb & 1) : rb) * 2 + (hf ^ 1))) * 32] + (lane & 1), MFIRST, MO, mb + B_E);
      RTS(3);
      if (elect_one()) {
        const uint32_t t0 = clock64();
        mbar_arrive(mb + B_F15);
        RTS(4);
#pragma unroll
        for (int p = 2; p < 5; p++) {
          if (p < 4) while ((uint32_t)clock64() - t0 < (p == 2 ? ADELAY : ADELAY2)) NAP;
          bulk_load_mc(sm + ring_of(p, rank), src + (p - 1) * 512, UNIT, mb + B_BF + 8 * p);
        }
#pragma unroll 1
        for (int p = 5; p < 15; p++) {
          uint32_t dst = sm + ring_of(p, rank), bar = mb + B_BF + 8 * (p % 7);
          const uint4* q = src + frag_of(p);
          asm volatile("" : "+r"(dst), "+r"(bar), "+l"(q));
          mbar_wait(mb + B_E + 8 * ((p - 4) & 7), p >= 12);
          bulk_load_mc(dst, q, UNIT, bar);
        }
        asm volatile("mbarrier.arrive.shared::cta.b64 _, [%0], 8;" :: "r"(mb + B_GATE) : "memory");
        const uint4* s15 = &P.s->obuf[(rb * 4 + hf) * 64 * 128 + frag_of(15)];
        RTS_DUMP;
        mbar_wait(mb + B_E + 24, 1);
        bulk_load(sm + ring_of(15, 0), s15, UNIT, mb + B_BF + 8); bulk_load(sm + ring_of(15, 1), s15 + 2 * 64 * 128, UNIT, mb + B_BF + 8);
      }
    } else if (wid == 11) {
      IDS(get_b());
      if (fidx >= 0) {
        const uint32_t o = (rank * 32 + lane) * (F_ * 2) + (fidx >> 1) * 128;
        const char* q0 = (const char*)P.wg + o, *q1 = (const char*)P.wu + o;
        mbar_wait(mb + B_FULL + 24, 0);
        mbar_wait(mb + B_FULL + 8 * (PULL0 & 3), PULL0 >> 2);
#pragma unroll 1
        for (int r = 0; r < 16; r++, q0 += 64 * F_ * 2, q1 += 64 * F_ * 2) {
          if (mbar_test(mb + B_HOLD, 0)) { l2_prefetch(q0); l2_prefetch(q1); continue; }
          asm volatile("cp.async.ca.shared.global.L2::128B [%0], [%1], 4;\ncp.async.commit_group;\ncp.async.wait_group %3;\n"
                       "cp.async.ca.shared.global.L2::128B [%0], [%2], 4;\ncp.async.commit_group;\ncp.async.wait_group %3;" :: "r"(mb + B_DUMMY), "l"(q0), "l"(q1), "n"(PDEPTH) : "memory");
          if (lane == 0) g_dbgv(3, r + 1);
        }
        mbar_wait(mb + B_F15, 0);
        bar_sync(15, 288);
        if (lane == 0) PTS(1);
        q0 = (const char*)P.wd + fidx * 65536 + lane * 128;
        const uint32_t bar = mb + B_BF + 48;
        if (lane == 0) mbar_expect_tx(bar, 8192);
#pragma unroll 1
        for (int i = 0; i < 16 + PLAG; i++) {
          if (i < 16) l2_prefetch(q0 + i * 4096);
          if (i >= PLAG && elect_one()) tma_2d(sm + OFF_COLSUM, &T.m[M_L], 0, fidx * 512 + (i - PLAG) * 32, bar, false);
          const uint32_t t1 = clock64();
          while ((uint32_t)clock64() - t1 < PSTEP) {}
        }
        mbar_wait(bar, 0);
        __syncwarp();
        if (lane == 0) { mbar_arrive(bar); PTS(4); }
        asm volatile("cp.async.wait_all;" ::: "memory");
      } else bar_sync(15, 288);
      bar_arrive(14, 64);
    } else {
      const uint32_t eb = (lane << 24) + bars + B_EMPTY;
      float c[6];
      if (wid == 10) {
        float sx[4] = {0.f, 0.f, 0.f, 0.f}, qx[4] = {0.f, 0.f, 0.f, 0.f};
        const uint32_t xa = sm + ((hf * 4 + (cg & 3)) * 32 + lane) * 128 + ((lane & 7) << 4);
#pragma unroll 1
        for (int kb = 0; kb < 8; kb++) {
          uint4 xv[8];
          const uint32_t so = xa + (kb & 3) * STAGE_B;
          mbar_wait(mb + B_FULL + 8 * (kb & 3), kb >> 2);
#pragma unroll
          for (int i = 0; i < 8; i++) xv[i] = lds4(so ^ (i << 4));
#pragma unroll
          for (int i = 0; i < (NOHELP ? 1 : 8); i++) {
            const uint32_t e[4] = {xv[i].x, xv[i].y, xv[i].z, xv[i].w};
#pragma unroll
            for (int j = 0; j < 4; j++) {
              const float d0 = bf_lo(e[j]), d1 = bf_hi(e[j]);
              sx[j & SMASK] += d0 + d1; qx[j & SMASK] = fmaf(d0, d0, fmaf(d1, d1, qx[j & SMASK]));
            }
          }
          __syncwarp();
          if (lane < 2) mbar_arrive_rem(eb + 8 * (kb & 3));
          if (kb == RST2) {
        {
          const uint32_t ep = ld_rlx(&P.s->epoch);
          float s = 0.f;
#pragma unroll
          for (int i = 0; i < 4; i++) {
            const uint4 v = ld_cg4((const uint4*)P.wr + lane + i * 32);
            s += (bf_lo(v.x) + bf_hi(v.x)) + (bf_lo(v.y) + bf_hi(v.y)) + (bf_lo(v.z) + bf_hi(v.z)) + (bf_lo(v.w) + bf_hi(v.w));
          }
#pragma unroll
          for (int o = 16; o; o >>= 1) s += __shfl_xor_sync(~0u, s, o);
          if (lane == 0) sts1(mb + B_SW, (__float_as_uint(s) & ~255u) | ((ep + 1) & 255));
        }
        asm volatile("cp.async.bulk.wait_group 0;\nfence.proxy.async.global;" ::: "memory");
        fence_gpu();
        if (lane == 0) PTS(0);
          }
          if (kb == RST) {
        if (elect_one()) {
#pragma unroll 1
          for (int i = 0; i < 16; i++) bulk_store(&P.s->obuf[((rb * 4 + (i >> 2)) * 64 + (((i >> 2) & 1) == hf ? 32 + s3 * 4 + (i & 3) : (i & 3) * 8 + s3)) * 128], sm + OFF_STATS, 2048);
          bulk_store(&P.s->kvp[(cg * 8 + rb) * 256], sm + OFF_STATS, 2048); bulk_store(&P.s->kvp[(cg * 8 + rb) * 256 + 128], sm + OFF_STATS, 2048);
          bulk_store(&P.s->zp[(cg * 8 + rb) * 16], sm + OFF_STATS, 256);
          if (s3 == 0) bulk_store(&P.s->when[(16 + rb * 2 + hf) * 32], sm + OFF_STATS, 128);
          if (rb == 0) bulk_store(&P.s->when[cg * 32], sm + OFF_STATS, 128);
          asm volatile("cp.async.bulk.commit_group;" ::: "memory");
          #pragma unroll
          for (int i = M_O; i < M_N; i++) tmap_prefetch(&T.m[i]);
        }
        __syncwarp();
          }
        }
        c[0] = ((sx[0] + sx[1]) + (sx[2] + sx[3])) * (2.f / D_);
        c[1] = fmaxf(fmaf(-c[0], c[0], ((qx[0] + qx[1]) + (qx[2] + qx[3])) * (2.f / D_)), 0.f);
      } else {
        float a[12];
#pragma unroll
        for (int i = 0; i < 12; i++) a[i] = 0.f;
        const int r2 = lane >> 4, c16 = lane & 15;
        const uint32_t a0 = sm + 32768 + (rb >> 1) * 2048 + r2 * 128 + (((c16 >> 1) ^ r2) << 4) + (c16 & 1) * 8;
#pragma unroll 1
        for (int it = 0; it < 16; it++) {
          uint2 w[12];
          const int s = (it >> 1) & 3;
          const uint32_t so = a0 + s * STAGE_B + (it & 1) * 1024;
          if (!(it & 1)) { mbar_wait(mb + B_FULL + 8 * s, it >> 3); TSD(8 + (it >> 1)); }
          static_for<0, 12>([&](auto ic) { constexpr int i = decltype(ic)::value;
            const float2 v = lds2f_o<(i >> 2) * 8192 + (i & 3) * 256>(so ^ ((i & 3) << 5)); w[i] = make_uint2(__float_as_uint(v.x), __float_as_uint(v.y)); });
#pragma unroll
          for (int i = 0; i < (NOHELP ? 1 : 12); i++) { float* q = a + (i >> 2) * 4; q[0] += bf_lo(w[i].x); q[1] += bf_hi(w[i].x); q[2] += bf_lo(w[i].y); q[3] += bf_hi(w[i].y); }
          __syncwarp();
          if (lane < 2 && (it & 1)) mbar_arrive_rem(eb + 8 * s);
        }
#pragma unroll
        for (int i = 0; i < 6; i++) {
          const int o = (i >> 1) * 4 + (i & 1);
          c[i] = (r2 ? a[o + 2] : a[o]) + __shfl_xor_sync(~0u, r2 ? a[o] : a[o + 2], 16);
        }
      }
      TS(5);
      bar_sync(10, 64);
      TS(6);
      {
        const uint32_t tag = lds1(mb + B_SW) & 255;
        auto tagged = [&](float v) { return ((__float_as_uint(v) + 128) & ~255u) | tag; };
        if (wid == 9) {
#pragma unroll
          for (int sg = 0; sg < 3; sg++) {
            st_rlx2((uint2*)&P.s->csp[(cg * 8 + rb) * 48] + sg * 32 + (lane & 15) * 2 + (lane >> 4), tagged(c[sg * 2]), tagged(c[sg * 2 + 1]));
          }
        } else st_rlx2((uint2*)&P.s->st1[(rb * 8 + hf * 4 + (cg & 3)) * 48 + lane] + ((cg >> 2) & 1), tagged(c[0]), tagged(c[1]));
        __nanosleep(GDELAY);
#pragma unroll 1
        for (int h = wid - 9; h < 2; h++) {
          const int q = h * 24 + min(lane, 23);
          const uint4* gp = wid == 10 ? &P.s->st1[rb * 8 * 48 + lane] : &P.s->csp[cg * 8 * 48 + q];
          uint4 v[8];
#pragma unroll 1
          for (int it = 0;; it++) {
            uint32_t x = 0;
#pragma unroll
            for (int i = 0; i < 8; i++) v[i] = ld_rlx4(gp + i * 48);
#pragma unroll
            for (int i = 0; i < 8; i++) { v[i].x ^= tag; v[i].y ^= tag; v[i].z ^= tag; v[i].w ^= tag; x |= v[i].x | v[i].y | v[i].z | v[i].w; }
            if (!__any_sync(~0u, (x & 255) != 0)) break;
            SPINCHK(it, 3);
          }
          if (wid == 10) {
#pragma unroll
            for (int i = 0; i < 8; i++) {
              const float m0 = __uint_as_float(v[i].x), m1 = __uint_as_float(v[i].z), dm = 0.5f * (m0 - m1);
              sts2f(sm + OFF_STATS + (i * 32 + lane) * 8, -0.5f * (m0 + m1), rsq(fmaf(dm, dm, 0.5f * (__uint_as_float(v[i].y) + __uint_as_float(v[i].w))) + 1e-5f));
            }
          } else {
            float s4[4] = {0.f, 0.f, 0.f, 0.f};
#pragma unroll
            for (int i = 0; i < 8; i++) { s4[0] += __uint_as_float(v[i].x); s4[1] += __uint_as_float(v[i].y); s4[2] += __uint_as_float(v[i].z); s4[3] += __uint_as_float(v[i].w); }
            sts4(sm + OFF_COLSUM + q * 16, __float_as_uint(s4[0]), __float_as_uint(s4[1]), __float_as_uint(s4[2]), __float_as_uint(s4[3]));
          }
        }
        mbar_arrive(mb + B_AUX);
      }
      TS(2);
      IDS(get_b());
      const uint64_t btab = rank ? BT1 : BT0;
      if (wid == 9) {
        {
          const uint4 sv = make_uint4(SENT, SENT, SENT, SENT);
          uint4* y = &P.s->ybuf[b * NFFN * 2 + lane];
#pragma unroll
          for (int i = 0; i < 7; i++) y[i * 32] = sv;
          if (lane < 16) P.s->st2[b * 16 + lane] = make_uint4(0, 0, 0, 0); else P.s->hsel[b * 16 + lane - 16] = sv;
          if (b < 8) P.s->cand[b * 32 + lane] = SENT;
          fence_gpu();
          bar_sync(0, 288);
          if (lane < 16) sts4(sm + OFF_STATS + lane * 128 + ((lane & 7) << 4), 0x3F803F80u, 0x3F803F80u, 0x3F803F80u, 0x3F803F80u);
          fence_async_smem();
          __syncwarp();
          if (lane == 0) mbar_arrive(mb + B_LATE);
        }
        TS(3);
        TS_DUMP(2);
        {
          const int p = lane & 15, sl = p % 7;
          const bool sliced = p > 0 && p < 9;
          const uint32_t c = sliced ? ((p - 1) >> 1) * 16 | ((hf ^ 1) * 8 + ((p - 1) & 1) * 4) << 8 | 128 << 16 : (hf * 8 + src_of(p)) << 8;
          const uint32_t ev = mb + (p < BHOLD ? B_EVA : p < 4 ? B_KVP : p < 6 ? B45 : B_E + 8 * ((p < 7 ? 1 : p - 4) & 7) + (p >= 12));
          mbar_wait(mb + B_EVA, 0);
          sts4(sm + OFF_COLSUM + 512 + p * 16, sm + unit_of(btab, sl), mb + B_BF + 8 * sl, c, ev);
          __syncwarp();
        }
        if (elect_one()) {
#pragma unroll 1
          for (int p = 0; p < 16; p++) {
            const uint4 e = lds4(sm + OFF_COLSUM + 512 + p * 16);
            if (p == 4) mbar_wait(mb + B_WR, 0);
            mbar_wait(e.w & ~1u, e.w & 1);
            mbar_expect_tx(e.y, p > 1 ? 4 * UNIT : 2 * UNIT);
            tma_4d(e.x, (const CUtensorMap*)((const char*)&T.m[M_O] + (e.z >> 16)), 0, e.z & 255, (e.z >> 8) & 255, c3 * 2, e.y, p >= EFB);
          }
          PTS(16);
        }
      } else {
        const uint32_t* wp = (const uint32_t*)(P.wr + c3 * 128) + (lane & 7) * 8 + (lane >> 3);
        const uint32_t w0 = ld_rlx(wp), w1 = ld_rlx(wp + 4);
#pragma unroll 1
        for (int i = 0; i < 4; i++) { l2_prefetch((const char*)P.wo + b * 16384 + i * 4096 + lane * 128); __nanosleep(300); }
        const int p = lane & 15, p2 = min(p + 2, 15);
        const uint32_t t0 = dlo(sb, 8192) + (unit_of(btab, p % 7) >> 4), t1 = ring_of(p + 1, lane >> 4), t2 = mb + B_BF + 8 * (p2 % 7);
        mbar_wait(mb + B_EVB, 0);
        bar_sync(14, 64);
        sts2f(sm + OFF_COLSUM + lane * 8, __uint_as_float(w0), __uint_as_float(w1));
        sts1(sm + OFF_COLSUM + 256 + lane * 4, 0x3F803F80u);
        sts4(sm + OFF_STATS + lane * 16, t0, t1, t2, (p2 / 7) & 1);
        __syncwarp();
        if (elect_one()) {
          mbar_arrive(mb + B_WR);
          if (fidx >= 0) {
            mbar_expect_tx(mb + B_FFN, 131072); mbar_expect_tx(mb + B_FFD, 32768);
            uint64_t gt = rank ? GT1 : GT0;
#pragma unroll 1
            for (int f = 0; f < 8; f++, gt >>= 5) {
              uint32_t d0 = sm + unit_of(gt, 0);
              asm volatile("" : "+r"(d0));
              if (f == 3) mbar_wait(mb + B_GATE, 1);
              mbar_wait(mb + (f < FEARLY ? B_KVB : B_E + (f < 3 ? 3 + 2 * f : (f + 5) >> 1) * 8), f < FEARLY || f >= 3);
              tma_3d(d0, &T.m[M_G], fidx * 32, f * 128, 0, mb + B_FFN, EFF);
              tma_3d(d0 + UNIT, &T.m[M_U], fidx * 32, f * 128, 0, mb + B_FFN, EFF);
            }
            PTS(17);
            mbar_expect_tx(mb + B_KVP, 32768);
#pragma unroll
            for (int w = 0; w < 8; w++) {
              if (w == 2) mbar_wait(mb + B_E + 56, 1);
              if (w == 6) mbar_wait(mb + B_E16, 1);
              if (w == DLATE) mbar_wait(mb + B_EVA, 1);
              tma_3d(sm + ((DT0 >> (5 * w)) & 31) * UNIT + (w < 4 ? 0 : w < 6 ? 14 * UNIT : -14 * UNIT) * rank, &T.m[M_D], 0, fidx * 32, 2 * w, mb + (w < 4 ? B_FFD : B_KVP), EFF);
            }
            PTS(18);
          }
        }
      }
    }
    __syncwarp();
    IDS(get_b());
    mbar_wait(mb + B_EVB, 0);
    mbar_wait(mb + B_OUT, 0);
    const float2 cf = lds2f(sm + OFF_STATS + 64);
    const int cand0 = 2047 - (__float_as_int(cf.x) & 2047), cand1 = 2047 - (__float_as_int(cf.y) & 2047), rr = lane >> 4;
    __nv_bfloat16* const ob = P.out + c3 * 128 + (lane & 15) * 8;
    auto store_row = [&](uint32_t ha, uint32_t la, int row, bool on) {
      const uint4 v = lds4(ha);
      const float2 pr = lds2f(la);
      const float f = 1.f + pr.x, n = pr.y;
      asm volatile("{\n.reg .pred p;\nsetp.ne.u32 p, %5, 0;\n@p st.global.v4.u32 [%0], {%1,%2,%3,%4};\n}" :: "l"(ob + row * D_),
                   "r"(pack2(fmaf(bf_lo(v.x), f, n), fmaf(bf_hi(v.x), f, n))), "r"(pack2(fmaf(bf_lo(v.y), f, n), fmaf(bf_hi(v.y), f, n))),
                   "r"(pack2(fmaf(bf_lo(v.z), f, n), fmaf(bf_hi(v.z), f, n))), "r"(pack2(fmaf(bf_lo(v.w), f, n), fmaf(bf_hi(v.w), f, n))), "r"((uint32_t)on) : "memory");
    };
    {
      uint32_t t0 = clock64() + ODELAY;
      uint32_t ha = sm + 4 * UNIT + ((wid >> 1) & 1) * STAGE_B + ((wid & 1) * 32 + rr) * 256 + (((lane & 15) ^ rr) << 4), la = sm + OFF_LNP + ((wid & 3) * 32 + rr) * 8;
      int row = rb * 256 + hf * 64 + (wid & 2) * 64 + (wid & 1) * 32 + rr;
#pragma unroll 1
      for (int i = 0; i < 16; i += OUNR, ha += 512 * OUNR, la += 16 * OUNR, row += 2 * OUNR, t0 += OPACE) {
        while ((int)((uint32_t)clock64() - t0) < 0) NAP;
#pragma unroll
        for (int j = 0; j < OUNR; j++) store_row((ha ^ (((i + j) & 3) << 5)) + j * 512, la + j * 16, row + 2 * j, row + 2 * j != cand0 && row + 2 * j != cand1 && !NOOUT);
      }
      if (wid == 11 && lane == 0) { PTS(14); SPANS(2); }
    }
    if (wid == 8) {
      const uint32_t kc = __float_as_uint(rr ? cf.y : cf.x);
      const int c = rr ? cand1 : cand0;
      mbar_wait(mb + B_SEL, 0);
      const float2 sel = lds2f(sm + OFF_STATS + 80);
      store_row(sm + 4 * UNIT + ((c >> 7) & 1) * STAGE_B + (c & 63) * 256 + (((lane & 15) ^ (c & 7)) << 4), sm + OFF_LNP + (((c >> 1) & 64) + (c & 63)) * 8, c,
                kc != __float_as_uint(sel.x) && kc != __float_as_uint(sel.y) && (c >> 8) == rb && ((c >> 6) & 1) == hf);
    }
  } else {
    asm volatile("setmaxnreg.inc.sync.aligned.u32 224;");
    const int t128 = tid & 127, warp = wid & 3, g = lane >> 2, t = lane & 3;
    const uint32_t sk = rank * (2 * STAGE_B);
    uint4 ost[2][4];
    uint4 abuf[3][4];
    uint4* od1;
    const uint4* ain;
    int b1;
    const uint32_t eb = (lane << 24) + bars + B_E;
    float acc[64];
    uint4 wb[4];
    uint32_t hp[32];
    {
      float acc1[96], acc0[96];
#pragma unroll
      for (int i = 0; i < 96; i++) { acc0[i] = 0.f; acc1[i] = 0.f; }
      const uint32_t xo0 = dlo(sb, 16) + (wg * 2 + hf) * 512, xo1 = dlo(sb, 16) + (wg * 2 + (hf ^ 1)) * 512;
      constexpr uint32_t ST = STAGE_B >> 4, WD = dlo(sb + 49152, 8192), WV = dlo(sb + 32768, 8192);
      const uint32_t eb0 = (t128 << 24) + bars + B_EMPTY;
#pragma unroll 1
      for (int kb = 0; kb < 12; kb++) {
        const int s = kb & 3;
        mbar_wait(mb + B_FULL + 8 * s, (kb >> 2) & 1);
        if (kb == 0) TS(1);
        if (kb == 0 && !wg) bar_sync(2, 256);
        pin(acc0); pin(acc1);
        wg_fence();
#pragma unroll
        for (int k = 0; k < 4; k++) {
          const uint64_t db = dsc<1024, 1>(WV + s * ST + k * 128);
          wgmma_n192_ss<0, 1, 0>(acc0, dsc<1024, 1>(s * ST + xo0 + k * 2), db, 1);
          wgmma_n192_ss<0, 1, 0>(acc1, dsc<1024, 1>(s * ST + xo1 + k * 2), db, 1);
        }
        wg_commit();
        if (kb == 0 && wg) bar_arrive(2, 256);
        wg_wait<0>();
        pin(acc0); pin(acc1);
        if (t128 < 2 && kb < 11) mbar_arrive_rem(eb0 + 8 * s);
      }
      mbar_wait(mb + B_FULL, 1);
      if (t128 < 8) mbar_arrive_rem(t128 < 4 ? (wg << 24) + bars + B_EMPTY + 24 : mb + B_EMPTY);
      TS(2);
      mbar_wait(mb + B_AUX, 0);
      float rs[2][2], nm[2][2];
#pragma unroll
      for (int m = 0; m < 2; m++)
#pragma unroll
        for (int h = 0; h < 2; h++) { const float2 v = lds2f(sm + OFF_STATS + ((wg * 2 + (m ^ hf)) * 64 + warp * 16 + h * 8 + g) * 8); nm[m][h] = v.x; rs[m][h] = v.y; }
      auto center = [&](auto jc) {
        constexpr int j = decltype(jc)::value;
        const float2 cs = lds2f_o<sb + OFF_COLSUM + j * 32>(own + t * 8);
        acc1[j * 4] = fmaf(nm[1][0], cs.x, acc1[j * 4]); acc1[j * 4 + 1] = fmaf(nm[1][0], cs.y, acc1[j * 4 + 1]);
        acc1[j * 4 + 2] = fmaf(nm[1][1], cs.x, acc1[j * 4 + 2]); acc1[j * 4 + 3] = fmaf(nm[1][1], cs.y, acc1[j * 4 + 3]);
        acc0[j * 4] = fmaf(nm[0][0], cs.x, acc0[j * 4]); acc0[j * 4 + 1] = fmaf(nm[0][0], cs.y, acc0[j * 4 + 1]);
        acc0[j * 4 + 2] = fmaf(nm[0][1], cs.x, acc0[j * 4 + 2]); acc0[j * 4 + 3] = fmaf(nm[0][1], cs.y, acc0[j * 4 + 3]);
      };
      static_for<0, 16>(center);
      const float L2E = 1.4426950408889634f;
      uint32_t fa = sm + sk + (warp * 16 + (lane & 15)) * 128 + (((lane >> 4) ^ (lane & 7)) << 4);
      asm volatile("" : "+r"(fa));
      uint32_t xf0[32], xf1[32];
      auto pack_kv = [&](float (&a)[96], int i, float r0, float r1, uint32_t* o, uint32_t z = 0) {
        const float* p = a + i * 8;
        if (i < 4) {
          const float rl0 = __uint_as_float(__float_as_uint(r0 * L2E) | z), rl1 = __uint_as_float(__float_as_uint(r1 * L2E) | z);
          const uint32_t q0 = pack2(r0, r0), q1 = pack2(r1, r1);
          o[0] = phi2(p[0], p[1], rl0, q0); o[1] = phi2(p[2], p[3], rl1, q1); o[2] = phi2(p[4], p[5], rl0, q0); o[3] = phi2(p[6], p[7], rl1, q1);
        } else if (VH) {
          const uint32_t q0 = pack2(r0, r0), q1 = pack2(r1, r1);
          o[0] = hmul2(pack2(p[0], p[1]), q0); o[1] = hmul2(pack2(p[2], p[3]), q1); o[2] = hmul2(pack2(p[4], p[5]), q0); o[3] = hmul2(pack2(p[6], p[7]), q1);
        } else {
          if (VZ) { r0 = __uint_as_float(__float_as_uint(r0) | z); r1 = __uint_as_float(__float_as_uint(r1) | z); }
          o[0] = pack2(p[0] * r0, p[1] * r0); o[1] = pack2(p[2] * r1, p[3] * r1); o[2] = pack2(p[4] * r0, p[5] * r0); o[3] = pack2(p[6] * r1, p[7] * r1);
        }
      };
      auto swap_kv = [&](uint32_t (&xf)[32], uint32_t tile, int i, const uint32_t* o, uint32_t z = 0) {
        const uint32_t ad = (fa + tile * UNIT) ^ ((i & 3) << 5);
        if (i < 4) { ldsm4_o<0>(ad, xf[i * 4], xf[i * 4 + 1], xf[i * 4 + 2], xf[i * 4 + 3]); stsm4_o<0>(ad, o[0], o[1], o[2], o[3]); }
        else { ldsm4_o<STAGE_B>(ad | z, xf[i * 4], xf[i * 4 + 1], xf[i * 4 + 2], xf[i * 4 + 3]); stsm4_o<STAGE_B>(ad, o[0], o[1], o[2], o[3]); }
      };
      auto mma_q = [&](float (&a)[96], uint32_t (&xf)[32], uint32_t xo, bool ss) {
        const uint32_t r = __shfl_sync(~0u, sk >> 4, 0), o = 2 * ST - r;
#pragma unroll
        for (int j = 0; j < 8; j++) {
          if (ss) wgmma_n64_ss<0, 1, 64>(a, dsc<1024, 1>(o + (j >> 2) * ST + xo + (j & 3) * 2), dsc<1024, 1>(WD + o + (j >> 2) * ST + (j & 3) * 128), 1);
          else wgmma_n64_rs<1, 64>(a, xf[j * 4], xf[j * 4 + 1], xf[j * 4 + 2], xf[j * 4 + 3], dsc<1024, 1>(WD + r + (j >> 2) * ST + (j & 3) * 128), 1);
        }
      };
      auto epi_q = [&](float (&a)[96], float r0, float r1, uint32_t (&o)[16]) {
        const float rl0 = r0 * 1.44269511f, rl1 = r1 * 1.44269511f;
        const uint32_t q0 = dup2(r0), q1 = dup2(r1);
#pragma unroll
        for (int j = 0; j < 8; j++) { o[j * 2] = phi2(a[64 + j * 4], a[65 + j * 4], rl0, q0); o[j * 2 + 1] = phi2(a[66 + j * 4], a[67 + j * 4], rl1, q1); }
        pinu(o);
      };
      auto mma_kv1 = [&](float (&a)[96], uint32_t xo, int s) {
#pragma unroll
        for (int k = 0; k < 4; k++) wgmma_n128_ss<0, 1, 0>(a, dsc<1024, 1>(s * ST + xo + k * 2), dsc<1024, 1>(WV + s * ST + k * 128), 1);
      };
      auto epi_kv = [&](float (&a)[96], uint32_t (&xf)[32], uint32_t tile, float r0, float r1) {
        uint32_t o[8][4];
#pragma unroll
        for (int j = 3; j >= 0; j--) {
          const uint32_t z = j < 3 ? (xf[(j + 5) * 4] | (VZ && j < 2 ? o[j + 2][0] | o[j + 6][0] : 0)) & blockIdx.y : 0;
          pack_kv(a, j + 4, r0, r1, o[j + 4], z);
          swap_kv(xf, tile, j + 4, o[j + 4], (o[j + 4][2] | o[j + 4][3]) & blockIdx.y);
          pack_kv(a, j, r0, r1, o[j], z);
          swap_kv(xf, tile, j, o[j]);
        }
      };
      bar_arrive(15, 288); bar_arrive(0, 288);
      mbar_wait(mb + B_FULL + 8, 1);
      if (!wg) bar_sync(3, 256);
      pinr<0, 64>(acc0); pinr<0, 64>(acc1);
      wg_fence();
      mma_kv1(acc1, xo1, 0); mma_kv1(acc0, xo0, 0); mma_kv1(acc1, xo1, 1);
      if (GSPLIT == 2) mma_kv1(acc0, xo0, 1);
      mbar_wait(mb + B_FULL + 16, 1);
      wg_fence();
      mma_kv1(acc1, xo1, 2);
      mbar_wait(mb + (wg ? B_FULL + 24 : B_F15), wg);
      wg_fence();
      mma_kv1(acc1, xo1, 3);
      wg_commit();
      bar_arrive(4 - wg, 256);
      static_for<16, 24>(center);
      pinr<64, 96>(acc0); pinr<64, 96>(acc1);
      mbar_wait(mb + B_FULL + 8, 1);
      wg_wait<0>();
      pinr<0, 64>(acc0); pinr<0, 64>(acc1);
      TS(9);
      epi_kv(acc1, xf1, wg * 2 + (hf ^ 1), rs[1][0], rs[1][1]);
      pinu(xf1);
      if (FPOS == 3) fence_async_smem();
      bar_sync(5 - wg, 256);
      wg_fence();
      if (GSPLIT == 1) mma_kv1(acc0, xo0, 1);
      mma_kv1(acc0, xo0, 2); mma_kv1(acc0, xo0, 3);
      wg_commit();
      if (FPOS == 1) fence_async_smem();
      mma_q(acc1, xf1, xo1, false);
      wg_commit();
      if (FPOS) bar_arrive(6 - wg, 256);
      else if (wg) bar_arrive(5, 256);
      else { fence_async_smem(); bar_arrive(6, 256); }
      wg_wait<1>();
      pinr<0, 64>(acc0);
      if (lane == 0) mbar_arrive(mb + B_EVA);
      TS(6);
      epi_kv(acc0, xf0, wg * 2 + hf, rs[0][0], rs[0][1]);
      fence_async_smem();
      pinu(xf0);
      TS(15);
      if (!wg) bar_arrive(7, 256);
      const uint32_t kvb = 2 * STAGE_B + (2 + (hf ^ 1)) * UNIT - sk;
      b1 = get_b();
      od1 = &P.s->obuf[(((b1 >> 4) * 4 + wg * 2 + (hf ^ 1)) * 64 + (b1 & 7)) * 128 + t128];
      ain = &P.s->obuf[((b1 >> 4) * 4 + wg * 2 + hf) * 64 * 128 + t128];
      uint32_t ka0 = sm + kvb + wid * 1024 + (lane & 7) * 128 + (((lane >> 3) ^ (lane & 7)) << 4), ka1 = sm + kvb + wid * 1024 + (t * 2 + g) * 128 + ((4 ^ (t * 2 + g)) << 4);
      const uint8_t* g0 = smem_raw + sk + STAGE_B + tid * 16, *g1 = smem_raw + sk + UNIT + g * 256 + wid * 32 + t * 8;
      const uint8_t* h0 = (const uint8_t*)&P.s->kvp[(b1 & 15) * 8 * 256 + tid], *h1 = (const uint8_t*)&P.s->zp[((b1 & 15) * 8 + g) * 16] + wid * 32 + t * 8;
      asm volatile("" : "+r"(ka0), "+r"(ka1), "+l"(g0), "+l"(g1), "+l"(h0), "+l"(h1), "+l"(od1));
      if (wg) {
        float ka[36];
        auto mma_kv = [&](uint32_t tile, int i, int acc) {
          const uint32_t o = (sk >> 4) + tile * 512 + i * 128;
          wgmma_n72_ss<1, 1, 0>(ka, dsc<1024, 1>(dlo(sb, 8192) + o), dsc<1024, 1>(dlo(sb + STAGE_B, OFF_STATS - STAGE_B) + o * (1u - (1u << 16))), acc);
        };
#pragma unroll
        for (int i = 0; i < 36; i++) ka[i] = 0.f;
        mbar_wait(mb + B_LATE, 0);
        bar_sync(6, 256);
        wg_fence();
#pragma unroll
        for (int i = 0; i < 4; i++) {
          mma_kv(2, i, i); mma_kv(3, i, 1);
          if (FPOS != 2) mma_kv(hf ^ 1, i, 1);
#pragma unroll
          for (int j = 2 * i; j < 2 * i + 2; j++)
            wgmma_n64_rs<1, 64>(acc0, xf0[j * 4], xf0[j * 4 + 1], xf0[j * 4 + 2], xf0[j * 4 + 3], dsc<1024, 1>(WD + (sk >> 4) + (j >> 2) * ST + (j & 3) * 128), 1);
        }
        const int kq = (b1 & 15) * 8 + (b1 >> 4);
        uint4* dst = &P.s->kvp[kq * 256 + warp * 64 + lane];
        uint32_t* dz = (uint32_t*)&P.s->zp[kq * 16] + warp * 16 + g + t * 8;
        asm volatile("" : "+l"(dst), "+l"(dz));
        bar_sync(7, 256);
#pragma unroll
        for (int i = 0; i < (FPOS == 2 ? 8 : 4); i++) mma_kv(FPOS == 2 ? 0 : hf, i, 1);
        wg_commit();
        bar_arrive(8, 256);
        wg_wait<0>();
        pin(ka); pinr<64, 96>(acc0);
        uint32_t kw[8];
#pragma unroll
        for (int i = 0; i < 8; i++) {
          const int j = (i & 3) * 4 + (i >> 2) * 2;
          asm("{\n.reg .pred p;\nsetp.ne.u32 p, %5, 0;\n@p cvt.rn.bf16x2.f32 %0, %4, %3;\n@!p cvt.rn.bf16x2.f32 %0, %2, %1;\n}"
              : "=r"(kw[i]) : "f"(ka[j]), "f"(ka[j + 1]), "f"(ka[16 + j]), "f"(ka[17 + j]), "r"(warp & 2));
        }
        st_rlx4(dst, make_uint4(kw[0], kw[1], kw[2], kw[3]));
        st_rlx4(dst + 32, make_uint4(kw[4], kw[5], kw[6], kw[7]));
        if (t < 2) st_rlx(dz, __float_as_uint(t ? ka[34] : ka[32]));
        if (lane == 0) mbar_arrive(mb + B_EVB);
        TS(8);
        const uint32_t t1 = clock64();
        while ((uint32_t)clock64() - t1 < SDELAY) {}
      } else {
        bar_sync(8, 256);
        wg_fence();
        mma_q(acc0, xf0, xo0, false);
      }
      if (!wg) bar_sync(9, 256);
      wg_fence();
      mma_q(acc1, xf1, xo1, true);
      wg_commit();
      if (wg) bar_arrive(9, 256); else mma_q(acc0, xf0, xo0, true);
      wg_commit();
      wg_wait<1>();
      pinr<64, 96>(acc1);
      TS(7);
      uint32_t pq[16];
      epi_q(acc1, rs[1][0], rs[1][1], pq);
      bar_sync(11 + wg + zero_after(pq), 128);
      if (wg) {
        wg_fence();
        mma_q(acc0, xf0, xo0, true);
        wg_commit();
      }
      TS(5);
      {
        uint4 gv[8]; uint2 gz;
        uint32_t m[8], a[4];
        float z0, z1;
#pragma unroll
        for (int s = 0; s < 8; s++) { m[s] = ~blockIdx.y; asm volatile("" : "=r"(gv[s].x), "=r"(gv[s].y), "=r"(gv[s].z), "=r"(gv[s].w), "+r"(m[s])); }
        mbar_wait(mb + B_KVP, 0);
        TS(28);
#pragma unroll 1
        for (int it = 0; it < SPIN_LIMIT; it++) {
          gz = ld_gen2(g1);
#pragma unroll
          for (int s = 0; s < 8; s++) if (m[s] == SENT) gv[s] = ld_gen4(g0 + s * 4096);
          g0 = h0; g1 = h1;
          uint32_t mm = max(gz.x, gz.y);
          z0 = __uint_as_float(gz.x); z1 = __uint_as_float(gz.y);
#pragma unroll
          for (int o = 4; o < 32; o <<= 1) { z0 += __shfl_xor_sync(~0u, z0, o); z1 += __shfl_xor_sync(~0u, z1, o); }
#pragma unroll
          for (int s = 0; s < 8; s++) m[s] = max4(0, gv[s]);
#pragma unroll
          for (int s = 0; s < 8; s += 2) mm = __vimax3_u32(mm, m[s], m[s + 1]);
          a[0] = hadd2(hadd2(hadd2(gv[0].x, gv[1].x), hadd2(gv[2].x, gv[3].x)), hadd2(hadd2(gv[4].x, gv[5].x), hadd2(gv[6].x, gv[7].x)));
          a[1] = hadd2(hadd2(hadd2(gv[0].y, gv[1].y), hadd2(gv[2].y, gv[3].y)), hadd2(hadd2(gv[4].y, gv[5].y), hadd2(gv[6].y, gv[7].y)));
          a[2] = hadd2(hadd2(hadd2(gv[0].z, gv[1].z), hadd2(gv[2].z, gv[3].z)), hadd2(hadd2(gv[4].z, gv[5].z), hadd2(gv[6].z, gv[7].z)));
          a[3] = hadd2(hadd2(hadd2(gv[0].w, gv[1].w), hadd2(gv[2].w, gv[3].w)), hadd2(hadd2(gv[4].w, gv[5].w), hadd2(gv[6].w, gv[7].w)));
          pinu(a);
          if (!__any_sync(~0u, mm == SENT)) break;
          TSV(20, 1);
        }
        TS(23);
        wg_wait<0>();
        pinr<64, 96>(acc0);
        if (lane == 0) mbar_arrive(mb + B_KVB);
        stsm4(ka0, a[0], a[1], a[2], a[3]);
        const uint32_t zz = pack2(g ? z1 : z0, g ? z1 : z0);
        if (lane < 8) sts4(ka1, zz, zz, zz, zz);
        fence_async_smem();
        bar_sync(1, 256);
      }
      TS(21);
      auto make_o = [&](uint4 (&o)[4], auto first) {
        float oa[2][20];
        wg_fence();
#pragma unroll
        for (int ks = 0; ks < 4; ks++)
          wgmma_n40_rs<1, 0>(oa[ks >> 1], pq[ks * 4], pq[ks * 4 + 1], pq[ks * 4 + 2], pq[ks * 4 + 3], dsc<1024, 1>(dlo(sb, 8192) + (kvb >> 4) + ks * 128), ks & 1);
        wg_commit();
        if constexpr (!decltype(first)::value) {
          pinu(xf0);
#pragma unroll
          for (int q = 0; q < 32; q++) { acc[q * 2] = bf_lo(xf0[q]); acc[q * 2 + 1] = bf_hi(xf0[q]); }
          pin(acc);
          if (!R1MID) {
            mbar_wait(mb + B_F15, 1);
#pragma unroll
            for (int i = 0; i < 4; i++) abuf[1][i] = ld_rlx4(ain + i * 128);
            TS(3);
          }
          mbar_wait(mb + B_BF, 0);
        }
        wg_wait<0>();
        pin(oa[0]); pin(oa[1]);
        if (decltype(first)::value && lane < 2) mbar_arrive_rem(eb);
#pragma unroll
        for (int h = 0; h < 2; h++) {
          const float (&d)[20] = oa[h];
          const float i0 = rcp(d[16] + 1e-6f), i1 = rcp(d[18] + 1e-6f);
#pragma unroll
          for (int k2 = 0; k2 < 2; k2++) {
            o[h * 2 + k2] = make_uint4(pack2(d[k2 * 8] * i0, d[k2 * 8 + 1] * i0), pack2(d[k2 * 8 + 2] * i1, d[k2 * 8 + 3] * i1),
                                       pack2(d[k2 * 8 + 4] * i0, d[k2 * 8 + 5] * i0), pack2(d[k2 * 8 + 6] * i1, d[k2 * 8 + 7] * i1));
            if (decltype(first)::value && !h && k2 <= AFIRST) st_rlx4(od1 + k2 * 1024, o[k2]);
            if (decltype(first)::value && !h && k2 == AFIRST) { sched_fence(); TS(24); }
          }
        }
      };
      make_o(ost[1], std::true_type{});
      if (!AFIRST) { st_rlx4(od1 + 1024 + ((ost[1][2].x | ost[1][3].w) & blockIdx.y), ost[1][1]); sched_fence(); }
      auto read1 = [&](uint32_t z) {
        mbar_wait(mb + B_F15 + z, 1);
#pragma unroll
        for (int i = 0; i < 4; i++) abuf[1][i] = ld_rlx4(ain + i * 128);
        TS(3);
      };
      if (R1MID) {
        const float rl0 = rs[0][0] * 1.44269511f, rl1 = rs[0][1] * 1.44269511f;
        const uint32_t q0 = dup2(rs[0][0]), q1 = dup2(rs[0][1]);
        uint32_t z = 0;
#pragma unroll
        for (int j = 0; j < 8; j++) {
          pq[j * 2] = phi2(acc0[64 + j * 4], acc0[65 + j * 4], rl0, q0); pq[j * 2 + 1] = phi2(acc0[66 + j * 4], acc0[67 + j * 4], rl1, q1);
          if (j < R1MID) z |= pq[j * 2] | pq[j * 2 + 1];
          if (j == R1MID - 1) read1(z & 0x80008000u);
        }
      } else epi_q(acc0, rs[0][0], rs[0][1], pq);
      if (AEARLY == 1) { st_rlx4(od1 + 2048, ost[1][2]); st_rlx4(od1 + 3072, ost[1][3]); }
      make_o(ost[0], std::false_type{});
    }
   {
    IDS(b1);
    const int mb3 = rb * 4 + wg * 2 + hf;
    uint4* rp = &P.s->st2[mb3 * 64 + warp * 16 + g + t * 8];
    {
      uint4* const od0 = &P.s->obuf[(mb3 * 64 + 32 + s3 * 4) * 128 + t128];
#pragma unroll
      for (int i = 0; i < 4; i++) pin4(ost[0][i]);
      wg_fence();
#pragma unroll
      for (int k = 0; k < 4; k++) wgmma_n128_rs<1, 0>(acc, ost[0][k].x, ost[0][k].y, ost[0][k].z, ost[0][k].w, dsc<1024, 1>(dlo(sb + 4 * UNIT, 8192) + k * 128), 1);
      wg_commit();
      TS(29);
      if (AEARLY == 0) { st_rlx4(od1 + 2048, ost[1][2]); st_rlx4(od1 + 3072, ost[1][3]); }
      if (AEARLY == 2) st_rlx4(od1 + 2048, ost[1][2]);
      uint32_t la = sm + t128 * 16, ev = eb + 8;
      asm volatile("" : "+r"(la), "+r"(ev));
      auto fetch = [&](uint32_t off, uint4 (&a)[4]) { const uint32_t ra = la + off; a[0] = lds4_o<0>(ra); a[1] = lds4_o<2048>(ra); a[2] = lds4_o<4096>(ra); a[3] = lds4_o<6144>(ra); };
      auto check = [&](int p, uint4 (&a)[4]) {
        if (__any_sync(~0u, max(max4(max4(0, a[0]), a[1]), max4(max4(0, a[2]), a[3])) == SENT)) {
          int pl = p; asm volatile("" : "+r"(pl));
          const uint4* q = ain + frag_of(pl);
#pragma unroll 1
          for (int it = 0;; it++) {
            uint32_t mm = 0;
#pragma unroll
            for (int i = 0; i < 4; i++) { const uint32_t m = max4(0, a[i]); mm = max(mm, m); if (m == SENT) a[i] = ld_rlx4(q + i * 128); }
            if (!__any_sync(~0u, mm == SENT)) break;
            TSV(27, p < 3 ? 1 : p < 5 ? 100 : 10000);
            SPINCHK(it, 5);
          }
        }
        if (lane < 2) mbar_arrive_rem(ev);
        ev = (ev & ~0x38u) | ((ev + 8) & 0x38u);
      };
      auto mma = [&](int p, uint32_t bs, uint4 (&a)[4]) {
#pragma unroll
        for (int i = 0; i < 4; i++) pin4(a[i]);
        wg_fence();
#pragma unroll
        for (int k = 0; k < 4; k++) wgmma_n128_rs<1, 0>(acc, a[k].x, a[k].y, a[k].z, a[k].w, dsc<1024, 1>(bs + k * 128), 1);
        wg_commit();
      };
      uint32_t ta = sm + OFF_STATS + wg * 256 + 48;
      mbar_wait(mb + B_WR, 0);
      uint4 tp = lds4(ta);
      mbar_wait(mb + B_BF + 8, 0);
      check(1, abuf[1]);
      if (P1F) { mbar_wait(mb + B_BF + 16, 0); fetch(ring_of(2, wg), abuf[2]); }
      mma(1, dlo(sb + 11 * UNIT, 8192), abuf[1]);
      if (!P1F) { mbar_wait(mb + B_BF + 16, 0); fetch(ring_of(2, wg), abuf[2]); }
      TS(25);
      if (AEARLY == 2) st_rlx4(od1 + 3072, ost[1][3]);
      st_rlx4(od0, ost[0][0]); st_rlx4(od0 + 128, ost[0][1]);
      check(2, abuf[2]);
      mbar_wait(mb + B_BF + 24, 0);
      fetch(ring_of(3, wg), abuf[0]);
      mma(2, dlo(sb + 18 * UNIT, 8192), abuf[2]);
      st_rlx4(od0 + 256, ost[0][2]); st_rlx4(od0 + 384, ost[0][3]);
      wg_wait<2>();
      check(3, abuf[0]);
      mbar_wait(mb + B_BF + 32, 0);
      TS(26);
#pragma unroll 1
      for (int p = 3; p < 15; p += 3) {
        static_for<0, 3>([&](auto jc) {
          constexpr int j = decltype(jc)::value;
          const uint4 tc = tp;
          const uint32_t bs = __shfl_sync(~0u, tc.x, 0);
          wg_wait<1>();
#pragma unroll
          for (int i = 0; i < 4; i++) pin4(abuf[(j + 1) % 3][i]);
          tp = lds4_o<16 * j + 16>(ta);
          fetch(tc.y, abuf[(j + 1) % 3]);
          mma(p + j, bs, abuf[j]);
          if (!CHKF) mbar_wait(tc.z, tc.w);
          check(p + j + 1, abuf[(j + 1) % 3]);
          if (CHKF) mbar_wait(tc.z, tc.w);
        });
        ta += 48;
      }
      {
        const uint32_t wa0 = sm + OFF_COLSUM + ((g & 1) ? t * 64 : 256);
        wb[0] = lds4_o<0>(wa0); wb[1] = lds4_o<16>(wa0); wb[2] = lds4_o<32>(wa0); wb[3] = lds4_o<48>(wa0);
      }
      mma(15, __shfl_sync(~0u, tp.x, 0), abuf[0]);
      wg_wait<2>();
      if (lane == 0) mbar_arrive(mb + B_E16);
      asm volatile("" : "+l"(rp));
      sched_fence();
      wg_wait<0>();
      pin(acc);
#pragma unroll
      for (int i = 0; i < 4; i++) { pin4(abuf[0][i]); pin4(abuf[1][i]); pin4(abuf[2][i]); }
    }
    TS(10);
    {
      float q0[2] = {0.f, 0.f}, q1[2] = {0.f, 0.f}, c[2][4] = {};
#pragma unroll
      for (int j = 0; j < 16; j++) {
        hp[j * 2] = pack2(acc[j * 4], acc[j * 4 + 1]); hp[j * 2 + 1] = pack2(acc[j * 4 + 2], acc[j * 4 + 3]);
        q0[j & 1] = fmaf(acc[j * 4], acc[j * 4], fmaf(acc[j * 4 + 1], acc[j * 4 + 1], q0[j & 1]));
        q1[j & 1] = fmaf(acc[j * 4 + 2], acc[j * 4 + 2], fmaf(acc[j * 4 + 3], acc[j * 4 + 3], q1[j & 1]));
        if (j & 1) {
          const uint32_t a[4] = {hp[j * 2 - 2], hp[j * 2 - 1], hp[j * 2], hp[j * 2 + 1]};
          mma16816(c[(j >> 1) & 1], a, (j & 2) ? wb[j >> 2].z : wb[j >> 2].x, (j & 2) ? wb[j >> 2].w : wb[j >> 2].y);
        }
      }
      const bool od = t & 1;
      float q = (od ? q1[0] + q1[1] : q0[0] + q0[1]) + __shfl_xor_sync(~0u, od ? q0[0] + q0[1] : q1[0] + q1[1], 1);
      q += __shfl_xor_sync(~0u, q, 2);
      asm volatile("{\n.reg .pred p;\nsetp.lt.u32 p, %5, 2;\n@p red.relaxed.gpu.global.add.v4.f32 [%0], {%1,%2,%3,%4};\n}"
                   :: "l"(rp), "f"(od ? c[0][2] + c[1][2] : c[0][0] + c[1][0]), "f"(q), "f"(od ? c[0][3] + c[1][3] : c[0][1] + c[1][1]), "f"(1.f), "r"(t) : "memory");
    }
    TS(11);
    const uint32_t ts = clock64();
    const uint32_t msc = sm + OFF_STATS;
    const uint32_t hst = sm + 4 * UNIT + wg * STAGE_B + warp * 4096, gslot = sm + unit_of(rank ? GT1 : GT0, wid);
    bar_sync(1, 256);
#pragma unroll
    for (int j = 0; j < 8; j++)
      stsm4(hst + (lane & 15) * 256 + (((2 * j + (lane >> 4)) ^ (lane & 7)) << 4), hp[j * 4], hp[j * 4 + 1], hp[j * 4 + 2], hp[j * 4 + 3]);
    uint32_t wa[8][4][4], wd[8][2][4];
    const uint32_t a0 = gslot + ((lane >> 4) * 8 + (lane & 7)) * 64 + ((((lane >> 3) & 1) ^ ((lane >> 1) & 3)) << 4);
    auto load_gu = [&](auto ic) { constexpr int i = decltype(ic)::value; ldsm4t_o<(i >> 2) * 1024 + ((i >> 1) & 1) * 8192>(a0 ^ ((i & 1) << 5), wa[i >> 2][i & 3]); };
    uint32_t tx;
    {
      const int row = rb * 256 + tid;
      const uint4* sp = &P.s->st2[row], *sq = &P.s->st2[row ^ 256];
      const float sw = __uint_as_float((lds1(mb + B_SW) & ~255u) | 128);
      uint4 v[2];
      uint4* d = &P.s->hsel[c3 * 128 + (g & 3) * 32 + ((rb & 6) + (lane >> 4)) * 4 + t];
      uint32_t* dk = &P.s->cand[c3 * 32 + (rb & 6) + (lane >> 4)];
      asm volatile("" : "+l"(d), "+l"(dk));
      if (fidx >= 0) mbar_wait(mb + B_FFN, 0);
      static_for<0, GU1>(load_gu);
      while ((uint32_t)clock64() - ts < SDEL2) {}
      v[0] = ld_rlx4(sp); v[1] = ld_rlx4(sq);
      static_for<GU1, GU2>(load_gu);
#pragma unroll 1
      for (int it = 0; __any_sync(~0u, min(v[0].w, v[1].w) != 0x41000000u) && it < SPIN_LIMIT; it++) {
        if (v[0].w != 0x41000000u) v[0] = ld_rlx4(sp);
        if (v[1].w != 0x41000000u) v[1] = ld_rlx4(sq);
        TSV(22, 1);
      }
      if (lane == 0) mbar_arrive(mb + B_EVA);
      TS(12);
      uint32_t k[2];
#pragma unroll
      for (int i = 0; i < 2; i++) {
        const float mean = __uint_as_float(v[i].x) * (1.f / D_);
        const float rstd = rsq(fmaxf(fmaf(-mean, mean, __uint_as_float(v[i].y) * (1.f / D_)), 0.f) + 1e-5f);
        const uint32_t u = __float_as_uint(rstd * fmaf(-mean, sw, __uint_as_float(v[i].z)));
        k[i] = min(((u ^ ((uint32_t)((int)u >> 31) | 0x80000000u)) & ~2047u), 0xFFFFF000u) | (2047 - (row ^ (i << 8)));
        if (i == 0 && (warp >> 1) == hf) sts2f(sm + OFF_LNP + (wg * 64 + (tid & 63)) * 8, rstd, -mean * rstd);
      }
      const uint32_t hi = max(k[0], k[1]);
      uint32_t m1 = __reduce_max_sync(~0u, hi), m2 = __reduce_max_sync(~0u, hi == m1 ? min(k[0], k[1]) : hi);
      if (lane == 0) sts2f(msc + wid * 8, __uint_as_float(m1), __uint_as_float(m2));
      bar_sync(1, 256);
      const uint32_t kk = lds1(msc + (lane & 15) * 4);
      m1 = __reduce_max_sync(~0u, kk); m2 = __reduce_max_sync(~0u, kk == m1 ? 0 : kk);
      const int c0 = 2047 - (m1 & 2047), c1 = 2047 - (m2 & 2047);
      if ((c0 >> 4) == mb3 * 4 + warp || (c1 >> 4) == mb3 * 4 + warp) {
        const int ra = (lane & 4) ? c1 : c0, rd = (lane & 16) ? c1 : c0;
        uint32_t h0, h1, h2, h3;
        ldsm4_o<0>(hst + (ra & 15) * 256 + ((((lane & 3) * 4 + (lane >> 3)) ^ (ra & 7)) << 4), h0, h1, h2, h3);
        const float2 pr = lds2f(sm + OFF_LNP + (wid * 16 + (rd & 15)) * 8);
        if ((rd >> 4) == mb3 * 4 + warp) {
          st_rlx4(d, make_uint4(pack2(fmaf(bf_lo(h0), pr.x, pr.y), fmaf(bf_hi(h0), pr.x, pr.y)), pack2(fmaf(bf_lo(h1), pr.x, pr.y), fmaf(bf_hi(h1), pr.x, pr.y)),
                                pack2(fmaf(bf_lo(h2), pr.x, pr.y), fmaf(bf_hi(h2), pr.x, pr.y)), pack2(fmaf(bf_lo(h3), pr.x, pr.y), fmaf(bf_hi(h3), pr.x, pr.y))));
          if (!(lane & 15)) st_rlx(dk, (lane & 16) ? m2 : m1);
          st_rlx4(d + 1024, make_uint4(h0, h1, h2, h3));
        }
      }
      tx = clock64();
      if (tid == 0) { sts2f(msc + 64, __uint_as_float(m1), __uint_as_float(m2)); mbar_arrive(mb + B_OUT); }
    }
    TS(13);
    static_for<GU2, 32>(load_gu);
    const uint32_t dl = sm + (wid & 1) * 4096 + ((lane >> 4) * 8 + (lane & 7)) * 128 + ((((lane >> 3) & 1) ^ (lane & 7)) << 4);
    uint32_t da = dl + unit_of(DT0, wid >> 1), db = dl + unit_of(rank ? DT1 : DT0, 4 + (wid >> 1));
    uint32_t* yp = (uint32_t*)&P.s->ybuf[((wid * 8 + t * 2) * NFFN + fidx) * 2] + g;
    uint32_t k1, k2;
    uint2 key;
    {
      float gu[2][4][4];
      uint4 xb[4];
      uint32_t m[4];
      const uint4* xp = &P.s->hsel[wid * 128 + lane];
      const uint2* kp = (const uint2*)&P.s->cand[wid * 32] + t;
      uint32_t ps = gslot + g * 32;
      asm volatile("" : "+l"(xp), "+l"(kp), "+l"(yp), "+r"(db), "+r"(ps));
      if (fidx >= 0) mbar_wait(mb + B_FFD, 0);
      static_for<0, 8>([&](auto ic) { constexpr int i = decltype(ic)::value; ldsm4t_o<(i & 1) * 2048>(da ^ ((i >> 1) << 5), wd[i >> 1][i & 1]); });
      while ((uint32_t)clock64() - tx < XDELAY) {}
      key = ld_rlx2(kp);
#pragma unroll
      for (int i = 0; i < 4; i++) xb[i] = ld_rlx4(xp + i * 32);
      if (fidx >= 0) mbar_wait(mb + B_KVP, 1);
#pragma unroll 1
      for (int it = 0; it < SPIN_LIMIT; it++) {
#pragma unroll
        for (int i = 0; i < 4; i++) m[i] = max4(0, xb[i]);
        if (!__any_sync(~0u, __vimax3_u32(__vimax3_u32(max(key.x, key.y), m[0], m[1]), m[2], m[3]) == SENT)) break;
        key = ld_rlx2(kp);
#pragma unroll
        for (int i = 0; i < 4; i++) if (m[i] == SENT) xb[i] = ld_rlx4(xp + i * 32);
        TSV(20, 100);
      }
      TS(14);
      const uint32_t hi = max(key.x, key.y);
      k1 = __reduce_max_sync(~0u, hi); k2 = __reduce_max_sync(~0u, hi == k1 ? min(key.x, key.y) : hi);
#pragma unroll
      for (int i = 0; i < 32; i++) gu[i >> 4][(i >> 2) & 3][i & 3] = 0.f;
#pragma unroll
      for (int ks = 0; ks < 8; ks++) {
#pragma unroll
        for (int i = 0; i < 4; i++) mma16816(gu[ks & 1][i], wa[ks][i], (ks & 1) ? xb[ks >> 1].z : xb[ks >> 1].x, (ks & 1) ? xb[ks >> 1].w : xb[ks >> 1].y);
        if (ks == 1) {
          const uint32_t dd = db | (__float_as_uint(gu[1][3][0]) & blockIdx.y);
          static_for<0, 8>([&](auto ic) { constexpr int i = decltype(ic)::value; ldsm4t_o<(i & 1) * 2048>(dd ^ ((i >> 1) << 5), wd[4 + (i >> 1)][i & 1]); });
        }
      }
#pragma unroll
      for (int c = 0; c < 2; c++) {
        const uint32_t kc = c ? key.y : key.x;
        float o[8];
#pragma unroll
        for (int j = 0; j < 8; j++) o[j] = gu[0][(j >> 2) + (j & 1) * 2][(j & 2) + c] + gu[1][(j >> 2) + (j & 1) * 2][(j & 2) + c];
        asm volatile("{\n.reg .pred p;\nsetp.ge.u32 p, %9, %10;\n@p st.shared.v4.f32 [%0], {%1,%2,%3,%4};\n@p st.shared.v4.f32 [%0+16], {%5,%6,%7,%8};\n}"
                     :: "r"(ps + (kc == k1 ? 0 : 256)), "f"(o[0]), "f"(o[1]), "f"(o[2]), "f"(o[3]), "f"(o[4]), "f"(o[5]), "f"(o[6]), "f"(o[7]), "r"(kc), "r"(k2) : "memory");
      }
    }
    TS(4);
    bar_sync(1, 256);
    {
      float g0 = 0.f, g1 = 0.f, u0 = 0.f, u1 = 0.f;
      static_for<0, 8>([&](auto wc) { constexpr int w = decltype(wc)::value;
        constexpr uint32_t o = sb + ((GT0 >> (5 * w)) & 31) * UNIT;
        const uint32_t ad = own + lane * 8 + (w == 0 || w == 7 ? sk : w < 3 ? -sk : 0);
        const float2 a = lds2f_o<o>(ad), c = lds2f_o<o + 256>(ad);
        g0 += a.x; u0 += a.y; g1 += c.x; u1 += c.y; });
      const uint32_t act = pack2(g0 * rcp(1.f + ex2(-1.4426950408889634f * g0)) * u0, g1 * rcp(1.f + ex2(-1.4426950408889634f * g1)) * u1);
      uint32_t bq[4];
#pragma unroll
      for (int i = 0; i < 4; i++) {
        const uint32_t lo = __shfl_sync(~0u, act, 8 * t + i), hi = __shfl_sync(~0u, act, 8 * t + 4 + i);
        bq[i] = __byte_perm(lo, hi, (g & 1) ? 0x7632 : 0x5410);
      }
      TS(16);
      float ya[8][4];
#pragma unroll
      for (int i = 0; i < 8; i++) { ya[i][0] = 0.f; ya[i][1] = 0.f; ya[i][2] = 0.f; ya[i][3] = 0.f; }
#pragma unroll
      for (int ks = 0; ks < 2; ks++)
#pragma unroll
        for (int i = 0; i < 8; i++) mma16816(ya[i], wd[i][ks], bq[ks * 2], bq[ks * 2 + 1]);
#pragma unroll
      for (int h = 0; h < 2; h++) {
        float o[4];
#pragma unroll
        for (int j = 0; j < 4; j++) o[j] = t == 0 ? ya[h * 4][j] : t == 1 ? ya[h * 4 + 1][j] : t == 2 ? ya[h * 4 + 2][j] : ya[h * 4 + 3][j];
        asm volatile("{\n.reg .pred p;\nsetp.ge.s32 p, %3, 0;\n@p st.relaxed.gpu.global.u32 [%0], %1;\n@p st.relaxed.gpu.global.u32 [%0+%4], %2;\n}"
                     :: "l"(yp + h * (64 * NFFN * 8)), "r"(pack2(o[0], o[1])), "r"(pack2(o[2], o[3])), "r"(fidx), "n"(NFFN * 32) : "memory");
      }
    }
    if (tid == 0) { sts2f(msc + 80, __uint_as_float(k1), __uint_as_float(k2)); mbar_arrive(mb + B_SEL); }
    TS(17);
    const uint32_t ty = clock64();
    if (wid == 0) {
      const uint32_t* yq = (const uint32_t*)&P.s->ybuf[b * NFFN * 2] + t * 8 + g;
      const uint32_t ks = (t & 1) ? k2 : k1, grp = 3 - ((ks >> 9) & 3);
      const int fs = grp * 2 + (__shfl_sync(~0u, key.y, grp) == ks);
      const uint32_t* fq = (const uint32_t*)P.s->hsel + (((b >> 4) * 4 + ((b >> 2) & 3)) * 32 + fs * 4 + (g >> 1)) * 4 + (b & 3);
      float gate = rcp(1.f + ex2(-1.4426950408889634f * __uint_as_float(ks ^ (~(uint32_t)((int)ks >> 31) | 0x80000000u))));
      __nv_bfloat16* op = P.out + (size_t)(2047 - (ks & 2047)) * D_ + b * 8 + g;
      uint32_t sel = (g & 2) ? 0x3F800000u : 0x00003F80u;
      uint32_t fn = ld_rlx(fq), fh = ld_rlx(fq + 4096), v[7][4];
      uint32_t m[7];
#pragma unroll
      for (int i = 0; i < 7; i++) { m[i] = ~blockIdx.y; asm volatile("" : "=r"(v[i][0]), "=r"(v[i][1]), "=r"(v[i][2]), "=r"(v[i][3]), "+r"(m[i])); }
      asm volatile("" : "+l"(yq), "+l"(op), "+f"(gate), "+r"(sel));
      while ((uint32_t)clock64() - ty < YDELAY) {}
      float y[2][4];
#pragma unroll 1
      for (int it = 0; it < SPIN_LIMIT; it++) {
        static_for<0, 7>([&](auto ic) { constexpr int i = decltype(ic)::value;
          asm volatile("{\n.reg .pred p;\nsetp.eq.u32 p, %5, 0xFFFFFFFF;\n@p ld.relaxed.gpu.global.u32 %0, [%4+%6];\n@p ld.relaxed.gpu.global.u32 %1, [%4+%6+128];\n"
                       "@p ld.relaxed.gpu.global.u32 %2, [%4+%6+256];\n@p ld.relaxed.gpu.global.u32 %3, [%4+%6+384];\n}"
                       : "+r"(v[i][0]), "+r"(v[i][1]), "+r"(v[i][2]), "+r"(v[i][3]) : "l"(yq), "r"(YPRED ? m[i] : SENT), "n"(i * 512) : "memory"); });
        uint32_t mm = max(fn, fh);
        if (mm == SENT) { fn = ld_rlx(fq); fh = ld_rlx(fq + 4096); }
#pragma unroll
        for (int i = 0; i < 8; i++) y[i >> 2][i & 3] = 0.f;
#pragma unroll
        for (int i = 0; i < 7; i++) { m[i] = __vimax3_u32(max(v[i][0], v[i][1]), v[i][2], v[i][3]); mm = max(mm, m[i]); mma16816(y[i & 1], v[i], sel, sel); }
        TSV(22, 100);
        pin(y[0]); pin(y[1]);
        if (!__any_sync(~0u, mm == SENT)) break;
      }
      TS(18);
      const float base = (g & 1) ? bf_hi(fh) + bf_hi(fn) : bf_lo(fh) + bf_lo(fn);
      if (t < 2) *op = __float2bfloat16(fmaf((y[0][0] + y[1][0]) + (y[0][2] + y[1][2]), gate, base));
      if (b == 0 && lane == 0) P.s->epoch = lds1(mb + B_SW) & 255;
    }
    if (tid == 0) SPANS(1);
    TS(19); TSG(31);
    if (warp == 0) TS_DUMP(wg);
   }
  }
}

typedef CUresult (*EncodeFn)(CUtensorMap*, CUtensorMapDataType, cuuint32_t, void*, const cuuint64_t*, const cuuint64_t*, const cuuint32_t*,
                             const cuuint32_t*, CUtensorMapInterleave, CUtensorMapSwizzle, CUtensorMapL2promotion, CUtensorMapFloatOOBfill);
void make_map(EncodeFn enc, CUtensorMap* m, const void* p, int rank, std::initializer_list<cuuint64_t> dims, std::initializer_list<cuuint64_t> str,
              std::initializer_list<cuuint32_t> box, CUtensorMapSwizzle sw) {
  const cuuint32_t es[4] = {1, 1, 1, 1};
  enc(m, CU_TENSOR_MAP_DATA_TYPE_BFLOAT16, rank, const_cast<void*>(p), dims.begin(), str.begin(), box.begin(), es, CU_TENSOR_MAP_INTERLEAVE_NONE, sw,
      CU_TENSOR_MAP_L2_PROMOTION_L2_128B, CU_TENSOR_MAP_FLOAT_OOB_FILL_NONE);
}

}

extern "C" void kernel_launch(void* const* d_in, const int* in_sizes, int n_in, void* d_out, int out_size) {
  (void)in_sizes; (void)n_in; (void)out_size;
  Ptrs P;
  P.x = (const __nv_bfloat16*)d_in[0]; P.wqkv = (const __nv_bfloat16*)d_in[1]; P.wo = (const __nv_bfloat16*)d_in[2];
  P.wr = (const __nv_bfloat16*)d_in[4]; P.wg = (const __nv_bfloat16*)d_in[5]; P.wu = (const __nv_bfloat16*)d_in[6];
  P.wd = (const __nv_bfloat16*)d_in[7]; P.out = (__nv_bfloat16*)d_out;
  cudaGetSymbolAddress((void**)&P.s, g_scratch);
  void* fn = nullptr;
  cudaDriverEntryPointQueryResult q;
  cudaGetDriverEntryPoint("cuTensorMapEncodeTiled", &fn, cudaEnableDefault, &q);
  EncodeFn enc = (EncodeFn)fn;
  Maps T;
  constexpr CUtensorMapSwizzle S128 = CU_TENSOR_MAP_SWIZZLE_128B, S64 = CU_TENSOR_MAP_SWIZZLE_64B;
  make_map(enc, &T.m[M_X], P.x, 2, {D_, S_}, {D_ * 2}, {64, 128}, S128);
  make_map(enc, &T.m[M_W], P.wqkv, 3, {D_, D_, 3}, {3 * D_ * 2, D_ * 2}, {64, 64, 2}, S128);
  make_map(enc, &T.m[M_Q], P.wqkv, 2, {3 * D_, D_}, {3 * D_ * 2}, {64, 64}, S128);
  make_map(enc, &T.m[M_O], P.wo, 4, {64, 64, 16, 16}, {D_ * 2, 64 * D_ * 2, 128}, {64, 64, 1, 2}, S128);
  make_map(enc, &T.m[M_S], P.wo, 4, {64, 64, 16, 16}, {D_ * 2, 64 * D_ * 2, 128}, {64, 16, 4, 2}, S128);
  make_map(enc, &T.m[M_G], P.wg, 3, {F_, D_, 1}, {F_ * 2, F_ * 2 * D_}, {32, 128, 1}, S64);
  make_map(enc, &T.m[M_U], P.wu, 3, {F_, D_, 1}, {F_ * 2, F_ * 2 * D_}, {32, 128, 1}, S64);
  make_map(enc, &T.m[M_D], P.wd, 3, {64, F_, 16}, {D_ * 2, 128}, {64, 32, 2}, S128);
  make_map(enc, &T.m[M_L], P.wd, 2, {64, F_ * 16}, {128}, {8, 32}, CU_TENSOR_MAP_SWIZZLE_NONE);
  cudaFuncSetAttribute(fused_kernel, cudaFuncAttributeMaxDynamicSharedMemorySize, SMEM_BYTES);
  fused_kernel<<<NCTA, 384, SMEM_BYTES>>>(P, T);
}
```

```cpp
#include <cuda_runtime.h>
#include <cuda.h>
#include <cuda_bf16.h>
#include <stdint.h>
#include <type_traits>
#include <initializer_list>

namespace {

constexpr int S_ = 2048, D_ = 1024, F_ = 3584;
constexpr int NCTA = 128, NFFN = 112;
constexpr uint32_t SENT = 0xFFFFFFFFu;
constexpr int SPIN_LIMIT = 1 << 20;

#define ADELAY 200
#define ADELAY2 600
#define PFA 6
#define PF0 8
#define WPF0 8
#define DPER 1200
#define PDEPTH 2
#define PSTART 4000
#define PPER 1700
#define PEARLY 5
#define PLEAD 0
#define RST 1
#define PSUB 2
#define HOLDP 1
#define QHOLD 1
#define NPULL 12
#define CDELAY 0
#define NOUTW 4
#define YDELAY 650
#define EFX 0
#define EFW 1
#define EFF 1
#define KLEAD 13
#define GDELAY 400
#define NDIR 6
#define PULL0 3
#define FD0 600
#define FD1 800
#define SPF 1
#define MPF 1
#define TLBW 2
#define GORD 0
#define GSPLIT 2
#define EFW0 0
#define EFX0 0
#define EFWK 8
#define PSLEEP 20
#define P3PULL 1
#define RST2 4
#define KDELAY 450
#define AEARLY 0
#define BHOLD 4
#define SDELAY 100
#define FSTAG 150
#define OFL 0
#define CHKF 1
#define BEV 1
#define DLATE 4
#define P3GATE 3
#define ACCSW 0
#define B45 B_E
#define SDEL2 500
#define XDELAY 500
#define GU1 8
#define GU2 20
#define WD1 10
#define ODELAY 0
#define NOOUT 0
constexpr int OUNR =
  2;
#define P3N 2
#define HALFMAP 1
#define KWARP 7
#define FEARLY 1
#define MFIRST 350
#define MKV 850
#define MO 800
#define MST 0
#define MSTE 13
#define AFIRST 0
#define MWIDE 0
#define PLAG 8
#define PSTEP 0
#define EFA 0
#define EFO 0
#define EFB 0
#define EFXK 12
#define P1F 1
#define R1MID 5
#define OPACE 450
#define VH 1
#define VZ 0
#define FPOS 1
#define NOHELP 0
#define NAPNS 20
#define NAP do { if (NAPNS) __nanosleep(NAPNS); } while (0)
#define SMASK 3
#define YPRED 1
#define NC 1
#define DPOS 0
#define DBEH 0
#define MSTG 1
#define PSTOP 3
#define DMASK 0x5550
#define PFST 1
#define W0OFF 2
#define MAPM 2
#define XWPF 0
constexpr uint32_t STAGE_B = 57344;
constexpr uint32_t OFF_STATS = 229376;
constexpr uint32_t OFF_COLSUM = 231424;
constexpr uint32_t OFF_BARS = 232192;
constexpr uint32_t SMEM_BYTES = 232448;
constexpr uint32_t B_FULL = 0, B_EMPTY = 32, B_E = 64, B_AUX = 128, B_EVA = 136, B_EVB = 144, B_BF = 152, B_LATE = 232, B_FFN = 240, B_SW = 248;
constexpr uint32_t B_OUT = B_FULL, B_SEL = B_FULL + 8, B_WR = B_FULL + 16, B_FFD = B_FULL + 24, B_E16 = B_EMPTY + 16, B_KVB = B_EMPTY + 8, B_DUMMY = B_SW + 4,
                   B_GATE = B_EMPTY + 24, B_ID = B_BF + 56, B_KVP = B_BF + 64, B_F15 = B_BF + 72;
#define B_HOLD B_F15
#define HOLDPAR 0
constexpr uint32_t UNIT = 8192;
constexpr uint32_t sb = 1024;
constexpr uint32_t bars = sb + OFF_BARS;
constexpr uint64_t tab5(int a, int b, int c, int d, int e, int f, int g, int h, int i = 0, int j = 0) {
  return (uint64_t)a | (uint64_t)b << 5 | (uint64_t)c << 10 | (uint64_t)d << 15 | (uint64_t)e << 20 | (uint64_t)f << 25 | (uint64_t)g << 30 | (uint64_t)h << 35 |
         (uint64_t)i << 40 | (uint64_t)j << 45;
}
constexpr uint64_t BT0 = tab5(4, 11, 18, 25, 7, 9, 16, 0), BT1 = tab5(4, 11, 18, 25, 21, 23, 2, 0);
constexpr uint64_t GT0 = tab5(2, 21, 23, 18, 0, 25, 14, 7), GT1 = tab5(16, 7, 9, 18, 0, 25, 14, 21);
constexpr uint64_t DT0 = tab5(6, 13, 20, 27, 9, 10, 16, 17), DT1 = tab5(6, 13, 20, 27, 23, 24, 2, 3);
__device__ __forceinline__ uint32_t unit_of(uint64_t tab, int i) { return ((uint32_t)(tab >> (5 * i)) & 31) * UNIT; }
__device__ __forceinline__ uint32_t ring_of(int p, int w) { return (p & 1) * (2 * STAGE_B) + ((p & 2) ? 49152 + w * STAGE_B : w * UNIT); }
constexpr uint32_t OFF_LNP = OFF_STATS + 1024;

struct Scratch {
  uint4 obuf[32 * 64 * 128];
  uint4 kvp[16 * 8 * 256];
  uint4 zp[16 * 8 * 16];
  uint4 ybuf[NCTA * NFFN * 2];
  uint4 st1[64 * 48];
  uint4 csp[16 * 8 * 48];
  uint4 st2[S_];
  uint4 hsel[(NC + 1) * 8 * 128];
  uint32_t cand[NC * 8 * 32];
  uint32_t when[36 * 32];
  unsigned epoch;
};
__device__ __align__(1024) Scratch g_scratch;
#define TS_DECL
#define TS(i)
#define TSG(i)
#define TSV(i, v)
#define TSD(i)
#define RTS_DECL
#define RTS(i)
#define RTS_DUMP
#define TS_DUMP(slot)
#define PTS(i)
#define g_dbgv(i, v)

#define SPANS(i)
__device__ __forceinline__ uint32_t smem_u32(const void* p) { return (uint32_t)__cvta_generic_to_shared(p); }
__device__ __forceinline__ void mbar_init(uint32_t bar, uint32_t cnt) { asm volatile("mbarrier.init.shared::cta.b64 [%0], %1;" :: "r"(bar), "r"(cnt) : "memory"); }
__device__ __forceinline__ void mbar_expect_tx(uint32_t bar, uint32_t bytes) { asm volatile("mbarrier.arrive.expect_tx.shared::cta.b64 _, [%0], %1;" :: "r"(bar), "r"(bytes) : "memory"); }
__device__ __forceinline__ void mbar_arrive(uint32_t bar) { asm volatile("mbarrier.arrive.shared::cta.b64 _, [%0];" :: "r"(bar) : "memory"); }
#define SPINCHK(it, code) if ((it) > SPIN_LIMIT) break
__device__ __forceinline__ void mbar_wait(uint32_t bar, uint32_t parity) {
  asm volatile("{\n.reg .pred p;\n.reg .u32 c;\nmov.u32 c, 0;\n"
               "WL:\nmbarrier.try_wait.parity.shared::cta.b64 p, [%0], %1;\n@p bra WD;\n"
               "add.u32 c, c, 1;\nsetp.lt.u32 p, c, 1048576;\n@p bra WL;\nWD:\n}" :: "r"(bar), "r"(parity) : "memory");
}
__device__ __forceinline__ bool mbar_test(uint32_t bar, uint32_t parity) {
  uint32_t ok;
  asm volatile("{\n.reg .pred p;\nmbarrier.test_wait.parity.shared::cta.b64 p, [%1], %2;\nselp.u32 %0, 1, 0, p;\n}" : "=r"(ok) : "r"(bar), "r"(parity) : "memory");
  return ok;
}
__device__ __forceinline__ uint64_t l2_stream() { uint64_t p; asm("createpolicy.fractional.L2::evict_first.b64 %0, 1.0;" : "=l"(p)); return p; }
__device__ __forceinline__ void tma_2d(uint32_t dst, const CUtensorMap* tm, int c0, int c1, uint32_t bar, bool stream) {
  if (stream) asm volatile("cp.async.bulk.tensor.2d.shared::cluster.global.mbarrier::complete_tx::bytes.L2::cache_hint [%0], [%1, {%3, %4}], [%2], %5;"
                           :: "r"(dst), "l"(tm), "r"(bar), "r"(c0), "r"(c1), "l"(l2_stream()) : "memory");
  else asm volatile("cp.async.bulk.tensor.2d.shared::cluster.global.mbarrier::complete_tx::bytes [%0], [%1, {%3, %4}], [%2];"
                    :: "r"(dst), "l"(tm), "r"(bar), "r"(c0), "r"(c1) : "memory");
}
__device__ __forceinline__ void tma_3d(uint32_t dst, const CUtensorMap* tm, int c0, int c1, int c2, uint32_t bar, bool stream) {
  if (stream) asm volatile("cp.async.bulk.tensor.3d.shared::cluster.global.mbarrier::complete_tx::bytes.L2::cache_hint [%0], [%1, {%3, %4, %5}], [%2], %6;"
                           :: "r"(dst), "l"(tm), "r"(bar), "r"(c0), "r"(c1), "r"(c2), "l"(l2_stream()) : "memory");
  else asm volatile("cp.async.bulk.tensor.3d.shared::cluster.global.mbarrier::complete_tx::bytes [%0], [%1, {%3, %4, %5}], [%2];"
                    :: "r"(dst), "l"(tm), "r"(bar), "r"(c0), "r"(c1), "r"(c2) : "memory");
}
__device__ __forceinline__ void tma_pf_3d(const CUtensorMap* tm, int c0, int c1, int c2) {
  asm volatile("cp.async.bulk.prefetch.tensor.3d.L2.global [%0, {%1, %2, %3}];" :: "l"(tm), "r"(c0), "r"(c1), "r"(c2) : "memory");
}
__device__ __forceinline__ void tma_4d(uint32_t dst, const CUtensorMap* tm, int c0, int c1, int c2, int c3, uint32_t bar, bool stream) {
  if (stream) asm volatile("cp.async.bulk.tensor.4d.shared::cluster.global.mbarrier::complete_tx::bytes.L2::cache_hint [%0], [%1, {%3, %4, %5, %6}], [%2], %7;"
                           :: "r"(dst), "l"(tm), "r"(bar), "r"(c0), "r"(c1), "r"(c2), "r"(c3), "l"(l2_stream()) : "memory");
  else asm volatile("cp.async.bulk.tensor.4d.shared::cluster.global.mbarrier::complete_tx::bytes [%0], [%1, {%3, %4, %5, %6}], [%2];"
                    :: "r"(dst), "l"(tm), "r"(bar), "r"(c0), "r"(c1), "r"(c2), "r"(c3) : "memory");
}
__device__ __forceinline__ void tma_2d_mc(uint32_t dst, const CUtensorMap* tm, int c0, int c1, uint32_t bar, bool stream) {
  if (stream) asm volatile("cp.async.bulk.tensor.2d.shared::cluster.global.mbarrier::complete_tx::bytes.multicast::cluster.L2::cache_hint [%0], [%1, {%3, %4}], [%2], %5, %6;"
                           :: "r"(dst), "l"(tm), "r"(bar), "r"(c0), "r"(c1), "h"((uint16_t)3), "l"(l2_stream()) : "memory");
  else asm volatile("cp.async.bulk.tensor.2d.shared::cluster.global.mbarrier::complete_tx::bytes.multicast::cluster [%0], [%1, {%3, %4}], [%2], %5;"
                    :: "r"(dst), "l"(tm), "r"(bar), "r"(c0), "r"(c1), "h"((uint16_t)3) : "memory");
}
__device__ __forceinline__ bool elect_one() {
  uint32_t p;
  asm volatile("{\n.reg .pred q;\nelect.sync _|q, 0xFFFFFFFF;\nselp.u32 %0, 1, 0, q;\n}" : "=r"(p));
  return p;
}
__device__ __forceinline__ void bulk_load_mc(uint32_t dst, const void* src, uint32_t bytes, uint32_t bar) {
  if (EFA) asm volatile("cp.async.bulk.shared::cluster.global.mbarrier::complete_tx::bytes.multicast::cluster.L2::cache_hint [%0], [%1], %2, [%3], %4, %5;"
                        :: "r"(dst), "l"(src), "r"(bytes), "r"(bar), "h"((uint16_t)3), "l"(l2_stream()) : "memory");
  else asm volatile("cp.async.bulk.shared::cluster.global.mbarrier::complete_tx::bytes.multicast::cluster [%0], [%1], %2, [%3], %4;"
                    :: "r"(dst), "l"(src), "r"(bytes), "r"(bar), "h"((uint16_t)3) : "memory");
}
__device__ __forceinline__ void bulk_load(uint32_t dst, const void* src, uint32_t bytes, uint32_t bar) {
  asm volatile("cp.async.bulk.shared::cluster.global.mbarrier::complete_tx::bytes [%0], [%1], %2, [%3];" :: "r"(dst), "l"(src), "r"(bytes), "r"(bar) : "memory");
}
__device__ __forceinline__ void st_out(void* p, uint4 v) {
  if (EFO == 1) asm volatile("st.global.L2::cache_hint.v4.u32 [%0], {%1,%2,%3,%4}, %5;" :: "l"(p), "r"(v.x), "r"(v.y), "r"(v.z), "r"(v.w), "l"(l2_stream()) : "memory");
  else if (EFO == 2) asm volatile("st.global.cs.v4.u32 [%0], {%1,%2,%3,%4};" :: "l"(p), "r"(v.x), "r"(v.y), "r"(v.z), "r"(v.w) : "memory");
  else asm volatile("st.global.v4.u32 [%0], {%1,%2,%3,%4};" :: "l"(p), "r"(v.x), "r"(v.y), "r"(v.z), "r"(v.w) : "memory");
}
__device__ __forceinline__ void bulk_store(void* dst, uint32_t src, uint32_t bytes) {
  asm volatile("cp.async.bulk.global.shared::cta.bulk_group [%0], [%1], %2;" :: "l"(dst), "r"(src), "r"(bytes) : "memory");
}
__device__ __forceinline__ void mbar_arrive_rem(uint32_t bar) { asm volatile("mbarrier.arrive.shared::cluster.b64 _, [%0];" :: "r"(bar) : "memory"); }
__device__ __forceinline__ void st_async4(uint32_t addr, const uint4& v, uint32_t bar) {
  asm volatile("st.async.shared::cluster.mbarrier::complete_tx::bytes.v4.b32 [%0], {%1,%2,%3,%4}, [%5];" :: "r"(addr), "r"(v.x), "r"(v.y), "r"(v.z), "r"(v.w), "r"(bar) : "memory");
}
template <uint32_t O> __device__ __forceinline__ void ldsm4_o(uint32_t addr, uint32_t& a, uint32_t& b, uint32_t& c, uint32_t& d) {
  asm volatile("ldmatrix.sync.aligned.m8n8.x4.shared.b16 {%0,%1,%2,%3}, [%4+%5];" : "=r"(a), "=r"(b), "=r"(c), "=r"(d) : "r"(addr), "n"(O) : "memory");
}
template <uint32_t O> __device__ __forceinline__ void ldsm4t_o(uint32_t addr, uint32_t (&r)[4]) {
  asm volatile("ldmatrix.sync.aligned.m8n8.x4.trans.shared.b16 {%0,%1,%2,%3}, [%4+%5];" : "=r"(r[0]), "=r"(r[1]), "=r"(r[2]), "=r"(r[3]) : "r"(addr), "n"(O) : "memory");
}
__device__ __forceinline__ void mma16816(float (&c)[4], const uint32_t (&a)[4], uint32_t b0, uint32_t b1) {
  asm("mma.sync.aligned.m16n8k16.row.col.f32.bf16.bf16.f32 {%0,%1,%2,%3}, {%4,%5,%6,%7}, {%8,%9}, {%0,%1,%2,%3};"
      : "+f"(c[0]), "+f"(c[1]), "+f"(c[2]), "+f"(c[3]) : "r"(a[0]), "r"(a[1]), "r"(a[2]), "r"(a[3]), "r"(b0), "r"(b1));
}
__device__ __forceinline__ void l2_prefetch(const void* p) { asm volatile("prefetch.global.L2 [%0];" :: "l"(p) : "memory"); }
__device__ __forceinline__ uint32_t ld_line(const void* p) { uint32_t v; asm volatile("ld.global.cg.L2::128B.u32 %0, [%1];" : "=r"(v) : "l"(p) : "memory"); return v; }
__device__ __forceinline__ void tmap_prefetch(const CUtensorMap* tm) { asm volatile("prefetch.tensormap [%0];" :: "l"(tm) : "memory"); }
__device__ __forceinline__ void wg_fence() { asm volatile("wgmma.fence.sync.aligned;" ::: "memory"); }
__device__ __forceinline__ void wg_commit() { asm volatile("wgmma.commit_group.sync.aligned;" ::: "memory"); }
template <int N> __device__ __forceinline__ void wg_wait() { asm volatile("wgmma.wait_group.sync.aligned %0;" :: "n"(N) : "memory"); }
template <int N> __device__ __forceinline__ void pin(float (&d)[N]) {
#pragma unroll
  for (int i = 0; i < N; i++) asm volatile("" : "+f"(d[i]) :: "memory");
}
__device__ __forceinline__ void pin4(uint4& v) { asm volatile("" : "+r"(v.x), "+r"(v.y), "+r"(v.z), "+r"(v.w) :: "memory"); }
template <uint32_t SBO, uint32_t SWZ> __device__ __forceinline__ uint64_t dsc(uint32_t lo) { return ((uint64_t)((SBO >> 4) | (SWZ << 30)) << 32) | lo; }
__host__ __device__ constexpr uint32_t dlo(uint32_t addr, uint32_t lbo) { return (addr >> 4) | ((lbo >> 4) << 16); }
__device__ __forceinline__ void bar_sync(int id, int n) { asm volatile("bar.sync %0, %1;" :: "r"(id), "r"(n) : "memory"); }
__device__ __forceinline__ void bar_arrive(int id, int n) { asm volatile("bar.arrive %0, %1;" :: "r"(id), "r"(n) : "memory"); }
__device__ __forceinline__ void fence_async_smem() { asm volatile("fence.proxy.async.shared::cta;" ::: "memory"); }
__device__ __forceinline__ void fence_gpu() { asm volatile("fence.acq_rel.gpu;" ::: "memory"); }
__device__ __forceinline__ uint4 ld_cg4(const void* p) { uint4 v; asm volatile("ld.global.cg.v4.u32 {%0,%1,%2,%3}, [%4];" : "=r"(v.x), "=r"(v.y), "=r"(v.z), "=r"(v.w) : "l"(p) : "memory"); return v; }
__device__ __forceinline__ uint4 ld_rlx4(const void* p) { uint4 v; asm volatile("ld.relaxed.gpu.global.v4.u32 {%0,%1,%2,%3}, [%4];" : "=r"(v.x), "=r"(v.y), "=r"(v.z), "=r"(v.w) : "l"(p) : "memory"); return v; }
__device__ __forceinline__ uint32_t ld_rlx(const void* p) { uint32_t v; asm volatile("ld.relaxed.gpu.global.u32 %0, [%1];" : "=r"(v) : "l"(p) : "memory"); return v; }
__device__ __forceinline__ void st_rlx4(void* p, uint4 v) { asm volatile("st.relaxed.gpu.global.v4.u32 [%0], {%1,%2,%3,%4};" :: "l"(p), "r"(v.x), "r"(v.y), "r"(v.z), "r"(v.w) : "memory"); }
__device__ __forceinline__ void st_rlx2(void* p, uint32_t a, uint32_t b) { asm volatile("st.relaxed.gpu.global.v2.u32 [%0], {%1,%2};" :: "l"(p), "r"(a), "r"(b) : "memory"); }
__device__ __forceinline__ void st_rlx(void* p, uint32_t a) { asm volatile("st.relaxed.gpu.global.u32 [%0], %1;" :: "l"(p), "r"(a) : "memory"); }
__device__ __forceinline__ void red4(void* p, float a, float b, float c, float d) { asm volatile("red.relaxed.gpu.global.add.v4.f32 [%0], {%1,%2,%3,%4};" :: "l"(p), "f"(a), "f"(b), "f"(c), "f"(d) : "memory"); }
__device__ __forceinline__ uint32_t pack2(float lo, float hi) { uint32_t r; asm("cvt.rn.bf16x2.f32 %0, %1, %2;" : "=r"(r) : "f"(hi), "f"(lo)); return r; }
__device__ __forceinline__ float bf_lo(uint32_t v) { return __uint_as_float(v << 16); }
__device__ __forceinline__ float bf_hi(uint32_t v) { return __uint_as_float(v & 0xFFFF0000u); }
__device__ __forceinline__ void stsm4(uint32_t addr, uint32_t a, uint32_t b, uint32_t c, uint32_t d) {
  asm volatile("stmatrix.sync.aligned.m8n8.x4.shared.b16 [%0], {%1,%2,%3,%4};" :: "r"(addr), "r"(a), "r"(b), "r"(c), "r"(d) : "memory");
}
template <uint32_t O> __device__ __forceinline__ void stsm4_o(uint32_t addr, uint32_t a, uint32_t b, uint32_t c, uint32_t d) {
  asm volatile("stmatrix.sync.aligned.m8n8.x4.shared.b16 [%0+%5], {%1,%2,%3,%4};" :: "r"(addr), "r"(a), "r"(b), "r"(c), "r"(d), "n"(O) : "memory");
}
__device__ __forceinline__ void sts4(uint32_t addr, uint32_t a, uint32_t b, uint32_t c, uint32_t d) { asm volatile("st.shared.v4.u32 [%0], {%1,%2,%3,%4};" :: "r"(addr), "r"(a), "r"(b), "r"(c), "r"(d) : "memory"); }
__device__ __forceinline__ void sts2f(uint32_t addr, float a, float b) { asm volatile("st.shared.v2.f32 [%0], {%1,%2};" :: "r"(addr), "f"(a), "f"(b) : "memory"); }
__device__ __forceinline__ void sts1(uint32_t addr, uint32_t a) { asm volatile("st.shared.u32 [%0], %1;" :: "r"(addr), "r"(a) : "memory"); }
__device__ __forceinline__ float2 lds2f(uint32_t addr) { float2 v; asm volatile("ld.shared.v2.f32 {%0,%1}, [%2];" : "=f"(v.x), "=f"(v.y) : "r"(addr) : "memory"); return v; }
template <uint32_t O> __device__ __forceinline__ float2 lds2f_o(uint32_t addr) { float2 v; asm volatile("ld.shared.v2.f32 {%0,%1}, [%2+%3];" : "=f"(v.x), "=f"(v.y) : "r"(addr), "n"(O) : "memory"); return v; }
template <int I, int N, class F> __device__ __forceinline__ void static_for(F&& f) { if constexpr (I < N) { f(std::integral_constant<int, I>{}); static_for<I + 1, N>(f); } }
__device__ __forceinline__ uint4 lds4(uint32_t addr) { uint4 v; asm volatile("ld.shared.v4.u32 {%0,%1,%2,%3}, [%4];" : "=r"(v.x), "=r"(v.y), "=r"(v.z), "=r"(v.w) : "r"(addr) : "memory"); return v; }
__device__ __forceinline__ uint32_t lds1(uint32_t addr) { uint32_t v; asm volatile("ld.shared.u32 %0, [%1];" : "=r"(v) : "r"(addr) : "memory"); return v; }
__device__ __forceinline__ float ex2(float x) { float y; asm("ex2.approx.ftz.f32 %0, %1;" : "=f"(y) : "f"(x)); return y; }
__device__ __forceinline__ uint32_t max4(uint32_t m, const uint4& v) { return __vimax3_u32(__vimax3_u32(m, v.x, v.y), v.z, v.w); }
__device__ __forceinline__ float rsq(float x) { float y; asm("rsqrt.approx.ftz.f32 %0, %1;" : "=f"(y) : "f"(x)); return y; }
__device__ __forceinline__ float rcp(float x) { float y; asm("rcp.approx.ftz.f32 %0, %1;" : "=f"(y) : "f"(x)); return y; }
__device__ __forceinline__ uint2 ld_rlx2(const void* p) { uint2 v; asm volatile("ld.relaxed.gpu.global.v2.u32 {%0,%1}, [%2];" : "=r"(v.x), "=r"(v.y) : "l"(p) : "memory"); return v; }
template <uint32_t O> __device__ __forceinline__ uint4 lds4_o(uint32_t addr) { uint4 v; asm volatile("ld.shared.v4.u32 {%0,%1,%2,%3}, [%4+%5];" : "=r"(v.x), "=r"(v.y), "=r"(v.z), "=r"(v.w) : "r"(addr), "n"(O) : "memory"); return v; }
__device__ __forceinline__ uint32_t phi2(float u0, float u1, float rl, uint32_t r2) {
  uint32_t pu, r;
  asm("cvt.rn.relu.bf16x2.f32 %0, %1, %2;" : "=r"(pu) : "f"(u1), "f"(u0));
  asm("fma.rn.bf16x2 %0, %1, %2, %3;" : "=r"(r) : "r"(pu), "r"(r2), "r"(pack2(__saturatef(ex2(u0 * rl) + 1e-6f), __saturatef(ex2(u1 * rl) + 1e-6f))));
  return r;
}
__device__ __forceinline__ uint32_t dup2(float r) { uint32_t v; asm("cvt.rn.relu.bf16x2.f32 %0, %1, %1;" : "=r"(v) : "f"(r)); return v; }
__device__ __forceinline__ uint32_t zero_after(const uint32_t (&v)[16]) {
  uint32_t z = 0;
#pragma unroll
  for (int i = 0; i < 16; i++) z |= v[i];
  return z & 0x80008000u;
}
__device__ __forceinline__ uint32_t hadd2(uint32_t a, uint32_t b) { uint32_t v; asm("add.rn.bf16x2 %0, %1, %2;" : "=r"(v) : "r"(a), "r"(b)); return v; }
__device__ __forceinline__ void sched_fence() { asm volatile("{\n.reg .pred p;\n.reg .u64 c;\nSF:\nmov.u64 c, %clock64;\nsetp.eq.u64 p, c, 0;\n@p bra SF;\n}" ::: "memory"); }
__device__ __forceinline__ uint4 ld_gen4(const void* p) { uint4 v; asm volatile("ld.relaxed.gpu.v4.u32 {%0,%1,%2,%3}, [%4];" : "=r"(v.x), "=r"(v.y), "=r"(v.z), "=r"(v.w) : "l"(p) : "memory"); return v; }
__device__ __forceinline__ uint2 ld_gen2(const void* p) { uint2 v; asm volatile("ld.relaxed.gpu.v2.u32 {%0,%1}, [%2];" : "=r"(v.x), "=r"(v.y) : "l"(p) : "memory"); return v; }
__device__ __forceinline__ uint32_t now_ns() { uint32_t v; asm volatile("mov.u32 %0, %%globaltimer_lo;" : "=r"(v) :: "memory"); return v; }
__device__ __forceinline__ void meet(uint32_t* mine, const uint4* all, int first, int after, uint32_t bar) {
  const uint32_t t0 = now_ns() & ~1u;
  if ((threadIdx.x & 31) == 0) st_rlx(mine, t0);
  while ((int)(now_ns() - t0) < first) NAP;
  uint4 v;
#pragma unroll 1
  for (int it = 0; it < SPIN_LIMIT; it++) { v = ld_rlx4(all); if (!__any_sync(~0u, max4(0, v) == SENT)) break; }
  const int d = min(__reduce_max_sync(~0u, max(max((int)(v.x - t0), (int)(v.y - t0)), max((int)(v.z - t0), (int)(v.w - t0)))), 100000) + after;
  mbar_wait(bar, 0);
  while ((int)(now_ns() - t0) < d) NAP;
}
__device__ __forceinline__ uint32_t hmul2(uint32_t a, uint32_t b) { uint32_t v; asm("mul.rn.bf16x2 %0, %1, %2;" : "=r"(v) : "r"(a), "r"(b)); return v; }
__device__ __forceinline__ uint32_t lane_id() { uint32_t v; asm volatile("mov.u32 %0, %%laneid;" : "=r"(v)); return v; }
template <int A, int B, int N> __device__ __forceinline__ void pinr(float (&d)[N]) {
#pragma unroll
  for (int i = A; i < B; i++) asm volatile("" : "+f"(d[i]) :: "memory");
}
template <int N> __device__ __forceinline__ void pinu(uint32_t (&d)[N]) {
#pragma unroll
  for (int i = 0; i < N; i++) asm volatile("" : "+r"(d[i]) :: "memory");
}

template<int TA, int TB, int OFF, int SZ> __device__ __forceinline__ void wgmma_n192_ss(float (&d)[SZ], uint64_t da, uint64_t db, int scale_d) {
  asm volatile("{\n.reg .pred p;\nsetp.ne.b32 p, %98, 0;\n"
    "wgmma.mma_async.sync.aligned.m64n192k16.f32.bf16.bf16 {%0,%1,%2,%3,%4,%5,%6,%7,%8,%9,%10,%11,%12,%13,%14,%15,%16,%17,%18,%19,%20,%21,%22,%23,%24,%25,%26,%27,%28,%29,%30,%31,%32,%33,%34,%35,%36,%37,%38,%39,%40,%41,%42,%43,%44,%45,%46,%47,%48,%49,%50,%51,%52,%53,%54,%55,%56,%57,%58,%59,%60,%61,%62,%63,%64,%65,%66,%67,%68,%69,%70,%71,%72,%73,%74,%75,%76,%77,%78,%79,%80,%81,%82,%83,%84,%85,%86,%87,%88,%89,%90,%91,%92,%93,%94,%95}, %96, %97, p, 1, 1, %99, %100;\n}\n"
    : "+f"(d[OFF+0]), "+f"(d[OFF+1]), "+f"(d[OFF+2]), "+f"(d[OFF+3]), "+f"(d[OFF+4]), "+f"(d[OFF+5]), "+f"(d[OFF+6]), "+f"(d[OFF+7]),
      "+f"(d[OFF+8]), "+f"(d[OFF+9]), "+f"(d[OFF+10]), "+f"(d[OFF+11]), "+f"(d[OFF+12]), "+f"(d[OFF+13]), "+f"(d[OFF+14]), "+f"(d[OFF+15]),
      "+f"(d[OFF+16]), "+f"(d[OFF+17]), "+f"(d[OFF+18]), "+f"(d[OFF+19]), "+f"(d[OFF+20]), "+f"(d[OFF+21]), "+f"(d[OFF+22]), "+f"(d[OFF+23]),
      "+f"(d[OFF+24]), "+f"(d[OFF+25]), "+f"(d[OFF+26]), "+f"(d[OFF+27]), "+f"(d[OFF+28]), "+f"(d[OFF+29]), "+f"(d[OFF+30]), "+f"(d[OFF+31]),
      "+f"(d[OFF+32]), "+f"(d[OFF+33]), "+f"(d[OFF+34]), "+f"(d[OFF+35]), "+f"(d[OFF+36]), "+f"(d[OFF+37]), "+f"(d[OFF+38]), "+f"(d[OFF+39]),
      "+f"(d[OFF+40]), "+f"(d[OFF+41]), "+f"(d[OFF+42]), "+f"(d[OFF+43]), "+f"(d[OFF+44]), "+f"(d[OFF+45]), "+f"(d[OFF+46]), "+f"(d[OFF+47]),
      "+f"(d[OFF+48]), "+f"(d[OFF+49]), "+f"(d[OFF+50]), "+f"(d[OFF+51]), "+f"(d[OFF+52]), "+f"(d[OFF+53]), "+f"(d[OFF+54]), "+f"(d[OFF+55]),
      "+f"(d[OFF+56]), "+f"(d[OFF+57]), "+f"(d[OFF+58]), "+f"(d[OFF+59]), "+f"(d[OFF+60]), "+f"(d[OFF+61]), "+f"(d[OFF+62]), "+f"(d[OFF+63]),
      "+f"(d[OFF+64]), "+f"(d[OFF+65]), "+f"(d[OFF+66]), "+f"(d[OFF+67]), "+f"(d[OFF+68]), "+f"(d[OFF+69]), "+f"(d[OFF+70]), "+f"(d[OFF+71]),
      "+f"(d[OFF+72]), "+f"(d[OFF+73]), "+f"(d[OFF+74]), "+f"(d[OFF+75]), "+f"(d[OFF+76]), "+f"(d[OFF+77]), "+f"(d[OFF+78]), "+f"(d[OFF+79]),
      "+f"(d[OFF+80]), "+f"(d[OFF+81]), "+f"(d[OFF+82]), "+f"(d[OFF+83]), "+f"(d[OFF+84]), "+f"(d[OFF+85]), "+f"(d[OFF+86]), "+f"(d[OFF+87]),
      "+f"(d[OFF+88]), "+f"(d[OFF+89]), "+f"(d[OFF+90]), "+f"(d[OFF+91]), "+f"(d[OFF+92]), "+f"(d[OFF+93]), "+f"(d[OFF+94]), "+f"(d[OFF+95])
    : "l"(da), "l"(db), "r"(scale_d), "n"(TA), "n"(TB));
}
template<int TA, int TB, int OFF, int SZ> __device__ __forceinline__ void wgmma_n128_ss(float (&d)[SZ], uint64_t da, uint64_t db, int scale_d) {
  asm volatile("{\n.reg .pred p;\nsetp.ne.b32 p, %66, 0;\n"
    "wgmma.mma_async.sync.aligned.m64n128k16.f32.bf16.bf16 {%0,%1,%2,%3,%4,%5,%6,%7,%8,%9,%10,%11,%12,%13,%14,%15,%16,%17,%18,%19,%20,%21,%22,%23,%24,%25,%26,%27,%28,%29,%30,%31,%32,%33,%34,%35,%36,%37,%38,%39,%40,%41,%42,%43,%44,%45,%46,%47,%48,%49,%50,%51,%52,%53,%54,%55,%56,%57,%58,%59,%60,%61,%62,%63}, %64, %65, p, 1, 1, %67, %68;\n}\n"
    : "+f"(d[OFF+0]), "+f"(d[OFF+1]), "+f"(d[OFF+2]), "+f"(d[OFF+3]), "+f"(d[OFF+4]), "+f"(d[OFF+5]), "+f"(d[OFF+6]), "+f"(d[OFF+7]),
      "+f"(d[OFF+8]), "+f"(d[OFF+9]), "+f"(d[OFF+10]), "+f"(d[OFF+11]), "+f"(d[OFF+12]), "+f"(d[OFF+13]), "+f"(d[OFF+14]), "+f"(d[OFF+15]),
      "+f"(d[OFF+16]), "+f"(d[OFF+17]), "+f"(d[OFF+18]), "+f"(d[OFF+19]), "+f"(d[OFF+20]), "+f"(d[OFF+21]), "+f"(d[OFF+22]), "+f"(d[OFF+23]),
      "+f"(d[OFF+24]), "+f"(d[OFF+25]), "+f"(d[OFF+26]), "+f"(d[OFF+27]), "+f"(d[OFF+28]), "+f"(d[OFF+29]), "+f"(d[OFF+30]), "+f"(d[OFF+31]),
      "+f"(d[OFF+32]), "+f"(d[OFF+33]), "+f"(d[OFF+34]), "+f"(d[OFF+35]), "+f"(d[OFF+36]), "+f"(d[OFF+37]), "+f"(d[OFF+38]), "+f"(d[OFF+39]),
      "+f"(d[OFF+40]), "+f"(d[OFF+41]), "+f"(d[OFF+42]), "+f"(d[OFF+43]), "+f"(d[OFF+44]), "+f"(d[OFF+45]), "+f"(d[OFF+46]), "+f"(d[OFF+47]),
      "+f"(d[OFF+48]), "+f"(d[OFF+49]), "+f"(d[OFF+50]), "+f"(d[OFF+51]), "+f"(d[OFF+52]), "+f"(d[OFF+53]), "+f"(d[OFF+54]), "+f"(d[OFF+55]),
      "+f"(d[OFF+56]), "+f"(d[OFF+57]), "+f"(d[OFF+58]), "+f"(d[OFF+59]), "+f"(d[OFF+60]), "+f"(d[OFF+61]), "+f"(d[OFF+62]), "+f"(d[OFF+63])
    : "l"(da), "l"(db), "r"(scale_d), "n"(TA), "n"(TB));
}
template<int TA, int TB, int OFF, int SZ> __device__ __forceinline__ void wgmma_n64_ss(float (&d)[SZ], uint64_t da, uint64_t db, int scale_d) {
  asm volatile("{\n.reg .pred p;\nsetp.ne.b32 p, %34, 0;\n"
    "wgmma.mma_async.sync.aligned.m64n64k16.f32.bf16.bf16 {%0,%1,%2,%3,%4,%5,%6,%7,%8,%9,%10,%11,%12,%13,%14,%15,%16,%17,%18,%19,%20,%21,%22,%23,%24,%25,%26,%27,%28,%29,%30,%31}, %32, %33, p, 1, 1, %35, %36;\n}\n"
    : "+f"(d[OFF+0]), "+f"(d[OFF+1]), "+f"(d[OFF+2]), "+f"(d[OFF+3]), "+f"(d[OFF+4]), "+f"(d[OFF+5]), "+f"(d[OFF+6]), "+f"(d[OFF+7]),
      "+f"(d[OFF+8]), "+f"(d[OFF+9]), "+f"(d[OFF+10]), "+f"(d[OFF+11]), "+f"(d[OFF+12]), "+f"(d[OFF+13]), "+f"(d[OFF+14]), "+f"(d[OFF+15]),
      "+f"(d[OFF+16]), "+f"(d[OFF+17]), "+f"(d[OFF+18]), "+f"(d[OFF+19]), "+f"(d[OFF+20]), "+f"(d[OFF+21]), "+f"(d[OFF+22]), "+f"(d[OFF+23]),
      "+f"(d[OFF+24]), "+f"(d[OFF+25]), "+f"(d[OFF+26]), "+f"(d[OFF+27]), "+f"(d[OFF+28]), "+f"(d[OFF+29]), "+f"(d[OFF+30]), "+f"(d[OFF+31])
    : "l"(da), "l"(db), "r"(scale_d), "n"(TA), "n"(TB));
}
template<int TA, int TB, int OFF, int SZ> __device__ __forceinline__ void wgmma_n72_ss(float (&d)[SZ], uint64_t da, uint64_t db, int scale_d) {
  asm volatile("{\n.reg .pred p;\nsetp.ne.b32 p, %38, 0;\n"
    "wgmma.mma_async.sync.aligned.m64n72k16.f32.bf16.bf16 {%0,%1,%2,%3,%4,%5,%6,%7,%8,%9,%10,%11,%12,%13,%14,%15,%16,%17,%18,%19,%20,%21,%22,%23,%24,%25,%26,%27,%28,%29,%30,%31,%32,%33,%34,%35}, %36, %37, p, 1, 1, %39, %40;\n}\n"
    : "+f"(d[OFF+0]), "+f"(d[OFF+1]), "+f"(d[OFF+2]), "+f"(d[OFF+3]), "+f"(d[OFF+4]), "+f"(d[OFF+5]), "+f"(d[OFF+6]), "+f"(d[OFF+7]),
      "+f"(d[OFF+8]), "+f"(d[OFF+9]), "+f"(d[OFF+10]), "+f"(d[OFF+11]), "+f"(d[OFF+12]), "+f"(d[OFF+13]), "+f"(d[OFF+14]), "+f"(d[OFF+15]),
      "+f"(d[OFF+16]), "+f"(d[OFF+17]), "+f"(d[OFF+18]), "+f"(d[OFF+19]), "+f"(d[OFF+20]), "+f"(d[OFF+21]), "+f"(d[OFF+22]), "+f"(d[OFF+23]),
      "+f"(d[OFF+24]), "+f"(d[OFF+25]), "+f"(d[OFF+26]), "+f"(d[OFF+27]), "+f"(d[OFF+28]), "+f"(d[OFF+29]), "+f"(d[OFF+30]), "+f"(d[OFF+31]),
      "+f"(d[OFF+32]), "+f"(d[OFF+33]), "+f"(d[OFF+34]), "+f"(d[OFF+35])
    : "l"(da), "l"(db), "r"(scale_d), "n"(TA), "n"(TB));
}
template<int TB, int OFF, int SZ> __device__ __forceinline__ void wgmma_n64_rs(float (&d)[SZ], uint32_t a0, uint32_t a1, uint32_t a2, uint32_t a3, uint64_t db, int scale_d) {
  asm volatile("{\n.reg .pred p;\nsetp.ne.b32 p, %37, 0;\n"
    "wgmma.mma_async.sync.aligned.m64n64k16.f32.bf16.bf16 {%0,%1,%2,%3,%4,%5,%6,%7,%8,%9,%10,%11,%12,%13,%14,%15,%16,%17,%18,%19,%20,%21,%22,%23,%24,%25,%26,%27,%28,%29,%30,%31}, {%32,%33,%34,%35}, %36, p, 1, 1, %38;\n}\n"
    : "+f"(d[OFF+0]), "+f"(d[OFF+1]), "+f"(d[OFF+2]), "+f"(d[OFF+3]), "+f"(d[OFF+4]), "+f"(d[OFF+5]), "+f"(d[OFF+6]), "+f"(d[OFF+7]),
      "+f"(d[OFF+8]), "+f"(d[OFF+9]), "+f"(d[OFF+10]), "+f"(d[OFF+11]), "+f"(d[OFF+12]), "+f"(d[OFF+13]), "+f"(d[OFF+14]), "+f"(d[OFF+15]),
      "+f"(d[OFF+16]), "+f"(d[OFF+17]), "+f"(d[OFF+18]), "+f"(d[OFF+19]), "+f"(d[OFF+20]), "+f"(d[OFF+21]), "+f"(d[OFF+22]), "+f"(d[OFF+23]),
      "+f"(d[OFF+24]), "+f"(d[OFF+25]), "+f"(d[OFF+26]), "+f"(d[OFF+27]), "+f"(d[OFF+28]), "+f"(d[OFF+29]), "+f"(d[OFF+30]), "+f"(d[OFF+31])
    : "r"(a0), "r"(a1), "r"(a2), "r"(a3), "l"(db), "r"(scale_d), "n"(TB));
}
template<int TB, int OFF, int SZ> __device__ __forceinline__ void wgmma_n40_rs(float (&d)[SZ], uint32_t a0, uint32_t a1, uint32_t a2, uint32_t a3, uint64_t db, int scale_d) {
  asm volatile("{\n.reg .pred p;\nsetp.ne.b32 p, %25, 0;\n"
    "wgmma.mma_async.sync.aligned.m64n40k16.f32.bf16.bf16 {%0,%1,%2,%3,%4,%5,%6,%7,%8,%9,%10,%11,%12,%13,%14,%15,%16,%17,%18,%19}, {%20,%21,%22,%23}, %24, p, 1, 1, %26;\n}\n"
    : "+f"(d[OFF+0]), "+f"(d[OFF+1]), "+f"(d[OFF+2]), "+f"(d[OFF+3]), "+f"(d[OFF+4]), "+f"(d[OFF+5]), "+f"(d[OFF+6]), "+f"(d[OFF+7]),
      "+f"(d[OFF+8]), "+f"(d[OFF+9]), "+f"(d[OFF+10]), "+f"(d[OFF+11]), "+f"(d[OFF+12]), "+f"(d[OFF+13]), "+f"(d[OFF+14]), "+f"(d[OFF+15]),
      "+f"(d[OFF+16]), "+f"(d[OFF+17]), "+f"(d[OFF+18]), "+f"(d[OFF+19])
    : "r"(a0), "r"(a1), "r"(a2), "r"(a3), "l"(db), "r"(scale_d), "n"(TB));
}
template<int TB, int OFF, int SZ> __device__ __forceinline__ void wgmma_n128_rs(float (&d)[SZ], uint32_t a0, uint32_t a1, uint32_t a2, uint32_t a3, uint64_t db, int scale_d) {
  asm volatile("{\n.reg .pred p;\nsetp.ne.b32 p, %69, 0;\n"
    "wgmma.mma_async.sync.aligned.m64n128k16.f32.bf16.bf16 {%0,%1,%2,%3,%4,%5,%6,%7,%8,%9,%10,%11,%12,%13,%14,%15,%16,%17,%18,%19,%20,%21,%22,%23,%24,%25,%26,%27,%28,%29,%30,%31,%32,%33,%34,%35,%36,%37,%38,%39,%40,%41,%42,%43,%44,%45,%46,%47,%48,%49,%50,%51,%52,%53,%54,%55,%56,%57,%58,%59,%60,%61,%62,%63}, {%64,%65,%66,%67}, %68, p, 1, 1, %70;\n}\n"
    : "+f"(d[OFF+0]), "+f"(d[OFF+1]), "+f"(d[OFF+2]), "+f"(d[OFF+3]), "+f"(d[OFF+4]), "+f"(d[OFF+5]), "+f"(d[OFF+6]), "+f"(d[OFF+7]),
      "+f"(d[OFF+8]), "+f"(d[OFF+9]), "+f"(d[OFF+10]), "+f"(d[OFF+11]), "+f"(d[OFF+12]), "+f"(d[OFF+13]), "+f"(d[OFF+14]), "+f"(d[OFF+15]),
      "+f"(d[OFF+16]), "+f"(d[OFF+17]), "+f"(d[OFF+18]), "+f"(d[OFF+19]), "+f"(d[OFF+20]), "+f"(d[OFF+21]), "+f"(d[OFF+22]), "+f"(d[OFF+23]),
      "+f"(d[OFF+24]), "+f"(d[OFF+25]), "+f"(d[OFF+26]), "+f"(d[OFF+27]), "+f"(d[OFF+28]), "+f"(d[OFF+29]), "+f"(d[OFF+30]), "+f"(d[OFF+31]),
      "+f"(d[OFF+32]), "+f"(d[OFF+33]), "+f"(d[OFF+34]), "+f"(d[OFF+35]), "+f"(d[OFF+36]), "+f"(d[OFF+37]), "+f"(d[OFF+38]), "+f"(d[OFF+39]),
      "+f"(d[OFF+40]), "+f"(d[OFF+41]), "+f"(d[OFF+42]), "+f"(d[OFF+43]), "+f"(d[OFF+44]), "+f"(d[OFF+45]), "+f"(d[OFF+46]), "+f"(d[OFF+47]),
      "+f"(d[OFF+48]), "+f"(d[OFF+49]), "+f"(d[OFF+50]), "+f"(d[OFF+51]), "+f"(d[OFF+52]), "+f"(d[OFF+53]), "+f"(d[OFF+54]), "+f"(d[OFF+55]),
      "+f"(d[OFF+56]), "+f"(d[OFF+57]), "+f"(d[OFF+58]), "+f"(d[OFF+59]), "+f"(d[OFF+60]), "+f"(d[OFF+61]), "+f"(d[OFF+62]), "+f"(d[OFF+63])
    : "r"(a0), "r"(a1), "r"(a2), "r"(a3), "l"(db), "r"(scale_d), "n"(TB));
}

struct Ptrs { const __nv_bfloat16 *x, *wqkv, *wo, *wr, *wg, *wu, *wd; __nv_bfloat16* out; Scratch* s; };

enum { M_X, M_W, M_Q, M_O, M_S, M_G, M_U, M_D, M_L, M_N };
struct Maps { CUtensorMap m[M_N]; };

__global__ void __cluster_dims__(2, 1, 1) __launch_bounds__(384, 1) fused_kernel(const Ptrs P, const __grid_constant__ Maps T) {
  extern __shared__ __align__(1024) uint8_t smem_raw[];
  TS_DECL; TS(0); TSG(30);
  if (threadIdx.x == 320) SPANS(0);
  const uint32_t rank = blockIdx.x & 1;
  uint32_t own = rank << 24;
  asm("" : "+r"(own));
  const uint32_t sm = own + sb, mb = own + bars;
  int b0;
  { const int j = blockIdx.x >> 1, u = j - 36, v = j * 2 - 8 + (max(u * 37 + 256, 0) >> 8) * (u < 0 ? 0 : 2), w = j < 4 ? j * 16 + 64 : v;
    b0 = ((w & 15) | (w & 48) << 1 | (w & 64) >> 2) + rank; }
#define IDS(B) \
  const int b = (B), rb = b >> 4, cg = b & 15, hf = cg >> 3, s3 = cg & 7, c3 = s3 ^ ((rb & 1) << 2), jp = cg >> 1, km = (~c3 & 6) << 1; \
  const int fidx = jp == rb ? -1 : b - 2 * rb - (jp > rb ? 2 : 0); \
  auto kcol = [&](int kb) { return (kb ^ (kb < 8 ? km & 8 : km)) * 64; }; \
  auto src_of = [&](int p) { return p == 0 ? s3 : p == 15 ? s3 ^ 1 : (((jp & 3) ^ ((p - 7) >> 1)) << 1) + ((p - 1) & 1); }; \
  auto frag_of = [&](int p) { return p < 9 ? (p - 1) * 512 : 4096 + src_of(p) * 512; }; \
  (void)hf; (void)fidx; (void)kcol; (void)frag_of
  auto get_b = [&]() { return __shfl_sync(~0u, (int)lds1(mb + B_ID), 0); };
  IDS(b0);
  auto load_w = [&](uint32_t st, int kc, uint32_t bar, bool last) { tma_3d(st + 32768, &T.m[M_W], cg * 64, kc, 1, bar, last); tma_2d(st + 49152, &T.m[M_Q], cg * 64, kc, bar, last); };
  RTS_DECL;
  if (threadIdx.x < 32 && elect_one()) {
    mbar_init(mb + B_FULL, 1);
    asm volatile("fence.mbarrier_init.release.cluster;" ::: "memory");
    mbar_expect_tx(mb + B_FULL, STAGE_B);
    load_w(sm, kcol(0), mb + B_FULL, false);
    tma_2d(sm + 16384, &T.m[M_X], kcol(0), rb * 256 + 128, mb + B_FULL, false);
    tma_2d(sm, &T.m[M_X], kcol(0), rb * 256, mb + B_FULL, false);
  }
  const int tid = threadIdx.x, wid = __shfl_sync(~0u, tid >> 5, 0), wg = wid >> 2, lane = lane_id();
  const uint32_t tk = clock64();
  if (wid < 4) {
    const int i = tid - 64;
    if (SPF && tid >= 32 && tid < 112)
      l2_prefetch(i < 0 ? P.x + (rb * 256 + (hf * 4 + (cg & 3)) * 32 + lane) * D_ + kcol(0) : P.wqkv + (kcol(0) + (rb >> 1) * 16 + (i & 15)) * 3072 + (i >> 4) * 1024 + cg * 64);
  } else if (wid == 9) {
    if (elect_one()) {
#pragma unroll
      for (int i = 1; i < 31; i++) if (8 * i != B_ID) mbar_init(mb + 8 * i, i < 4 ? 1 : i < 8 ? 8 : i < 16 ? 16 : i == 16 ? 64 : i == 17 ? 8 : i == 18 ? 4 : 1);
      asm volatile("fence.mbarrier_init.release.cluster;" ::: "memory");
      fence_async_smem();
    }
  } else if (wid == 11) {
#pragma unroll
    for (int i = 0; i < 4; i++) sts4(sm + OFF_STATS + i * 512 + lane * 16, SENT, SENT, SENT, SENT);
    sts1(mb + B_ID, b);
    if (smem_u32(smem_raw) != sm) asm volatile("trap;");
    fence_async_smem();
  }
  __syncthreads();
  asm volatile("barrier.cluster.arrive.relaxed.aligned;\nbarrier.cluster.wait.aligned;" ::: "memory");

  if (wg == 2) {
    asm volatile("setmaxnreg.dec.sync.aligned.u32 56;");
    if (wid == 8) {
      if (elect_one()) {
#pragma unroll 1
        for (int kb = 1; kb < 15; kb++) {
          const uint32_t fb = mb + B_FULL + 8 * (kb & 3), st = sm + (kb & 3) * STAGE_B;
          const int kc = kcol(kb);
          if (kb < 4) while ((uint32_t)clock64() - tk < FD0 + kb * FD1) {}
          else mbar_wait(fb + B_EMPTY, ((kb >> 2) & 1) ^ 1);
          mbar_expect_tx(fb, STAGE_B);
          tma_2d_mc(st + rank * 16384, &T.m[M_X], kc, rb * 256 + rank * 128, fb, kb >= EFXK);
          load_w(st, kc, fb, EFW && kb >= EFWK);
          if (kb >= 8 && kb < 11) asm volatile("mbarrier.arrive.shared::cta.b64 _, [%0], %1;" :: "r"(fb + B_EMPTY), "r"(4) : "memory");
        }
        {
          const uint32_t st = sm + 3 * STAGE_B, fa = mb + B_FULL + 24, fb = mb + B_F15;
          const int kc = kcol(15);
          mbar_wait(fa, 0);
          mbar_expect_tx(fa, 32768); mbar_expect_tx(fb, 24576);
          if (rank) { mbar_wait(mb + B_EMPTY + 24, 0); tma_2d_mc(st + 16384, &T.m[M_X], kc, rb * 256 + 128, fa, EFXK < 16); }
          mbar_wait(mb + B_EMPTY, 1);
          tma_3d(st + 32768, &T.m[M_W], cg * 64, kc, 1, fa, EFW);
          if (!rank) { mbar_wait(mb + B_EMPTY + 24, 0); tma_2d_mc(st, &T.m[M_X], kc, rb * 256, fb, EFXK < 16); }
          tma_2d(st + 49152, &T.m[M_Q], cg * 64, kc, fb, EFW);
        }
        mbar_expect_tx(mb + B_KVP, 32768 + 2048);
      }
      __syncwarp();
      const uint4* kp = &P.s->kvp[cg * 8 * 256], *zq = &P.s->zp[cg * 8 * 16], *src = &P.s->obuf[(rb * 4 + rank * 2 + hf) * 64 * 128];
      asm volatile("" : "+l"(kp), "+l"(zq), "+l"(src));
      mbar_wait(mb + B_EVA, 0);
      meet(&P.s->when[cg * 32 + rb], (const uint4*)&P.s->when[cg * 32] + (lane & 1), MFIRST, MKV, mb + B_EVB);
      if (elect_one()) {
        bulk_load(sm + rank * (2 * STAGE_B) + STAGE_B, kp, 32768, mb + B_KVP);
        bulk_load(sm + rank * (2 * STAGE_B) + UNIT, zq, 2048, mb + B_KVP);
      }
      RTS(1);
      mbar_wait(mb + B_KVP, 0);
      RTS(2);
      meet(&P.s->when[(16 + rb * 2 + hf) * 32 + s3], (const uint4*)&P.s->when[(16 + (MWIDE == 2 ? lane >> 1 : (MWIDE ? (lane & 6) + (rb & 1) : rb) * 2 + (hf ^ 1))) * 32] + (lane & 1), MFIRST, MO, mb + B_E);
      RTS(3);
      if (elect_one()) {
        const uint32_t t0 = clock64();
        mbar_arrive(mb + B_F15);
        RTS(4);
#pragma unroll
        for (int p = 2; p < 5; p++) {
          if (p < 4) while ((uint32_t)clock64() - t0 < (p == 2 ? ADELAY : ADELAY2)) NAP;
          bulk_load_mc(sm + ring_of(p, rank), src + (p - 1) * 512, UNIT, mb + B_BF + 8 * p);
        }
#pragma unroll 1
        for (int p = 5; p < 15; p++) {
          uint32_t dst = sm + ring_of(p, rank), bar = mb + B_BF + 8 * (p % 7);
          const uint4* q = src + frag_of(p);
          asm volatile("" : "+r"(dst), "+r"(bar), "+l"(q));
          mbar_wait(mb + B_E + 8 * ((p - 4) & 7), p >= 12);
          bulk_load_mc(dst, q, UNIT, bar);
        }
        asm volatile("mbarrier.arrive.shared::cta.b64 _, [%0], 8;" :: "r"(mb + B_GATE) : "memory");
        const uint4* s15 = &P.s->obuf[(rb * 4 + hf) * 64 * 128 + frag_of(15)];
        RTS_DUMP;
        mbar_wait(mb + B_E + 24, 1);
        bulk_load(sm + ring_of(15, 0), s15, UNIT, mb + B_BF + 8); bulk_load(sm + ring_of(15, 1), s15 + 2 * 64 * 128, UNIT, mb + B_BF + 8);
      }
    } else if (wid == 11) {
      IDS(get_b());
      if (fidx >= 0) {
        const uint32_t o = (rank * 32 + lane) * (F_ * 2) + (fidx >> 1) * 128;
        const char* q0 = (const char*)P.wg + o, *q1 = (const char*)P.wu + o;
        mbar_wait(mb + B_FULL + 24, 0);
        mbar_wait(mb + B_FULL + 8 * (PULL0 & 3), PULL0 >> 2);
#pragma unroll 1
        for (int r = 0; r < 16; r++, q0 += 64 * F_ * 2, q1 += 64 * F_ * 2) {
          if (mbar_test(mb + B_HOLD, 0)) { l2_prefetch(q0); l2_prefetch(q1); continue; }
          asm volatile("cp.async.ca.shared.global.L2::128B [%0], [%1], 4;\ncp.async.commit_group;\ncp.async.wait_group %3;\n"
                       "cp.async.ca.shared.global.L2::128B [%0], [%2], 4;\ncp.async.commit_group;\ncp.async.wait_group %3;" :: "r"(mb + B_DUMMY), "l"(q0), "l"(q1), "n"(PDEPTH) : "memory");
          if (lane == 0) g_dbgv(3, r + 1);
        }
        mbar_wait(mb + B_F15, 0);
        bar_sync(15, 288);
        if (lane == 0) PTS(1);
        q0 = (const char*)P.wd + fidx * 65536 + lane * 128;
        const uint32_t bar = mb + B_BF + 48;
        if (lane == 0) mbar_expect_tx(bar, 8192);
#pragma unroll 1
        for (int i = 0; i < 16 + PLAG; i++) {
          if (i < 16) l2_prefetch(q0 + i * 4096);
          if (i >= PLAG && elect_one()) tma_2d(sm + OFF_COLSUM, &T.m[M_L], 0, fidx * 512 + (i - PLAG) * 32, bar, false);
          const uint32_t t1 = clock64();
          while ((uint32_t)clock64() - t1 < PSTEP) {}
        }
        mbar_wait(bar, 0);
        __syncwarp();
        if (lane == 0) { mbar_arrive(bar); PTS(4); }
        asm volatile("cp.async.wait_all;" ::: "memory");
      } else bar_sync(15, 288);
      bar_arrive(14, 64);
      if (MST) {
        mbar_wait(mb + B_EVB, 0); mbar_wait(mb + B_GATE, 1);
        meet(&P.s->when[1024 + b], (const uint4*)&P.s->when[1024 + (MSTG ? 0 : (b & 96))] + (MSTG ? lane : lane & 7), MFIRST, MST, mb + B_EVB);
        if (lane == 0) { mbar_arrive(mb + B_LATE); PTS(2); }
      }
    } else {
      const uint32_t eb = (lane << 24) + bars + B_EMPTY;
      float c[6];
      if (wid == 10) {
        float sx[4] = {0.f, 0.f, 0.f, 0.f}, qx[4] = {0.f, 0.f, 0.f, 0.f};
        const uint32_t xa = sm + ((hf * 4 + (cg & 3)) * 32 + lane) * 128 + ((lane & 7) << 4);
#pragma unroll 1
        for (int kb = 0; kb < 8; kb++) {
          uint4 xv[8];
          const uint32_t so = xa + (kb & 3) * STAGE_B;
          mbar_wait(mb + B_FULL + 8 * (kb & 3), kb >> 2);
#pragma unroll
          for (int i = 0; i < 8; i++) xv[i] = lds4(so ^ (i << 4));
#pragma unroll
          for (int i = 0; i < (NOHELP ? 1 : 8); i++) {
            const uint32_t e[4] = {xv[i].x, xv[i].y, xv[i].z, xv[i].w};
#pragma unroll
            for (int j = 0; j < 4; j++) {
              const float d0 = bf_lo(e[j]), d1 = bf_hi(e[j]);
              sx[j & SMASK] += d0 + d1; qx[j & SMASK] = fmaf(d0, d0, fmaf(d1, d1, qx[j & SMASK]));
            }
          }
          __syncwarp();
          if (lane < 2) mbar_arrive_rem(eb + 8 * (kb & 3));
          if (kb == RST2) {
        {
          const uint32_t ep = ld_rlx(&P.s->epoch);
          float s = 0.f;
#pragma unroll
          for (int i = 0; i < 4; i++) {
            const uint4 v = ld_cg4((const uint4*)P.wr + lane + i * 32);
            s += (bf_lo(v.x) + bf_hi(v.x)) + (bf_lo(v.y) + bf_hi(v.y)) + (bf_lo(v.z) + bf_hi(v.z)) + (bf_lo(v.w) + bf_hi(v.w));
          }
#pragma unroll
          for (int o = 16; o; o >>= 1) s += __shfl_xor_sync(~0u, s, o);
          if (lane == 0) sts1(mb + B_SW, (__float_as_uint(s) & ~255u) | ((ep + 1) & 255));
        }
        asm volatile("cp.async.bulk.wait_group 0;\nfence.proxy.async.global;" ::: "memory");
        fence_gpu();
        if (lane == 0) PTS(0);
          }
          if (kb == RST) {
        if (elect_one()) {
#pragma unroll 1
          for (int i = 0; i < 16; i++) bulk_store(&P.s->obuf[((rb * 4 + (i >> 2)) * 64 + (((i >> 2) & 1) == hf ? 32 + s3 * 4 + (i & 3) : (i & 3) * 8 + s3)) * 128], sm + OFF_STATS, 2048);
          bulk_store(&P.s->kvp[(cg * 8 + rb) * 256], sm + OFF_STATS, 2048); bulk_store(&P.s->kvp[(cg * 8 + rb) * 256 + 128], sm + OFF_STATS, 2048);
          bulk_store(&P.s->zp[(cg * 8 + rb) * 16], sm + OFF_STATS, 256);
          if (s3 == 0) bulk_store(&P.s->when[(16 + rb * 2 + hf) * 32], sm + OFF_STATS, 128);
          if (rb == 0) bulk_store(&P.s->when[cg * 32], sm + OFF_STATS, 128);
          asm volatile("cp.async.bulk.commit_group;" ::: "memory");
          #pragma unroll
          for (int i = M_O; i < M_N; i++) tmap_prefetch(&T.m[i]);
        }
        __syncwarp();
          }
        }
        c[0] = ((sx[0] + sx[1]) + (sx[2] + sx[3])) * (2.f / D_);
        c[1] = fmaxf(fmaf(-c[0], c[0], ((qx[0] + qx[1]) + (qx[2] + qx[3])) * (2.f / D_)), 0.f);
      } else {
        float a[12];
#pragma unroll
        for (int i = 0; i < 12; i++) a[i] = 0.f;
        const int r2 = lane >> 4, c16 = lane & 15;
        const uint32_t a0 = sm + 32768 + (rb >> 1) * 2048 + r2 * 128 + (((c16 >> 1) ^ r2) << 4) + (c16 & 1) * 8;
#pragma unroll 1
        for (int it = 0; it < 16; it++) {
          uint2 w[12];
          const int s = (it >> 1) & 3;
          const uint32_t so = a0 + s * STAGE_B + (it & 1) * 1024;
          if (!(it & 1)) { mbar_wait(mb + B_FULL + 8 * s, it >> 3); TSD(8 + (it >> 1)); }
          static_for<0, 12>([&](auto ic) { constexpr int i = decltype(ic)::value;
            const float2 v = lds2f_o<(i >> 2) * 8192 + (i & 3) * 256>(so ^ ((i & 3) << 5)); w[i] = make_uint2(__float_as_uint(v.x), __float_as_uint(v.y)); });
#pragma unroll
          for (int i = 0; i < (NOHELP ? 1 : 12); i++) { float* q = a + (i >> 2) * 4; q[0] += bf_lo(w[i].x); q[1] += bf_hi(w[i].x); q[2] += bf_lo(w[i].y); q[3] += bf_hi(w[i].y); }
          __syncwarp();
          if (lane < 2 && (it & 1)) mbar_arrive_rem(eb + 8 * s);
        }
#pragma unroll
        for (int i = 0; i < 6; i++) {
          const int o = (i >> 1) * 4 + (i & 1);
          c[i] = (r2 ? a[o + 2] : a[o]) + __shfl_xor_sync(~0u, r2 ? a[o] : a[o + 2], 16);
        }
      }
      TS(5);
      bar_sync(10, 64);
      TS(6);
      {
        const uint32_t tag = lds1(mb + B_SW) & 255;
        auto tagged = [&](float v) { return ((__float_as_uint(v) + 128) & ~255u) | tag; };
        if (wid == 9) {
#pragma unroll
          for (int sg = 0; sg < 3; sg++) {
            st_rlx2((uint2*)&P.s->csp[(cg * 8 + rb) * 48] + sg * 32 + (lane & 15) * 2 + (lane >> 4), tagged(c[sg * 2]), tagged(c[sg * 2 + 1]));
          }
        } else st_rlx2((uint2*)&P.s->st1[(rb * 8 + hf * 4 + (cg & 3)) * 48 + lane] + ((cg >> 2) & 1), tagged(c[0]), tagged(c[1]));
        __nanosleep(GDELAY);
#pragma unroll 1
        for (int h = wid - 9; h < 2; h++) {
          const int q = h * 24 + min(lane, 23);
          const uint4* gp = wid == 10 ? &P.s->st1[rb * 8 * 48 + lane] : &P.s->csp[cg * 8 * 48 + q];
          uint4 v[8];
#pragma unroll 1
          for (int it = 0;; it++) {
            uint32_t x = 0;
#pragma unroll
            for (int i = 0; i < 8; i++) v[i] = ld_rlx4(gp + i * 48);
#pragma unroll
            for (int i = 0; i < 8; i++) { v[i].x ^= tag; v[i].y ^= tag; v[i].z ^= tag; v[i].w ^= tag; x |= v[i].x | v[i].y | v[i].z | v[i].w; }
            if (!__any_sync(~0u, (x & 255) != 0)) break;
            SPINCHK(it, 3);
          }
          if (wid == 10) {
#pragma unroll
            for (int i = 0; i < 8; i++) {
              const float m0 = __uint_as_float(v[i].x), m1 = __uint_as_float(v[i].z), dm = 0.5f * (m0 - m1);
              sts2f(sm + OFF_STATS + (i * 32 + lane) * 8, -0.5f * (m0 + m1), rsq(fmaf(dm, dm, 0.5f * (__uint_as_float(v[i].y) + __uint_as_float(v[i].w))) + 1e-5f));
            }
          } else {
            float s4[4] = {0.f, 0.f, 0.f, 0.f};
#pragma unroll
            for (int i = 0; i < 8; i++) { s4[0] += __uint_as_float(v[i].x); s4[1] += __uint_as_float(v[i].y); s4[2] += __uint_as_float(v[i].z); s4[3] += __uint_as_float(v[i].w); }
            sts4(sm + OFF_COLSUM + q * 16, __float_as_uint(s4[0]), __float_as_uint(s4[1]), __float_as_uint(s4[2]), __float_as_uint(s4[3]));
          }
        }
        mbar_arrive(mb + B_AUX);
      }
      TS(2);
      IDS(get_b());
      const uint64_t btab = rank ? BT1 : BT0;
      if (wid == 9) {
        {
          const uint4 sv = make_uint4(SENT, SENT, SENT, SENT);
          uint4* y = &P.s->ybuf[b * NFFN * 2 + lane];
#pragma unroll
          for (int i = 0; i < 7; i++) y[i * 32] = sv;
          if (lane < 16) P.s->st2[b * 16 + lane] = make_uint4(0, 0, 0, 0);
          for (int i = lane; i < (NC + 1) * 8; i += 32) P.s->hsel[b * (NC + 1) * 8 + i] = sv;
          if (b < 8 * NC) P.s->cand[b * 32 + lane] = SENT;
          if (b >= 124) P.s->when[(b - 92) * 32 + lane] = SENT;
          fence_gpu();
          bar_sync(0, 288);
          if (lane < 16) sts4(sm + OFF_STATS + lane * 128 + ((lane & 7) << 4), 0x3F803F80u, 0x3F803F80u, 0x3F803F80u, 0x3F803F80u);
          fence_async_smem();
          __syncwarp();
          if (lane == 0) mbar_arrive(mb + B_LATE);
        }
        TS(3);
        TS_DUMP(2);
        {
          const int p = lane & 15, sl = p % 7;
          const bool sliced = p > 0 && p < 9;
          const uint32_t c = sliced ? ((p - 1) >> 1) * 16 | ((hf ^ 1) * 8 + ((p - 1) & 1) * 4) << 8 | 128 << 16 : (hf * 8 + src_of(p)) << 8;
          const uint32_t ev = mb + (p < BHOLD ? B_EVA : p < 4 ? B_KVP : p < 6 ? B45 : B_E + 8 * ((p < 7 ? 1 : p - 4) & 7) + (p >= 12));
          mbar_wait(mb + B_EVA, 0);
          sts4(sm + OFF_COLSUM + 512 + p * 16, sm + unit_of(btab, sl), mb + B_BF + 8 * sl, c, ev);
          __syncwarp();
        }
        if (elect_one()) {
#pragma unroll 1
          for (int p = 0; p < 16; p++) {
            const uint4 e = lds4(sm + OFF_COLSUM + 512 + p * 16);
            if (p == 4) mbar_wait(mb + B_WR, 0);
            mbar_wait(e.w & ~1u, e.w & 1);
            mbar_expect_tx(e.y, p > 1 ? 4 * UNIT : 2 * UNIT);
            tma_4d(e.x, (const CUtensorMap*)((const char*)&T.m[M_O] + (e.z >> 16)), 0, e.z & 255, (e.z >> 8) & 255, c3 * 2, e.y, p >= EFB);
          }
          PTS(16);
        }
      } else {
        const uint32_t* wp = (const uint32_t*)(P.wr + c3 * 128) + (lane & 7) * 8 + (lane >> 3);
        const uint32_t w0 = ld_rlx(wp), w1 = ld_rlx(wp + 4);
#pragma unroll 1
        for (int i = 0; i < 4; i++) { l2_prefetch((const char*)P.wo + b * 16384 + i * 4096 + lane * 128); __nanosleep(300); }
        const int p = lane & 15, p2 = min(p + 2, 15);
        const uint32_t t0 = dlo(sb, 8192) + (unit_of(btab, p % 7) >> 4), t1 = ring_of(p + 1, lane >> 4), t2 = mb + B_BF + 8 * (p2 % 7);
        mbar_wait(mb + B_EVB, 0);
        bar_sync(14, 64);
        sts2f(sm + OFF_COLSUM + lane * 8, __uint_as_float(w0), __uint_as_float(w1));
        sts1(sm + OFF_COLSUM + 256 + lane * 4, 0x3F803F80u);
        sts4(sm + OFF_STATS + lane * 16, t0, t1, t2, (p2 / 7) & 1);
        __syncwarp();
        if (elect_one()) {
          mbar_arrive(mb + B_WR);
          if (fidx >= 0) {
            mbar_expect_tx(mb + B_FFN, 131072); mbar_expect_tx(mb + B_FFD, 32768);
            uint64_t gt = rank ? GT1 : GT0;
#pragma unroll 1
            for (int f = 0; f < 8; f++, gt >>= 5) {
              uint32_t d0 = sm + unit_of(gt, 0);
              asm volatile("" : "+r"(d0));
              if (f == 3) mbar_wait(mb + B_GATE, 1);
              mbar_wait(mb + (f < FEARLY ? B_KVB : B_E + (f < 3 ? 3 + 2 * f : (f + 5) >> 1) * 8), f < FEARLY || f >= 3);
              tma_3d(d0, &T.m[M_G], fidx * 32, f * 128, 0, mb + B_FFN, EFF);
              tma_3d(d0 + UNIT, &T.m[M_U], fidx * 32, f * 128, 0, mb + B_FFN, EFF);
            }
            PTS(17);
            mbar_expect_tx(mb + B_KVP, 32768);
#pragma unroll
            for (int w = 0; w < 8; w++) {
              if (w == 2) mbar_wait(mb + B_E + 56, 1);
              if (w == 6) mbar_wait(mb + B_E16, 1);
              if (w == DLATE) mbar_wait(mb + B_EVA, 1);
              tma_3d(sm + ((DT0 >> (5 * w)) & 31) * UNIT + (w < 4 ? 0 : w < 6 ? 14 * UNIT : -14 * UNIT) * rank, &T.m[M_D], 0, fidx * 32, 2 * w, mb + (w < 4 ? B_FFD : B_KVP), EFF);
            }
            PTS(18);
          }
        }
      }
    }
    __syncwarp();
    IDS(get_b());
    mbar_wait(mb + B_EVB, 0);
    mbar_wait(mb + B_OUT, 0);
    const float2 cf = lds2f(sm + OFF_STATS + 64);
    const int cand0 = 2047 - (__float_as_int(cf.x) & 2047), cand1 = 2047 - (__float_as_int(cf.y) & 2047), rr = lane >> 4;
    __nv_bfloat16* const ob = P.out + c3 * 128 + (lane & 15) * 8;
    auto store_row = [&](uint32_t ha, uint32_t la, int row, bool on) {
      const uint4 v = lds4(ha);
      const float2 pr = lds2f(la);
      const float f = 1.f + pr.x, n = pr.y;
      asm volatile("{\n.reg .pred p;\nsetp.ne.u32 p, %5, 0;\n@p st.global.v4.u32 [%0], {%1,%2,%3,%4};\n}" :: "l"(ob + row * D_),
                   "r"(pack2(fmaf(bf_lo(v.x), f, n), fmaf(bf_hi(v.x), f, n))), "r"(pack2(fmaf(bf_lo(v.y), f, n), fmaf(bf_hi(v.y), f, n))),
                   "r"(pack2(fmaf(bf_lo(v.z), f, n), fmaf(bf_hi(v.z), f, n))), "r"(pack2(fmaf(bf_lo(v.w), f, n), fmaf(bf_hi(v.w), f, n))), "r"((uint32_t)on) : "memory");
    };
    {
      uint32_t t0 = clock64() + ODELAY;
      uint32_t ha = sm + 4 * UNIT + ((wid >> 1) & 1) * STAGE_B + ((wid & 1) * 32 + rr) * 256 + (((lane & 15) ^ rr) << 4), la = sm + OFF_LNP + ((wid & 3) * 32 + rr) * 8;
      int row = rb * 256 + hf * 64 + (wid & 2) * 64 + (wid & 1) * 32 + rr;
#pragma unroll 1
      for (int i = 0; i < 16; i += OUNR, ha += 512 * OUNR, la += 16 * OUNR, row += 2 * OUNR, t0 += OPACE) {
        while ((int)((uint32_t)clock64() - t0) < 0) NAP;
#pragma unroll
        for (int j = 0; j < OUNR; j++) store_row((ha ^ (((i + j) & 3) << 5)) + j * 512, la + j * 16, row + 2 * j, row + 2 * j != cand0 && row + 2 * j != cand1 && !NOOUT);
      }
      if (wid == 11 && lane == 0) { PTS(14); SPANS(2); }
    }
    if (wid == 8) {
      const uint32_t kc = __float_as_uint(rr ? cf.y : cf.x);
      const int c = rr ? cand1 : cand0;
      mbar_wait(mb + B_SEL, 0);
      const float2 sel = lds2f(sm + OFF_STATS + 80);
      store_row(sm + 4 * UNIT + ((c >> 7) & 1) * STAGE_B + (c & 63) * 256 + (((lane & 15) ^ (c & 7)) << 4), sm + OFF_LNP + (((c >> 1) & 64) + (c & 63)) * 8, c,
                kc != __float_as_uint(sel.x) && kc != __float_as_uint(sel.y) && (c >> 8) == rb && ((c >> 6) & 1) == hf);
    }
  } else {
    asm volatile("setmaxnreg.inc.sync.aligned.u32 224;");
    const int t128 = tid & 127, warp = wid & 3, g = lane >> 2, t = lane & 3;
    const uint32_t sk = rank * (2 * STAGE_B);
    uint4 ost[2][4];
    uint4 abuf[3][4];
    uint4* od1;
    const uint4* ain;
    int b1;
    const uint32_t eb = (lane << 24) + bars + B_E;
    float acc[64];
    uint4 wb[4];
    uint32_t hp[32];
    {
      float acc1[96], acc0[96];
#pragma unroll
      for (int i = 0; i < 96; i++) { acc0[i] = 0.f; acc1[i] = 0.f; }
      const uint32_t xo0 = dlo(sb, 16) + (wg * 2 + hf) * 512, xo1 = dlo(sb, 16) + (wg * 2 + (hf ^ 1)) * 512;
      constexpr uint32_t ST = STAGE_B >> 4, WD = dlo(sb + 49152, 8192), WV = dlo(sb + 32768, 8192);
      const uint32_t eb0 = (t128 << 24) + bars + B_EMPTY;
#pragma unroll 1
      for (int kb = 0; kb < 12; kb++) {
        const int s = kb & 3;
        mbar_wait(mb + B_FULL + 8 * s, (kb >> 2) & 1);
        if (kb == 0) TS(1);
        if (kb == 0 && !wg) bar_sync(2, 256);
        pin(acc0); pin(acc1);
        wg_fence();
#pragma unroll
        for (int k = 0; k < 4; k++) {
          const uint64_t db = dsc<1024, 1>(WV + s * ST + k * 128);
          wgmma_n192_ss<0, 1, 0>(acc0, dsc<1024, 1>(s * ST + xo0 + k * 2), db, 1);
          wgmma_n192_ss<0, 1, 0>(acc1, dsc<1024, 1>(s * ST + xo1 + k * 2), db, 1);
        }
        wg_commit();
        if (kb == 0 && wg) bar_arrive(2, 256);
        wg_wait<0>();
        pin(acc0); pin(acc1);
        if (t128 < 2 && kb < 11) mbar_arrive_rem(eb0 + 8 * s);
      }
      mbar_wait(mb + B_FULL, 1);
      if (t128 < 8) mbar_arrive_rem(t128 < 4 ? (wg << 24) + bars + B_EMPTY + 24 : mb + B_EMPTY);
      TS(2);
      mbar_wait(mb + B_AUX, 0);
      float rs[2][2], nm[2][2];
#pragma unroll
      for (int m = 0; m < 2; m++)
#pragma unroll
        for (int h = 0; h < 2; h++) { const float2 v = lds2f(sm + OFF_STATS + ((wg * 2 + (m ^ hf)) * 64 + warp * 16 + h * 8 + g) * 8); nm[m][h] = v.x; rs[m][h] = v.y; }
      auto center = [&](auto jc) {
        constexpr int j = decltype(jc)::value;
        const float2 cs = lds2f_o<sb + OFF_COLSUM + j * 32>(own + t * 8);
        acc1[j * 4] = fmaf(nm[1][0], cs.x, acc1[j * 4]); acc1[j * 4 + 1] = fmaf(nm[1][0], cs.y, acc1[j * 4 + 1]);
        acc1[j * 4 + 2] = fmaf(nm[1][1], cs.x, acc1[j * 4 + 2]); acc1[j * 4 + 3] = fmaf(nm[1][1], cs.y, acc1[j * 4 + 3]);
        acc0[j * 4] = fmaf(nm[0][0], cs.x, acc0[j * 4]); acc0[j * 4 + 1] = fmaf(nm[0][0], cs.y, acc0[j * 4 + 1]);
        acc0[j * 4 + 2] = fmaf(nm[0][1], cs.x, acc0[j * 4 + 2]); acc0[j * 4 + 3] = fmaf(nm[0][1], cs.y, acc0[j * 4 + 3]);
      };
      static_for<0, 16>(center);
      const float L2E = 1.4426950408889634f;
      uint32_t fa = sm + sk + (warp * 16 + (lane & 15)) * 128 + (((lane >> 4) ^ (lane & 7)) << 4);
      asm volatile("" : "+r"(fa));
      uint32_t xf0[32], xf1[32];
      auto pack_kv = [&](float (&a)[96], int i, float r0, float r1, uint32_t* o, uint32_t z = 0) {
        const float* p = a + i * 8;
        if (i < 4) {
          const float rl0 = __uint_as_float(__float_as_uint(r0 * L2E) | z), rl1 = __uint_as_float(__float_as_uint(r1 * L2E) | z);
          const uint32_t q0 = pack2(r0, r0), q1 = pack2(r1, r1);
          o[0] = phi2(p[0], p[1], rl0, q0); o[1] = phi2(p[2], p[3], rl1, q1); o[2] = phi2(p[4], p[5], rl0, q0); o[3] = phi2(p[6], p[7], rl1, q1);
        } else if (VH) {
          const uint32_t q0 = pack2(r0, r0), q1 = pack2(r1, r1);
          o[0] = hmul2(pack2(p[0], p[1]), q0); o[1] = hmul2(pack2(p[2], p[3]), q1); o[2] = hmul2(pack2(p[4], p[5]), q0); o[3] = hmul2(pack2(p[6], p[7]), q1);
        } else {
          if (VZ) { r0 = __uint_as_float(__float_as_uint(r0) | z); r1 = __uint_as_float(__float_as_uint(r1) | z); }
          o[0] = pack2(p[0] * r0, p[1] * r0); o[1] = pack2(p[2] * r1, p[3] * r1); o[2] = pack2(p[4] * r0, p[5] * r0); o[3] = pack2(p[6] * r1, p[7] * r1);
        }
      };
      auto swap_kv = [&](uint32_t (&xf)[32], uint32_t tile, int i, const uint32_t* o, uint32_t z = 0) {
        const uint32_t ad = (fa + tile * UNIT) ^ ((i & 3) << 5);
        if (i < 4) { ldsm4_o<0>(ad, xf[i * 4], xf[i * 4 + 1], xf[i * 4 + 2], xf[i * 4 + 3]); stsm4_o<0>(ad, o[0], o[1], o[2], o[3]); }
        else { ldsm4_o<STAGE_B>(ad | z, xf[i * 4], xf[i * 4 + 1], xf[i * 4 + 2], xf[i * 4 + 3]); stsm4_o<STAGE_B>(ad, o[0], o[1], o[2], o[3]); }
      };
      auto mma_q = [&](float (&a)[96], uint32_t (&xf)[32], uint32_t xo, bool ss) {
        const uint32_t r = __shfl_sync(~0u, sk >> 4, 0), o = 2 * ST - r;
#pragma unroll
        for (int j = 0; j < 8; j++) {
          if (ss) wgmma_n64_ss<0, 1, 64>(a, dsc<1024, 1>(o + (j >> 2) * ST + xo + (j & 3) * 2), dsc<1024, 1>(WD + o + (j >> 2) * ST + (j & 3) * 128), 1);
          else wgmma_n64_rs<1, 64>(a, xf[j * 4], xf[j * 4 + 1], xf[j * 4 + 2], xf[j * 4 + 3], dsc<1024, 1>(WD + r + (j >> 2) * ST + (j & 3) * 128), 1);
        }
      };
      auto epi_q = [&](float (&a)[96], float r0, float r1, uint32_t (&o)[16]) {
        const float rl0 = r0 * 1.44269511f, rl1 = r1 * 1.44269511f;
        const uint32_t q0 = dup2(r0), q1 = dup2(r1);
#pragma unroll
        for (int j = 0; j < 8; j++) { o[j * 2] = phi2(a[64 + j * 4], a[65 + j * 4], rl0, q0); o[j * 2 + 1] = phi2(a[66 + j * 4], a[67 + j * 4], rl1, q1); }
        pinu(o);
      };
      auto mma_kv1 = [&](float (&a)[96], uint32_t xo, int s) {
#pragma unroll
        for (int k = 0; k < 4; k++) wgmma_n128_ss<0, 1, 0>(a, dsc<1024, 1>(s * ST + xo + k * 2), dsc<1024, 1>(WV + s * ST + k * 128), 1);
      };
      auto epi_kv = [&](float (&a)[96], uint32_t (&xf)[32], uint32_t tile, float r0, float r1) {
        uint32_t o[8][4];
#pragma unroll
        for (int j = 3; j >= 0; j--) {
          const uint32_t z = j < 3 ? (xf[(j + 5) * 4] | (VZ && j < 2 ? o[j + 2][0] | o[j + 6][0] : 0)) & blockIdx.y : 0;
          pack_kv(a, j + 4, r0, r1, o[j + 4], z);
          swap_kv(xf, tile, j + 4, o[j + 4], (o[j + 4][2] | o[j + 4][3]) & blockIdx.y);
          pack_kv(a, j, r0, r1, o[j], z);
          swap_kv(xf, tile, j, o[j]);
        }
      };
      bar_arrive(15, 288); bar_arrive(0, 288);
      mbar_wait(mb + B_FULL + 8, 1);
      if (!wg) bar_sync(3, 256);
      pinr<0, 64>(acc0); pinr<0, 64>(acc1);
      wg_fence();
      mma_kv1(acc1, xo1, 0); mma_kv1(acc0, xo0, 0); mma_kv1(acc1, xo1, 1);
      if (GSPLIT == 2) mma_kv1(acc0, xo0, 1);
      mbar_wait(mb + B_FULL + 16, 1);
      wg_fence();
      mma_kv1(acc1, xo1, 2);
      mbar_wait(mb + (wg ? B_FULL + 24 : B_F15), wg);
      wg_fence();
      mma_kv1(acc1, xo1, 3);
      wg_commit();
      bar_arrive(4 - wg, 256);
      static_for<16, 24>(center);
      pinr<64, 96>(acc0); pinr<64, 96>(acc1);
      mbar_wait(mb + B_FULL + 8, 1);
      wg_wait<0>();
      pinr<0, 64>(acc0); pinr<0, 64>(acc1);
      TS(9);
      epi_kv(acc1, xf1, wg * 2 + (hf ^ 1), rs[1][0], rs[1][1]);
      pinu(xf1);
      if (FPOS == 3) fence_async_smem();
      bar_sync(5 - wg, 256);
      wg_fence();
      if (GSPLIT == 1) mma_kv1(acc0, xo0, 1);
      mma_kv1(acc0, xo0, 2); mma_kv1(acc0, xo0, 3);
      wg_commit();
      if (FPOS == 1) fence_async_smem();
      mma_q(acc1, xf1, xo1, false);
      wg_commit();
      if (FPOS) bar_arrive(6 - wg, 256);
      else if (wg) bar_arrive(5, 256);
      else { fence_async_smem(); bar_arrive(6, 256); }
      wg_wait<1>();
      pinr<0, 64>(acc0);
      if (lane == 0) mbar_arrive(mb + B_EVA);
      TS(6);
      epi_kv(acc0, xf0, wg * 2 + hf, rs[0][0], rs[0][1]);
      fence_async_smem();
      pinu(xf0);
      TS(15);
      if (!wg) bar_arrive(7, 256);
      const uint32_t kvb = 2 * STAGE_B + (2 + (hf ^ 1)) * UNIT - sk;
      b1 = get_b();
      od1 = &P.s->obuf[(((b1 >> 4) * 4 + wg * 2 + (hf ^ 1)) * 64 + (b1 & 7)) * 128 + t128];
      ain = &P.s->obuf[((b1 >> 4) * 4 + wg * 2 + hf) * 64 * 128 + t128];
      uint32_t ka0 = sm + kvb + wid * 1024 + (lane & 7) * 128 + (((lane >> 3) ^ (lane & 7)) << 4), ka1 = sm + kvb + wid * 1024 + (t * 2 + g) * 128 + ((4 ^ (t * 2 + g)) << 4);
      const uint8_t* g0 = smem_raw + sk + STAGE_B + tid * 16, *g1 = smem_raw + sk + UNIT + g * 256 + wid * 32 + t * 8;
      const uint8_t* h0 = (const uint8_t*)&P.s->kvp[(b1 & 15) * 8 * 256 + tid], *h1 = (const uint8_t*)&P.s->zp[((b1 & 15) * 8 + g) * 16] + wid * 32 + t * 8;
      asm volatile("" : "+r"(ka0), "+r"(ka1), "+l"(g0), "+l"(g1), "+l"(h0), "+l"(h1), "+l"(od1));
      if (wg) {
        float ka[36];
        auto mma_kv = [&](uint32_t tile, int i, int acc) {
          const uint32_t o = (sk >> 4) + tile * 512 + i * 128;
          wgmma_n72_ss<1, 1, 0>(ka, dsc<1024, 1>(dlo(sb, 8192) + o), dsc<1024, 1>(dlo(sb + STAGE_B, OFF_STATS - STAGE_B) + o * (1u - (1u << 16))), acc);
        };
#pragma unroll
        for (int i = 0; i < 36; i++) ka[i] = 0.f;
        mbar_wait(mb + B_LATE, 0);
        bar_sync(6, 256);
        wg_fence();
#pragma unroll
        for (int i = 0; i < 4; i++) {
          mma_kv(2, i, i); mma_kv(3, i, 1);
          if (FPOS != 2) mma_kv(hf ^ 1, i, 1);
#pragma unroll
          for (int j = 2 * i; j < 2 * i + 2; j++)
            wgmma_n64_rs<1, 64>(acc0, xf0[j * 4], xf0[j * 4 + 1], xf0[j * 4 + 2], xf0[j * 4 + 3], dsc<1024, 1>(WD + (sk >> 4) + (j >> 2) * ST + (j & 3) * 128), 1);
        }
        const int kq = (b1 & 15) * 8 + (b1 >> 4);
        uint4* dst = &P.s->kvp[kq * 256 + warp * 64 + lane];
        uint32_t* dz = (uint32_t*)&P.s->zp[kq * 16] + warp * 16 + g + t * 8;
        asm volatile("" : "+l"(dst), "+l"(dz));
        bar_sync(7, 256);
#pragma unroll
        for (int i = 0; i < (FPOS == 2 ? 8 : 4); i++) mma_kv(FPOS == 2 ? 0 : hf, i, 1);
        wg_commit();
        bar_arrive(8, 256);
        wg_wait<0>();
        pin(ka); pinr<64, 96>(acc0);
        uint32_t kw[8];
#pragma unroll
        for (int i = 0; i < 8; i++) {
          const int j = (i & 3) * 4 + (i >> 2) * 2;
          asm("{\n.reg .pred p;\nsetp.ne.u32 p, %5, 0;\n@p cvt.rn.bf16x2.f32 %0, %4, %3;\n@!p cvt.rn.bf16x2.f32 %0, %2, %1;\n}"
              : "=r"(kw[i]) : "f"(ka[j]), "f"(ka[j + 1]), "f"(ka[16 + j]), "f"(ka[17 + j]), "r"(warp & 2));
        }
        st_rlx4(dst, make_uint4(kw[0], kw[1], kw[2], kw[3]));
        st_rlx4(dst + 32, make_uint4(kw[4], kw[5], kw[6], kw[7]));
        if (t < 2) st_rlx(dz, __float_as_uint(t ? ka[34] : ka[32]));
        if (lane == 0) mbar_arrive(mb + B_EVB);
        TS(8);
        const uint32_t t1 = clock64();
        while ((uint32_t)clock64() - t1 < SDELAY) {}
      } else {
        bar_sync(8, 256);
        wg_fence();
        mma_q(acc0, xf0, xo0, false);
      }
      if (!wg) bar_sync(9, 256);
      wg_fence();
      mma_q(acc1, xf1, xo1, true);
      wg_commit();
      if (wg) bar_arrive(9, 256); else mma_q(acc0, xf0, xo0, true);
      wg_commit();
      wg_wait<1>();
      pinr<64, 96>(acc1);
      TS(7);
      uint32_t pq[16];
      epi_q(acc1, rs[1][0], rs[1][1], pq);
      bar_sync(11 + wg + zero_after(pq), 128);
      if (wg) {
        wg_fence();
        mma_q(acc0, xf0, xo0, true);
        wg_commit();
      }
      TS(5);
      {
        uint4 gv[8]; uint2 gz;
        uint32_t m[8], a[4];
        float z0, z1;
#pragma unroll
        for (int s = 0; s < 8; s++) { m[s] = ~blockIdx.y; asm volatile("" : "=r"(gv[s].x), "=r"(gv[s].y), "=r"(gv[s].z), "=r"(gv[s].w), "+r"(m[s])); }
        mbar_wait(mb + B_KVP, 0);
        TS(28);
#pragma unroll 1
        for (int it = 0; it < SPIN_LIMIT; it++) {
          gz = ld_gen2(g1);
#pragma unroll
          for (int s = 0; s < 8; s++) if (m[s] == SENT) gv[s] = ld_gen4(g0 + s * 4096);
          g0 = h0; g1 = h1;
          uint32_t mm = max(gz.x, gz.y);
          z0 = __uint_as_float(gz.x); z1 = __uint_as_float(gz.y);
#pragma unroll
          for (int o = 4; o < 32; o <<= 1) { z0 += __shfl_xor_sync(~0u, z0, o); z1 += __shfl_xor_sync(~0u, z1, o); }
#pragma unroll
          for (int s = 0; s < 8; s++) m[s] = max4(0, gv[s]);
#pragma unroll
          for (int s = 0; s < 8; s += 2) mm = __vimax3_u32(mm, m[s], m[s + 1]);
          a[0] = hadd2(hadd2(hadd2(gv[0].x, gv[1].x), hadd2(gv[2].x, gv[3].x)), hadd2(hadd2(gv[4].x, gv[5].x), hadd2(gv[6].x, gv[7].x)));
          a[1] = hadd2(hadd2(hadd2(gv[0].y, gv[1].y), hadd2(gv[2].y, gv[3].y)), hadd2(hadd2(gv[4].y, gv[5].y), hadd2(gv[6].y, gv[7].y)));
          a[2] = hadd2(hadd2(hadd2(gv[0].z, gv[1].z), hadd2(gv[2].z, gv[3].z)), hadd2(hadd2(gv[4].z, gv[5].z), hadd2(gv[6].z, gv[7].z)));
          a[3] = hadd2(hadd2(hadd2(gv[0].w, gv[1].w), hadd2(gv[2].w, gv[3].w)), hadd2(hadd2(gv[4].w, gv[5].w), hadd2(gv[6].w, gv[7].w)));
          pinu(a);
          if (!__any_sync(~0u, mm == SENT)) break;
          TSV(20, 1);
        }
        TS(23);
        wg_wait<0>();
        pinr<64, 96>(acc0);
        if (lane == 0) mbar_arrive(mb + B_KVB);
        stsm4(ka0, a[0], a[1], a[2], a[3]);
        const uint32_t zz = pack2(g ? z1 : z0, g ? z1 : z0);
        if (lane < 8) sts4(ka1, zz, zz, zz, zz);
        fence_async_smem();
        bar_sync(1, 256);
      }
      TS(21);
      auto make_o = [&](uint4 (&o)[4], auto first) {
        float oa[2][20];
        wg_fence();
#pragma unroll
        for (int ks = 0; ks < 4; ks++)
          wgmma_n40_rs<1, 0>(oa[ks >> 1], pq[ks * 4], pq[ks * 4 + 1], pq[ks * 4 + 2], pq[ks * 4 + 3], dsc<1024, 1>(dlo(sb, 8192) + (kvb >> 4) + ks * 128), ks & 1);
        wg_commit();
        if constexpr (!decltype(first)::value) {
          pinu(xf0);
#pragma unroll
          for (int q = 0; q < 32; q++) { acc[q * 2] = bf_lo(xf0[q]); acc[q * 2 + 1] = bf_hi(xf0[q]); }
          pin(acc);
          if (!R1MID) {
            mbar_wait(mb + B_F15, 1);
#pragma unroll
            for (int i = 0; i < 4; i++) abuf[1][i] = ld_rlx4(ain + i * 128);
            TS(3);
          }
          mbar_wait(mb + B_BF, 0);
        }
        wg_wait<0>();
        pin(oa[0]); pin(oa[1]);
        if (decltype(first)::value && lane < 2) mbar_arrive_rem(eb);
#pragma unroll
        for (int h = 0; h < 2; h++) {
          const float (&d)[20] = oa[h];
          const float i0 = rcp(d[16] + 1e-6f), i1 = rcp(d[18] + 1e-6f);
#pragma unroll
          for (int k2 = 0; k2 < 2; k2++) {
            o[h * 2 + k2] = make_uint4(pack2(d[k2 * 8] * i0, d[k2 * 8 + 1] * i0), pack2(d[k2 * 8 + 2] * i1, d[k2 * 8 + 3] * i1),
                                       pack2(d[k2 * 8 + 4] * i0, d[k2 * 8 + 5] * i0), pack2(d[k2 * 8 + 6] * i1, d[k2 * 8 + 7] * i1));
            if (decltype(first)::value && !h && k2 <= AFIRST) st_rlx4(od1 + k2 * 1024, o[k2]);
            if (decltype(first)::value && !h && k2 == AFIRST) { sched_fence(); TS(24); }
          }
        }
      };
      make_o(ost[1], std::true_type{});
      if (!AFIRST) { st_rlx4(od1 + 1024 + ((ost[1][2].x | ost[1][3].w) & blockIdx.y), ost[1][1]); sched_fence(); }
      auto read1 = [&](uint32_t z) {
        mbar_wait(mb + B_F15 + z, 1);
#pragma unroll
        for (int i = 0; i < 4; i++) abuf[1][i] = ld_rlx4(ain + i * 128);
        TS(3);
      };
      if (R1MID) {
        const float rl0 = rs[0][0] * 1.44269511f, rl1 = rs[0][1] * 1.44269511f;
        const uint32_t q0 = dup2(rs[0][0]), q1 = dup2(rs[0][1]);
        uint32_t z = 0;
#pragma unroll
        for (int j = 0; j < 8; j++) {
          pq[j * 2] = phi2(acc0[64 + j * 4], acc0[65 + j * 4], rl0, q0); pq[j * 2 + 1] = phi2(acc0[66 + j * 4], acc0[67 + j * 4], rl1, q1);
          if (j < R1MID) z |= pq[j * 2] | pq[j * 2 + 1];
          if (j == R1MID - 1) read1(z & 0x80008000u);
        }
      } else epi_q(acc0, rs[0][0], rs[0][1], pq);
      if (AEARLY == 1) { st_rlx4(od1 + 2048, ost[1][2]); st_rlx4(od1 + 3072, ost[1][3]); }
      make_o(ost[0], std::false_type{});
    }
   {
    IDS(b1);
    const int mb3 = rb * 4 + wg * 2 + hf;
    uint4* rp = &P.s->st2[mb3 * 64 + warp * 16 + g + t * 8];
    {
      uint4* const od0 = &P.s->obuf[(mb3 * 64 + 32 + s3 * 4) * 128 + t128];
#pragma unroll
      for (int i = 0; i < 4; i++) pin4(ost[0][i]);
      wg_fence();
#pragma unroll
      for (int k = 0; k < 4; k++) wgmma_n128_rs<1, 0>(acc, ost[0][k].x, ost[0][k].y, ost[0][k].z, ost[0][k].w, dsc<1024, 1>(dlo(sb + 4 * UNIT, 8192) + k * 128), 1);
      wg_commit();
      TS(29);
      if (AEARLY == 0) { st_rlx4(od1 + 2048, ost[1][2]); st_rlx4(od1 + 3072, ost[1][3]); }
      if (AEARLY == 2) st_rlx4(od1 + 2048, ost[1][2]);
      uint32_t la = sm + t128 * 16, ev = eb + 8;
      asm volatile("" : "+r"(la), "+r"(ev));
      auto fetch = [&](uint32_t off, uint4 (&a)[4]) { const uint32_t ra = la + off; a[0] = lds4_o<0>(ra); a[1] = lds4_o<2048>(ra); a[2] = lds4_o<4096>(ra); a[3] = lds4_o<6144>(ra); };
      auto check = [&](int p, uint4 (&a)[4]) {
        if (__any_sync(~0u, max(max4(max4(0, a[0]), a[1]), max4(max4(0, a[2]), a[3])) == SENT)) {
          int pl = p; asm volatile("" : "+r"(pl));
          const uint4* q = ain + frag_of(pl);
#pragma unroll 1
          for (int it = 0;; it++) {
            uint32_t mm = 0;
#pragma unroll
            for (int i = 0; i < 4; i++) { const uint32_t m = max4(0, a[i]); mm = max(mm, m); if (m == SENT) a[i] = ld_rlx4(q + i * 128); }
            if (!__any_sync(~0u, mm == SENT)) break;
            TSV(27, p < 3 ? 1 : p < 5 ? 100 : 10000);
            SPINCHK(it, 5);
          }
        }
        if (lane < 2) mbar_arrive_rem(ev);
        ev = (ev & ~0x38u) | ((ev + 8) & 0x38u);
      };
      auto mma = [&](int p, uint32_t bs, uint4 (&a)[4]) {
#pragma unroll
        for (int i = 0; i < 4; i++) pin4(a[i]);
        wg_fence();
#pragma unroll
        for (int k = 0; k < 4; k++) wgmma_n128_rs<1, 0>(acc, a[k].x, a[k].y, a[k].z, a[k].w, dsc<1024, 1>(bs + k * 128), 1);
        wg_commit();
      };
      uint32_t ta = sm + OFF_STATS + wg * 256 + 48;
      mbar_wait(mb + B_WR, 0);
      uint4 tp = lds4(ta);
      mbar_wait(mb + B_BF + 8, 0);
      check(1, abuf[1]);
      if (P1F) { mbar_wait(mb + B_BF + 16, 0); fetch(ring_of(2, wg), abuf[2]); }
      mma(1, dlo(sb + 11 * UNIT, 8192), abuf[1]);
      if (!P1F) { mbar_wait(mb + B_BF + 16, 0); fetch(ring_of(2, wg), abuf[2]); }
      TS(25);
      if (AEARLY == 2) st_rlx4(od1 + 3072, ost[1][3]);
      st_rlx4(od0, ost[0][0]); st_rlx4(od0 + 128, ost[0][1]);
      check(2, abuf[2]);
      mbar_wait(mb + B_BF + 24, 0);
      fetch(ring_of(3, wg), abuf[0]);
      mma(2, dlo(sb + 18 * UNIT, 8192), abuf[2]);
      st_rlx4(od0 + 256, ost[0][2]); st_rlx4(od0 + 384, ost[0][3]);
      wg_wait<2>();
      check(3, abuf[0]);
      mbar_wait(mb + B_BF + 32, 0);
      TS(26);
#pragma unroll 1
      for (int p = 3; p < 15; p += 3) {
        static_for<0, 3>([&](auto jc) {
          constexpr int j = decltype(jc)::value;
          const uint4 tc = tp;
          const uint32_t bs = __shfl_sync(~0u, tc.x, 0);
          wg_wait<1>();
#pragma unroll
          for (int i = 0; i < 4; i++) pin4(abuf[(j + 1) % 3][i]);
          tp = lds4_o<16 * j + 16>(ta);
          fetch(tc.y, abuf[(j + 1) % 3]);
          mma(p + j, bs, abuf[j]);
          if (!CHKF) mbar_wait(tc.z, tc.w);
          check(p + j + 1, abuf[(j + 1) % 3]);
          if (CHKF) mbar_wait(tc.z, tc.w);
        });
        ta += 48;
      }
      {
        const uint32_t wa0 = sm + OFF_COLSUM + ((g & 1) ? t * 64 : 256);
        wb[0] = lds4_o<0>(wa0); wb[1] = lds4_o<16>(wa0); wb[2] = lds4_o<32>(wa0); wb[3] = lds4_o<48>(wa0);
      }
      mma(15, __shfl_sync(~0u, tp.x, 0), abuf[0]);
      wg_wait<2>();
      if (lane == 0) mbar_arrive(mb + B_E16);
      asm volatile("" : "+l"(rp));
      sched_fence();
      wg_wait<0>();
      pin(acc);
#pragma unroll
      for (int i = 0; i < 4; i++) { pin4(abuf[0][i]); pin4(abuf[1][i]); pin4(abuf[2][i]); }
    }
    TS(10);
    {
      float q0[2] = {0.f, 0.f}, q1[2] = {0.f, 0.f}, c[2][4] = {};
#pragma unroll
      for (int j = 0; j < 16; j++) {
        hp[j * 2] = pack2(acc[j * 4], acc[j * 4 + 1]); hp[j * 2 + 1] = pack2(acc[j * 4 + 2], acc[j * 4 + 3]);
        q0[j & 1] = fmaf(acc[j * 4], acc[j * 4], fmaf(acc[j * 4 + 1], acc[j * 4 + 1], q0[j & 1]));
        q1[j & 1] = fmaf(acc[j * 4 + 2], acc[j * 4 + 2], fmaf(acc[j * 4 + 3], acc[j * 4 + 3], q1[j & 1]));
        if (j & 1) {
          const uint32_t a[4] = {hp[j * 2 - 2], hp[j * 2 - 1], hp[j * 2], hp[j * 2 + 1]};
          mma16816(c[(j >> 1) & 1], a, (j & 2) ? wb[j >> 2].z : wb[j >> 2].x, (j & 2) ? wb[j >> 2].w : wb[j >> 2].y);
        }
      }
      const bool od = t & 1;
      float q = (od ? q1[0] + q1[1] : q0[0] + q0[1]) + __shfl_xor_sync(~0u, od ? q0[0] + q0[1] : q1[0] + q1[1], 1);
      q += __shfl_xor_sync(~0u, q, 2);
      asm volatile("{\n.reg .pred p;\nsetp.lt.u32 p, %5, 2;\n@p red.relaxed.gpu.global.add.v4.f32 [%0], {%1,%2,%3,%4};\n}"
                   :: "l"(rp), "f"(od ? c[0][2] + c[1][2] : c[0][0] + c[1][0]), "f"(q), "f"(od ? c[0][3] + c[1][3] : c[0][1] + c[1][1]), "f"(1.f), "r"(t) : "memory");
    }
    TS(11);
    const uint32_t ts = clock64();
    const uint32_t msc = sm + OFF_STATS;
    const uint32_t hst = sm + 4 * UNIT + wg * STAGE_B + warp * 4096, gslot = sm + unit_of(rank ? GT1 : GT0, wid);
    bar_sync(1, 256);
#pragma unroll
    for (int j = 0; j < 8; j++)
      stsm4(hst + (lane & 15) * 256 + (((2 * j + (lane >> 4)) ^ (lane & 7)) << 4), hp[j * 4], hp[j * 4 + 1], hp[j * 4 + 2], hp[j * 4 + 3]);
    uint32_t wa[8][4][4], wd[8][2][4];
    const uint32_t a0 = gslot + ((lane >> 4) * 8 + (lane & 7)) * 64 + ((((lane >> 3) & 1) ^ ((lane >> 1) & 3)) << 4);
    auto load_gu = [&](auto ic) { constexpr int i = decltype(ic)::value; ldsm4t_o<(i >> 2) * 1024 + ((i >> 1) & 1) * 8192>(a0 ^ ((i & 1) << 5), wa[i >> 2][i & 3]); };
    uint32_t tx;
    {
      const int row = rb * 256 + tid;
      const uint4* sp = &P.s->st2[row], *sq = &P.s->st2[row ^ 256];
      const float sw = __uint_as_float((lds1(mb + B_SW) & ~255u) | 128);
      uint4 v[2];
      uint4* d = &P.s->hsel[c3 * 128 + (g & 3) * 32 + ((rb & 6) + (lane >> 4)) * 4 + t];
      uint32_t* dk = &P.s->cand[((lane & 15) * 8 + c3) * 32 + (rb & 6) + (lane >> 4)];
      asm volatile("" : "+l"(d), "+l"(dk));
      if (GU1 && fidx >= 0) mbar_wait(mb + B_FFN, 0);
      static_for<0, GU1>(load_gu);
      while ((uint32_t)clock64() - ts < SDEL2) {}
      if (MST) mbar_wait(mb + B_LATE, 1);
      v[0] = ld_rlx4(sp); v[1] = ld_rlx4(sq);
      if (DPOS == 1 && lane == 0) mbar_arrive(mb + B_EVA);
      if (!GU1 && GU2 && fidx >= 0) mbar_wait(mb + B_FFN, 0);
      static_for<GU1, GU2>(load_gu);
      if (DPOS == 2 && lane == 0) mbar_arrive(mb + B_EVA);
#pragma unroll 1
      for (int it = 0; __any_sync(~0u, min(v[0].w, v[1].w) != 0x41000000u) && it < SPIN_LIMIT; it++) {
        if (v[0].w != 0x41000000u) v[0] = ld_rlx4(sp);
        if (v[1].w != 0x41000000u) v[1] = ld_rlx4(sq);
        TSV(22, 1);
      }
      if (DPOS == 0 && lane == 0) mbar_arrive(mb + B_EVA);
      TS(12);
      uint32_t k[2];
#pragma unroll
      for (int i = 0; i < 2; i++) {
        const float mean = __uint_as_float(v[i].x) * (1.f / D_);
        const float rstd = rsq(fmaxf(fmaf(-mean, mean, __uint_as_float(v[i].y) * (1.f / D_)), 0.f) + 1e-5f);
        const uint32_t u = __float_as_uint(rstd * fmaf(-mean, sw, __uint_as_float(v[i].z)));
        k[i] = min(((u ^ ((uint32_t)((int)u >> 31) | 0x80000000u)) & ~2047u), 0xFFFFF000u) | (2047 - (row ^ (i << 8)));
        if (i == 0 && (warp >> 1) == hf) sts2f(sm + OFF_LNP + (wg * 64 + (tid & 63)) * 8, rstd, -mean * rstd);
      }
      const uint32_t hi = max(k[0], k[1]);
      uint32_t m1 = __reduce_max_sync(~0u, hi), m2 = __reduce_max_sync(~0u, hi == m1 ? min(k[0], k[1]) : hi);
      if (lane == 0) sts2f(msc + wid * 8, __uint_as_float(m1), __uint_as_float(m2));
      bar_sync(1, 256);
      const uint32_t kk = lds1(msc + (lane & 15) * 4);
      m1 = __reduce_max_sync(~0u, kk); m2 = __reduce_max_sync(~0u, kk == m1 ? 0 : kk);
      const int c0 = 2047 - (m1 & 2047), c1 = 2047 - (m2 & 2047);
      if ((c0 >> 4) == mb3 * 4 + warp || (c1 >> 4) == mb3 * 4 + warp) {
        const int ra = (lane & 4) ? c1 : c0, rd = (lane & 16) ? c1 : c0;
        uint32_t h0, h1, h2, h3;
        ldsm4_o<0>(hst + (ra & 15) * 256 + ((((lane & 3) * 4 + (lane >> 3)) ^ (ra & 7)) << 4), h0, h1, h2, h3);
        const float2 pr = lds2f(sm + OFF_LNP + (wid * 16 + (rd & 15)) * 8);
        if ((rd >> 4) == mb3 * 4 + warp) {
          const uint4 xn = make_uint4(pack2(fmaf(bf_lo(h0), pr.x, pr.y), fmaf(bf_hi(h0), pr.x, pr.y)), pack2(fmaf(bf_lo(h1), pr.x, pr.y), fmaf(bf_hi(h1), pr.x, pr.y)),
                                      pack2(fmaf(bf_lo(h2), pr.x, pr.y), fmaf(bf_hi(h2), pr.x, pr.y)), pack2(fmaf(bf_lo(h3), pr.x, pr.y), fmaf(bf_hi(h3), pr.x, pr.y)));
#pragma unroll
          for (int i = 0; i < NC; i++) st_rlx4(d + i * 1024, xn);
          if ((lane & 15) < NC) st_rlx(dk, (lane & 16) ? m2 : m1);
          st_rlx4(d + NC * 1024, make_uint4(h0, h1, h2, h3));
        }
      }
      tx = clock64();
      if (tid == 0) { sts2f(msc + 64, __uint_as_float(m1), __uint_as_float(m2)); mbar_arrive(mb + B_OUT); }
    }
    TS(13);
    if (!GU2 && fidx >= 0) mbar_wait(mb + B_FFN, 0);
    static_for<GU2, 32>(load_gu);
    const uint32_t dl = sm + (wid & 1) * 4096 + ((lane >> 4) * 8 + (lane & 7)) * 128 + ((((lane >> 3) & 1) ^ (lane & 7)) << 4);
    uint32_t da = dl + unit_of(DT0, wid >> 1), db = dl + unit_of(rank ? DT1 : DT0, 4 + (wid >> 1));
    uint32_t* yp = (uint32_t*)&P.s->ybuf[((wid * 8 + t * 2) * NFFN + fidx) * 2] + g;
    uint32_t k1, k2;
    uint2 key;
    uint32_t pl = sm + unit_of(rank ? GT1 : GT0, g) + (g & 1) * 64 + wid * 64 + t * 16, pa = msc + 128 + wid * 16 + ((t & 1) * 2 + (lane >> 4)) * 4 + (t >> 1) * 2;
    {
      float gu[2][4][4];
      uint4 xb[4];
      uint32_t m[4];
      const uint4* xp = &P.s->hsel[((jp & (NC - 1)) * 8 + wid) * 128 + lane];
      const uint2* kp = (const uint2*)&P.s->cand[((jp & (NC - 1)) * 8 + wid) * 32] + t;
      uint32_t ps = gslot + (wid & 1) * 64 + g * 32;
      asm volatile("" : "+l"(xp), "+l"(kp), "+l"(yp), "+r"(db), "+r"(ps), "+r"(pl), "+r"(pa));
      if (fidx >= 0) mbar_wait(mb + B_FFD, 0);
      static_for<0, 8>([&](auto ic) { constexpr int i = decltype(ic)::value; ldsm4t_o<(i & 1) * 2048>(da ^ ((i >> 1) << 5), wd[i >> 1][i & 1]); });
      while ((uint32_t)clock64() - tx < XDELAY) {}
      key = ld_rlx2(kp);
#pragma unroll
      for (int i = 0; i < 4; i++) xb[i] = ld_rlx4(xp + i * 32);
      if (!DBEH && fidx >= 0) mbar_wait(mb + B_KVP, 1);
#pragma unroll 1
      for (int it = 0; it < SPIN_LIMIT; it++) {
#pragma unroll
        for (int i = 0; i < 4; i++) m[i] = max4(0, xb[i]);
        if (!__any_sync(~0u, __vimax3_u32(__vimax3_u32(max(key.x, key.y), m[0], m[1]), m[2], m[3]) == SENT)) break;
        key = ld_rlx2(kp);
#pragma unroll
        for (int i = 0; i < 4; i++) if (m[i] == SENT) xb[i] = ld_rlx4(xp + i * 32);
        TSV(20, 100);
      }
      TS(14);
      const uint32_t hi = max(key.x, key.y);
      k1 = __reduce_max_sync(~0u, hi); k2 = __reduce_max_sync(~0u, hi == k1 ? min(key.x, key.y) : hi);
#pragma unroll
      for (int i = 0; i < 32; i++) gu[i >> 4][(i >> 2) & 3][i & 3] = 0.f;
#pragma unroll
      for (int ks = 0; ks < 8; ks++) {
#pragma unroll
        for (int i = 0; i < 4; i++) mma16816(gu[ks & 1][i], wa[ks][i], (ks & 1) ? xb[ks >> 1].z : xb[ks >> 1].x, (ks & 1) ? xb[ks >> 1].w : xb[ks >> 1].y);
        if (!DBEH && ks == 1) {
          const uint32_t dd = db | (__float_as_uint(gu[1][3][0]) & blockIdx.y);
          static_for<0, 8>([&](auto ic) { constexpr int i = decltype(ic)::value; ldsm4t_o<(i & 1) * 2048>(dd ^ ((i >> 1) << 5), wd[4 + (i >> 1)][i & 1]); });
          xb[3].z |= (wd[4][0][0] | wd[4][1][0] | wd[5][0][0] | wd[5][1][0] | wd[6][0][0] | wd[6][1][0] | wd[7][0][0] | wd[7][1][0]) & blockIdx.y;
        }
      }
#pragma unroll
      for (int c = 0; c < 2; c++) {
        const uint32_t kc = c ? key.y : key.x;
        float o[8];
#pragma unroll
        for (int j = 0; j < 8; j++) o[j] = gu[0][(j >> 2) + (j & 1) * 2][(j & 2) + c] + gu[1][(j >> 2) + (j & 1) * 2][(j & 2) + c];
        asm volatile("{\n.reg .pred p;\nsetp.ge.u32 p, %9, %10;\n@p st.shared.v4.f32 [%0], {%1,%2,%3,%4};\n@p st.shared.v4.f32 [%0+16], {%5,%6,%7,%8};\n}"
                     :: "r"(ps + (kc == k1 ? 0 : 256)), "f"(o[0]), "f"(o[1]), "f"(o[2]), "f"(o[3]), "f"(o[4]), "f"(o[5]), "f"(o[6]), "f"(o[7]), "r"(kc), "r"(k2) : "memory");
      }
    }
    TS(4);
    if (DBEH && fidx >= 0) mbar_wait(mb + B_KVP, 1);
    bar_sync(1, 256);
    {
      const uint4 pv = lds4(pl);
      const bool hi = lane & 16;
      float ga = __uint_as_float(hi ? pv.z : pv.x) + __shfl_xor_sync(~0u, __uint_as_float(hi ? pv.x : pv.z), 16);
      float up = __uint_as_float(hi ? pv.w : pv.y) + __shfl_xor_sync(~0u, __uint_as_float(hi ? pv.y : pv.w), 16);
      ga += __shfl_xor_sync(~0u, ga, 8); up += __shfl_xor_sync(~0u, up, 8);
      ga += __shfl_xor_sync(~0u, ga, 4); up += __shfl_xor_sync(~0u, up, 4);
      asm volatile("st.shared.u16 [%0], %1;" :: "r"(pa), "h"((uint16_t)pack2(ga * rcp(1.f + ex2(-1.4426950408889634f * ga)) * up, 0.f)) : "memory");
      bar_sync(1, 256);
      const uint4 bv = lds4(msc + 128 + (lane & 7) * 16);
      const uint32_t bq[4] = {bv.x, bv.y, bv.z, bv.w};
      TS(16);
      float ya[8][4];
#pragma unroll
      for (int i = 0; i < 8; i++) { ya[i][0] = 0.f; ya[i][1] = 0.f; ya[i][2] = 0.f; ya[i][3] = 0.f; }
#pragma unroll
      for (int ks = 0; ks < 2; ks++)
#pragma unroll
        for (int i = 0; i < 8; i++) mma16816(ya[i], wd[i][ks], bq[ks * 2], bq[ks * 2 + 1]);
#pragma unroll
      for (int h = 0; h < 2; h++) {
        float o[4];
#pragma unroll
        for (int j = 0; j < 4; j++) o[j] = t == 0 ? ya[h * 4][j] : t == 1 ? ya[h * 4 + 1][j] : t == 2 ? ya[h * 4 + 2][j] : ya[h * 4 + 3][j];
        asm volatile("{\n.reg .pred p;\nsetp.ge.s32 p, %3, 0;\n@p st.relaxed.gpu.global.u32 [%0], %1;\n@p st.relaxed.gpu.global.u32 [%0+%4], %2;\n}"
                     :: "l"(yp + h * (64 * NFFN * 8)), "r"(pack2(o[0], o[1])), "r"(pack2(o[2], o[3])), "r"(fidx), "n"(NFFN * 32) : "memory");
      }
    }
    if (tid == 0) { sts2f(msc + 80, __uint_as_float(k1), __uint_as_float(k2)); mbar_arrive(mb + B_SEL); }
    TS(17);
    const uint32_t ty = clock64();
    if (wid == 0) {
      const uint32_t* yq = (const uint32_t*)&P.s->ybuf[b * NFFN * 2] + t * 8 + g;
      const uint32_t ks = (t & 1) ? k2 : k1, grp = 3 - ((ks >> 9) & 3);
      const int fs = grp * 2 + (__shfl_sync(~0u, key.y, grp) == ks);
      const uint32_t* fq = (const uint32_t*)P.s->hsel + (((b >> 4) * 4 + ((b >> 2) & 3)) * 32 + fs * 4 + (g >> 1)) * 4 + (b & 3);
      float gate = rcp(1.f + ex2(-1.4426950408889634f * __uint_as_float(ks ^ (~(uint32_t)((int)ks >> 31) | 0x80000000u))));
      __nv_bfloat16* op = P.out + (size_t)(2047 - (ks & 2047)) * D_ + b * 8 + g;
      uint32_t sel = (g & 2) ? 0x3F800000u : 0x00003F80u;
      uint32_t fn = ld_rlx(fq), fh = ld_rlx(fq + NC * 4096), v[7][4];
      uint32_t m[7];
#pragma unroll
      for (int i = 0; i < 7; i++) { m[i] = ~blockIdx.y; asm volatile("" : "=r"(v[i][0]), "=r"(v[i][1]), "=r"(v[i][2]), "=r"(v[i][3]), "+r"(m[i])); }
      asm volatile("" : "+l"(yq), "+l"(op), "+f"(gate), "+r"(sel));
      while ((uint32_t)clock64() - ty < YDELAY) {}
      float y[2][4];
#pragma unroll 1
      for (int it = 0; it < SPIN_LIMIT; it++) {
        static_for<0, 7>([&](auto ic) { constexpr int i = decltype(ic)::value;
          asm volatile("{\n.reg .pred p;\nsetp.eq.u32 p, %5, 0xFFFFFFFF;\n@p ld.relaxed.gpu.global.u32 %0, [%4+%6];\n@p ld.relaxed.gpu.global.u32 %1, [%4+%6+128];\n"
                       "@p ld.relaxed.gpu.global.u32 %2, [%4+%6+256];\n@p ld.relaxed.gpu.global.u32 %3, [%4+%6+384];\n}"
                       : "+r"(v[i][0]), "+r"(v[i][1]), "+r"(v[i][2]), "+r"(v[i][3]) : "l"(yq), "r"(YPRED ? m[i] : SENT), "n"(i * 512) : "memory"); });
        uint32_t mm = max(fn, fh);
        if (mm == SENT) { fn = ld_rlx(fq); fh = ld_rlx(fq + NC * 4096); }
#pragma unroll
        for (int i = 0; i < 8; i++) y[i >> 2][i & 3] = 0.f;
#pragma unroll
        for (int i = 0; i < 7; i++) { m[i] = __vimax3_u32(max(v[i][0], v[i][1]), v[i][2], v[i][3]); mm = max(mm, m[i]); mma16816(y[i & 1], v[i], sel, sel); }
        TSV(22, 100);
        pin(y[0]); pin(y[1]);
        if (!__any_sync(~0u, mm == SENT)) break;
      }
      TS(18);
      const float base = (g & 1) ? bf_hi(fh) + bf_hi(fn) : bf_lo(fh) + bf_lo(fn);
      if (t < 2) *op = __float2bfloat16(fmaf((y[0][0] + y[1][0]) + (y[0][2] + y[1][2]), gate, base));
      if (b == 0 && lane == 0) P.s->epoch = lds1(mb + B_SW) & 255;
    }
    if (tid == 0) SPANS(1);
    TS(19); TSG(31);
    if (warp == 0) TS_DUMP(wg);
   }
  }
}

typedef CUresult (*EncodeFn)(CUtensorMap*, CUtensorMapDataType, cuuint32_t, void*, const cuuint64_t*, const cuuint64_t*, const cuuint32_t*,
                             const cuuint32_t*, CUtensorMapInterleave, CUtensorMapSwizzle, CUtensorMapL2promotion, CUtensorMapFloatOOBfill);
void make_map(EncodeFn enc, CUtensorMap* m, const void* p, int rank, std::initializer_list<cuuint64_t> dims, std::initializer_list<cuuint64_t> str,
              std::initializer_list<cuuint32_t> box, CUtensorMapSwizzle sw) {
  const cuuint32_t es[4] = {1, 1, 1, 1};
  enc(m, CU_TENSOR_MAP_DATA_TYPE_BFLOAT16, rank, const_cast<void*>(p), dims.begin(), str.begin(), box.begin(), es, CU_TENSOR_MAP_INTERLEAVE_NONE, sw,
      CU_TENSOR_MAP_L2_PROMOTION_L2_128B, CU_TENSOR_MAP_FLOAT_OOB_FILL_NONE);
}

}

extern "C" void kernel_launch(void* const* d_in, const int* in_sizes, int n_in, void* d_out, int out_size) {
  (void)in_sizes; (void)n_in; (void)out_size;
  Ptrs P;
  P.x = (const __nv_bfloat16*)d_in[0]; P.wqkv = (const __nv_bfloat16*)d_in[1]; P.wo = (const __nv_bfloat16*)d_in[2];
  P.wr = (const __nv_bfloat16*)d_in[4]; P.wg = (const __nv_bfloat16*)d_in[5]; P.wu = (const __nv_bfloat16*)d_in[6];
  P.wd = (const __nv_bfloat16*)d_in[7]; P.out = (__nv_bfloat16*)d_out;
  cudaGetSymbolAddress((void**)&P.s, g_scratch);
  void* fn = nullptr;
  cudaDriverEntryPointQueryResult q;
  cudaGetDriverEntryPoint("cuTensorMapEncodeTiled", &fn, cudaEnableDefault, &q);
  EncodeFn enc = (EncodeFn)fn;
  Maps T;
  constexpr CUtensorMapSwizzle S128 = CU_TENSOR_MAP_SWIZZLE_128B, S64 = CU_TENSOR_MAP_SWIZZLE_64B;
  make_map(enc, &T.m[M_X], P.x, 2, {D_, S_}, {D_ * 2}, {64, 128}, S128);
  make_map(enc, &T.m[M_W], P.wqkv, 3, {D_, D_, 3}, {3 * D_ * 2, D_ * 2}, {64, 64, 2}, S128);
  make_map(enc, &T.m[M_Q], P.wqkv, 2, {3 * D_, D_}, {3 * D_ * 2}, {64, 64}, S128);
  make_map(enc, &T.m[M_O], P.wo, 4, {64, 64, 16, 16}, {D_ * 2, 64 * D_ * 2, 128}, {64, 64, 1, 2}, S128);
  make_map(enc, &T.m[M_S], P.wo, 4, {64, 64, 16, 16}, {D_ * 2, 64 * D_ * 2, 128}, {64, 16, 4, 2}, S128);
  make_map(enc, &T.m[M_G], P.wg, 3, {F_, D_, 1}, {F_ * 2, F_ * 2 * D_}, {32, 128, 1}, S64);
  make_map(enc, &T.m[M_U], P.wu, 3, {F_, D_, 1}, {F_ * 2, F_ * 2 * D_}, {32, 128, 1}, S64);
  make_map(enc, &T.m[M_D], P.wd, 3, {64, F_, 16}, {D_ * 2, 128}, {64, 32, 2}, S128);
  make_map(enc, &T.m[M_L], P.wd, 2, {64, F_ * 16}, {128}, {8, 32}, CU_TENSOR_MAP_SWIZZLE_NONE);
  cudaFuncSetAttribute(fused_kernel, cudaFuncAttributeMaxDynamicSharedMemorySize, SMEM_BYTES);
  fused_kernel<<<NCTA, 384, SMEM_BYTES>>>(P, T);
}
```

```cpp
#include <cuda_runtime.h>
#include <cuda.h>
#include <cuda_bf16.h>
#include <stdint.h>
#include <type_traits>
#include <initializer_list>

namespace {

constexpr int S_ = 2048, D_ = 1024, F_ = 3584;
constexpr int NCTA = 128, NFFN = 112;
constexpr uint32_t SENT = 0xFFFFFFFFu;
constexpr int SPIN_LIMIT = 1 << 20;

#define FD0 600
#define FD1 800
#define GDELAY 400
#define PULL0 3
#define PLAG 8
#define SDELAY 100
#define MFIRST 350
#define MKV 850
#define MO 800
#define ADELAY 200
#define ADELAY2 600
#define R1MID 5
#define SDEL2 500
#define XDELAY 500
#define YDELAY 650
#define GU1 8
#define GU2 20
#define OPACE 450
#define ACCSW 0
#define NAP __nanosleep(20)
constexpr uint32_t STAGE_B = 57344;
constexpr uint32_t OFF_STATS = 229376;
constexpr uint32_t OFF_COLSUM = 231424;
constexpr uint32_t OFF_BARS = 232192;
constexpr uint32_t SMEM_BYTES = 232448;
constexpr uint32_t B_FULL = 0, B_EMPTY = 32, B_E = 64, B_AUX = 128, B_EVA = 136, B_EVB = 144, B_BF = 152, B_LATE = 232, B_FFN = 240, B_SW = 248;
constexpr uint32_t B_OUT = B_FULL, B_SEL = B_FULL + 8, B_WR = B_FULL + 16, B_FFD = B_FULL + 24, B_E16 = B_EMPTY + 16, B_KVB = B_EMPTY + 8, B_DUMMY = B_SW + 4,
                   B_GATE = B_EMPTY + 24, B_ID = B_BF + 56, B_KVP = B_BF + 64, B_F15 = B_BF + 72;
constexpr uint32_t UNIT = 8192;
constexpr uint32_t sb = 1024;
constexpr uint32_t bars = sb + OFF_BARS;
constexpr uint64_t tab5(int a, int b, int c, int d, int e, int f, int g, int h, int i = 0, int j = 0) {
  return (uint64_t)a | (uint64_t)b << 5 | (uint64_t)c << 10 | (uint64_t)d << 15 | (uint64_t)e << 20 | (uint64_t)f << 25 | (uint64_t)g << 30 | (uint64_t)h << 35 |
         (uint64_t)i << 40 | (uint64_t)j << 45;
}
constexpr uint64_t BT0 = tab5(4, 11, 18, 25, 7, 9, 16, 0), BT1 = tab5(4, 11, 18, 25, 21, 23, 2, 0);
constexpr uint64_t GT0 = tab5(2, 21, 23, 18, 0, 25, 14, 7), GT1 = tab5(16, 7, 9, 18, 0, 25, 14, 21);
constexpr uint64_t DT0 = tab5(6, 13, 20, 27, 9, 10, 16, 17), DT1 = tab5(6, 13, 20, 27, 23, 24, 2, 3);
__device__ __forceinline__ uint32_t unit_of(uint64_t tab, int i) { return ((uint32_t)(tab >> (5 * i)) & 31) * UNIT; }
__device__ __forceinline__ uint32_t ring_of(int p, int w) { return (p & 1) * (2 * STAGE_B) + ((p & 2) ? 49152 + w * STAGE_B : w * UNIT); }
constexpr uint32_t OFF_LNP = OFF_STATS + 1024;

struct Scratch {
  uint4 obuf[32 * 64 * 128];
  uint4 kvp[16 * 8 * 256];
  uint4 zp[16 * 8 * 16];
  uint4 ybuf[NCTA * NFFN * 2];
  uint4 st1[64 * 48];
  uint4 csp[16 * 8 * 48];
  uint4 st2[S_];
  uint4 hsel[2 * 8 * 128];
  uint32_t cand[8 * 32];
  uint32_t when[32 * 32];
  unsigned epoch;
};
__device__ __align__(1024) Scratch g_scratch;
__device__ __forceinline__ uint32_t smem_u32(const void* p) { return (uint32_t)__cvta_generic_to_shared(p); }
__device__ __forceinline__ void mbar_init(uint32_t bar, uint32_t cnt) { asm volatile("mbarrier.init.shared::cta.b64 [%0], %1;" :: "r"(bar), "r"(cnt) : "memory"); }
__device__ __forceinline__ void mbar_expect_tx(uint32_t bar, uint32_t bytes) { asm volatile("mbarrier.arrive.expect_tx.shared::cta.b64 _, [%0], %1;" :: "r"(bar), "r"(bytes) : "memory"); }
__device__ __forceinline__ void mbar_arrive(uint32_t bar) { asm volatile("mbarrier.arrive.shared::cta.b64 _, [%0];" :: "r"(bar) : "memory"); }
#define SPINCHK(it) if ((it) > SPIN_LIMIT) break
__device__ __forceinline__ void mbar_wait(uint32_t bar, uint32_t parity) {
  asm volatile("{\n.reg .pred p;\n.reg .u32 c;\nmov.u32 c, 0;\n"
               "WL:\nmbarrier.try_wait.parity.shared::cta.b64 p, [%0], %1;\n@p bra WD;\n"
               "add.u32 c, c, 1;\nsetp.lt.u32 p, c, 1048576;\n@p bra WL;\nWD:\n}" :: "r"(bar), "r"(parity) : "memory");
}
__device__ __forceinline__ bool mbar_test(uint32_t bar, uint32_t parity) {
  uint32_t ok;
  asm volatile("{\n.reg .pred p;\nmbarrier.test_wait.parity.shared::cta.b64 p, [%1], %2;\nselp.u32 %0, 1, 0, p;\n}" : "=r"(ok) : "r"(bar), "r"(parity) : "memory");
  return ok;
}
__device__ __forceinline__ uint64_t l2_stream() { uint64_t p; asm("createpolicy.fractional.L2::evict_first.b64 %0, 1.0;" : "=l"(p)); return p; }
__device__ __forceinline__ void tma_2d(uint32_t dst, const CUtensorMap* tm, int c0, int c1, uint32_t bar, bool stream) {
  if (stream) asm volatile("cp.async.bulk.tensor.2d.shared::cluster.global.mbarrier::complete_tx::bytes.L2::cache_hint [%0], [%1, {%3, %4}], [%2], %5;"
                           :: "r"(dst), "l"(tm), "r"(bar), "r"(c0), "r"(c1), "l"(l2_stream()) : "memory");
  else asm volatile("cp.async.bulk.tensor.2d.shared::cluster.global.mbarrier::complete_tx::bytes [%0], [%1, {%3, %4}], [%2];"
                    :: "r"(dst), "l"(tm), "r"(bar), "r"(c0), "r"(c1) : "memory");
}
__device__ __forceinline__ void tma_3d(uint32_t dst, const CUtensorMap* tm, int c0, int c1, int c2, uint32_t bar, bool stream) {
  if (stream) asm volatile("cp.async.bulk.tensor.3d.shared::cluster.global.mbarrier::complete_tx::bytes.L2::cache_hint [%0], [%1, {%3, %4, %5}], [%2], %6;"
                           :: "r"(dst), "l"(tm), "r"(bar), "r"(c0), "r"(c1), "r"(c2), "l"(l2_stream()) : "memory");
  else asm volatile("cp.async.bulk.tensor.3d.shared::cluster.global.mbarrier::complete_tx::bytes [%0], [%1, {%3, %4, %5}], [%2];"
                    :: "r"(dst), "l"(tm), "r"(bar), "r"(c0), "r"(c1), "r"(c2) : "memory");
}
__device__ __forceinline__ void tma_4d(uint32_t dst, const CUtensorMap* tm, int c0, int c1, int c2, int c3, uint32_t bar) {
  asm volatile("cp.async.bulk.tensor.4d.shared::cluster.global.mbarrier::complete_tx::bytes.L2::cache_hint [%0], [%1, {%3, %4, %5, %6}], [%2], %7;"
               :: "r"(dst), "l"(tm), "r"(bar), "r"(c0), "r"(c1), "r"(c2), "r"(c3), "l"(l2_stream()) : "memory");
}
__device__ __forceinline__ void tma_2d_mc(uint32_t dst, const CUtensorMap* tm, int c0, int c1, uint32_t bar, bool stream) {
  if (stream) asm volatile("cp.async.bulk.tensor.2d.shared::cluster.global.mbarrier::complete_tx::bytes.multicast::cluster.L2::cache_hint [%0], [%1, {%3, %4}], [%2], %5, %6;"
                           :: "r"(dst), "l"(tm), "r"(bar), "r"(c0), "r"(c1), "h"((uint16_t)3), "l"(l2_stream()) : "memory");
  else asm volatile("cp.async.bulk.tensor.2d.shared::cluster.global.mbarrier::complete_tx::bytes.multicast::cluster [%0], [%1, {%3, %4}], [%2], %5;"
                    :: "r"(dst), "l"(tm), "r"(bar), "r"(c0), "r"(c1), "h"((uint16_t)3) : "memory");
}
__device__ __forceinline__ bool elect_one() {
  uint32_t p;
  asm volatile("{\n.reg .pred q;\nelect.sync _|q, 0xFFFFFFFF;\nselp.u32 %0, 1, 0, q;\n}" : "=r"(p));
  return p;
}
__device__ __forceinline__ void bulk_load_mc(uint32_t dst, const void* src, uint32_t bytes, uint32_t bar) {
  asm volatile("cp.async.bulk.shared::cluster.global.mbarrier::complete_tx::bytes.multicast::cluster [%0], [%1], %2, [%3], %4;"
               :: "r"(dst), "l"(src), "r"(bytes), "r"(bar), "h"((uint16_t)3) : "memory");
}
__device__ __forceinline__ void bulk_load(uint32_t dst, const void* src, uint32_t bytes, uint32_t bar) {
  asm volatile("cp.async.bulk.shared::cluster.global.mbarrier::complete_tx::bytes [%0], [%1], %2, [%3];" :: "r"(dst), "l"(src), "r"(bytes), "r"(bar) : "memory");
}
__device__ __forceinline__ void bulk_store(void* dst, uint32_t src, uint32_t bytes) {
  asm volatile("cp.async.bulk.global.shared::cta.bulk_group [%0], [%1], %2;" :: "l"(dst), "r"(src), "r"(bytes) : "memory");
}
__device__ __forceinline__ void mbar_arrive_rem(uint32_t bar) { asm volatile("mbarrier.arrive.shared::cluster.b64 _, [%0];" :: "r"(bar) : "memory"); }
template <uint32_t O> __device__ __forceinline__ void ldsm4_o(uint32_t addr, uint32_t& a, uint32_t& b, uint32_t& c, uint32_t& d) {
  asm volatile("ldmatrix.sync.aligned.m8n8.x4.shared.b16 {%0,%1,%2,%3}, [%4+%5];" : "=r"(a), "=r"(b), "=r"(c), "=r"(d) : "r"(addr), "n"(O) : "memory");
}
template <uint32_t O> __device__ __forceinline__ void ldsm4t_o(uint32_t addr, uint32_t (&r)[4]) {
  asm volatile("ldmatrix.sync.aligned.m8n8.x4.trans.shared.b16 {%0,%1,%2,%3}, [%4+%5];" : "=r"(r[0]), "=r"(r[1]), "=r"(r[2]), "=r"(r[3]) : "r"(addr), "n"(O) : "memory");
}
__device__ __forceinline__ void mma16816(float (&c)[4], const uint32_t (&a)[4], uint32_t b0, uint32_t b1) {
  asm("mma.sync.aligned.m16n8k16.row.col.f32.bf16.bf16.f32 {%0,%1,%2,%3}, {%4,%5,%6,%7}, {%8,%9}, {%0,%1,%2,%3};"
      : "+f"(c[0]), "+f"(c[1]), "+f"(c[2]), "+f"(c[3]) : "r"(a[0]), "r"(a[1]), "r"(a[2]), "r"(a[3]), "r"(b0), "r"(b1));
}
__device__ __forceinline__ void l2_prefetch(const void* p) { asm volatile("prefetch.global.L2 [%0];" :: "l"(p) : "memory"); }
__device__ __forceinline__ void tmap_prefetch(const CUtensorMap* tm) { asm volatile("prefetch.tensormap [%0];" :: "l"(tm) : "memory"); }
__device__ __forceinline__ void wg_fence() { asm volatile("wgmma.fence.sync.aligned;" ::: "memory"); }
__device__ __forceinline__ void wg_commit() { asm volatile("wgmma.commit_group.sync.aligned;" ::: "memory"); }
template <int N> __device__ __forceinline__ void wg_wait() { asm volatile("wgmma.wait_group.sync.aligned %0;" :: "n"(N) : "memory"); }
template <int N> __device__ __forceinline__ void pin(float (&d)[N]) {
#pragma unroll
  for (int i = 0; i < N; i++) asm volatile("" : "+f"(d[i]) :: "memory");
}
__device__ __forceinline__ void pin4(uint4& v) { asm volatile("" : "+r"(v.x), "+r"(v.y), "+r"(v.z), "+r"(v.w) :: "memory"); }
template <uint32_t SBO, uint32_t SWZ> __device__ __forceinline__ uint64_t dsc(uint32_t lo) { return ((uint64_t)((SBO >> 4) | (SWZ << 30)) << 32) | lo; }
__host__ __device__ constexpr uint32_t dlo(uint32_t addr, uint32_t lbo) { return (addr >> 4) | ((lbo >> 4) << 16); }
__device__ __forceinline__ void bar_sync(int id, int n) { asm volatile("bar.sync %0, %1;" :: "r"(id), "r"(n) : "memory"); }
__device__ __forceinline__ void bar_arrive(int id, int n) { asm volatile("bar.arrive %0, %1;" :: "r"(id), "r"(n) : "memory"); }
__device__ __forceinline__ void fence_async_smem() { asm volatile("fence.proxy.async.shared::cta;" ::: "memory"); }
__device__ __forceinline__ void fence_gpu() { asm volatile("fence.acq_rel.gpu;" ::: "memory"); }
__device__ __forceinline__ uint4 ld_cg4(const void* p) { uint4 v; asm volatile("ld.global.cg.v4.u32 {%0,%1,%2,%3}, [%4];" : "=r"(v.x), "=r"(v.y), "=r"(v.z), "=r"(v.w) : "l"(p) : "memory"); return v; }
__device__ __forceinline__ uint4 ld_rlx4(const void* p) { uint4 v; asm volatile("ld.relaxed.gpu.global.v4.u32 {%0,%1,%2,%3}, [%4];" : "=r"(v.x), "=r"(v.y), "=r"(v.z), "=r"(v.w) : "l"(p) : "memory"); return v; }
__device__ __forceinline__ uint32_t ld_rlx(const void* p) { uint32_t v; asm volatile("ld.relaxed.gpu.global.u32 %0, [%1];" : "=r"(v) : "l"(p) : "memory"); return v; }
__device__ __forceinline__ void st_rlx4(void* p, uint4 v) { asm volatile("st.relaxed.gpu.global.v4.u32 [%0], {%1,%2,%3,%4};" :: "l"(p), "r"(v.x), "r"(v.y), "r"(v.z), "r"(v.w) : "memory"); }
__device__ __forceinline__ void st_rlx2(void* p, uint32_t a, uint32_t b) { asm volatile("st.relaxed.gpu.global.v2.u32 [%0], {%1,%2};" :: "l"(p), "r"(a), "r"(b) : "memory"); }
__device__ __forceinline__ void st_rlx(void* p, uint32_t a) { asm volatile("st.relaxed.gpu.global.u32 [%0], %1;" :: "l"(p), "r"(a) : "memory"); }
__device__ __forceinline__ uint32_t pack2(float lo, float hi) { uint32_t r; asm("cvt.rn.bf16x2.f32 %0, %1, %2;" : "=r"(r) : "f"(hi), "f"(lo)); return r; }
__device__ __forceinline__ float bf_lo(uint32_t v) { return __uint_as_float(v << 16); }
__device__ __forceinline__ float bf_hi(uint32_t v) { return __uint_as_float(v & 0xFFFF0000u); }
__device__ __forceinline__ void stsm4(uint32_t addr, uint32_t a, uint32_t b, uint32_t c, uint32_t d) {
  asm volatile("stmatrix.sync.aligned.m8n8.x4.shared.b16 [%0], {%1,%2,%3,%4};" :: "r"(addr), "r"(a), "r"(b), "r"(c), "r"(d) : "memory");
}
template <uint32_t O> __device__ __forceinline__ void stsm4_o(uint32_t addr, uint32_t a, uint32_t b, uint32_t c, uint32_t d) {
  asm volatile("stmatrix.sync.aligned.m8n8.x4.shared.b16 [%0+%5], {%1,%2,%3,%4};" :: "r"(addr), "r"(a), "r"(b), "r"(c), "r"(d), "n"(O) : "memory");
}
__device__ __forceinline__ void sts4(uint32_t addr, uint32_t a, uint32_t b, uint32_t c, uint32_t d) { asm volatile("st.shared.v4.u32 [%0], {%1,%2,%3,%4};" :: "r"(addr), "r"(a), "r"(b), "r"(c), "r"(d) : "memory"); }
__device__ __forceinline__ void sts2f(uint32_t addr, float a, float b) { asm volatile("st.shared.v2.f32 [%0], {%1,%2};" :: "r"(addr), "f"(a), "f"(b) : "memory"); }
__device__ __forceinline__ void sts1(uint32_t addr, uint32_t a) { asm volatile("st.shared.u32 [%0], %1;" :: "r"(addr), "r"(a) : "memory"); }
__device__ __forceinline__ float2 lds2f(uint32_t addr) { float2 v; asm volatile("ld.shared.v2.f32 {%0,%1}, [%2];" : "=f"(v.x), "=f"(v.y) : "r"(addr) : "memory"); return v; }
template <uint32_t O> __device__ __forceinline__ float2 lds2f_o(uint32_t addr) { float2 v; asm volatile("ld.shared.v2.f32 {%0,%1}, [%2+%3];" : "=f"(v.x), "=f"(v.y) : "r"(addr), "n"(O) : "memory"); return v; }
template <int I, int N, class F> __device__ __forceinline__ void static_for(F&& f) { if constexpr (I < N) { f(std::integral_constant<int, I>{}); static_for<I + 1, N>(f); } }
__device__ __forceinline__ uint4 lds4(uint32_t addr) { uint4 v; asm volatile("ld.shared.v4.u32 {%0,%1,%2,%3}, [%4];" : "=r"(v.x), "=r"(v.y), "=r"(v.z), "=r"(v.w) : "r"(addr) : "memory"); return v; }
__device__ __forceinline__ uint32_t lds1(uint32_t addr) { uint32_t v; asm volatile("ld.shared.u32 %0, [%1];" : "=r"(v) : "r"(addr) : "memory"); return v; }
__device__ __forceinline__ float ex2(float x) { float y; asm("ex2.approx.ftz.f32 %0, %1;" : "=f"(y) : "f"(x)); return y; }
__device__ __forceinline__ uint32_t max4(uint32_t m, const uint4& v) { return __vimax3_u32(__vimax3_u32(m, v.x, v.y), v.z, v.w); }
__device__ __forceinline__ float rsq(float x) { float y; asm("rsqrt.approx.ftz.f32 %0, %1;" : "=f"(y) : "f"(x)); return y; }
__device__ __forceinline__ float rcp(float x) { float y; asm("rcp.approx.ftz.f32 %0, %1;" : "=f"(y) : "f"(x)); return y; }
__device__ __forceinline__ uint2 ld_rlx2(const void* p) { uint2 v; asm volatile("ld.relaxed.gpu.global.v2.u32 {%0,%1}, [%2];" : "=r"(v.x), "=r"(v.y) : "l"(p) : "memory"); return v; }
template <uint32_t O> __device__ __forceinline__ uint4 lds4_o(uint32_t addr) { uint4 v; asm volatile("ld.shared.v4.u32 {%0,%1,%2,%3}, [%4+%5];" : "=r"(v.x), "=r"(v.y), "=r"(v.z), "=r"(v.w) : "r"(addr), "n"(O) : "memory"); return v; }
__device__ __forceinline__ uint32_t phi2(float u0, float u1, float rl, uint32_t r2) {
  uint32_t pu, r;
  asm("cvt.rn.relu.bf16x2.f32 %0, %1, %2;" : "=r"(pu) : "f"(u1), "f"(u0));
  asm("fma.rn.bf16x2 %0, %1, %2, %3;" : "=r"(r) : "r"(pu), "r"(r2), "r"(pack2(__saturatef(ex2(u0 * rl) + 1e-6f), __saturatef(ex2(u1 * rl) + 1e-6f))));
  return r;
}
__device__ __forceinline__ uint32_t dup2(float r) { uint32_t v; asm("cvt.rn.relu.bf16x2.f32 %0, %1, %1;" : "=r"(v) : "f"(r)); return v; }
__device__ __forceinline__ uint32_t zero_after(const uint32_t (&v)[16]) {
  uint32_t z = 0;
#pragma unroll
  for (int i = 0; i < 16; i++) z |= v[i];
  return z & 0x80008000u;
}
__device__ __forceinline__ uint32_t hadd2(uint32_t a, uint32_t b) { uint32_t v; asm("add.rn.bf16x2 %0, %1, %2;" : "=r"(v) : "r"(a), "r"(b)); return v; }
__device__ __forceinline__ void sched_fence() { asm volatile("{\n.reg .pred p;\n.reg .u64 c;\nSF:\nmov.u64 c, %clock64;\nsetp.eq.u64 p, c, 0;\n@p bra SF;\n}" ::: "memory"); }
__device__ __forceinline__ uint32_t now_ns() { uint32_t v; asm volatile("mov.u32 %0, %%globaltimer_lo;" : "=r"(v) :: "memory"); return v; }
__device__ __forceinline__ void meet(uint32_t* mine, const uint4* all, int first, int after, uint32_t bar) {
  const uint32_t t0 = now_ns() & ~1u;
  if ((threadIdx.x & 31) == 0) st_rlx(mine, t0);
  while ((int)(now_ns() - t0) < first) NAP;
  uint4 v;
#pragma unroll 1
  for (int it = 0; it < SPIN_LIMIT; it++) { v = ld_rlx4(all); if (!__any_sync(~0u, max4(0, v) == SENT)) break; }
  const int d = min(__reduce_max_sync(~0u, max(max((int)(v.x - t0), (int)(v.y - t0)), max((int)(v.z - t0), (int)(v.w - t0)))), 100000) + after;
  mbar_wait(bar, 0);
  while ((int)(now_ns() - t0) < d) NAP;
}
__device__ __forceinline__ uint32_t hmul2(uint32_t a, uint32_t b) { uint32_t v; asm("mul.rn.bf16x2 %0, %1, %2;" : "=r"(v) : "r"(a), "r"(b)); return v; }
__device__ __forceinline__ uint32_t lane_id() { uint32_t v; asm volatile("mov.u32 %0, %%laneid;" : "=r"(v)); return v; }
template <int A, int B, int N> __device__ __forceinline__ void pinr(float (&d)[N]) {
#pragma unroll
  for (int i = A; i < B; i++) asm volatile("" : "+f"(d[i]) :: "memory");
}
template <int N> __device__ __forceinline__ void pinu(uint32_t (&d)[N]) {
#pragma unroll
  for (int i = 0; i < N; i++) asm volatile("" : "+r"(d[i]) :: "memory");
}

template<int TA, int TB, int OFF, int SZ> __device__ __forceinline__ void wgmma_n192_ss(float (&d)[SZ], uint64_t da, uint64_t db, int scale_d) {
  asm volatile("{\n.reg .pred p;\nsetp.ne.b32 p, %98, 0;\n"
    "wgmma.mma_async.sync.aligned.m64n192k16.f32.bf16.bf16 {%0,%1,%2,%3,%4,%5,%6,%7,%8,%9,%10,%11,%12,%13,%14,%15,%16,%17,%18,%19,%20,%21,%22,%23,%24,%25,%26,%27,%28,%29,%30,%31,%32,%33,%34,%35,%36,%37,%38,%39,%40,%41,%42,%43,%44,%45,%46,%47,%48,%49,%50,%51,%52,%53,%54,%55,%56,%57,%58,%59,%60,%61,%62,%63,%64,%65,%66,%67,%68,%69,%70,%71,%72,%73,%74,%75,%76,%77,%78,%79,%80,%81,%82,%83,%84,%85,%86,%87,%88,%89,%90,%91,%92,%93,%94,%95}, %96, %97, p, 1, 1, %99, %100;\n}\n"
    : "+f"(d[OFF+0]), "+f"(d[OFF+1]), "+f"(d[OFF+2]), "+f"(d[OFF+3]), "+f"(d[OFF+4]), "+f"(d[OFF+5]), "+f"(d[OFF+6]), "+f"(d[OFF+7]),
      "+f"(d[OFF+8]), "+f"(d[OFF+9]), "+f"(d[OFF+10]), "+f"(d[OFF+11]), "+f"(d[OFF+12]), "+f"(d[OFF+13]), "+f"(d[OFF+14]), "+f"(d[OFF+15]),
      "+f"(d[OFF+16]), "+f"(d[OFF+17]), "+f"(d[OFF+18]), "+f"(d[OFF+19]), "+f"(d[OFF+20]), "+f"(d[OFF+21]), "+f"(d[OFF+22]), "+f"(d[OFF+23]),
      "+f"(d[OFF+24]), "+f"(d[OFF+25]), "+f"(d[OFF+26]), "+f"(d[OFF+27]), "+f"(d[OFF+28]), "+f"(d[OFF+29]), "+f"(d[OFF+30]), "+f"(d[OFF+31]),
      "+f"(d[OFF+32]), "+f"(d[OFF+33]), "+f"(d[OFF+34]), "+f"(d[OFF+35]), "+f"(d[OFF+36]), "+f"(d[OFF+37]), "+f"(d[OFF+38]), "+f"(d[OFF+39]),
      "+f"(d[OFF+40]), "+f"(d[OFF+41]), "+f"(d[OFF+42]), "+f"(d[OFF+43]), "+f"(d[OFF+44]), "+f"(d[OFF+45]), "+f"(d[OFF+46]), "+f"(d[OFF+47]),
      "+f"(d[OFF+48]), "+f"(d[OFF+49]), "+f"(d[OFF+50]), "+f"(d[OFF+51]), "+f"(d[OFF+52]), "+f"(d[OFF+53]), "+f"(d[OFF+54]), "+f"(d[OFF+55]),
      "+f"(d[OFF+56]), "+f"(d[OFF+57]), "+f"(d[OFF+58]), "+f"(d[OFF+59]), "+f"(d[OFF+60]), "+f"(d[OFF+61]), "+f"(d[OFF+62]), "+f"(d[OFF+63]),
      "+f"(d[OFF+64]), "+f"(d[OFF+65]), "+f"(d[OFF+66]), "+f"(d[OFF+67]), "+f"(d[OFF+68]), "+f"(d[OFF+69]), "+f"(d[OFF+70]), "+f"(d[OFF+71]),
      "+f"(d[OFF+72]), "+f"(d[OFF+73]), "+f"(d[OFF+74]), "+f"(d[OFF+75]), "+f"(d[OFF+76]), "+f"(d[OFF+77]), "+f"(d[OFF+78]), "+f"(d[OFF+79]),
      "+f"(d[OFF+80]), "+f"(d[OFF+81]), "+f"(d[OFF+82]), "+f"(d[OFF+83]), "+f"(d[OFF+84]), "+f"(d[OFF+85]), "+f"(d[OFF+86]), "+f"(d[OFF+87]),
      "+f"(d[OFF+88]), "+f"(d[OFF+89]), "+f"(d[OFF+90]), "+f"(d[OFF+91]), "+f"(d[OFF+92]), "+f"(d[OFF+93]), "+f"(d[OFF+94]), "+f"(d[OFF+95])
    : "l"(da), "l"(db), "r"(scale_d), "n"(TA), "n"(TB));
}
template<int TA, int TB, int OFF, int SZ> __device__ __forceinline__ void wgmma_n128_ss(float (&d)[SZ], uint64_t da, uint64_t db, int scale_d) {
  asm volatile("{\n.reg .pred p;\nsetp.ne.b32 p, %66, 0;\n"
    "wgmma.mma_async.sync.aligned.m64n128k16.f32.bf16.bf16 {%0,%1,%2,%3,%4,%5,%6,%7,%8,%9,%10,%11,%12,%13,%14,%15,%16,%17,%18,%19,%20,%21,%22,%23,%24,%25,%26,%27,%28,%29,%30,%31,%32,%33,%34,%35,%36,%37,%38,%39,%40,%41,%42,%43,%44,%45,%46,%47,%48,%49,%50,%51,%52,%53,%54,%55,%56,%57,%58,%59,%60,%61,%62,%63}, %64, %65, p, 1, 1, %67, %68;\n}\n"
    : "+f"(d[OFF+0]), "+f"(d[OFF+1]), "+f"(d[OFF+2]), "+f"(d[OFF+3]), "+f"(d[OFF+4]), "+f"(d[OFF+5]), "+f"(d[OFF+6]), "+f"(d[OFF+7]),
      "+f"(d[OFF+8]), "+f"(d[OFF+9]), "+f"(d[OFF+10]), "+f"(d[OFF+11]), "+f"(d[OFF+12]), "+f"(d[OFF+13]), "+f"(d[OFF+14]), "+f"(d[OFF+15]),
      "+f"(d[OFF+16]), "+f"(d[OFF+17]), "+f"(d[OFF+18]), "+f"(d[OFF+19]), "+f"(d[OFF+20]), "+f"(d[OFF+21]), "+f"(d[OFF+22]), "+f"(d[OFF+23]),
      "+f"(d[OFF+24]), "+f"(d[OFF+25]), "+f"(d[OFF+26]), "+f"(d[OFF+27]), "+f"(d[OFF+28]), "+f"(d[OFF+29]), "+f"(d[OFF+30]), "+f"(d[OFF+31]),
      "+f"(d[OFF+32]), "+f"(d[OFF+33]), "+f"(d[OFF+34]), "+f"(d[OFF+35]), "+f"(d[OFF+36]), "+f"(d[OFF+37]), "+f"(d[OFF+38]), "+f"(d[OFF+39]),
      "+f"(d[OFF+40]), "+f"(d[OFF+41]), "+f"(d[OFF+42]), "+f"(d[OFF+43]), "+f"(d[OFF+44]), "+f"(d[OFF+45]), "+f"(d[OFF+46]), "+f"(d[OFF+47]),
      "+f"(d[OFF+48]), "+f"(d[OFF+49]), "+f"(d[OFF+50]), "+f"(d[OFF+51]), "+f"(d[OFF+52]), "+f"(d[OFF+53]), "+f"(d[OFF+54]), "+f"(d[OFF+55]),
      "+f"(d[OFF+56]), "+f"(d[OFF+57]), "+f"(d[OFF+58]), "+f"(d[OFF+59]), "+f"(d[OFF+60]), "+f"(d[OFF+61]), "+f"(d[OFF+62]), "+f"(d[OFF+63])
    : "l"(da), "l"(db), "r"(scale_d), "n"(TA), "n"(TB));
}
template<int TA, int TB, int OFF, int SZ> __device__ __forceinline__ void wgmma_n64_ss(float (&d)[SZ], uint64_t da, uint64_t db, int scale_d) {
  asm volatile("{\n.reg .pred p;\nsetp.ne.b32 p, %34, 0;\n"
    "wgmma.mma_async.sync.aligned.m64n64k16.f32.bf16.bf16 {%0,%1,%2,%3,%4,%5,%6,%7,%8,%9,%10,%11,%12,%13,%14,%15,%16,%17,%18,%19,%20,%21,%22,%23,%24,%25,%26,%27,%28,%29,%30,%31}, %32, %33, p, 1, 1, %35, %36;\n}\n"
    : "+f"(d[OFF+0]), "+f"(d[OFF+1]), "+f"(d[OFF+2]), "+f"(d[OFF+3]), "+f"(d[OFF+4]), "+f"(d[OFF+5]), "+f"(d[OFF+6]), "+f"(d[OFF+7]),
      "+f"(d[OFF+8]), "+f"(d[OFF+9]), "+f"(d[OFF+10]), "+f"(d[OFF+11]), "+f"(d[OFF+12]), "+f"(d[OFF+13]), "+f"(d[OFF+14]), "+f"(d[OFF+15]),
      "+f"(d[OFF+16]), "+f"(d[OFF+17]), "+f"(d[OFF+18]), "+f"(d[OFF+19]), "+f"(d[OFF+20]), "+f"(d[OFF+21]), "+f"(d[OFF+22]), "+f"(d[OFF+23]),
      "+f"(d[OFF+24]), "+f"(d[OFF+25]), "+f"(d[OFF+26]), "+f"(d[OFF+27]), "+f"(d[OFF+28]), "+f"(d[OFF+29]), "+f"(d[OFF+30]), "+f"(d[OFF+31])
    : "l"(da), "l"(db), "r"(scale_d), "n"(TA), "n"(TB));
}
template<int TA, int TB, int OFF, int SZ> __device__ __forceinline__ void wgmma_n72_ss(float (&d)[SZ], uint64_t da, uint64_t db, int scale_d) {
  asm volatile("{\n.reg .pred p;\nsetp.ne.b32 p, %38, 0;\n"
    "wgmma.mma_async.sync.aligned.m64n72k16.f32.bf16.bf16 {%0,%1,%2,%3,%4,%5,%6,%7,%8,%9,%10,%11,%12,%13,%14,%15,%16,%17,%18,%19,%20,%21,%22,%23,%24,%25,%26,%27,%28,%29,%30,%31,%32,%33,%34,%35}, %36, %37, p, 1, 1, %39, %40;\n}\n"
    : "+f"(d[OFF+0]), "+f"(d[OFF+1]), "+f"(d[OFF+2]), "+f"(d[OFF+3]), "+f"(d[OFF+4]), "+f"(d[OFF+5]), "+f"(d[OFF+6]), "+f"(d[OFF+7]),
      "+f"(d[OFF+8]), "+f"(d[OFF+9]), "+f"(d[OFF+10]), "+f"(d[OFF+11]), "+f"(d[OFF+12]), "+f"(d[OFF+13]), "+f"(d[OFF+14]), "+f"(d[OFF+15]),
      "+f"(d[OFF+16]), "+f"(d[OFF+17]), "+f"(d[OFF+18]), "+f"(d[OFF+19]), "+f"(d[OFF+20]), "+f"(d[OFF+21]), "+f"(d[OFF+22]), "+f"(d[OFF+23]),
      "+f"(d[OFF+24]), "+f"(d[OFF+25]), "+f"(d[OFF+26]), "+f"(d[OFF+27]), "+f"(d[OFF+28]), "+f"(d[OFF+29]), "+f"(d[OFF+30]), "+f"(d[OFF+31]),
      "+f"(d[OFF+32]), "+f"(d[OFF+33]), "+f"(d[OFF+34]), "+f"(d[OFF+35])
    : "l"(da), "l"(db), "r"(scale_d), "n"(TA), "n"(TB));
}
template<int TB, int OFF, int SZ> __device__ __forceinline__ void wgmma_n64_rs(float (&d)[SZ], uint32_t a0, uint32_t a1, uint32_t a2, uint32_t a3, uint64_t db, int scale_d) {
  asm volatile("{\n.reg .pred p;\nsetp.ne.b32 p, %37, 0;\n"
    "wgmma.mma_async.sync.aligned.m64n64k16.f32.bf16.bf16 {%0,%1,%2,%3,%4,%5,%6,%7,%8,%9,%10,%11,%12,%13,%14,%15,%16,%17,%18,%19,%20,%21,%22,%23,%24,%25,%26,%27,%28,%29,%30,%31}, {%32,%33,%34,%35}, %36, p, 1, 1, %38;\n}\n"
    : "+f"(d[OFF+0]), "+f"(d[OFF+1]), "+f"(d[OFF+2]), "+f"(d[OFF+3]), "+f"(d[OFF+4]), "+f"(d[OFF+5]), "+f"(d[OFF+6]), "+f"(d[OFF+7]),
      "+f"(d[OFF+8]), "+f"(d[OFF+9]), "+f"(d[OFF+10]), "+f"(d[OFF+11]), "+f"(d[OFF+12]), "+f"(d[OFF+13]), "+f"(d[OFF+14]), "+f"(d[OFF+15]),
      "+f"(d[OFF+16]), "+f"(d[OFF+17]), "+f"(d[OFF+18]), "+f"(d[OFF+19]), "+f"(d[OFF+20]), "+f"(d[OFF+21]), "+f"(d[OFF+22]), "+f"(d[OFF+23]),
      "+f"(d[OFF+24]), "+f"(d[OFF+25]), "+f"(d[OFF+26]), "+f"(d[OFF+27]), "+f"(d[OFF+28]), "+f"(d[OFF+29]), "+f"(d[OFF+30]), "+f"(d[OFF+31])
    : "r"(a0), "r"(a1), "r"(a2), "r"(a3), "l"(db), "r"(scale_d), "n"(TB));
}
template<int TB, int OFF, int SZ> __device__ __forceinline__ void wgmma_n40_rs(float (&d)[SZ], uint32_t a0, uint32_t a1, uint32_t a2, uint32_t a3, uint64_t db, int scale_d) {
  asm volatile("{\n.reg .pred p;\nsetp.ne.b32 p, %25, 0;\n"
    "wgmma.mma_async.sync.aligned.m64n40k16.f32.bf16.bf16 {%0,%1,%2,%3,%4,%5,%6,%7,%8,%9,%10,%11,%12,%13,%14,%15,%16,%17,%18,%19}, {%20,%21,%22,%23}, %24, p, 1, 1, %26;\n}\n"
    : "+f"(d[OFF+0]), "+f"(d[OFF+1]), "+f"(d[OFF+2]), "+f"(d[OFF+3]), "+f"(d[OFF+4]), "+f"(d[OFF+5]), "+f"(d[OFF+6]), "+f"(d[OFF+7]),
      "+f"(d[OFF+8]), "+f"(d[OFF+9]), "+f"(d[OFF+10]), "+f"(d[OFF+11]), "+f"(d[OFF+12]), "+f"(d[OFF+13]), "+f"(d[OFF+14]), "+f"(d[OFF+15]),
      "+f"(d[OFF+16]), "+f"(d[OFF+17]), "+f"(d[OFF+18]), "+f"(d[OFF+19])
    : "r"(a0), "r"(a1), "r"(a2), "r"(a3), "l"(db), "r"(scale_d), "n"(TB));
}
template<int TB, int OFF, int SZ> __device__ __forceinline__ void wgmma_n128_rs(float (&d)[SZ], uint32_t a0, uint32_t a1, uint32_t a2, uint32_t a3, uint64_t db, int scale_d) {
  asm volatile("{\n.reg .pred p;\nsetp.ne.b32 p, %69, 0;\n"
    "wgmma.mma_async.sync.aligned.m64n128k16.f32.bf16.bf16 {%0,%1,%2,%3,%4,%5,%6,%7,%8,%9,%10,%11,%12,%13,%14,%15,%16,%17,%18,%19,%20,%21,%22,%23,%24,%25,%26,%27,%28,%29,%30,%31,%32,%33,%34,%35,%36,%37,%38,%39,%40,%41,%42,%43,%44,%45,%46,%47,%48,%49,%50,%51,%52,%53,%54,%55,%56,%57,%58,%59,%60,%61,%62,%63}, {%64,%65,%66,%67}, %68, p, 1, 1, %70;\n}\n"
    : "+f"(d[OFF+0]), "+f"(d[OFF+1]), "+f"(d[OFF+2]), "+f"(d[OFF+3]), "+f"(d[OFF+4]), "+f"(d[OFF+5]), "+f"(d[OFF+6]), "+f"(d[OFF+7]),
      "+f"(d[OFF+8]), "+f"(d[OFF+9]), "+f"(d[OFF+10]), "+f"(d[OFF+11]), "+f"(d[OFF+12]), "+f"(d[OFF+13]), "+f"(d[OFF+14]), "+f"(d[OFF+15]),
      "+f"(d[OFF+16]), "+f"(d[OFF+17]), "+f"(d[OFF+18]), "+f"(d[OFF+19]), "+f"(d[OFF+20]), "+f"(d[OFF+21]), "+f"(d[OFF+22]), "+f"(d[OFF+23]),
      "+f"(d[OFF+24]), "+f"(d[OFF+25]), "+f"(d[OFF+26]), "+f"(d[OFF+27]), "+f"(d[OFF+28]), "+f"(d[OFF+29]), "+f"(d[OFF+30]), "+f"(d[OFF+31]),
      "+f"(d[OFF+32]), "+f"(d[OFF+33]), "+f"(d[OFF+34]), "+f"(d[OFF+35]), "+f"(d[OFF+36]), "+f"(d[OFF+37]), "+f"(d[OFF+38]), "+f"(d[OFF+39]),
      "+f"(d[OFF+40]), "+f"(d[OFF+41]), "+f"(d[OFF+42]), "+f"(d[OFF+43]), "+f"(d[OFF+44]), "+f"(d[OFF+45]), "+f"(d[OFF+46]), "+f"(d[OFF+47]),
      "+f"(d[OFF+48]), "+f"(d[OFF+49]), "+f"(d[OFF+50]), "+f"(d[OFF+51]), "+f"(d[OFF+52]), "+f"(d[OFF+53]), "+f"(d[OFF+54]), "+f"(d[OFF+55]),
      "+f"(d[OFF+56]), "+f"(d[OFF+57]), "+f"(d[OFF+58]), "+f"(d[OFF+59]), "+f"(d[OFF+60]), "+f"(d[OFF+61]), "+f"(d[OFF+62]), "+f"(d[OFF+63])
    : "r"(a0), "r"(a1), "r"(a2), "r"(a3), "l"(db), "r"(scale_d), "n"(TB));
}

struct Ptrs { const __nv_bfloat16 *x, *wqkv, *wo, *wr, *wg, *wu, *wd; __nv_bfloat16* out; Scratch* s; };

enum { M_X, M_W, M_Q, M_O, M_S, M_G, M_U, M_D, M_L, M_N };
struct Maps { CUtensorMap m[M_N]; };

__global__ void __cluster_dims__(2, 1, 1) __launch_bounds__(384, 1) fused_kernel(const Ptrs P, const __grid_constant__ Maps T) {
  extern __shared__ __align__(1024) uint8_t smem_raw[];
  const uint32_t rank = blockIdx.x & 1;
  uint32_t own = rank << 24;
  asm("" : "+r"(own));
  const uint32_t sm = own + sb, mb = own + bars;
  int b0;
  { const int j = blockIdx.x >> 1, u = j - 36, v = j * 2 - 8 + (max(u * 37 + 256, 0) >> 8) * (u < 0 ? 0 : 2), w = j < 4 ? j * 16 + 64 : v;
    b0 = ((w & 15) | (w & 48) << 1 | (w & 64) >> 2) + rank; }
#define IDS(B) \
  const int b = (B), rb = b >> 4, cg = b & 15, hf = cg >> 3, s3 = cg & 7, c3 = s3 ^ ((rb & 1) << 2), jp = cg >> 1, km = (~c3 & 6) << 1; \
  const int fidx = jp == rb ? -1 : b - 2 * rb - (jp > rb ? 2 : 0); \
  [[maybe_unused]] auto kcol = [&](int kb) { return (kb ^ (kb < 8 ? km & 8 : km)) * 64; }; \
  auto src_of = [&](int p) { return p == 0 ? s3 : p == 15 ? s3 ^ 1 : (((jp & 3) ^ ((p - 7) >> 1)) << 1) + ((p - 1) & 1); }; \
  [[maybe_unused]] auto frag_of = [&](int p) { return p < 9 ? (p - 1) * 512 : 4096 + src_of(p) * 512; }; \
  (void)hf; (void)fidx
  auto get_b = [&]() { return __shfl_sync(~0u, (int)lds1(mb + B_ID), 0); };
  IDS(b0);
  auto load_w = [&](uint32_t st, int kc, uint32_t bar, bool last) { tma_3d(st + 32768, &T.m[M_W], cg * 64, kc, 1, bar, last); tma_2d(st + 49152, &T.m[M_Q], cg * 64, kc, bar, last); };
  if (threadIdx.x < 32 && elect_one()) {
    mbar_init(mb + B_FULL, 1);
    asm volatile("fence.mbarrier_init.release.cluster;" ::: "memory");
    mbar_expect_tx(mb + B_FULL, STAGE_B);
    load_w(sm, kcol(0), mb + B_FULL, false);
    tma_2d(sm + 16384, &T.m[M_X], kcol(0), rb * 256 + 128, mb + B_FULL, false);
    tma_2d(sm, &T.m[M_X], kcol(0), rb * 256, mb + B_FULL, false);
  }
  const int tid = threadIdx.x, wid = __shfl_sync(~0u, tid >> 5, 0), wg = wid >> 2, lane = lane_id();
  const uint32_t tk = clock64();
  if (wid < 4) {
    const int i = tid - 64;
    if (tid >= 32 && tid < 112)
      l2_prefetch(i < 0 ? P.x + (rb * 256 + (hf * 4 + (cg & 3)) * 32 + lane) * D_ + kcol(0) : P.wqkv + (kcol(0) + (rb >> 1) * 16 + (i & 15)) * 3072 + (i >> 4) * 1024 + cg * 64);
  } else if (wid == 9) {
    if (elect_one()) {
#pragma unroll
      for (int i = 1; i < 31; i++) if (8 * i != B_ID) mbar_init(mb + 8 * i, i < 4 ? 1 : i < 8 ? 8 : i < 16 ? 16 : i == 16 ? 64 : i == 17 ? 8 : i == 18 ? 4 : 1);
      asm volatile("fence.mbarrier_init.release.cluster;" ::: "memory");
      fence_async_smem();
    }
  } else if (wid == 11) {
#pragma unroll
    for (int i = 0; i < 4; i++) sts4(sm + OFF_STATS + i * 512 + lane * 16, SENT, SENT, SENT, SENT);
    sts1(mb + B_ID, b);
    if (smem_u32(smem_raw) != sm) asm volatile("trap;");
    fence_async_smem();
  }
  __syncthreads();
  asm volatile("barrier.cluster.arrive.relaxed.aligned;\nbarrier.cluster.wait.aligned;" ::: "memory");

  if (wg == 2) {
    asm volatile("setmaxnreg.dec.sync.aligned.u32 56;");
    if (wid == 8) {
      if (elect_one()) {
#pragma unroll 1
        for (int kb = 1; kb < 15; kb++) {
          const uint32_t fb = mb + B_FULL + 8 * (kb & 3), st = sm + (kb & 3) * STAGE_B;
          const int kc = kcol(kb);
          if (kb < 4) while ((uint32_t)clock64() - tk < FD0 + kb * FD1) {}
          else mbar_wait(fb + B_EMPTY, ((kb >> 2) & 1) ^ 1);
          mbar_expect_tx(fb, STAGE_B);
          tma_2d_mc(st + rank * 16384, &T.m[M_X], kc, rb * 256 + rank * 128, fb, kb >= 12);
          load_w(st, kc, fb, kb >= 8);
          if (kb >= 8 && kb < 11) asm volatile("mbarrier.arrive.shared::cta.b64 _, [%0], %1;" :: "r"(fb + B_EMPTY), "r"(4) : "memory");
        }
        {
          const uint32_t st = sm + 3 * STAGE_B, fa = mb + B_FULL + 24, fb = mb + B_F15;
          const int kc = kcol(15);
          mbar_wait(fa, 0);
          mbar_expect_tx(fa, 32768); mbar_expect_tx(fb, 24576);
          if (rank) { mbar_wait(mb + B_EMPTY + 24, 0); tma_2d_mc(st + 16384, &T.m[M_X], kc, rb * 256 + 128, fa, true); }
          mbar_wait(mb + B_EMPTY, 1);
          tma_3d(st + 32768, &T.m[M_W], cg * 64, kc, 1, fa, true);
          if (!rank) { mbar_wait(mb + B_EMPTY + 24, 0); tma_2d_mc(st, &T.m[M_X], kc, rb * 256, fb, true); }
          tma_2d(st + 49152, &T.m[M_Q], cg * 64, kc, fb, true);
        }
        mbar_expect_tx(mb + B_KVP, 32768 + 2048);
      }
      __syncwarp();
      const uint4* kp = &P.s->kvp[cg * 8 * 256], *zq = &P.s->zp[cg * 8 * 16], *src = &P.s->obuf[(rb * 4 + rank * 2 + hf) * 64 * 128];
      asm volatile("" : "+l"(kp), "+l"(zq), "+l"(src));
      mbar_wait(mb + B_EVA, 0);
      meet(&P.s->when[cg * 32 + rb], (const uint4*)&P.s->when[cg * 32] + (lane & 1), MFIRST, MKV, mb + B_EVB);
      if (elect_one()) {
        bulk_load(sm + rank * (2 * STAGE_B) + STAGE_B, kp, 32768, mb + B_KVP);
        bulk_load(sm + rank * (2 * STAGE_B) + UNIT, zq, 2048, mb + B_KVP);
      }
      mbar_wait(mb + B_KVP, 0);
      meet(&P.s->when[(16 + rb * 2 + hf) * 32 + s3], (const uint4*)&P.s->when[(16 + rb * 2 + (hf ^ 1)) * 32] + (lane & 1), MFIRST, MO, mb + B_E);
      if (elect_one()) {
        const uint32_t t0 = clock64();
        mbar_arrive(mb + B_F15);
#pragma unroll
        for (int p = 2; p < 5; p++) {
          if (p < 4) while ((uint32_t)clock64() - t0 < (p == 2 ? ADELAY : ADELAY2)) NAP;
          bulk_load_mc(sm + ring_of(p, rank), src + (p - 1) * 512, UNIT, mb + B_BF + 8 * p);
        }
#pragma unroll 1
        for (int p = 5; p < 15; p++) {
          uint32_t dst = sm + ring_of(p, rank), bar = mb + B_BF + 8 * (p % 7);
          const uint4* q = src + frag_of(p);
          asm volatile("" : "+r"(dst), "+r"(bar), "+l"(q));
          mbar_wait(mb + B_E + 8 * ((p - 4) & 7), p >= 12);
          bulk_load_mc(dst, q, UNIT, bar);
        }
        asm volatile("mbarrier.arrive.shared::cta.b64 _, [%0], 8;" :: "r"(mb + B_GATE) : "memory");
        const uint4* s15 = &P.s->obuf[(rb * 4 + hf) * 64 * 128 + frag_of(15)];
        mbar_wait(mb + B_E + 24, 1);
        bulk_load(sm + ring_of(15, 0), s15, UNIT, mb + B_BF + 8); bulk_load(sm + ring_of(15, 1), s15 + 2 * 64 * 128, UNIT, mb + B_BF + 8);
      }
    } else if (wid == 11) {
      IDS(get_b());
      if (fidx >= 0) {
        const uint32_t o = (rank * 32 + lane) * (F_ * 2) + (fidx >> 1) * 128;
        const char* q0 = (const char*)P.wg + o, *q1 = (const char*)P.wu + o;
        mbar_wait(mb + B_FULL + 24, 0);
        mbar_wait(mb + B_FULL + 8 * (PULL0 & 3), PULL0 >> 2);
#pragma unroll 1
        for (int r = 0; r < 16; r++, q0 += 64 * F_ * 2, q1 += 64 * F_ * 2) {
          if (mbar_test(mb + B_F15, 0)) { l2_prefetch(q0); l2_prefetch(q1); continue; }
          asm volatile("cp.async.ca.shared.global.L2::128B [%0], [%1], 4;\ncp.async.commit_group;\ncp.async.wait_group %3;\n"
                       "cp.async.ca.shared.global.L2::128B [%0], [%2], 4;\ncp.async.commit_group;\ncp.async.wait_group %3;" :: "r"(mb + B_DUMMY), "l"(q0), "l"(q1), "n"(2) : "memory");
        }
        mbar_wait(mb + B_F15, 0);
        bar_sync(15, 288);
        q0 = (const char*)P.wd + fidx * 65536 + lane * 128;
        const uint32_t bar = mb + B_BF + 48;
        if (lane == 0) mbar_expect_tx(bar, 8192);
#pragma unroll 1
        for (int i = 0; i < 16 + PLAG; i++) {
          if (i < 16) l2_prefetch(q0 + i * 4096);
          if (i >= PLAG && elect_one()) tma_2d(sm + OFF_COLSUM, &T.m[M_L], 0, fidx * 512 + (i - PLAG) * 32, bar, false);
        }
        mbar_wait(bar, 0);
        __syncwarp();
        if (lane == 0) { mbar_arrive(bar); }
        asm volatile("cp.async.wait_all;" ::: "memory");
      } else bar_sync(15, 288);
      bar_arrive(14, 64);
    } else {
      const uint32_t eb = (lane << 24) + bars + B_EMPTY;
      float c[6];
      if (wid == 10) {
        float sx[4] = {0.f, 0.f, 0.f, 0.f}, qx[4] = {0.f, 0.f, 0.f, 0.f};
        const uint32_t xa = sm + ((hf * 4 + (cg & 3)) * 32 + lane) * 128 + ((lane & 7) << 4);
#pragma unroll 1
        for (int kb = 0; kb < 8; kb++) {
          uint4 xv[8];
          const uint32_t so = xa + (kb & 3) * STAGE_B;
          mbar_wait(mb + B_FULL + 8 * (kb & 3), kb >> 2);
#pragma unroll
          for (int i = 0; i < 8; i++) xv[i] = lds4(so ^ (i << 4));
#pragma unroll
          for (int i = 0; i < 8; i++) {
            const uint32_t e[4] = {xv[i].x, xv[i].y, xv[i].z, xv[i].w};
#pragma unroll
            for (int j = 0; j < 4; j++) {
              const float d0 = bf_lo(e[j]), d1 = bf_hi(e[j]);
              sx[j] += d0 + d1; qx[j] = fmaf(d0, d0, fmaf(d1, d1, qx[j]));
            }
          }
          __syncwarp();
          if (lane < 2) mbar_arrive_rem(eb + 8 * (kb & 3));
          if (kb == 4) {
        {
          const uint32_t ep = ld_rlx(&P.s->epoch);
          float s = 0.f;
#pragma unroll
          for (int i = 0; i < 4; i++) {
            const uint4 v = ld_cg4((const uint4*)P.wr + lane + i * 32);
            s += (bf_lo(v.x) + bf_hi(v.x)) + (bf_lo(v.y) + bf_hi(v.y)) + (bf_lo(v.z) + bf_hi(v.z)) + (bf_lo(v.w) + bf_hi(v.w));
          }
#pragma unroll
          for (int o = 16; o; o >>= 1) s += __shfl_xor_sync(~0u, s, o);
          if (lane == 0) sts1(mb + B_SW, (__float_as_uint(s) & ~255u) | ((ep + 1) & 255));
        }
        asm volatile("cp.async.bulk.wait_group 0;\nfence.proxy.async.global;" ::: "memory");
        fence_gpu();
          }
          if (kb == 1) {
        if (elect_one()) {
#pragma unroll 1
          for (int i = 0; i < 16; i++) bulk_store(&P.s->obuf[((rb * 4 + (i >> 2)) * 64 + (((i >> 2) & 1) == hf ? 32 + s3 * 4 + (i & 3) : (i & 3) * 8 + s3)) * 128], sm + OFF_STATS, 2048);
          bulk_store(&P.s->kvp[(cg * 8 + rb) * 256], sm + OFF_STATS, 2048); bulk_store(&P.s->kvp[(cg * 8 + rb) * 256 + 128], sm + OFF_STATS, 2048);
          bulk_store(&P.s->zp[(cg * 8 + rb) * 16], sm + OFF_STATS, 256);
          if (s3 == 0) bulk_store(&P.s->when[(16 + rb * 2 + hf) * 32], sm + OFF_STATS, 128);
          if (rb == 0) bulk_store(&P.s->when[cg * 32], sm + OFF_STATS, 128);
          asm volatile("cp.async.bulk.commit_group;" ::: "memory");
          #pragma unroll
          for (int i = M_O; i < M_N; i++) tmap_prefetch(&T.m[i]);
        }
        __syncwarp();
          }
        }
        c[0] = ((sx[0] + sx[1]) + (sx[2] + sx[3])) * (2.f / D_);
        c[1] = fmaxf(fmaf(-c[0], c[0], ((qx[0] + qx[1]) + (qx[2] + qx[3])) * (2.f / D_)), 0.f);
      } else {
        float a[12];
#pragma unroll
        for (int i = 0; i < 12; i++) a[i] = 0.f;
        const int r2 = lane >> 4, c16 = lane & 15;
        const uint32_t a0 = sm + 32768 + (rb >> 1) * 2048 + r2 * 128 + (((c16 >> 1) ^ r2) << 4) + (c16 & 1) * 8;
#pragma unroll 1
        for (int it = 0; it < 16; it++) {
          uint2 w[12];
          const int s = (it >> 1) & 3;
          const uint32_t so = a0 + s * STAGE_B + (it & 1) * 1024;
          if (!(it & 1)) { mbar_wait(mb + B_FULL + 8 * s, it >> 3); }
          static_for<0, 12>([&](auto ic) { constexpr int i = decltype(ic)::value;
            const float2 v = lds2f_o<(i >> 2) * 8192 + (i & 3) * 256>(so ^ ((i & 3) << 5)); w[i] = make_uint2(__float_as_uint(v.x), __float_as_uint(v.y)); });
#pragma unroll
          for (int i = 0; i < 12; i++) { float* q = a + (i >> 2) * 4; q[0] += bf_lo(w[i].x); q[1] += bf_hi(w[i].x); q[2] += bf_lo(w[i].y); q[3] += bf_hi(w[i].y); }
          __syncwarp();
          if (lane < 2 && (it & 1)) mbar_arrive_rem(eb + 8 * s);
        }
#pragma unroll
        for (int i = 0; i < 6; i++) {
          const int o = (i >> 1) * 4 + (i & 1);
          c[i] = (r2 ? a[o + 2] : a[o]) + __shfl_xor_sync(~0u, r2 ? a[o] : a[o + 2], 16);
        }
      }
      bar_sync(10, 64);
      {
        const uint32_t tag = lds1(mb + B_SW) & 255;
        auto tagged = [&](float v) { return ((__float_as_uint(v) + 128) & ~255u) | tag; };
        if (wid == 9) {
#pragma unroll
          for (int sg = 0; sg < 3; sg++) {
            st_rlx2((uint2*)&P.s->csp[(cg * 8 + rb) * 48] + sg * 32 + (lane & 15) * 2 + (lane >> 4), tagged(c[sg * 2]), tagged(c[sg * 2 + 1]));
          }
        } else st_rlx2((uint2*)&P.s->st1[(rb * 8 + hf * 4 + (cg & 3)) * 48 + lane] + ((cg >> 2) & 1), tagged(c[0]), tagged(c[1]));
        __nanosleep(GDELAY);
#pragma unroll 1
        for (int h = wid - 9; h < 2; h++) {
          const int q = h * 24 + min(lane, 23);
          const uint4* gp = wid == 10 ? &P.s->st1[rb * 8 * 48 + lane] : &P.s->csp[cg * 8 * 48 + q];
          uint4 v[8];
#pragma unroll 1
          for (int it = 0;; it++) {
            uint32_t x = 0;
#pragma unroll
            for (int i = 0; i < 8; i++) v[i] = ld_rlx4(gp + i * 48);
#pragma unroll
            for (int i = 0; i < 8; i++) { v[i].x ^= tag; v[i].y ^= tag; v[i].z ^= tag; v[i].w ^= tag; x |= v[i].x | v[i].y | v[i].z | v[i].w; }
            if (!__any_sync(~0u, (x & 255) != 0)) break;
            SPINCHK(it);
          }
          if (wid == 10) {
#pragma unroll
            for (int i = 0; i < 8; i++) {
              const float m0 = __uint_as_float(v[i].x), m1 = __uint_as_float(v[i].z), dm = 0.5f * (m0 - m1);
              sts2f(sm + OFF_STATS + (i * 32 + lane) * 8, -0.5f * (m0 + m1), rsq(fmaf(dm, dm, 0.5f * (__uint_as_float(v[i].y) + __uint_as_float(v[i].w))) + 1e-5f));
            }
          } else {
            float s4[4] = {0.f, 0.f, 0.f, 0.f};
#pragma unroll
            for (int i = 0; i < 8; i++) { s4[0] += __uint_as_float(v[i].x); s4[1] += __uint_as_float(v[i].y); s4[2] += __uint_as_float(v[i].z); s4[3] += __uint_as_float(v[i].w); }
            sts4(sm + OFF_COLSUM + q * 16, __float_as_uint(s4[0]), __float_as_uint(s4[1]), __float_as_uint(s4[2]), __float_as_uint(s4[3]));
          }
        }
        mbar_arrive(mb + B_AUX);
      }
      IDS(get_b());
      const uint64_t btab = rank ? BT1 : BT0;
      if (wid == 9) {
        {
          const uint4 sv = make_uint4(SENT, SENT, SENT, SENT);
          uint4* y = &P.s->ybuf[b * NFFN * 2 + lane];
#pragma unroll
          for (int i = 0; i < 7; i++) y[i * 32] = sv;
          if (lane < 16) P.s->st2[b * 16 + lane] = make_uint4(0, 0, 0, 0); else P.s->hsel[b * 16 + lane - 16] = sv;
          if (b < 8) P.s->cand[b * 32 + lane] = SENT;
          fence_gpu();
          bar_sync(0, 288);
          if (lane < 16) sts4(sm + OFF_STATS + lane * 128 + ((lane & 7) << 4), 0x3F803F80u, 0x3F803F80u, 0x3F803F80u, 0x3F803F80u);
          fence_async_smem();
          __syncwarp();
          if (lane == 0) mbar_arrive(mb + B_LATE);
        }
        {
          const int p = lane & 15, sl = p % 7;
          const bool sliced = p > 0 && p < 9;
          const uint32_t c = sliced ? ((p - 1) >> 1) * 16 | ((hf ^ 1) * 8 + ((p - 1) & 1) * 4) << 8 | 128 << 16 : (hf * 8 + src_of(p)) << 8;
          const uint32_t ev = mb + (p < 4 ? B_EVA : B_E + 8 * ((p < 7 ? p == 6 : p - 4) & 7) + (p >= 12));
          mbar_wait(mb + B_EVA, 0);
          sts4(sm + OFF_COLSUM + 512 + p * 16, sm + unit_of(btab, sl), mb + B_BF + 8 * sl, c, ev);
          __syncwarp();
        }
        if (elect_one()) {
#pragma unroll 1
          for (int p = 0; p < 16; p++) {
            const uint4 e = lds4(sm + OFF_COLSUM + 512 + p * 16);
            if (p == 4) mbar_wait(mb + B_WR, 0);
            mbar_wait(e.w & ~1u, e.w & 1);
            mbar_expect_tx(e.y, p > 1 ? 4 * UNIT : 2 * UNIT);
            tma_4d(e.x, (const CUtensorMap*)((const char*)&T.m[M_O] + (e.z >> 16)), 0, e.z & 255, (e.z >> 8) & 255, c3 * 2, e.y);
          }
        }
      } else {
        const uint32_t* wp = (const uint32_t*)(P.wr + c3 * 128) + (lane & 7) * 8 + (lane >> 3);
        const uint32_t w0 = ld_rlx(wp), w1 = ld_rlx(wp + 4);
#pragma unroll 1
        for (int i = 0; i < 4; i++) { l2_prefetch((const char*)P.wo + b * 16384 + i * 4096 + lane * 128); __nanosleep(300); }
        const int p = lane & 15, p2 = min(p + 2, 15);
        const uint32_t t0 = dlo(sb, 8192) + (unit_of(btab, p % 7) >> 4), t1 = ring_of(p + 1, lane >> 4), t2 = mb + B_BF + 8 * (p2 % 7);
        mbar_wait(mb + B_EVB, 0);
        bar_sync(14, 64);
        sts2f(sm + OFF_COLSUM + lane * 8, __uint_as_float(w0), __uint_as_float(w1));
        sts1(sm + OFF_COLSUM + 256 + lane * 4, 0x3F803F80u);
        sts4(sm + OFF_STATS + lane * 16, t0, t1, t2, (p2 / 7) & 1);
        __syncwarp();
        if (elect_one()) {
          mbar_arrive(mb + B_WR);
          if (fidx >= 0) {
            mbar_expect_tx(mb + B_FFN, 131072); mbar_expect_tx(mb + B_FFD, 32768);
            uint64_t gt = rank ? GT1 : GT0;
#pragma unroll 1
            for (int f = 0; f < 8; f++, gt >>= 5) {
              uint32_t d0 = sm + unit_of(gt, 0);
              asm volatile("" : "+r"(d0));
              if (f == 3) mbar_wait(mb + B_GATE, 1);
              mbar_wait(mb + (f < 1 ? B_KVB : B_E + (f < 3 ? 3 + 2 * f : (f + 5) >> 1) * 8), f < 1 || f >= 3);
              tma_3d(d0, &T.m[M_G], fidx * 32, f * 128, 0, mb + B_FFN, true);
              tma_3d(d0 + UNIT, &T.m[M_U], fidx * 32, f * 128, 0, mb + B_FFN, true);
            }
            mbar_expect_tx(mb + B_KVP, 32768);
#pragma unroll
            for (int w = 0; w < 8; w++) {
              if (w == 2) mbar_wait(mb + B_E + 56, 1);
              if (w == 6) mbar_wait(mb + B_E16, 1);
              if (w == 4) mbar_wait(mb + B_EVA, 1);
              tma_3d(sm + ((DT0 >> (5 * w)) & 31) * UNIT + (w < 4 ? 0 : w < 6 ? 14 * UNIT : 0 - 14 * UNIT) * rank, &T.m[M_D], 0, fidx * 32, 2 * w, mb + (w < 4 ? B_FFD : B_KVP), true);
            }
          }
        }
      }
    }
    __syncwarp();
    IDS(get_b());
    mbar_wait(mb + B_EVB, 0);
    mbar_wait(mb + B_OUT, 0);
    const float2 cf = lds2f(sm + OFF_STATS + 64);
    const int cand0 = 2047 - (__float_as_int(cf.x) & 2047), cand1 = 2047 - (__float_as_int(cf.y) & 2047), rr = lane >> 4;
    __nv_bfloat16* const ob = P.out + c3 * 128 + (lane & 15) * 8;
    auto store_row = [&](uint32_t ha, uint32_t la, int row, bool on) {
      const uint4 v = lds4(ha);
      const float2 pr = lds2f(la);
      const float f = 1.f + pr.x, n = pr.y;
      asm volatile("{\n.reg .pred p;\nsetp.ne.u32 p, %5, 0;\n@p st.global.v4.u32 [%0], {%1,%2,%3,%4};\n}" :: "l"(ob + row * D_),
                   "r"(pack2(fmaf(bf_lo(v.x), f, n), fmaf(bf_hi(v.x), f, n))), "r"(pack2(fmaf(bf_lo(v.y), f, n), fmaf(bf_hi(v.y), f, n))),
                   "r"(pack2(fmaf(bf_lo(v.z), f, n), fmaf(bf_hi(v.z), f, n))), "r"(pack2(fmaf(bf_lo(v.w), f, n), fmaf(bf_hi(v.w), f, n))), "r"((uint32_t)on) : "memory");
    };
    {
      uint32_t t0 = clock64();
      uint32_t ha = sm + 4 * UNIT + ((wid >> 1) & 1) * STAGE_B + ((wid & 1) * 32 + rr) * 256 + (((lane & 15) ^ rr) << 4), la = sm + OFF_LNP + ((wid & 3) * 32 + rr) * 8;
      int row = rb * 256 + hf * 64 + (wid & 2) * 64 + (wid & 1) * 32 + rr;
#pragma unroll 1
      for (int i = 0; i < 16; i += 2, ha += 512 * 2, la += 16 * 2, row += 2 * 2, t0 += OPACE) {
        while ((int)((uint32_t)clock64() - t0) < 0) NAP;
#pragma unroll
        for (int j = 0; j < 2; j++) store_row((ha ^ (((i + j) & 3) << 5)) + j * 512, la + j * 16, row + 2 * j, row + 2 * j != cand0 && row + 2 * j != cand1);
      }
    }
    if (wid == 8) {
      const uint32_t kc = __float_as_uint(rr ? cf.y : cf.x);
      const int c = rr ? cand1 : cand0;
      mbar_wait(mb + B_SEL, 0);
      const float2 sel = lds2f(sm + OFF_STATS + 80);
      store_row(sm + 4 * UNIT + ((c >> 7) & 1) * STAGE_B + (c & 63) * 256 + (((lane & 15) ^ (c & 7)) << 4), sm + OFF_LNP + (((c >> 1) & 64) + (c & 63)) * 8, c,
                kc != __float_as_uint(sel.x) && kc != __float_as_uint(sel.y) && (c >> 8) == rb && ((c >> 6) & 1) == hf);
    }
  } else {
    asm volatile("setmaxnreg.inc.sync.aligned.u32 224;");
    const int t128 = tid & 127, warp = wid & 3, g = lane >> 2, t = lane & 3;
    const uint32_t sk = rank * (2 * STAGE_B);
    uint4 ost[2][4];
    uint4 abuf[3][4];
    uint4* od1;
    const uint4* ain;
    int b1;
    const uint32_t eb = (lane << 24) + bars + B_E;
    float acc[64];
    uint4 wb[4];
    uint32_t hp[32];
    {
      float acc1[96], acc0[96];
#pragma unroll
      for (int i = 0; i < 96; i++) { acc0[i] = 0.f; acc1[i] = 0.f; }
      const uint32_t xo0 = dlo(sb, 16) + (wg * 2 + hf) * 512, xo1 = dlo(sb, 16) + (wg * 2 + (hf ^ 1)) * 512;
      constexpr uint32_t ST = STAGE_B >> 4, WD = dlo(sb + 49152, 8192), WV = dlo(sb + 32768, 8192);
      const uint32_t eb0 = (t128 << 24) + bars + B_EMPTY;
#pragma unroll 1
      for (int kb = 0; kb < 12; kb++) {
        const int s = kb & 3;
        mbar_wait(mb + B_FULL + 8 * s, (kb >> 2) & 1);
        if (kb == 0 && !wg) bar_sync(2, 256);
        pin(acc0); pin(acc1);
        wg_fence();
#pragma unroll
        for (int k = 0; k < 4; k++) {
          const uint64_t db = dsc<1024, 1>(WV + s * ST + k * 128);
          wgmma_n192_ss<0, 1, 0>(acc0, dsc<1024, 1>(s * ST + xo0 + k * 2), db, 1);
          wgmma_n192_ss<0, 1, 0>(acc1, dsc<1024, 1>(s * ST + xo1 + k * 2), db, 1);
        }
        wg_commit();
        if (kb == 0 && wg) bar_arrive(2, 256);
        wg_wait<0>();
        pin(acc0); pin(acc1);
        if (t128 < 2 && kb < 11) mbar_arrive_rem(eb0 + 8 * s);
      }
      mbar_wait(mb + B_FULL, 1);
      if (t128 < 8) mbar_arrive_rem(t128 < 4 ? (wg << 24) + bars + B_EMPTY + 24 : mb + B_EMPTY);
      mbar_wait(mb + B_AUX, 0);
      float rs[2][2], nm[2][2];
#pragma unroll
      for (int m = 0; m < 2; m++)
#pragma unroll
        for (int h = 0; h < 2; h++) { const float2 v = lds2f(sm + OFF_STATS + ((wg * 2 + (m ^ hf)) * 64 + warp * 16 + h * 8 + g) * 8); nm[m][h] = v.x; rs[m][h] = v.y; }
      auto center = [&](auto jc) {
        constexpr int j = decltype(jc)::value;
        const float2 cs = lds2f_o<sb + OFF_COLSUM + j * 32>(own + t * 8);
        acc1[j * 4] = fmaf(nm[1][0], cs.x, acc1[j * 4]); acc1[j * 4 + 1] = fmaf(nm[1][0], cs.y, acc1[j * 4 + 1]);
        acc1[j * 4 + 2] = fmaf(nm[1][1], cs.x, acc1[j * 4 + 2]); acc1[j * 4 + 3] = fmaf(nm[1][1], cs.y, acc1[j * 4 + 3]);
        acc0[j * 4] = fmaf(nm[0][0], cs.x, acc0[j * 4]); acc0[j * 4 + 1] = fmaf(nm[0][0], cs.y, acc0[j * 4 + 1]);
        acc0[j * 4 + 2] = fmaf(nm[0][1], cs.x, acc0[j * 4 + 2]); acc0[j * 4 + 3] = fmaf(nm[0][1], cs.y, acc0[j * 4 + 3]);
      };
      static_for<0, 16>(center);
      const float L2E = 1.4426950408889634f;
      uint32_t fa = sm + sk + (warp * 16 + (lane & 15)) * 128 + (((lane >> 4) ^ (lane & 7)) << 4);
      asm volatile("" : "+r"(fa));
      uint32_t xf0[32], xf1[32];
      auto pack_kv = [&](float (&a)[96], int i, float r0, float r1, uint32_t* o, uint32_t z = 0) {
        const float* p = a + i * 8;
        if (i < 4) {
          const float rl0 = __uint_as_float(__float_as_uint(r0 * L2E) | z), rl1 = __uint_as_float(__float_as_uint(r1 * L2E) | z);
          const uint32_t q0 = pack2(r0, r0), q1 = pack2(r1, r1);
          o[0] = phi2(p[0], p[1], rl0, q0); o[1] = phi2(p[2], p[3], rl1, q1); o[2] = phi2(p[4], p[5], rl0, q0); o[3] = phi2(p[6], p[7], rl1, q1);
        } else {
          const uint32_t q0 = pack2(r0, r0), q1 = pack2(r1, r1);
          o[0] = hmul2(pack2(p[0], p[1]), q0); o[1] = hmul2(pack2(p[2], p[3]), q1); o[2] = hmul2(pack2(p[4], p[5]), q0); o[3] = hmul2(pack2(p[6], p[7]), q1);
        }
      };
      auto swap_kv = [&](uint32_t (&xf)[32], uint32_t tile, int i, const uint32_t* o, uint32_t z = 0) {
        const uint32_t ad = (fa + tile * UNIT) ^ ((i & 3) << 5);
        if (i < 4) { ldsm4_o<0>(ad, xf[i * 4], xf[i * 4 + 1], xf[i * 4 + 2], xf[i * 4 + 3]); stsm4_o<0>(ad, o[0], o[1], o[2], o[3]); }
        else { ldsm4_o<STAGE_B>(ad | z, xf[i * 4], xf[i * 4 + 1], xf[i * 4 + 2], xf[i * 4 + 3]); stsm4_o<STAGE_B>(ad, o[0], o[1], o[2], o[3]); }
      };
      auto mma_q = [&](float (&a)[96], uint32_t (&xf)[32], uint32_t xo, bool ss) {
        const uint32_t r = __shfl_sync(~0u, sk >> 4, 0), o = 2 * ST - r;
#pragma unroll
        for (int j = 0; j < 8; j++) {
          if (ss) wgmma_n64_ss<0, 1, 64>(a, dsc<1024, 1>(o + (j >> 2) * ST + xo + (j & 3) * 2), dsc<1024, 1>(WD + o + (j >> 2) * ST + (j & 3) * 128), 1);
          else wgmma_n64_rs<1, 64>(a, xf[j * 4], xf[j * 4 + 1], xf[j * 4 + 2], xf[j * 4 + 3], dsc<1024, 1>(WD + r + (j >> 2) * ST + (j & 3) * 128), 1);
        }
      };
      auto epi_q = [&](float (&a)[96], float r0, float r1, uint32_t (&o)[16]) {
        const float rl0 = r0 * 1.44269511f, rl1 = r1 * 1.44269511f;
        const uint32_t q0 = dup2(r0), q1 = dup2(r1);
#pragma unroll
        for (int j = 0; j < 8; j++) { o[j * 2] = phi2(a[64 + j * 4], a[65 + j * 4], rl0, q0); o[j * 2 + 1] = phi2(a[66 + j * 4], a[67 + j * 4], rl1, q1); }
        pinu(o);
      };
      auto mma_kv1 = [&](float (&a)[96], uint32_t xo, int s) {
#pragma unroll
        for (int k = 0; k < 4; k++) wgmma_n128_ss<0, 1, 0>(a, dsc<1024, 1>(s * ST + xo + k * 2), dsc<1024, 1>(WV + s * ST + k * 128), 1);
      };
      auto epi_kv = [&](float (&a)[96], uint32_t (&xf)[32], uint32_t tile, float r0, float r1) {
        uint32_t o[8][4];
#pragma unroll
        for (int j = 3; j >= 0; j--) {
          const uint32_t z = j < 3 ? xf[(j + 5) * 4] & blockIdx.y : 0;
          pack_kv(a, j + 4, r0, r1, o[j + 4]);
          swap_kv(xf, tile, j + 4, o[j + 4], (o[j + 4][2] | o[j + 4][3]) & blockIdx.y);
          pack_kv(a, j, r0, r1, o[j], z);
          swap_kv(xf, tile, j, o[j]);
        }
      };
      bar_arrive(15, 288); bar_arrive(0, 288);
      mbar_wait(mb + B_FULL + 8, 1);
      if (!wg) bar_sync(3, 256);
      pinr<0, 64>(acc0); pinr<0, 64>(acc1);
      wg_fence();
      mma_kv1(acc1, xo1, 0); mma_kv1(acc0, xo0, 0); mma_kv1(acc1, xo1, 1); mma_kv1(acc0, xo0, 1);
      mbar_wait(mb + B_FULL + 16, 1);
      wg_fence();
      mma_kv1(acc1, xo1, 2);
      mbar_wait(mb + (wg ? B_FULL + 24 : B_F15), wg);
      wg_fence();
      mma_kv1(acc1, xo1, 3);
      wg_commit();
      bar_arrive(4 - wg, 256);
      static_for<16, 24>(center);
      pinr<64, 96>(acc0); pinr<64, 96>(acc1);
      mbar_wait(mb + B_FULL + 8, 1);
      wg_wait<0>();
      pinr<0, 64>(acc0); pinr<0, 64>(acc1);
      epi_kv(acc1, xf1, wg * 2 + (hf ^ 1), rs[1][0], rs[1][1]);
      pinu(xf1);
      bar_sync(5 - wg, 256);
      wg_fence();
      mma_kv1(acc0, xo0, 2); mma_kv1(acc0, xo0, 3);
      wg_commit();
      fence_async_smem();
      mma_q(acc1, xf1, xo1, false);
      wg_commit();
      bar_arrive(6 - wg, 256);
      wg_wait<1>();
      pinr<0, 64>(acc0);
      if (lane == 0) mbar_arrive(mb + B_EVA);
      epi_kv(acc0, xf0, wg * 2 + hf, rs[0][0], rs[0][1]);
      fence_async_smem();
      pinu(xf0);
      if (!wg) bar_arrive(7, 256);
      const uint32_t kvb = 2 * STAGE_B + (2 + (hf ^ 1)) * UNIT - sk;
      b1 = get_b();
      od1 = &P.s->obuf[(((b1 >> 4) * 4 + wg * 2 + (hf ^ 1)) * 64 + (b1 & 7)) * 128 + t128];
      ain = &P.s->obuf[((b1 >> 4) * 4 + wg * 2 + hf) * 64 * 128 + t128];
      uint32_t ka0 = sm + kvb + wid * 1024 + (lane & 7) * 128 + (((lane >> 3) ^ (lane & 7)) << 4), ka1 = sm + kvb + wid * 1024 + (t * 2 + g) * 128 + ((4 ^ (t * 2 + g)) << 4);
      uint32_t g0 = sm + sk + tid * 16, g1 = sm + sk + g * 256 + wid * 32 + t * 8;
      const uint8_t* h0 = (const uint8_t*)&P.s->kvp[(b1 & 15) * 8 * 256 + tid], *h1 = (const uint8_t*)&P.s->zp[((b1 & 15) * 8 + g) * 16] + wid * 32 + t * 8;
      asm volatile("" : "+r"(ka0), "+r"(ka1), "+r"(g0), "+r"(g1), "+l"(h0), "+l"(h1), "+l"(od1));
      if (wg) {
        float ka[36];
        auto mma_kv = [&](uint32_t tile, int i, int acc) {
          const uint32_t o = (sk >> 4) + tile * 512 + i * 128;
          wgmma_n72_ss<1, 1, 0>(ka, dsc<1024, 1>(dlo(sb, 8192) + o), dsc<1024, 1>(dlo(sb + STAGE_B, OFF_STATS - STAGE_B) + o * (1u - (1u << 16))), acc);
        };
#pragma unroll
        for (int i = 0; i < 36; i++) ka[i] = 0.f;
        mbar_wait(mb + B_LATE, 0);
        bar_sync(6, 256);
        wg_fence();
#pragma unroll
        for (int i = 0; i < 4; i++) {
          mma_kv(2, i, i); mma_kv(3, i, 1); mma_kv(hf ^ 1, i, 1);
#pragma unroll
          for (int j = 2 * i; j < 2 * i + 2; j++)
            wgmma_n64_rs<1, 64>(acc0, xf0[j * 4], xf0[j * 4 + 1], xf0[j * 4 + 2], xf0[j * 4 + 3], dsc<1024, 1>(WD + (sk >> 4) + (j >> 2) * ST + (j & 3) * 128), 1);
        }
        const int kq = (b1 & 15) * 8 + (b1 >> 4);
        uint4* dst = &P.s->kvp[kq * 256 + warp * 64 + lane];
        uint32_t* dz = (uint32_t*)&P.s->zp[kq * 16] + warp * 16 + g + t * 8;
        asm volatile("" : "+l"(dst), "+l"(dz));
        bar_sync(7, 256);
#pragma unroll
        for (int i = 0; i < 4; i++) mma_kv(hf, i, 1);
        wg_commit();
        bar_arrive(8, 256);
        wg_wait<0>();
        pin(ka); pinr<64, 96>(acc0);
        uint32_t kw[8];
#pragma unroll
        for (int i = 0; i < 8; i++) {
          const int j = (i & 3) * 4 + (i >> 2) * 2;
          asm("{\n.reg .pred p;\nsetp.ne.u32 p, %5, 0;\n@p cvt.rn.bf16x2.f32 %0, %4, %3;\n@!p cvt.rn.bf16x2.f32 %0, %2, %1;\n}"
              : "=r"(kw[i]) : "f"(ka[j]), "f"(ka[j + 1]), "f"(ka[16 + j]), "f"(ka[17 + j]), "r"(warp & 2));
        }
        st_rlx4(dst, make_uint4(kw[0], kw[1], kw[2], kw[3]));
        st_rlx4(dst + 32, make_uint4(kw[4], kw[5], kw[6], kw[7]));
        if (t < 2) st_rlx(dz, __float_as_uint(t ? ka[34] : ka[32]));
        if (lane == 0) mbar_arrive(mb + B_EVB);
        const uint32_t t1 = clock64();
        while ((uint32_t)clock64() - t1 < SDELAY) {}
      } else {
        bar_sync(8, 256);
        wg_fence();
        mma_q(acc0, xf0, xo0, false);
      }
      if (!wg) bar_sync(9, 256);
      wg_fence();
      mma_q(acc1, xf1, xo1, true);
      wg_commit();
      if (wg) { bar_arrive(9, 256); wg_wait<0>(); }
      else { wg_fence(); mma_q(acc0, xf0, xo0, true); wg_commit(); wg_wait<1>(); }
      pinr<64, 96>(acc1);
      uint32_t pq[16];
      epi_q(acc1, rs[1][0], rs[1][1], pq);
      bar_sync(11 + wg + zero_after(pq), 128);
      if (wg) {
        wg_fence();
        mma_q(acc0, xf0, xo0, true);
        wg_commit();
      }
      {
        uint4 gv[8]; uint2 gz;
        uint32_t m[8], a[4];
        float z0, z1;
        mbar_wait(mb + B_KVP, 0);
        { const float2 v = lds2f_o<UNIT>(g1); gz = make_uint2(__float_as_uint(v.x), __float_as_uint(v.y)); }
        static_for<0, 8>([&](auto sc) { constexpr int s = decltype(sc)::value; gv[s] = lds4_o<STAGE_B + s * 4096>(g0); });
#pragma unroll 1
        for (int it = 0; it < SPIN_LIMIT; it++) {
          uint32_t mm = max(gz.x, gz.y);
          z0 = __uint_as_float(gz.x); z1 = __uint_as_float(gz.y);
#pragma unroll
          for (int o = 4; o < 32; o <<= 1) { z0 += __shfl_xor_sync(~0u, z0, o); z1 += __shfl_xor_sync(~0u, z1, o); }
#pragma unroll
          for (int s = 0; s < 8; s++) m[s] = max4(0, gv[s]);
#pragma unroll
          for (int s = 0; s < 8; s += 2) mm = __vimax3_u32(mm, m[s], m[s + 1]);
          a[0] = hadd2(hadd2(hadd2(gv[0].x, gv[1].x), hadd2(gv[2].x, gv[3].x)), hadd2(hadd2(gv[4].x, gv[5].x), hadd2(gv[6].x, gv[7].x)));
          a[1] = hadd2(hadd2(hadd2(gv[0].y, gv[1].y), hadd2(gv[2].y, gv[3].y)), hadd2(hadd2(gv[4].y, gv[5].y), hadd2(gv[6].y, gv[7].y)));
          a[2] = hadd2(hadd2(hadd2(gv[0].z, gv[1].z), hadd2(gv[2].z, gv[3].z)), hadd2(hadd2(gv[4].z, gv[5].z), hadd2(gv[6].z, gv[7].z)));
          a[3] = hadd2(hadd2(hadd2(gv[0].w, gv[1].w), hadd2(gv[2].w, gv[3].w)), hadd2(hadd2(gv[4].w, gv[5].w), hadd2(gv[6].w, gv[7].w)));
          pinu(a);
          if (!__any_sync(~0u, mm == SENT)) break;
          gz = ld_rlx2(h1);
#pragma unroll
          for (int s = 0; s < 8; s++) if (m[s] == SENT) gv[s] = ld_rlx4(h0 + s * 4096);
        }
        wg_wait<0>();
        pinr<64, 96>(acc0);
        if (lane == 0) mbar_arrive(mb + B_KVB);
        stsm4(ka0, a[0], a[1], a[2], a[3]);
        const uint32_t zz = pack2(g ? z1 : z0, g ? z1 : z0);
        if (lane < 8) sts4(ka1, zz, zz, zz, zz);
        fence_async_smem();
        bar_sync(1, 256);
      }
      auto make_o = [&](uint4 (&o)[4], auto first) {
        float oa[2][20];
        wg_fence();
#pragma unroll
        for (int ks = 0; ks < 4; ks++)
          wgmma_n40_rs<1, 0>(oa[ks >> 1], pq[ks * 4], pq[ks * 4 + 1], pq[ks * 4 + 2], pq[ks * 4 + 3], dsc<1024, 1>(dlo(sb, 8192) + (kvb >> 4) + ks * 128), ks & 1);
        wg_commit();
        if constexpr (!decltype(first)::value) {
          pinu(xf0);
#pragma unroll
          for (int q = 0; q < 32; q++) { acc[q * 2] = bf_lo(xf0[q]); acc[q * 2 + 1] = bf_hi(xf0[q]); }
          pin(acc);
          mbar_wait(mb + B_BF, 0);
        }
        wg_wait<0>();
        pin(oa[0]); pin(oa[1]);
        if (decltype(first)::value && lane < 2) mbar_arrive_rem(eb);
#pragma unroll
        for (int h = 0; h < 2; h++) {
          const float (&d)[20] = oa[h];
          const float i0 = rcp(d[16] + 1e-6f), i1 = rcp(d[18] + 1e-6f);
#pragma unroll
          for (int k2 = 0; k2 < 2; k2++) {
            o[h * 2 + k2] = make_uint4(pack2(d[k2 * 8] * i0, d[k2 * 8 + 1] * i0), pack2(d[k2 * 8 + 2] * i1, d[k2 * 8 + 3] * i1),
                                       pack2(d[k2 * 8 + 4] * i0, d[k2 * 8 + 5] * i0), pack2(d[k2 * 8 + 6] * i1, d[k2 * 8 + 7] * i1));
            if (decltype(first)::value && !h && !k2) { st_rlx4(od1, o[0]); sched_fence(); }
          }
        }
      };
      make_o(ost[1], std::true_type{});
      st_rlx4(od1 + 1024 + ((ost[1][2].x | ost[1][3].w) & blockIdx.y), ost[1][1]);
      sched_fence();
      auto read1 = [&](uint32_t z) {
        mbar_wait(mb + B_F15 + z, 1);
#pragma unroll
        for (int i = 0; i < 4; i++) abuf[1][i] = ld_rlx4(ain + i * 128);
      };
      {
        const float rl0 = rs[0][0] * 1.44269511f, rl1 = rs[0][1] * 1.44269511f;
        const uint32_t q0 = dup2(rs[0][0]), q1 = dup2(rs[0][1]);
        uint32_t z = 0;
#pragma unroll
        for (int j = 0; j < 8; j++) {
          pq[j * 2] = phi2(acc0[64 + j * 4], acc0[65 + j * 4], rl0, q0); pq[j * 2 + 1] = phi2(acc0[66 + j * 4], acc0[67 + j * 4], rl1, q1);
          if (j < R1MID) z |= pq[j * 2] | pq[j * 2 + 1];
          if (j == R1MID - 1) read1(z & 0x80008000u);
        }
      }
      make_o(ost[0], std::false_type{});
    }
   {
    IDS(b1);
    const int mb3 = rb * 4 + wg * 2 + hf;
    uint4* rp = &P.s->st2[mb3 * 64 + warp * 16 + g + t * 8];
    {
      uint4* const od0 = &P.s->obuf[(mb3 * 64 + 32 + s3 * 4) * 128 + t128];
#pragma unroll
      for (int i = 0; i < 4; i++) pin4(ost[0][i]);
      wg_fence();
#pragma unroll
      for (int k = 0; k < 4; k++) wgmma_n128_rs<1, 0>(acc, ost[0][k].x, ost[0][k].y, ost[0][k].z, ost[0][k].w, dsc<1024, 1>(dlo(sb + 4 * UNIT, 8192) + k * 128), 1);
      wg_commit();
      st_rlx4(od1 + 2048, ost[1][2]); st_rlx4(od1 + 3072, ost[1][3]);
      uint32_t la = sm + t128 * 16, ev = eb + 8;
      asm volatile("" : "+r"(la), "+r"(ev));
      auto fetch = [&](uint32_t off, uint4 (&a)[4]) { const uint32_t ra = la + off; a[0] = lds4_o<0>(ra); a[1] = lds4_o<2048>(ra); a[2] = lds4_o<4096>(ra); a[3] = lds4_o<6144>(ra); };
      auto check = [&](int p, uint4 (&a)[4]) {
        if (__any_sync(~0u, max(max4(max4(0, a[0]), a[1]), max4(max4(0, a[2]), a[3])) == SENT)) {
          int pl = p; asm volatile("" : "+r"(pl));
          const uint4* q = ain + frag_of(pl);
#pragma unroll 1
          for (int it = 0;; it++) {
            uint32_t mm = 0;
#pragma unroll
            for (int i = 0; i < 4; i++) { const uint32_t m = max4(0, a[i]); mm = max(mm, m); if (m == SENT) a[i] = ld_rlx4(q + i * 128); }
            if (!__any_sync(~0u, mm == SENT)) break;
            SPINCHK(it);
          }
        }
        if (lane < 2) mbar_arrive_rem(ev);
        ev = (ev & ~0x38u) | ((ev + 8) & 0x38u);
      };
      auto mma = [&](int p, uint32_t bs, uint4 (&a)[4]) {
#pragma unroll
        for (int i = 0; i < 4; i++) pin4(a[i]);
        wg_fence();
#pragma unroll
        for (int k = 0; k < 4; k++) wgmma_n128_rs<1, 0>(acc, a[k].x, a[k].y, a[k].z, a[k].w, dsc<1024, 1>(bs + k * 128), 1);
        wg_commit();
      };
      uint32_t ta = sm + OFF_STATS + wg * 256 + 48;
      mbar_wait(mb + B_WR, 0);
      uint4 tp = lds4(ta);
      mbar_wait(mb + B_BF + 8, 0);
      check(1, abuf[1]);
      mbar_wait(mb + B_BF + 16, 0);
      fetch(ring_of(2, wg), abuf[2]);
      mma(1, dlo(sb + 11 * UNIT, 8192), abuf[1]);
      st_rlx4(od0, ost[0][0]); st_rlx4(od0 + 128, ost[0][1]);
      check(2, abuf[2]);
      mbar_wait(mb + B_BF + 24, 0);
      fetch(ring_of(3, wg), abuf[0]);
      mma(2, dlo(sb + 18 * UNIT, 8192), abuf[2]);
      st_rlx4(od0 + 256, ost[0][2]); st_rlx4(od0 + 384, ost[0][3]);
      wg_wait<2>();
      check(3, abuf[0]);
      mbar_wait(mb + B_BF + 32, 0);
#pragma unroll 1
      for (int p = 3; p < 15; p += 3) {
        static_for<0, 3>([&](auto jc) {
          constexpr int j = decltype(jc)::value;
          const uint4 tc = tp;
          const uint32_t bs = __shfl_sync(~0u, tc.x, 0);
          wg_wait<1>();
#pragma unroll
          for (int i = 0; i < 4; i++) pin4(abuf[(j + 1) % 3][i]);
          tp = lds4_o<16 * j + 16>(ta);
          fetch(tc.y, abuf[(j + 1) % 3]);
          mma(p + j, bs, abuf[j]);
          check(p + j + 1, abuf[(j + 1) % 3]);
          mbar_wait(tc.z, tc.w);
        });
        ta += 48;
      }
      {
        const uint32_t wa0 = sm + OFF_COLSUM + ((g & 1) ? t * 64 : 256);
        wb[0] = lds4_o<0>(wa0); wb[1] = lds4_o<16>(wa0); wb[2] = lds4_o<32>(wa0); wb[3] = lds4_o<48>(wa0);
      }
      mma(15, __shfl_sync(~0u, tp.x, 0), abuf[0]);
      wg_wait<2>();
      if (lane == 0) mbar_arrive(mb + B_E16);
      asm volatile("" : "+l"(rp));
      sched_fence();
      wg_wait<0>();
      pin(acc);
#pragma unroll
      for (int i = 0; i < 4; i++) { pin4(abuf[0][i]); pin4(abuf[1][i]); pin4(abuf[2][i]); }
    }
    {
      float q0[2] = {0.f, 0.f}, q1[2] = {0.f, 0.f}, c[2][4] = {};
#pragma unroll
      for (int j = 0; j < 16; j++) {
        hp[j * 2] = pack2(acc[j * 4], acc[j * 4 + 1]); hp[j * 2 + 1] = pack2(acc[j * 4 + 2], acc[j * 4 + 3]);
        q0[j & 1] = fmaf(acc[j * 4], acc[j * 4], fmaf(acc[j * 4 + 1], acc[j * 4 + 1], q0[j & 1]));
        q1[j & 1] = fmaf(acc[j * 4 + 2], acc[j * 4 + 2], fmaf(acc[j * 4 + 3], acc[j * 4 + 3], q1[j & 1]));
        if (j & 1) {
          const uint32_t a[4] = {hp[j * 2 - 2], hp[j * 2 - 1], hp[j * 2], hp[j * 2 + 1]};
          mma16816(c[(j >> 1) & 1], a, (j & 2) ? wb[j >> 2].z : wb[j >> 2].x, (j & 2) ? wb[j >> 2].w : wb[j >> 2].y);
        }
      }
      const bool od = t & 1;
      float q = (od ? q1[0] + q1[1] : q0[0] + q0[1]) + __shfl_xor_sync(~0u, od ? q0[0] + q0[1] : q1[0] + q1[1], 1);
      q += __shfl_xor_sync(~0u, q, 2);
      asm volatile("{\n.reg .pred p;\nsetp.lt.u32 p, %5, 2;\n@p red.relaxed.gpu.global.add.v4.f32 [%0], {%1,%2,%3,%4};\n}"
                   :: "l"(rp), "f"(od ? c[0][2] + c[1][2] : c[0][0] + c[1][0]), "f"(q), "f"(od ? c[0][3] + c[1][3] : c[0][1] + c[1][1]), "f"(1.f), "r"(t) : "memory");
    }
    const uint32_t ts = clock64();
    const uint32_t msc = sm + OFF_STATS;
    const uint32_t hst = sm + 4 * UNIT + wg * STAGE_B + warp * 4096, gslot = sm + unit_of(rank ? GT1 : GT0, wid);
    bar_sync(1, 256);
#pragma unroll
    for (int j = 0; j < 8; j++)
      stsm4(hst + (lane & 15) * 256 + (((2 * j + (lane >> 4)) ^ (lane & 7)) << 4), hp[j * 4], hp[j * 4 + 1], hp[j * 4 + 2], hp[j * 4 + 3]);
    uint32_t wa[8][4][4], wd[8][2][4];
    const uint32_t a0 = gslot + ((lane >> 4) * 8 + (lane & 7)) * 64 + ((((lane >> 3) & 1) ^ ((lane >> 1) & 3)) << 4);
    auto load_gu = [&](auto ic) { constexpr int i = decltype(ic)::value; ldsm4t_o<(i >> 2) * 1024 + ((i >> 1) & 1) * 8192>(a0 ^ ((i & 1) << 5), wa[i >> 2][i & 3]); };
    uint32_t tx;
    {
      const int row = rb * 256 + tid;
      const uint4* sp = &P.s->st2[row], *sq = &P.s->st2[row ^ 256];
      const float sw = __uint_as_float((lds1(mb + B_SW) & ~255u) | 128);
      uint4 v[2];
      uint4* d = &P.s->hsel[c3 * 128 + (g & 3) * 32 + ((rb & 6) + (lane >> 4)) * 4 + t];
      uint32_t* dk = &P.s->cand[c3 * 32 + (rb & 6) + (lane >> 4)];
      asm volatile("" : "+l"(d), "+l"(dk));
      if (fidx >= 0) mbar_wait(mb + B_FFN, 0);
      static_for<0, GU1>(load_gu);
      while ((uint32_t)clock64() - ts < SDEL2) {}
      v[0] = ld_rlx4(sp); v[1] = ld_rlx4(sq);
      static_for<GU1, GU2>(load_gu);
#pragma unroll 1
      for (int it = 0; __any_sync(~0u, min(v[0].w, v[1].w) != 0x41000000u) && it < SPIN_LIMIT; it++) {
        if (v[0].w != 0x41000000u) v[0] = ld_rlx4(sp);
        if (v[1].w != 0x41000000u) v[1] = ld_rlx4(sq);
      }
      if (lane == 0) mbar_arrive(mb + B_EVA);
      uint32_t k[2];
#pragma unroll
      for (int i = 0; i < 2; i++) {
        const float mean = __uint_as_float(v[i].x) * (1.f / D_);
        const float rstd = rsq(fmaxf(fmaf(-mean, mean, __uint_as_float(v[i].y) * (1.f / D_)), 0.f) + 1e-5f);
        const uint32_t u = __float_as_uint(rstd * fmaf(-mean, sw, __uint_as_float(v[i].z)));
        k[i] = min(((u ^ ((uint32_t)((int)u >> 31) | 0x80000000u)) & ~2047u), 0xFFFFF000u) | (2047 - (row ^ (i << 8)));
        if (i == 0 && (warp >> 1) == hf) sts2f(sm + OFF_LNP + (wg * 64 + (tid & 63)) * 8, rstd, -mean * rstd);
      }
      const uint32_t hi = max(k[0], k[1]);
      uint32_t m1 = __reduce_max_sync(~0u, hi), m2 = __reduce_max_sync(~0u, hi == m1 ? min(k[0], k[1]) : hi);
      if (lane == 0) sts2f(msc + wid * 8, __uint_as_float(m1), __uint_as_float(m2));
      bar_sync(1, 256);
      const uint32_t kk = lds1(msc + (lane & 15) * 4);
      m1 = __reduce_max_sync(~0u, kk); m2 = __reduce_max_sync(~0u, kk == m1 ? 0 : kk);
      const int c0 = 2047 - (m1 & 2047), c1 = 2047 - (m2 & 2047);
      if ((c0 >> 4) == mb3 * 4 + warp || (c1 >> 4) == mb3 * 4 + warp) {
        const int ra = (lane & 4) ? c1 : c0, rd = (lane & 16) ? c1 : c0;
        uint32_t h0, h1, h2, h3;
        ldsm4_o<0>(hst + (ra & 15) * 256 + ((((lane & 3) * 4 + (lane >> 3)) ^ (ra & 7)) << 4), h0, h1, h2, h3);
        const float2 pr = lds2f(sm + OFF_LNP + (wid * 16 + (rd & 15)) * 8);
        if ((rd >> 4) == mb3 * 4 + warp) {
          const uint4 xn = make_uint4(pack2(fmaf(bf_lo(h0), pr.x, pr.y), fmaf(bf_hi(h0), pr.x, pr.y)), pack2(fmaf(bf_lo(h1), pr.x, pr.y), fmaf(bf_hi(h1), pr.x, pr.y)),
                                      pack2(fmaf(bf_lo(h2), pr.x, pr.y), fmaf(bf_hi(h2), pr.x, pr.y)), pack2(fmaf(bf_lo(h3), pr.x, pr.y), fmaf(bf_hi(h3), pr.x, pr.y)));
          st_rlx4(d, xn);
          if (!(lane & 15)) st_rlx(dk, (lane & 16) ? m2 : m1);
          st_rlx4(d + 1024, make_uint4(h0, h1, h2, h3));
        }
      }
      tx = clock64();
      if (tid == 0) { sts2f(msc + 64, __uint_as_float(m1), __uint_as_float(m2)); mbar_arrive(mb + B_OUT); }
    }
    static_for<GU2, 32>(load_gu);
    const uint32_t dl = sm + (wid & 1) * 4096 + ((lane >> 4) * 8 + (lane & 7)) * 128 + ((((lane >> 3) & 1) ^ (lane & 7)) << 4);
    uint32_t da = dl + unit_of(DT0, wid >> 1), db = dl + unit_of(rank ? DT1 : DT0, 4 + (wid >> 1));
    uint32_t* yp = (uint32_t*)&P.s->ybuf[((wid * 8 + t * 2) * NFFN + fidx) * 2] + g;
    uint32_t k1, k2;
    uint2 key;
    uint32_t pl = sm + unit_of(rank ? GT1 : GT0, g) + (g & 1) * 64 + wid * 64 + t * 16, pa = msc + 128 + wid * 16 + ((t & 1) * 2 + (lane >> 4)) * 4 + (t >> 1) * 2;
    {
      float gu[2][4][4];
      uint4 xb[4];
      uint32_t m[4];
      const uint4* xp = &P.s->hsel[wid * 128 + lane];
      const uint2* kp = (const uint2*)&P.s->cand[wid * 32] + t;
      uint32_t ps = gslot + (wid & 1) * 64 + g * 32;
      asm volatile("" : "+l"(xp), "+l"(kp), "+l"(yp), "+r"(db), "+r"(ps), "+r"(pl), "+r"(pa));
      if (fidx >= 0) mbar_wait(mb + B_FFD, 0);
      static_for<0, 8>([&](auto ic) { constexpr int i = decltype(ic)::value; ldsm4t_o<(i & 1) * 2048>(da ^ ((i >> 1) << 5), wd[i >> 1][i & 1]); });
      while ((uint32_t)clock64() - tx < XDELAY) {}
      key = ld_rlx2(kp);
#pragma unroll
      for (int i = 0; i < 4; i++) xb[i] = ld_rlx4(xp + i * 32);
      if (fidx >= 0) mbar_wait(mb + B_KVP, 1);
#pragma unroll 1
      for (int it = 0; it < SPIN_LIMIT; it++) {
#pragma unroll
        for (int i = 0; i < 4; i++) m[i] = max4(0, xb[i]);
        if (!__any_sync(~0u, __vimax3_u32(__vimax3_u32(max(key.x, key.y), m[0], m[1]), m[2], m[3]) == SENT)) break;
        key = ld_rlx2(kp);
#pragma unroll
        for (int i = 0; i < 4; i++) if (m[i] == SENT) xb[i] = ld_rlx4(xp + i * 32);
      }
      const uint32_t hi = max(key.x, key.y);
      k1 = __reduce_max_sync(~0u, hi); k2 = __reduce_max_sync(~0u, hi == k1 ? min(key.x, key.y) : hi);
#pragma unroll
      for (int i = 0; i < 32; i++) gu[i >> 4][(i >> 2) & 3][i & 3] = 0.f;
#pragma unroll
      for (int ks = 0; ks < 8; ks++) {
#pragma unroll
        for (int i = 0; i < 4; i++) mma16816(gu[ks & 1][i], wa[ks][i], (ks & 1) ? xb[ks >> 1].z : xb[ks >> 1].x, (ks & 1) ? xb[ks >> 1].w : xb[ks >> 1].y);
        if (ks == 1) {
          const uint32_t dd = db | (__float_as_uint(gu[1][3][0]) & blockIdx.y);
          static_for<0, 8>([&](auto ic) { constexpr int i = decltype(ic)::value; ldsm4t_o<(i & 1) * 2048>(dd ^ ((i >> 1) << 5), wd[4 + (i >> 1)][i & 1]); });
          xb[3].z |= (wd[4][0][0] | wd[4][1][0] | wd[5][0][0] | wd[5][1][0] | wd[6][0][0] | wd[6][1][0] | wd[7][0][0] | wd[7][1][0]) & blockIdx.y;
        }
      }
#pragma unroll
      for (int c = 0; c < 2; c++) {
        const uint32_t kc = c ? key.y : key.x;
        float o[8];
#pragma unroll
        for (int j = 0; j < 8; j++) o[j] = gu[0][(j >> 2) + (j & 1) * 2][(j & 2) + c] + gu[1][(j >> 2) + (j & 1) * 2][(j & 2) + c];
        asm volatile("{\n.reg .pred p;\nsetp.ge.u32 p, %9, %10;\n@p st.shared.v4.f32 [%0], {%1,%2,%3,%4};\n@p st.shared.v4.f32 [%0+16], {%5,%6,%7,%8};\n}"
                     :: "r"(ps + (kc == k1 ? 0 : 256)), "f"(o[0]), "f"(o[1]), "f"(o[2]), "f"(o[3]), "f"(o[4]), "f"(o[5]), "f"(o[6]), "f"(o[7]), "r"(kc), "r"(k2) : "memory");
      }
    }
    bar_sync(1, 256);
    {
      const uint4 pv = lds4(pl);
      const bool hi = lane & 16;
      float ga = __uint_as_float(hi ? pv.z : pv.x) + __shfl_xor_sync(~0u, __uint_as_float(hi ? pv.x : pv.z), 16);
      float up = __uint_as_float(hi ? pv.w : pv.y) + __shfl_xor_sync(~0u, __uint_as_float(hi ? pv.y : pv.w), 16);
      ga += __shfl_xor_sync(~0u, ga, 8); up += __shfl_xor_sync(~0u, up, 8);
      ga += __shfl_xor_sync(~0u, ga, 4); up += __shfl_xor_sync(~0u, up, 4);
      asm volatile("st.shared.u16 [%0], %1;" :: "r"(pa), "h"((uint16_t)pack2(ga * rcp(1.f + ex2(-1.4426950408889634f * ga)) * up, 0.f)) : "memory");
      bar_sync(1, 256);
      const uint4 bv = lds4(msc + 128 + (lane & 7) * 16);
      const uint32_t bq[4] = {bv.x, bv.y, bv.z, bv.w};
      float ya[8][4];
#pragma unroll
      for (int i = 0; i < 8; i++) { ya[i][0] = 0.f; ya[i][1] = 0.f; ya[i][2] = 0.f; ya[i][3] = 0.f; }
#pragma unroll
      for (int ks = 0; ks < 2; ks++)
#pragma unroll
        for (int i = 0; i < 8; i++) mma16816(ya[i], wd[i][ks], bq[ks * 2], bq[ks * 2 + 1]);
#pragma unroll
      for (int h = 0; h < 2; h++) {
        float o[4];
#pragma unroll
        for (int j = 0; j < 4; j++) o[j] = t == 0 ? ya[h * 4][j] : t == 1 ? ya[h * 4 + 1][j] : t == 2 ? ya[h * 4 + 2][j] : ya[h * 4 + 3][j];
        asm volatile("{\n.reg .pred p;\nsetp.ge.s32 p, %3, 0;\n@p st.relaxed.gpu.global.u32 [%0], %1;\n@p st.relaxed.gpu.global.u32 [%0+%4], %2;\n}"
                     :: "l"(yp + h * (64 * NFFN * 8)), "r"(pack2(o[0], o[1])), "r"(pack2(o[2], o[3])), "r"(fidx), "n"(NFFN * 32) : "memory");
      }
    }
    if (tid == 0) { sts2f(msc + 80, __uint_as_float(k1), __uint_as_float(k2)); mbar_arrive(mb + B_SEL); }
    const uint32_t ty = clock64();
    if (wid == 0) {
      const uint32_t* yq = (const uint32_t*)&P.s->ybuf[b * NFFN * 2] + t * 8 + g;
      const uint32_t ks = (t & 1) ? k2 : k1, grp = 3 - ((ks >> 9) & 3);
      const int fs = grp * 2 + (__shfl_sync(~0u, key.y, grp) == ks);
      const uint32_t* fq = (const uint32_t*)P.s->hsel + (((b >> 4) * 4 + ((b >> 2) & 3)) * 32 + fs * 4 + (g >> 1)) * 4 + (b & 3);
      float gate = rcp(1.f + ex2(-1.4426950408889634f * __uint_as_float(ks ^ (~(uint32_t)((int)ks >> 31) | 0x80000000u))));
      __nv_bfloat16* op = P.out + (size_t)(2047 - (ks & 2047)) * D_ + b * 8 + g;
      uint32_t sel = (g & 2) ? 0x3F800000u : 0x00003F80u;
      uint32_t fn = ld_rlx(fq), fh = ld_rlx(fq + 4096), v[7][4];
      uint32_t m[7];
#pragma unroll
      for (int i = 0; i < 7; i++) { m[i] = ~blockIdx.y; asm volatile("" : "=r"(v[i][0]), "=r"(v[i][1]), "=r"(v[i][2]), "=r"(v[i][3]), "+r"(m[i])); }
      asm volatile("" : "+l"(yq), "+l"(op), "+f"(gate), "+r"(sel));
      while ((uint32_t)clock64() - ty < YDELAY) {}
      float y[2][4];
#pragma unroll 1
      for (int it = 0; it < SPIN_LIMIT; it++) {
        static_for<0, 7>([&](auto ic) { constexpr int i = decltype(ic)::value;
          asm volatile("{\n.reg .pred p;\nsetp.eq.u32 p, %5, 0xFFFFFFFF;\n@p ld.relaxed.gpu.global.u32 %0, [%4+%6];\n@p ld.relaxed.gpu.global.u32 %1, [%4+%6+128];\n"
                       "@p ld.relaxed.gpu.global.u32 %2, [%4+%6+256];\n@p ld.relaxed.gpu.global.u32 %3, [%4+%6+384];\n}"
                       : "+r"(v[i][0]), "+r"(v[i][1]), "+r"(v[i][2]), "+r"(v[i][3]) : "l"(yq), "r"(m[i]), "n"(i * 512) : "memory"); });
        uint32_t mm = max(fn, fh);
        if (mm == SENT) { fn = ld_rlx(fq); fh = ld_rlx(fq + 4096); }
#pragma unroll
        for (int i = 0; i < 8; i++) y[i >> 2][i & 3] = 0.f;
#pragma unroll
        for (int i = 0; i < 7; i++) { m[i] = __vimax3_u32(max(v[i][0], v[i][1]), v[i][2], v[i][3]); mm = max(mm, m[i]); mma16816(y[i & 1], v[i], sel, sel); }
        pin(y[0]); pin(y[1]);
        if (!__any_sync(~0u, mm == SENT)) break;
      }
      const float base = (g & 1) ? bf_hi(fh) + bf_hi(fn) : bf_lo(fh) + bf_lo(fn);
      if (t < 2) *op = __float2bfloat16(fmaf((y[0][0] + y[1][0]) + (y[0][2] + y[1][2]), gate, base));
      if (b == 0 && lane == 0) P.s->epoch = lds1(mb + B_SW) & 255;
    }
   }
  }
}

typedef CUresult (*EncodeFn)(CUtensorMap*, CUtensorMapDataType, cuuint32_t, void*, const cuuint64_t*, const cuuint64_t*, const cuuint32_t*,
                             const cuuint32_t*, CUtensorMapInterleave, CUtensorMapSwizzle, CUtensorMapL2promotion, CUtensorMapFloatOOBfill);
void make_map(EncodeFn enc, CUtensorMap* m, const void* p, int rank, std::initializer_list<cuuint64_t> dims, std::initializer_list<cuuint64_t> str,
              std::initializer_list<cuuint32_t> box, CUtensorMapSwizzle sw) {
  const cuuint32_t es[4] = {1, 1, 1, 1};
  enc(m, CU_TENSOR_MAP_DATA_TYPE_BFLOAT16, rank, const_cast<void*>(p), dims.begin(), str.begin(), box.begin(), es, CU_TENSOR_MAP_INTERLEAVE_NONE, sw,
      CU_TENSOR_MAP_L2_PROMOTION_L2_128B, CU_TENSOR_MAP_FLOAT_OOB_FILL_NONE);
}

}

extern "C" void kernel_launch(void* const* d_in, const int* in_sizes, int n_in, void* d_out, int out_size) {
  (void)in_sizes; (void)n_in; (void)out_size;
  Ptrs P;
  P.x = (const __nv_bfloat16*)d_in[0]; P.wqkv = (const __nv_bfloat16*)d_in[1]; P.wo = (const __nv_bfloat16*)d_in[2];
  P.wr = (const __nv_bfloat16*)d_in[4]; P.wg = (const __nv_bfloat16*)d_in[5]; P.wu = (const __nv_bfloat16*)d_in[6];
  P.wd = (const __nv_bfloat16*)d_in[7]; P.out = (__nv_bfloat16*)d_out;
  cudaGetSymbolAddress((void**)&P.s, g_scratch);
  void* fn = nullptr;
  cudaDriverEntryPointQueryResult q;
  cudaGetDriverEntryPoint("cuTensorMapEncodeTiled", &fn, cudaEnableDefault, &q);
  EncodeFn enc = (EncodeFn)fn;
  Maps T;
  constexpr CUtensorMapSwizzle S128 = CU_TENSOR_MAP_SWIZZLE_128B, S64 = CU_TENSOR_MAP_SWIZZLE_64B;
  make_map(enc, &T.m[M_X], P.x, 2, {D_, S_}, {D_ * 2}, {64, 128}, S128);
  make_map(enc, &T.m[M_W], P.wqkv, 3, {D_, D_, 3}, {3 * D_ * 2, D_ * 2}, {64, 64, 2}, S128);
  make_map(enc, &T.m[M_Q], P.wqkv, 2, {3 * D_, D_}, {3 * D_ * 2}, {64, 64}, S128);
  make_map(enc, &T.m[M_O], P.wo, 4, {64, 64, 16, 16}, {D_ * 2, 64 * D_ * 2, 128}, {64, 64, 1, 2}, S128);
  make_map(enc, &T.m[M_S], P.wo, 4, {64, 64, 16, 16}, {D_ * 2, 64 * D_ * 2, 128}, {64, 16, 4, 2}, S128);
  make_map(enc, &T.m[M_G], P.wg, 3, {F_, D_, 1}, {F_ * 2, F_ * 2 * D_}, {32, 128, 1}, S64);
  make_map(enc, &T.m[M_U], P.wu, 3, {F_, D_, 1}, {F_ * 2, F_ * 2 * D_}, {32, 128, 1}, S64);
  make_map(enc, &T.m[M_D], P.wd, 3, {64, F_, 16}, {D_ * 2, 128}, {64, 32, 2}, S128);
  make_map(enc, &T.m[M_L], P.wd, 2, {64, F_ * 16}, {128}, {8, 32}, CU_TENSOR_MAP_SWIZZLE_NONE);
  cudaFuncSetAttribute(fused_kernel, cudaFuncAttributeMaxDynamicSharedMemorySize, SMEM_BYTES);
  fused_kernel<<<NCTA, 384, SMEM_BYTES>>>(P, T);
}
```

```cpp
#include <cuda_runtime.h>
#include <cuda.h>
#include <cuda_bf16.h>
#include <stdint.h>
#include <type_traits>
#include <initializer_list>

namespace {

constexpr int S_ = 2048, D_ = 1024, F_ = 3584;
constexpr int NCTA = 128, NFFN = 112;
constexpr uint32_t SENT = 0xFFFFFFFFu;
constexpr int SPIN_LIMIT = 1 << 20;

#define FD0 700
#define FD1 800
#define GDELAY 400
#define PULL0 3
#define PLAG 8
#define SDELAY 100
#define MFIRST 350
#define MKV 850
#define MO 800
#define ADELAY 200
#define ADELAY2 600
#define R1MID 5
#define SDEL2 500
#define XDELAY 500
#define YDELAY 650
#define GU1 8
#define GU2 20
#define OPACE 450
#define NAP __nanosleep(20)
constexpr uint32_t STAGE_B = 57344;
constexpr uint32_t OFF_STATS = 229376;
constexpr uint32_t OFF_COLSUM = 231424;
constexpr uint32_t OFF_BARS = 232192;
constexpr uint32_t SMEM_BYTES = 232448;
constexpr uint32_t B_FULL = 0, B_EMPTY = 32, B_E = 64, B_AUX = 128, B_EVA = 136, B_EVB = 144, B_BF = 152, B_LATE = 232, B_FFN = 240, B_SW = 248;
constexpr uint32_t B_OUT = B_FULL, B_SEL = B_FULL + 8, B_WR = B_FULL + 16, B_FFD = B_FULL + 24, B_E16 = B_EMPTY + 16, B_KVB = B_EMPTY + 8, B_DUMMY = B_SW + 4,
                   B_GATE = B_EMPTY + 24, B_ID = B_BF + 56, B_KVP = B_BF + 64, B_F15 = B_BF + 72;
constexpr uint32_t UNIT = 8192;
constexpr uint32_t sb = 1024;
constexpr uint32_t bars = sb + OFF_BARS;
constexpr uint64_t tab5(int a, int b, int c, int d, int e, int f, int g, int h, int i = 0, int j = 0) {
  return (uint64_t)a | (uint64_t)b << 5 | (uint64_t)c << 10 | (uint64_t)d << 15 | (uint64_t)e << 20 | (uint64_t)f << 25 | (uint64_t)g << 30 | (uint64_t)h << 35 |
         (uint64_t)i << 40 | (uint64_t)j << 45;
}
constexpr uint64_t BT0 = tab5(4, 11, 18, 25, 7, 9, 16, 0), BT1 = tab5(4, 11, 18, 25, 21, 23, 2, 0);
constexpr uint64_t GT0 = tab5(2, 21, 23, 18, 0, 25, 14, 7), GT1 = tab5(16, 7, 9, 18, 0, 25, 14, 21);
constexpr uint64_t DT0 = tab5(6, 13, 20, 27, 9, 10, 16, 17), DT1 = tab5(6, 13, 20, 27, 23, 24, 2, 3);
__device__ __forceinline__ uint32_t unit_of(uint64_t tab, int i) { return ((uint32_t)(tab >> (5 * i)) & 31) * UNIT; }
__device__ __forceinline__ uint32_t ring_of(int p, int w) { return (p & 1) * (2 * STAGE_B) + ((p & 2) ? 49152 + w * STAGE_B : w * UNIT); }
constexpr uint32_t OFF_LNP = OFF_STATS + 1024;

struct Scratch {
  uint4 obuf[32 * 64 * 128];
  uint4 kvp[16 * 8 * 256];
  uint4 zp[16 * 8 * 16];
  uint4 ybuf[NCTA * NFFN * 2];
  uint4 st1[64 * 48];
  uint4 csp[16 * 8 * 48];
  uint4 st2[S_];
  uint4 hsel[2 * 8 * 128];
  uint32_t cand[8 * 32];
  uint32_t when[32 * 32];
  unsigned epoch;
};
__device__ __align__(1024) Scratch g_scratch;
__device__ __forceinline__ uint32_t smem_u32(const void* p) { return (uint32_t)__cvta_generic_to_shared(p); }
__device__ __forceinline__ void mbar_init(uint32_t bar, uint32_t cnt) { asm volatile("mbarrier.init.shared::cta.b64 [%0], %1;" :: "r"(bar), "r"(cnt) : "memory"); }
__device__ __forceinline__ void mbar_expect_tx(uint32_t bar, uint32_t bytes) { asm volatile("mbarrier.arrive.expect_tx.shared::cta.b64 _, [%0], %1;" :: "r"(bar), "r"(bytes) : "memory"); }
__device__ __forceinline__ void mbar_arrive(uint32_t bar) { asm volatile("mbarrier.arrive.shared::cta.b64 _, [%0];" :: "r"(bar) : "memory"); }
#define SPINCHK(it) if ((it) > SPIN_LIMIT) break
__device__ __forceinline__ void mbar_wait(uint32_t bar, uint32_t parity) {
  asm volatile("{\n.reg .pred p;\n.reg .u32 c;\nmov.u32 c, 0;\n"
               "WL:\nmbarrier.try_wait.parity.shared::cta.b64 p, [%0], %1;\n@p bra WD;\n"
               "add.u32 c, c, 1;\nsetp.lt.u32 p, c, 1048576;\n@p bra WL;\nWD:\n}" :: "r"(bar), "r"(parity) : "memory");
}
__device__ __forceinline__ bool mbar_test(uint32_t bar, uint32_t parity) {
  uint32_t ok;
  asm volatile("{\n.reg .pred p;\nmbarrier.test_wait.parity.shared::cta.b64 p, [%1], %2;\nselp.u32 %0, 1, 0, p;\n}" : "=r"(ok) : "r"(bar), "r"(parity) : "memory");
  return ok;
}
__device__ __forceinline__ uint64_t l2_stream() { uint64_t p; asm("createpolicy.fractional.L2::evict_first.b64 %0, 1.0;" : "=l"(p)); return p; }
__device__ __forceinline__ void tma_2d(uint32_t dst, const CUtensorMap* tm, int c0, int c1, uint32_t bar, bool stream) {
  if (stream) asm volatile("cp.async.bulk.tensor.2d.shared::cluster.global.mbarrier::complete_tx::bytes.L2::cache_hint [%0], [%1, {%3, %4}], [%2], %5;"
                           :: "r"(dst), "l"(tm), "r"(bar), "r"(c0), "r"(c1), "l"(l2_stream()) : "memory");
  else asm volatile("cp.async.bulk.tensor.2d.shared::cluster.global.mbarrier::complete_tx::bytes [%0], [%1, {%3, %4}], [%2];"
                    :: "r"(dst), "l"(tm), "r"(bar), "r"(c0), "r"(c1) : "memory");
}
__device__ __forceinline__ void tma_3d(uint32_t dst, const CUtensorMap* tm, int c0, int c1, int c2, uint32_t bar, bool stream) {
  if (stream) asm volatile("cp.async.bulk.tensor.3d.shared::cluster.global.mbarrier::complete_tx::bytes.L2::cache_hint [%0], [%1, {%3, %4, %5}], [%2], %6;"
                           :: "r"(dst), "l"(tm), "r"(bar), "r"(c0), "r"(c1), "r"(c2), "l"(l2_stream()) : "memory");
  else asm volatile("cp.async.bulk.tensor.3d.shared::cluster.global.mbarrier::complete_tx::bytes [%0], [%1, {%3, %4, %5}], [%2];"
                    :: "r"(dst), "l"(tm), "r"(bar), "r"(c0), "r"(c1), "r"(c2) : "memory");
}
__device__ __forceinline__ void tma_4d(uint32_t dst, const CUtensorMap* tm, int c0, int c1, int c2, int c3, uint32_t bar) {
  asm volatile("cp.async.bulk.tensor.4d.shared::cluster.global.mbarrier::complete_tx::bytes.L2::cache_hint [%0], [%1, {%3, %4, %5, %6}], [%2], %7;"
               :: "r"(dst), "l"(tm), "r"(bar), "r"(c0), "r"(c1), "r"(c2), "r"(c3), "l"(l2_stream()) : "memory");
}
__device__ __forceinline__ void tma_2d_mc(uint32_t dst, const CUtensorMap* tm, int c0, int c1, uint32_t bar, bool stream) {
  if (stream) asm volatile("cp.async.bulk.tensor.2d.shared::cluster.global.mbarrier::complete_tx::bytes.multicast::cluster.L2::cache_hint [%0], [%1, {%3, %4}], [%2], %5, %6;"
                           :: "r"(dst), "l"(tm), "r"(bar), "r"(c0), "r"(c1), "h"((uint16_t)3), "l"(l2_stream()) : "memory");
  else asm volatile("cp.async.bulk.tensor.2d.shared::cluster.global.mbarrier::complete_tx::bytes.multicast::cluster [%0], [%1, {%3, %4}], [%2], %5;"
                    :: "r"(dst), "l"(tm), "r"(bar), "r"(c0), "r"(c1), "h"((uint16_t)3) : "memory");
}
__device__ __forceinline__ bool elect_one() {
  uint32_t p;
  asm volatile("{\n.reg .pred q;\nelect.sync _|q, 0xFFFFFFFF;\nselp.u32 %0, 1, 0, q;\n}" : "=r"(p));
  return p;
}
__device__ __forceinline__ void bulk_load_mc(uint32_t dst, const void* src, uint32_t bytes, uint32_t bar) {
  asm volatile("cp.async.bulk.shared::cluster.global.mbarrier::complete_tx::bytes.multicast::cluster [%0], [%1], %2, [%3], %4;"
               :: "r"(dst), "l"(src), "r"(bytes), "r"(bar), "h"((uint16_t)3) : "memory");
}
__device__ __forceinline__ void bulk_load(uint32_t dst, const void* src, uint32_t bytes, uint32_t bar) {
  asm volatile("cp.async.bulk.shared::cluster.global.mbarrier::complete_tx::bytes [%0], [%1], %2, [%3];" :: "r"(dst), "l"(src), "r"(bytes), "r"(bar) : "memory");
}
__device__ __forceinline__ void bulk_store(void* dst, uint32_t src, uint32_t bytes) {
  asm volatile("cp.async.bulk.global.shared::cta.bulk_group [%0], [%1], %2;" :: "l"(dst), "r"(src), "r"(bytes) : "memory");
}
__device__ __forceinline__ void mbar_arrive_rem(uint32_t bar) { asm volatile("mbarrier.arrive.shared::cluster.b64 _, [%0];" :: "r"(bar) : "memory"); }
template <uint32_t O> __device__ __forceinline__ void ldsm4_o(uint32_t addr, uint32_t& a, uint32_t& b, uint32_t& c, uint32_t& d) {
  asm volatile("ldmatrix.sync.aligned.m8n8.x4.shared.b16 {%0,%1,%2,%3}, [%4+%5];" : "=r"(a), "=r"(b), "=r"(c), "=r"(d) : "r"(addr), "n"(O) : "memory");
}
template <uint32_t O> __device__ __forceinline__ void ldsm4t_o(uint32_t addr, uint32_t (&r)[4]) {
  asm volatile("ldmatrix.sync.aligned.m8n8.x4.trans.shared.b16 {%0,%1,%2,%3}, [%4+%5];" : "=r"(r[0]), "=r"(r[1]), "=r"(r[2]), "=r"(r[3]) : "r"(addr), "n"(O) : "memory");
}
__device__ __forceinline__ void mma16816(float (&c)[4], const uint32_t (&a)[4], uint32_t b0, uint32_t b1) {
  asm("mma.sync.aligned.m16n8k16.row.col.f32.bf16.bf16.f32 {%0,%1,%2,%3}, {%4,%5,%6,%7}, {%8,%9}, {%0,%1,%2,%3};"
      : "+f"(c[0]), "+f"(c[1]), "+f"(c[2]), "+f"(c[3]) : "r"(a[0]), "r"(a[1]), "r"(a[2]), "r"(a[3]), "r"(b0), "r"(b1));
}
__device__ __forceinline__ void l2_prefetch(const void* p) { asm volatile("prefetch.global.L2 [%0];" :: "l"(p) : "memory"); }
__device__ __forceinline__ void tmap_prefetch(const CUtensorMap* tm) { asm volatile("prefetch.tensormap [%0];" :: "l"(tm) : "memory"); }
__device__ __forceinline__ void wg_fence() { asm volatile("wgmma.fence.sync.aligned;" ::: "memory"); }
__device__ __forceinline__ void wg_commit() { asm volatile("wgmma.commit_group.sync.aligned;" ::: "memory"); }
template <int N> __device__ __forceinline__ void wg_wait() { asm volatile("wgmma.wait_group.sync.aligned %0;" :: "n"(N) : "memory"); }
template <int N> __device__ __forceinline__ void pin(float (&d)[N]) {
#pragma unroll
  for (int i = 0; i < N; i++) asm volatile("" : "+f"(d[i]) :: "memory");
}
__device__ __forceinline__ void pin4(uint4& v) { asm volatile("" : "+r"(v.x), "+r"(v.y), "+r"(v.z), "+r"(v.w) :: "memory"); }
template <uint32_t SBO, uint32_t SWZ> __device__ __forceinline__ uint64_t dsc(uint32_t lo) { return ((uint64_t)((SBO >> 4) | (SWZ << 30)) << 32) | lo; }
__host__ __device__ constexpr uint32_t dlo(uint32_t addr, uint32_t lbo) { return (addr >> 4) | ((lbo >> 4) << 16); }
__device__ __forceinline__ void bar_sync(int id, int n) { asm volatile("bar.sync %0, %1;" :: "r"(id), "r"(n) : "memory"); }
__device__ __forceinline__ void bar_arrive(int id, int n) { asm volatile("bar.arrive %0, %1;" :: "r"(id), "r"(n) : "memory"); }
__device__ __forceinline__ void fence_async_smem() { asm volatile("fence.proxy.async.shared::cta;" ::: "memory"); }
__device__ __forceinline__ void fence_gpu() { asm volatile("fence.acq_rel.gpu;" ::: "memory"); }
__device__ __forceinline__ uint4 ld_cg4(const void* p) { uint4 v; asm volatile("ld.global.cg.v4.u32 {%0,%1,%2,%3}, [%4];" : "=r"(v.x), "=r"(v.y), "=r"(v.z), "=r"(v.w) : "l"(p) : "memory"); return v; }
__device__ __forceinline__ uint4 ld_rlx4(const void* p) { uint4 v; asm volatile("ld.relaxed.gpu.global.v4.u32 {%0,%1,%2,%3}, [%4];" : "=r"(v.x), "=r"(v.y), "=r"(v.z), "=r"(v.w) : "l"(p) : "memory"); return v; }
__device__ __forceinline__ uint32_t ld_rlx(const void* p) { uint32_t v; asm volatile("ld.relaxed.gpu.global.u32 %0, [%1];" : "=r"(v) : "l"(p) : "memory"); return v; }
__device__ __forceinline__ void st_rlx4(void* p, uint4 v) { asm volatile("st.relaxed.gpu.global.v4.u32 [%0], {%1,%2,%3,%4};" :: "l"(p), "r"(v.x), "r"(v.y), "r"(v.z), "r"(v.w) : "memory"); }
__device__ __forceinline__ void st_rlx2(void* p, uint32_t a, uint32_t b) { asm volatile("st.relaxed.gpu.global.v2.u32 [%0], {%1,%2};" :: "l"(p), "r"(a), "r"(b) : "memory"); }
__device__ __forceinline__ void st_rlx(void* p, uint32_t a) { asm volatile("st.relaxed.gpu.global.u32 [%0], %1;" :: "l"(p), "r"(a) : "memory"); }
__device__ __forceinline__ uint32_t pack2(float lo, float hi) { uint32_t r; asm("cvt.rn.bf16x2.f32 %0, %1, %2;" : "=r"(r) : "f"(hi), "f"(lo)); return r; }
__device__ __forceinline__ float bf_lo(uint32_t v) { return __uint_as_float(v << 16); }
__device__ __forceinline__ float bf_hi(uint32_t v) { return __uint_as_float(v & 0xFFFF0000u); }
__device__ __forceinline__ void stsm4(uint32_t addr, uint32_t a, uint32_t b, uint32_t c, uint32_t d) {
  asm volatile("stmatrix.sync.aligned.m8n8.x4.shared.b16 [%0], {%1,%2,%3,%4};" :: "r"(addr), "r"(a), "r"(b), "r"(c), "r"(d) : "memory");
}
template <uint32_t O> __device__ __forceinline__ void stsm4_o(uint32_t addr, uint32_t a, uint32_t b, uint32_t c, uint32_t d) {
  asm volatile("stmatrix.sync.aligned.m8n8.x4.shared.b16 [%0+%5], {%1,%2,%3,%4};" :: "r"(addr), "r"(a), "r"(b), "r"(c), "r"(d), "n"(O) : "memory");
}
__device__ __forceinline__ void sts4(uint32_t addr, uint32_t a, uint32_t b, uint32_t c, uint32_t d) { asm volatile("st.shared.v4.u32 [%0], {%1,%2,%3,%4};" :: "r"(addr), "r"(a), "r"(b), "r"(c), "r"(d) : "memory"); }
__device__ __forceinline__ void sts2f(uint32_t addr, float a, float b) { asm volatile("st.shared.v2.f32 [%0], {%1,%2};" :: "r"(addr), "f"(a), "f"(b) : "memory"); }
__device__ __forceinline__ void sts1(uint32_t addr, uint32_t a) { asm volatile("st.shared.u32 [%0], %1;" :: "r"(addr), "r"(a) : "memory"); }
__device__ __forceinline__ float2 lds2f(uint32_t addr) { float2 v; asm volatile("ld.shared.v2.f32 {%0,%1}, [%2];" : "=f"(v.x), "=f"(v.y) : "r"(addr) : "memory"); return v; }
template <uint32_t O> __device__ __forceinline__ float2 lds2f_o(uint32_t addr) { float2 v; asm volatile("ld.shared.v2.f32 {%0,%1}, [%2+%3];" : "=f"(v.x), "=f"(v.y) : "r"(addr), "n"(O) : "memory"); return v; }
template <int I, int N, class F> __device__ __forceinline__ void static_for(F&& f) { if constexpr (I < N) { f(std::integral_constant<int, I>{}); static_for<I + 1, N>(f); } }
__device__ __forceinline__ uint4 lds4(uint32_t addr) { uint4 v; asm volatile("ld.shared.v4.u32 {%0,%1,%2,%3}, [%4];" : "=r"(v.x), "=r"(v.y), "=r"(v.z), "=r"(v.w) : "r"(addr) : "memory"); return v; }
__device__ __forceinline__ uint32_t lds1(uint32_t addr) { uint32_t v; asm volatile("ld.shared.u32 %0, [%1];" : "=r"(v) : "r"(addr) : "memory"); return v; }
__device__ __forceinline__ float ex2(float x) { float y; asm("ex2.approx.ftz.f32 %0, %1;" : "=f"(y) : "f"(x)); return y; }
__device__ __forceinline__ uint32_t max4(uint32_t m, const uint4& v) { return __vimax3_u32(__vimax3_u32(m, v.x, v.y), v.z, v.w); }
__device__ __forceinline__ float rsq(float x) { float y; asm("rsqrt.approx.ftz.f32 %0, %1;" : "=f"(y) : "f"(x)); return y; }
__device__ __forceinline__ float rcp(float x) { float y; asm("rcp.approx.ftz.f32 %0, %1;" : "=f"(y) : "f"(x)); return y; }
__device__ __forceinline__ uint2 ld_rlx2(const void* p) { uint2 v; asm volatile("ld.relaxed.gpu.global.v2.u32 {%0,%1}, [%2];" : "=r"(v.x), "=r"(v.y) : "l"(p) : "memory"); return v; }
template <uint32_t O> __device__ __forceinline__ uint4 lds4_o(uint32_t addr) { uint4 v; asm volatile("ld.shared.v4.u32 {%0,%1,%2,%3}, [%4+%5];" : "=r"(v.x), "=r"(v.y), "=r"(v.z), "=r"(v.w) : "r"(addr), "n"(O) : "memory"); return v; }
__device__ __forceinline__ uint32_t phi2(float u0, float u1, float rl, uint32_t r2) {
  uint32_t pu, r;
  asm("cvt.rn.relu.bf16x2.f32 %0, %1, %2;" : "=r"(pu) : "f"(u1), "f"(u0));
  asm("fma.rn.bf16x2 %0, %1, %2, %3;" : "=r"(r) : "r"(pu), "r"(r2), "r"(pack2(__saturatef(ex2(u0 * rl) + 1e-6f), __saturatef(ex2(u1 * rl) + 1e-6f))));
  return r;
}
__device__ __forceinline__ uint32_t dup2(float r) { uint32_t v; asm("cvt.rn.relu.bf16x2.f32 %0, %1, %1;" : "=r"(v) : "f"(r)); return v; }
__device__ __forceinline__ uint32_t zero_after(const uint32_t (&v)[16]) {
  uint32_t z = 0;
#pragma unroll
  for (int i = 0; i < 16; i++) z |= v[i];
  return z & 0x80008000u;
}
__device__ __forceinline__ uint32_t hadd2(uint32_t a, uint32_t b) { uint32_t v; asm("add.rn.bf16x2 %0, %1, %2;" : "=r"(v) : "r"(a), "r"(b)); return v; }
__device__ __forceinline__ void sched_fence() { asm volatile("{\n.reg .pred p;\n.reg .u64 c;\nSF:\nmov.u64 c, %clock64;\nsetp.eq.u64 p, c, 0;\n@p bra SF;\n}" ::: "memory"); }
__device__ __forceinline__ uint32_t now_ns() { uint32_t v; asm volatile("mov.u32 %0, %%globaltimer_lo;" : "=r"(v) :: "memory"); return v; }
__device__ __forceinline__ void meet(uint32_t* mine, const uint4* all, int first, int after, uint32_t bar) {
  const uint32_t t0 = now_ns() & ~1u;
  if ((threadIdx.x & 31) == 0) st_rlx(mine, t0);
  while ((int)(now_ns() - t0) < first) NAP;
  uint4 v;
#pragma unroll 1
  for (int it = 0; it < SPIN_LIMIT; it++) { v = ld_rlx4(all); if (!__any_sync(~0u, max4(0, v) == SENT)) break; }
  const int d = min(__reduce_max_sync(~0u, max(max((int)(v.x - t0), (int)(v.y - t0)), max((int)(v.z - t0), (int)(v.w - t0)))), 100000) + after;
  mbar_wait(bar, 0);
  while ((int)(now_ns() - t0) < d) NAP;
}
__device__ __forceinline__ uint32_t hmul2(uint32_t a, uint32_t b) { uint32_t v; asm("mul.rn.bf16x2 %0, %1, %2;" : "=r"(v) : "r"(a), "r"(b)); return v; }
__device__ __forceinline__ uint32_t lane_id() { uint32_t v; asm volatile("mov.u32 %0, %%laneid;" : "=r"(v)); return v; }
template <int A, int B, int N> __device__ __forceinline__ void pinr(float (&d)[N]) {
#pragma unroll
  for (int i = A; i < B; i++) asm volatile("" : "+f"(d[i]) :: "memory");
}
template <int N> __device__ __forceinline__ void pinu(uint32_t (&d)[N]) {
#pragma unroll
  for (int i = 0; i < N; i++) asm volatile("" : "+r"(d[i]) :: "memory");
}

template<int TA, int TB, int OFF, int SZ> __device__ __forceinline__ void wgmma_n192_ss(float (&d)[SZ], uint64_t da, uint64_t db, int scale_d) {
  asm volatile("{\n.reg .pred p;\nsetp.ne.b32 p, %98, 0;\n"
    "wgmma.mma_async.sync.aligned.m64n192k16.f32.bf16.bf16 {%0,%1,%2,%3,%4,%5,%6,%7,%8,%9,%10,%11,%12,%13,%14,%15,%16,%17,%18,%19,%20,%21,%22,%23,%24,%25,%26,%27,%28,%29,%30,%31,%32,%33,%34,%35,%36,%37,%38,%39,%40,%41,%42,%43,%44,%45,%46,%47,%48,%49,%50,%51,%52,%53,%54,%55,%56,%57,%58,%59,%60,%61,%62,%63,%64,%65,%66,%67,%68,%69,%70,%71,%72,%73,%74,%75,%76,%77,%78,%79,%80,%81,%82,%83,%84,%85,%86,%87,%88,%89,%90,%91,%92,%93,%94,%95}, %96, %97, p, 1, 1, %99, %100;\n}\n"
    : "+f"(d[OFF+0]), "+f"(d[OFF+1]), "+f"(d[OFF+2]), "+f"(d[OFF+3]), "+f"(d[OFF+4]), "+f"(d[OFF+5]), "+f"(d[OFF+6]), "+f"(d[OFF+7]),
      "+f"(d[OFF+8]), "+f"(d[OFF+9]), "+f"(d[OFF+10]), "+f"(d[OFF+11]), "+f"(d[OFF+12]), "+f"(d[OFF+13]), "+f"(d[OFF+14]), "+f"(d[OFF+15]),
      "+f"(d[OFF+16]), "+f"(d[OFF+17]), "+f"(d[OFF+18]), "+f"(d[OFF+19]), "+f"(d[OFF+20]), "+f"(d[OFF+21]), "+f"(d[OFF+22]), "+f"(d[OFF+23]),
      "+f"(d[OFF+24]), "+f"(d[OFF+25]), "+f"(d[OFF+26]), "+f"(d[OFF+27]), "+f"(d[OFF+28]), "+f"(d[OFF+29]), "+f"(d[OFF+30]), "+f"(d[OFF+31]),
      "+f"(d[OFF+32]), "+f"(d[OFF+33]), "+f"(d[OFF+34]), "+f"(d[OFF+35]), "+f"(d[OFF+36]), "+f"(d[OFF+37]), "+f"(d[OFF+38]), "+f"(d[OFF+39]),
      "+f"(d[OFF+40]), "+f"(d[OFF+41]), "+f"(d[OFF+42]), "+f"(d[OFF+43]), "+f"(d[OFF+44]), "+f"(d[OFF+45]), "+f"(d[OFF+46]), "+f"(d[OFF+47]),
      "+f"(d[OFF+48]), "+f"(d[OFF+49]), "+f"(d[OFF+50]), "+f"(d[OFF+51]), "+f"(d[OFF+52]), "+f"(d[OFF+53]), "+f"(d[OFF+54]), "+f"(d[OFF+55]),
      "+f"(d[OFF+56]), "+f"(d[OFF+57]), "+f"(d[OFF+58]), "+f"(d[OFF+59]), "+f"(d[OFF+60]), "+f"(d[OFF+61]), "+f"(d[OFF+62]), "+f"(d[OFF+63]),
      "+f"(d[OFF+64]), "+f"(d[OFF+65]), "+f"(d[OFF+66]), "+f"(d[OFF+67]), "+f"(d[OFF+68]), "+f"(d[OFF+69]), "+f"(d[OFF+70]), "+f"(d[OFF+71]),
      "+f"(d[OFF+72]), "+f"(d[OFF+73]), "+f"(d[OFF+74]), "+f"(d[OFF+75]), "+f"(d[OFF+76]), "+f"(d[OFF+77]), "+f"(d[OFF+78]), "+f"(d[OFF+79]),
      "+f"(d[OFF+80]), "+f"(d[OFF+81]), "+f"(d[OFF+82]), "+f"(d[OFF+83]), "+f"(d[OFF+84]), "+f"(d[OFF+85]), "+f"(d[OFF+86]), "+f"(d[OFF+87]),
      "+f"(d[OFF+88]), "+f"(d[OFF+89]), "+f"(d[OFF+90]), "+f"(d[OFF+91]), "+f"(d[OFF+92]), "+f"(d[OFF+93]), "+f"(d[OFF+94]), "+f"(d[OFF+95])
    : "l"(da), "l"(db), "r"(scale_d), "n"(TA), "n"(TB));
}
template<int TA, int TB, int OFF, int SZ> __device__ __forceinline__ void wgmma_n128_ss(float (&d)[SZ], uint64_t da, uint64_t db, int scale_d) {
  asm volatile("{\n.reg .pred p;\nsetp.ne.b32 p, %66, 0;\n"
    "wgmma.mma_async.sync.aligned.m64n128k16.f32.bf16.bf16 {%0,%1,%2,%3,%4,%5,%6,%7,%8,%9,%10,%11,%12,%13,%14,%15,%16,%17,%18,%19,%20,%21,%22,%23,%24,%25,%26,%27,%28,%29,%30,%31,%32,%33,%34,%35,%36,%37,%38,%39,%40,%41,%42,%43,%44,%45,%46,%47,%48,%49,%50,%51,%52,%53,%54,%55,%56,%57,%58,%59,%60,%61,%62,%63}, %64, %65, p, 1, 1, %67, %68;\n}\n"
    : "+f"(d[OFF+0]), "+f"(d[OFF+1]), "+f"(d[OFF+2]), "+f"(d[OFF+3]), "+f"(d[OFF+4]), "+f"(d[OFF+5]), "+f"(d[OFF+6]), "+f"(d[OFF+7]),
      "+f"(d[OFF+8]), "+f"(d[OFF+9]), "+f"(d[OFF+10]), "+f"(d[OFF+11]), "+f"(d[OFF+12]), "+f"(d[OFF+13]), "+f"(d[OFF+14]), "+f"(d[OFF+15]),
      "+f"(d[OFF+16]), "+f"(d[OFF+17]), "+f"(d[OFF+18]), "+f"(d[OFF+19]), "+f"(d[OFF+20]), "+f"(d[OFF+21]), "+f"(d[OFF+22]), "+f"(d[OFF+23]),
      "+f"(d[OFF+24]), "+f"(d[OFF+25]), "+f"(d[OFF+26]), "+f"(d[OFF+27]), "+f"(d[OFF+28]), "+f"(d[OFF+29]), "+f"(d[OFF+30]), "+f"(d[OFF+31]),
      "+f"(d[OFF+32]), "+f"(d[OFF+33]), "+f"(d[OFF+34]), "+f"(d[OFF+35]), "+f"(d[OFF+36]), "+f"(d[OFF+37]), "+f"(d[OFF+38]), "+f"(d[OFF+39]),
      "+f"(d[OFF+40]), "+f"(d[OFF+41]), "+f"(d[OFF+42]), "+f"(d[OFF+43]), "+f"(d[OFF+44]), "+f"(d[OFF+45]), "+f"(d[OFF+46]), "+f"(d[OFF+47]),
      "+f"(d[OFF+48]), "+f"(d[OFF+49]), "+f"(d[OFF+50]), "+f"(d[OFF+51]), "+f"(d[OFF+52]), "+f"(d[OFF+53]), "+f"(d[OFF+54]), "+f"(d[OFF+55]),
      "+f"(d[OFF+56]), "+f"(d[OFF+57]), "+f"(d[OFF+58]), "+f"(d[OFF+59]), "+f"(d[OFF+60]), "+f"(d[OFF+61]), "+f"(d[OFF+62]), "+f"(d[OFF+63])
    : "l"(da), "l"(db), "r"(scale_d), "n"(TA), "n"(TB));
}
template<int TA, int TB, int OFF, int SZ> __device__ __forceinline__ void wgmma_n64_ss(float (&d)[SZ], uint64_t da, uint64_t db, int scale_d) {
  asm volatile("{\n.reg .pred p;\nsetp.ne.b32 p, %34, 0;\n"
    "wgmma.mma_async.sync.aligned.m64n64k16.f32.bf16.bf16 {%0,%1,%2,%3,%4,%5,%6,%7,%8,%9,%10,%11,%12,%13,%14,%15,%16,%17,%18,%19,%20,%21,%22,%23,%24,%25,%26,%27,%28,%29,%30,%31}, %32, %33, p, 1, 1, %35, %36;\n}\n"
    : "+f"(d[OFF+0]), "+f"(d[OFF+1]), "+f"(d[OFF+2]), "+f"(d[OFF+3]), "+f"(d[OFF+4]), "+f"(d[OFF+5]), "+f"(d[OFF+6]), "+f"(d[OFF+7]),
      "+f"(d[OFF+8]), "+f"(d[OFF+9]), "+f"(d[OFF+10]), "+f"(d[OFF+11]), "+f"(d[OFF+12]), "+f"(d[OFF+13]), "+f"(d[OFF+14]), "+f"(d[OFF+15]),
      "+f"(d[OFF+16]), "+f"(d[OFF+17]), "+f"(d[OFF+18]), "+f"(d[OFF+19]), "+f"(d[OFF+20]), "+f"(d[OFF+21]), "+f"(d[OFF+22]), "+f"(d[OFF+23]),
      "+f"(d[OFF+24]), "+f"(d[OFF+25]), "+f"(d[OFF+26]), "+f"(d[OFF+27]), "+f"(d[OFF+28]), "+f"(d[OFF+29]), "+f"(d[OFF+30]), "+f"(d[OFF+31])
    : "l"(da), "l"(db), "r"(scale_d), "n"(TA), "n"(TB));
}
template<int TA, int TB, int OFF, int SZ> __device__ __forceinline__ void wgmma_n72_ss(float (&d)[SZ], uint64_t da, uint64_t db, int scale_d) {
  asm volatile("{\n.reg .pred p;\nsetp.ne.b32 p, %38, 0;\n"
    "wgmma.mma_async.sync.aligned.m64n72k16.f32.bf16.bf16 {%0,%1,%2,%3,%4,%5,%6,%7,%8,%9,%10,%11,%12,%13,%14,%15,%16,%17,%18,%19,%20,%21,%22,%23,%24,%25,%26,%27,%28,%29,%30,%31,%32,%33,%34,%35}, %36, %37, p, 1, 1, %39, %40;\n}\n"
    : "+f"(d[OFF+0]), "+f"(d[OFF+1]), "+f"(d[OFF+2]), "+f"(d[OFF+3]), "+f"(d[OFF+4]), "+f"(d[OFF+5]), "+f"(d[OFF+6]), "+f"(d[OFF+7]),
      "+f"(d[OFF+8]), "+f"(d[OFF+9]), "+f"(d[OFF+10]), "+f"(d[OFF+11]), "+f"(d[OFF+12]), "+f"(d[OFF+13]), "+f"(d[OFF+14]), "+f"(d[OFF+15]),
      "+f"(d[OFF+16]), "+f"(d[OFF+17]), "+f"(d[OFF+18]), "+f"(d[OFF+19]), "+f"(d[OFF+20]), "+f"(d[OFF+21]), "+f"(d[OFF+22]), "+f"(d[OFF+23]),
      "+f"(d[OFF+24]), "+f"(d[OFF+25]), "+f"(d[OFF+26]), "+f"(d[OFF+27]), "+f"(d[OFF+28]), "+f"(d[OFF+29]), "+f"(d[OFF+30]), "+f"(d[OFF+31]),
      "+f"(d[OFF+32]), "+f"(d[OFF+33]), "+f"(d[OFF+34]), "+f"(d[OFF+35])
    : "l"(da), "l"(db), "r"(scale_d), "n"(TA), "n"(TB));
}
template<int TB, int OFF, int SZ> __device__ __forceinline__ void wgmma_n64_rs(float (&d)[SZ], uint32_t a0, uint32_t a1, uint32_t a2, uint32_t a3, uint64_t db, int scale_d) {
  asm volatile("{\n.reg .pred p;\nsetp.ne.b32 p, %37, 0;\n"
    "wgmma.mma_async.sync.aligned.m64n64k16.f32.bf16.bf16 {%0,%1,%2,%3,%4,%5,%6,%7,%8,%9,%10,%11,%12,%13,%14,%15,%16,%17,%18,%19,%20,%21,%22,%23,%24,%25,%26,%27,%28,%29,%30,%31}, {%32,%33,%34,%35}, %36, p, 1, 1, %38;\n}\n"
    : "+f"(d[OFF+0]), "+f"(d[OFF+1]), "+f"(d[OFF+2]), "+f"(d[OFF+3]), "+f"(d[OFF+4]), "+f"(d[OFF+5]), "+f"(d[OFF+6]), "+f"(d[OFF+7]),
      "+f"(d[OFF+8]), "+f"(d[OFF+9]), "+f"(d[OFF+10]), "+f"(d[OFF+11]), "+f"(d[OFF+12]), "+f"(d[OFF+13]), "+f"(d[OFF+14]), "+f"(d[OFF+15]),
      "+f"(d[OFF+16]), "+f"(d[OFF+17]), "+f"(d[OFF+18]), "+f"(d[OFF+19]), "+f"(d[OFF+20]), "+f"(d[OFF+21]), "+f"(d[OFF+22]), "+f"(d[OFF+23]),
      "+f"(d[OFF+24]), "+f"(d[OFF+25]), "+f"(d[OFF+26]), "+f"(d[OFF+27]), "+f"(d[OFF+28]), "+f"(d[OFF+29]), "+f"(d[OFF+30]), "+f"(d[OFF+31])
    : "r"(a0), "r"(a1), "r"(a2), "r"(a3), "l"(db), "r"(scale_d), "n"(TB));
}
template<int TB, int OFF, int SZ> __device__ __forceinline__ void wgmma_n40_rs(float (&d)[SZ], uint32_t a0, uint32_t a1, uint32_t a2, uint32_t a3, uint64_t db, int scale_d) {
  asm volatile("{\n.reg .pred p;\nsetp.ne.b32 p, %25, 0;\n"
    "wgmma.mma_async.sync.aligned.m64n40k16.f32.bf16.bf16 {%0,%1,%2,%3,%4,%5,%6,%7,%8,%9,%10,%11,%12,%13,%14,%15,%16,%17,%18,%19}, {%20,%21,%22,%23}, %24, p, 1, 1, %26;\n}\n"
    : "+f"(d[OFF+0]), "+f"(d[OFF+1]), "+f"(d[OFF+2]), "+f"(d[OFF+3]), "+f"(d[OFF+4]), "+f"(d[OFF+5]), "+f"(d[OFF+6]), "+f"(d[OFF+7]),
      "+f"(d[OFF+8]), "+f"(d[OFF+9]), "+f"(d[OFF+10]), "+f"(d[OFF+11]), "+f"(d[OFF+12]), "+f"(d[OFF+13]), "+f"(d[OFF+14]), "+f"(d[OFF+15]),
      "+f"(d[OFF+16]), "+f"(d[OFF+17]), "+f"(d[OFF+18]), "+f"(d[OFF+19])
    : "r"(a0), "r"(a1), "r"(a2), "r"(a3), "l"(db), "r"(scale_d), "n"(TB));
}
template<int TB, int OFF, int SZ> __device__ __forceinline__ void wgmma_n128_rs(float (&d)[SZ], uint32_t a0, uint32_t a1, uint32_t a2, uint32_t a3, uint64_t db, int scale_d) {
  asm volatile("{\n.reg .pred p;\nsetp.ne.b32 p, %69, 0;\n"
    "wgmma.mma_async.sync.aligned.m64n128k16.f32.bf16.bf16 {%0,%1,%2,%3,%4,%5,%6,%7,%8,%9,%10,%11,%12,%13,%14,%15,%16,%17,%18,%19,%20,%21,%22,%23,%24,%25,%26,%27,%28,%29,%30,%31,%32,%33,%34,%35,%36,%37,%38,%39,%40,%41,%42,%43,%44,%45,%46,%47,%48,%49,%50,%51,%52,%53,%54,%55,%56,%57,%58,%59,%60,%61,%62,%63}, {%64,%65,%66,%67}, %68, p, 1, 1, %70;\n}\n"
    : "+f"(d[OFF+0]), "+f"(d[OFF+1]), "+f"(d[OFF+2]), "+f"(d[OFF+3]), "+f"(d[OFF+4]), "+f"(d[OFF+5]), "+f"(d[OFF+6]), "+f"(d[OFF+7]),
      "+f"(d[OFF+8]), "+f"(d[OFF+9]), "+f"(d[OFF+10]), "+f"(d[OFF+11]), "+f"(d[OFF+12]), "+f"(d[OFF+13]), "+f"(d[OFF+14]), "+f"(d[OFF+15]),
      "+f"(d[OFF+16]), "+f"(d[OFF+17]), "+f"(d[OFF+18]), "+f"(d[OFF+19]), "+f"(d[OFF+20]), "+f"(d[OFF+21]), "+f"(d[OFF+22]), "+f"(d[OFF+23]),
      "+f"(d[OFF+24]), "+f"(d[OFF+25]), "+f"(d[OFF+26]), "+f"(d[OFF+27]), "+f"(d[OFF+28]), "+f"(d[OFF+29]), "+f"(d[OFF+30]), "+f"(d[OFF+31]),
      "+f"(d[OFF+32]), "+f"(d[OFF+33]), "+f"(d[OFF+34]), "+f"(d[OFF+35]), "+f"(d[OFF+36]), "+f"(d[OFF+37]), "+f"(d[OFF+38]), "+f"(d[OFF+39]),
      "+f"(d[OFF+40]), "+f"(d[OFF+41]), "+f"(d[OFF+42]), "+f"(d[OFF+43]), "+f"(d[OFF+44]), "+f"(d[OFF+45]), "+f"(d[OFF+46]), "+f"(d[OFF+47]),
      "+f"(d[OFF+48]), "+f"(d[OFF+49]), "+f"(d[OFF+50]), "+f"(d[OFF+51]), "+f"(d[OFF+52]), "+f"(d[OFF+53]), "+f"(d[OFF+54]), "+f"(d[OFF+55]),
      "+f"(d[OFF+56]), "+f"(d[OFF+57]), "+f"(d[OFF+58]), "+f"(d[OFF+59]), "+f"(d[OFF+60]), "+f"(d[OFF+61]), "+f"(d[OFF+62]), "+f"(d[OFF+63])
    : "r"(a0), "r"(a1), "r"(a2), "r"(a3), "l"(db), "r"(scale_d), "n"(TB));
}

struct Ptrs { const __nv_bfloat16 *x, *wqkv, *wo, *wr, *wg, *wu, *wd; __nv_bfloat16* out; Scratch* s; };

enum { M_X, M_W, M_Q, M_O, M_S, M_G, M_U, M_D, M_L, M_N };
struct Maps { CUtensorMap m[M_N]; };

__global__ void __cluster_dims__(2, 1, 1) __launch_bounds__(384, 1) fused_kernel(const Ptrs P, const __grid_constant__ Maps T) {
  extern __shared__ __align__(1024) uint8_t smem_raw[];
  const uint32_t rank = blockIdx.x & 1;
  uint32_t own = rank << 24;
  asm("" : "+r"(own));
  const uint32_t sm = own + sb, mb = own + bars;
  int b0;
  { const int j = blockIdx.x >> 1, u = j - 36, v = j * 2 - 8 + (max(u * 37 + 256, 0) >> 8) * (u < 0 ? 0 : 2), w = j < 4 ? j * 16 + 64 : v;
    b0 = ((w & 15) | (w & 48) << 1 | (w & 64) >> 2) + rank; }
#define IDS(B) \
  const int b = (B), rb = b >> 4, cg = b & 15, hf = cg >> 3, s3 = cg & 7, c3 = s3 ^ ((rb & 1) << 2), jp = cg >> 1, km = (~c3 & 6) << 1; \
  const int fidx = jp == rb ? -1 : b - 2 * rb - (jp > rb ? 2 : 0); \
  [[maybe_unused]] auto kcol = [&](int kb) { return (kb ^ (kb < 8 ? km & 8 : km)) * 64; }; \
  auto src_of = [&](int p) { return p == 0 ? s3 : p == 15 ? s3 ^ 1 : (((jp & 3) ^ ((p - 7) >> 1)) << 1) + ((p - 1) & 1); }; \
  [[maybe_unused]] auto frag_of = [&](int p) { return p < 9 ? (p - 1) * 512 : 4096 + src_of(p) * 512; }; \
  (void)hf; (void)fidx
  auto get_b = [&]() { return __shfl_sync(~0u, (int)lds1(mb + B_ID), 0); };
  IDS(b0);
  auto load_w = [&](uint32_t st, int kc, uint32_t bar, bool last) { tma_3d(st + 32768, &T.m[M_W], cg * 64, kc, 1, bar, last); tma_2d(st + 49152, &T.m[M_Q], cg * 64, kc, bar, last); };
  if (threadIdx.x < 256) {
    const int r = threadIdx.x >> 3, c = threadIdx.x & 7, xr = (r & 16) * 8 + (r & 15);
    const uint32_t sw = ((c ^ r) & 7) << 4;
    const __nv_bfloat16* gw = P.wqkv + (kcol(0) + r) * 3072 + cg * 64 + c * 8, *gx = P.x + (rb * 256 + xr) * D_ + kcol(0) + c * 8;
#pragma unroll
    for (int i = 0; i < 6; i++)
      asm volatile("cp.async.cg.shared.global [%0], [%1], 16;" :: "r"(sm + 32768 + i * 4096 + r * 128 + sw), "l"(gw + (i & 1) * 32 * 3072 + ((i >> 1) + 1) % 3 * 1024) : "memory");
    asm volatile("cp.async.commit_group;" ::: "memory");
#pragma unroll
    for (int i = 0; i < 8; i++) asm volatile("cp.async.cg.shared.global [%0], [%1], 16;" :: "r"(sm + i * 2048 + xr * 128 + sw), "l"(gx + i * 16 * D_) : "memory");
    asm volatile("cp.async.commit_group;" ::: "memory");
  }
  const int tid = threadIdx.x, wid = __shfl_sync(~0u, tid >> 5, 0), wg = wid >> 2, lane = lane_id();
  const uint32_t tk = clock64();
  if (wid == 8) {
    if (elect_one()) { tmap_prefetch(&T.m[M_X]); tmap_prefetch(&T.m[M_W]); tmap_prefetch(&T.m[M_Q]); }
  } else if (wid == 9) {
    if (elect_one()) {
#pragma unroll
      for (int i = 0; i < 31; i++) if (8 * i != B_ID) mbar_init(mb + 8 * i, i < 4 ? 1 : i < 8 ? 8 : i < 16 ? 16 : i == 16 ? 64 : i == 17 ? 8 : i == 18 ? 4 : 1);
      asm volatile("fence.mbarrier_init.release.cluster;" ::: "memory");
      fence_async_smem();
    }
  } else if (wid == 11) {
#pragma unroll
    for (int i = 0; i < 4; i++) sts4(sm + OFF_STATS + i * 512 + lane * 16, SENT, SENT, SENT, SENT);
    sts1(mb + B_ID, b);
    if (smem_u32(smem_raw) != sm) asm volatile("trap;");
    fence_async_smem();
  }
  __syncthreads();
  asm volatile("barrier.cluster.arrive.relaxed.aligned;\nbarrier.cluster.wait.aligned;" ::: "memory");

  if (wg == 2) {
    asm volatile("setmaxnreg.dec.sync.aligned.u32 56;");
    if (wid == 8) {
      if (elect_one()) {
#pragma unroll 1
        for (int kb = 1; kb < 15; kb++) {
          const uint32_t fb = mb + B_FULL + 8 * (kb & 3), st = sm + (kb & 3) * STAGE_B;
          const int kc = kcol(kb);
          if (kb < 4) while ((uint32_t)clock64() - tk < FD0 + kb * FD1) {}
          else mbar_wait(fb + B_EMPTY, ((kb >> 2) & 1) ^ 1);
          mbar_expect_tx(fb, STAGE_B);
          tma_2d_mc(st + rank * 16384, &T.m[M_X], kc, rb * 256 + rank * 128, fb, kb >= 12);
          load_w(st, kc, fb, kb >= 8);
          if (kb >= 8 && kb < 11) asm volatile("mbarrier.arrive.shared::cta.b64 _, [%0], %1;" :: "r"(fb + B_EMPTY), "r"(4) : "memory");
        }
        {
          const uint32_t st = sm + 3 * STAGE_B, fa = mb + B_FULL + 24, fb = mb + B_F15;
          const int kc = kcol(15);
          mbar_wait(fa, 0);
          mbar_expect_tx(fa, 32768); mbar_expect_tx(fb, 24576);
          if (rank) { mbar_wait(mb + B_EMPTY + 24, 0); tma_2d_mc(st + 16384, &T.m[M_X], kc, rb * 256 + 128, fa, true); }
          mbar_wait(mb + B_EMPTY, 1);
          tma_3d(st + 32768, &T.m[M_W], cg * 64, kc, 1, fa, true);
          if (!rank) { mbar_wait(mb + B_EMPTY + 24, 0); tma_2d_mc(st, &T.m[M_X], kc, rb * 256, fb, true); }
          tma_2d(st + 49152, &T.m[M_Q], cg * 64, kc, fb, true);
        }
        mbar_expect_tx(mb + B_KVP, 32768 + 2048);
      }
      __syncwarp();
      const uint4* kp = &P.s->kvp[cg * 8 * 256], *zq = &P.s->zp[cg * 8 * 16], *src = &P.s->obuf[(rb * 4 + rank * 2 + hf) * 64 * 128];
      asm volatile("" : "+l"(kp), "+l"(zq), "+l"(src));
      mbar_wait(mb + B_EVA, 0);
      meet(&P.s->when[cg * 32 + rb], (const uint4*)&P.s->when[cg * 32] + (lane & 1), MFIRST, MKV, mb + B_EVB);
      if (elect_one()) {
        bulk_load(sm + rank * (2 * STAGE_B) + STAGE_B, kp, 32768, mb + B_KVP);
        bulk_load(sm + rank * (2 * STAGE_B) + UNIT, zq, 2048, mb + B_KVP);
      }
      mbar_wait(mb + B_KVP, 0);
      meet(&P.s->when[(16 + rb * 2 + hf) * 32 + s3], (const uint4*)&P.s->when[(16 + rb * 2 + (hf ^ 1)) * 32] + (lane & 1), MFIRST, MO, mb + B_E);
      if (elect_one()) {
        const uint32_t t0 = clock64();
        mbar_arrive(mb + B_F15);
#pragma unroll
        for (int p = 2; p < 5; p++) {
          if (p < 4) while ((uint32_t)clock64() - t0 < (p == 2 ? ADELAY : ADELAY2)) NAP;
          bulk_load_mc(sm + ring_of(p, rank), src + (p - 1) * 512, UNIT, mb + B_BF + 8 * p);
        }
#pragma unroll 1
        for (int p = 5; p < 15; p++) {
          uint32_t dst = sm + ring_of(p, rank), bar = mb + B_BF + 8 * (p % 7);
          const uint4* q = src + frag_of(p);
          asm volatile("" : "+r"(dst), "+r"(bar), "+l"(q));
          mbar_wait(mb + B_E + 8 * ((p - 4) & 7), p >= 12);
          bulk_load_mc(dst, q, UNIT, bar);
        }
        asm volatile("mbarrier.arrive.shared::cta.b64 _, [%0], 8;" :: "r"(mb + B_GATE) : "memory");
        const uint4* s15 = &P.s->obuf[(rb * 4 + hf) * 64 * 128 + frag_of(15)];
        mbar_wait(mb + B_E + 24, 1);
        bulk_load(sm + ring_of(15, 0), s15, UNIT, mb + B_BF + 8); bulk_load(sm + ring_of(15, 1), s15 + 2 * 64 * 128, UNIT, mb + B_BF + 8);
      }
    } else if (wid == 11) {
      IDS(get_b());
      if (fidx >= 0) {
        const uint32_t o = (rank * 32 + lane) * (F_ * 2) + (fidx >> 1) * 128;
        const char* q0 = (const char*)P.wg + o, *q1 = (const char*)P.wu + o;
        mbar_wait(mb + B_FULL + 24, 0);
        mbar_wait(mb + B_FULL + 8 * (PULL0 & 3), PULL0 >> 2);
#pragma unroll 1
        for (int r = 0; r < 16; r++, q0 += 64 * F_ * 2, q1 += 64 * F_ * 2) {
          if (mbar_test(mb + B_F15, 0)) { l2_prefetch(q0); l2_prefetch(q1); continue; }
          asm volatile("cp.async.ca.shared.global.L2::128B [%0], [%1], 4;\ncp.async.commit_group;\ncp.async.wait_group %3;\n"
                       "cp.async.ca.shared.global.L2::128B [%0], [%2], 4;\ncp.async.commit_group;\ncp.async.wait_group %3;" :: "r"(mb + B_DUMMY), "l"(q0), "l"(q1), "n"(2) : "memory");
        }
        mbar_wait(mb + B_F15, 0);
        bar_sync(15, 288);
        q0 = (const char*)P.wd + fidx * 65536 + lane * 128;
        const uint32_t bar = mb + B_BF + 48;
        if (lane == 0) mbar_expect_tx(bar, 8192);
#pragma unroll 1
        for (int i = 0; i < 16 + PLAG; i++) {
          if (i < 16) l2_prefetch(q0 + i * 4096);
          if (i >= PLAG && elect_one()) tma_2d(sm + OFF_COLSUM, &T.m[M_L], 0, fidx * 512 + (i - PLAG) * 32, bar, false);
        }
        mbar_wait(bar, 0);
        __syncwarp();
        if (lane == 0) { mbar_arrive(bar); }
        asm volatile("cp.async.wait_all;" ::: "memory");
      } else bar_sync(15, 288);
      bar_arrive(14, 64);
    } else {
      const uint32_t eb = (lane << 24) + bars + B_EMPTY;
      float c[6];
      if (wid == 10) {
        float sx[4] = {0.f, 0.f, 0.f, 0.f}, qx[4] = {0.f, 0.f, 0.f, 0.f};
        const uint32_t xa = sm + ((hf * 4 + (cg & 3)) * 32 + lane) * 128 + ((lane & 7) << 4);
#pragma unroll 1
        for (int kb = 0; kb < 8; kb++) {
          uint4 xv[8];
          const uint32_t so = xa + (kb & 3) * STAGE_B;
          mbar_wait(mb + B_FULL + 8 * (kb & 3), kb >> 2);
#pragma unroll
          for (int i = 0; i < 8; i++) xv[i] = lds4(so ^ (i << 4));
#pragma unroll
          for (int i = 0; i < 8; i++) {
            const uint32_t e[4] = {xv[i].x, xv[i].y, xv[i].z, xv[i].w};
#pragma unroll
            for (int j = 0; j < 4; j++) {
              const float d0 = bf_lo(e[j]), d1 = bf_hi(e[j]);
              sx[j] += d0 + d1; qx[j] = fmaf(d0, d0, fmaf(d1, d1, qx[j]));
            }
          }
          __syncwarp();
          if (lane < 2) mbar_arrive_rem(eb + 8 * (kb & 3));
          if (kb == 4) {
        {
          const uint32_t ep = ld_rlx(&P.s->epoch);
          float s = 0.f;
#pragma unroll
          for (int i = 0; i < 4; i++) {
            const uint4 v = ld_cg4((const uint4*)P.wr + lane + i * 32);
            s += (bf_lo(v.x) + bf_hi(v.x)) + (bf_lo(v.y) + bf_hi(v.y)) + (bf_lo(v.z) + bf_hi(v.z)) + (bf_lo(v.w) + bf_hi(v.w));
          }
#pragma unroll
          for (int o = 16; o; o >>= 1) s += __shfl_xor_sync(~0u, s, o);
          if (lane == 0) sts1(mb + B_SW, (__float_as_uint(s) & ~255u) | ((ep + 1) & 255));
        }
        asm volatile("cp.async.bulk.wait_group 0;\nfence.proxy.async.global;" ::: "memory");
        fence_gpu();
          }
          if (kb == 1) {
        if (elect_one()) {
#pragma unroll 1
          for (int i = 0; i < 16; i++) bulk_store(&P.s->obuf[((rb * 4 + (i >> 2)) * 64 + (((i >> 2) & 1) == hf ? 32 + s3 * 4 + (i & 3) : (i & 3) * 8 + s3)) * 128], sm + OFF_STATS, 2048);
          bulk_store(&P.s->kvp[(cg * 8 + rb) * 256], sm + OFF_STATS, 2048); bulk_store(&P.s->kvp[(cg * 8 + rb) * 256 + 128], sm + OFF_STATS, 2048);
          bulk_store(&P.s->zp[(cg * 8 + rb) * 16], sm + OFF_STATS, 256);
          if (s3 == 0) bulk_store(&P.s->when[(16 + rb * 2 + hf) * 32], sm + OFF_STATS, 128);
          if (rb == 0) bulk_store(&P.s->when[cg * 32], sm + OFF_STATS, 128);
          asm volatile("cp.async.bulk.commit_group;" ::: "memory");
          #pragma unroll
          for (int i = M_O; i < M_N; i++) tmap_prefetch(&T.m[i]);
        }
        __syncwarp();
          }
        }
        c[0] = ((sx[0] + sx[1]) + (sx[2] + sx[3])) * (2.f / D_);
        c[1] = fmaxf(fmaf(-c[0], c[0], ((qx[0] + qx[1]) + (qx[2] + qx[3])) * (2.f / D_)), 0.f);
      } else {
        float a[12];
#pragma unroll
        for (int i = 0; i < 12; i++) a[i] = 0.f;
        const int r2 = lane >> 4, c16 = lane & 15;
        const uint32_t a0 = sm + 32768 + (rb >> 1) * 2048 + r2 * 128 + (((c16 >> 1) ^ r2) << 4) + (c16 & 1) * 8;
#pragma unroll 1
        for (int it = 0; it < 16; it++) {
          uint2 w[12];
          const int s = (it >> 1) & 3;
          const uint32_t so = a0 + s * STAGE_B + (it & 1) * 1024;
          if (!(it & 1)) { mbar_wait(mb + B_FULL + 8 * s, it >> 3); }
          static_for<0, 12>([&](auto ic) { constexpr int i = decltype(ic)::value;
            const float2 v = lds2f_o<(i >> 2) * 8192 + (i & 3) * 256>(so ^ ((i & 3) << 5)); w[i] = make_uint2(__float_as_uint(v.x), __float_as_uint(v.y)); });
#pragma unroll
          for (int i = 0; i < 12; i++) { float* q = a + (i >> 2) * 4; q[0] += bf_lo(w[i].x); q[1] += bf_hi(w[i].x); q[2] += bf_lo(w[i].y); q[3] += bf_hi(w[i].y); }
          __syncwarp();
          if (lane < 2 && (it & 1)) mbar_arrive_rem(eb + 8 * s);
        }
#pragma unroll
        for (int i = 0; i < 6; i++) {
          const int o = (i >> 1) * 4 + (i & 1);
          c[i] = (r2 ? a[o + 2] : a[o]) + __shfl_xor_sync(~0u, r2 ? a[o] : a[o + 2], 16);
        }
      }
      bar_sync(10, 64);
      {
        const uint32_t tag = lds1(mb + B_SW) & 255;
        auto tagged = [&](float v) { return ((__float_as_uint(v) + 128) & ~255u) | tag; };
        if (wid == 9) {
#pragma unroll
          for (int sg = 0; sg < 3; sg++) {
            st_rlx2((uint2*)&P.s->csp[(cg * 8 + rb) * 48] + sg * 32 + (lane & 15) * 2 + (lane >> 4), tagged(c[sg * 2]), tagged(c[sg * 2 + 1]));
          }
        } else st_rlx2((uint2*)&P.s->st1[(rb * 8 + hf * 4 + (cg & 3)) * 48 + lane] + ((cg >> 2) & 1), tagged(c[0]), tagged(c[1]));
        __nanosleep(GDELAY);
#pragma unroll 1
        for (int h = wid - 9; h < 2; h++) {
          const int q = h * 24 + min(lane, 23);
          const uint4* gp = wid == 10 ? &P.s->st1[rb * 8 * 48 + lane] : &P.s->csp[cg * 8 * 48 + q];
          uint4 v[8];
#pragma unroll 1
          for (int it = 0;; it++) {
            uint32_t x = 0;
#pragma unroll
            for (int i = 0; i < 8; i++) v[i] = ld_rlx4(gp + i * 48);
#pragma unroll
            for (int i = 0; i < 8; i++) { v[i].x ^= tag; v[i].y ^= tag; v[i].z ^= tag; v[i].w ^= tag; x |= v[i].x | v[i].y | v[i].z | v[i].w; }
            if (!__any_sync(~0u, (x & 255) != 0)) break;
            SPINCHK(it);
          }
          if (wid == 10) {
#pragma unroll
            for (int i = 0; i < 8; i++) {
              const float m0 = __uint_as_float(v[i].x), m1 = __uint_as_float(v[i].z), dm = 0.5f * (m0 - m1);
              sts2f(sm + OFF_STATS + (i * 32 + lane) * 8, -0.5f * (m0 + m1), rsq(fmaf(dm, dm, 0.5f * (__uint_as_float(v[i].y) + __uint_as_float(v[i].w))) + 1e-5f));
            }
          } else {
            float s4[4] = {0.f, 0.f, 0.f, 0.f};
#pragma unroll
            for (int i = 0; i < 8; i++) { s4[0] += __uint_as_float(v[i].x); s4[1] += __uint_as_float(v[i].y); s4[2] += __uint_as_float(v[i].z); s4[3] += __uint_as_float(v[i].w); }
            sts4(sm + OFF_COLSUM + q * 16, __float_as_uint(s4[0]), __float_as_uint(s4[1]), __float_as_uint(s4[2]), __float_as_uint(s4[3]));
          }
        }
        mbar_arrive(mb + B_AUX);
      }
      IDS(get_b());
      const uint64_t btab = rank ? BT1 : BT0;
      if (wid == 9) {
        {
          const uint4 sv = make_uint4(SENT, SENT, SENT, SENT);
          uint4* y = &P.s->ybuf[b * NFFN * 2 + lane];
#pragma unroll
          for (int i = 0; i < 7; i++) y[i * 32] = sv;
          if (lane < 16) P.s->st2[b * 16 + lane] = make_uint4(0, 0, 0, 0); else P.s->hsel[b * 16 + lane - 16] = sv;
          if (b < 8) P.s->cand[b * 32 + lane] = SENT;
          fence_gpu();
          bar_sync(0, 288);
          if (lane < 16) sts4(sm + OFF_STATS + lane * 128 + ((lane & 7) << 4), 0x3F803F80u, 0x3F803F80u, 0x3F803F80u, 0x3F803F80u);
          fence_async_smem();
          __syncwarp();
          if (lane == 0) mbar_arrive(mb + B_LATE);
        }
        {
          const int p = lane & 15, sl = p % 7;
          const bool sliced = p > 0 && p < 9;
          const uint32_t c = sliced ? ((p - 1) >> 1) * 16 | ((hf ^ 1) * 8 + ((p - 1) & 1) * 4) << 8 | 128 << 16 : (hf * 8 + src_of(p)) << 8;
          const uint32_t ev = mb + (p < 4 ? B_EVA : B_E + 8 * ((p < 7 ? p == 6 : p - 4) & 7) + (p >= 12));
          mbar_wait(mb + B_EVA, 0);
          sts4(sm + OFF_COLSUM + 512 + p * 16, sm + unit_of(btab, sl), mb + B_BF + 8 * sl, c, ev);
          __syncwarp();
        }
        if (elect_one()) {
#pragma unroll 1
          for (int p = 0; p < 16; p++) {
            const uint4 e = lds4(sm + OFF_COLSUM + 512 + p * 16);
            if (p == 4) mbar_wait(mb + B_WR, 0);
            mbar_wait(e.w & ~1u, e.w & 1);
            mbar_expect_tx(e.y, p > 1 ? 4 * UNIT : 2 * UNIT);
            tma_4d(e.x, (const CUtensorMap*)((const char*)&T.m[M_O] + (e.z >> 16)), 0, e.z & 255, (e.z >> 8) & 255, c3 * 2, e.y);
          }
        }
      } else {
        const uint32_t* wp = (const uint32_t*)(P.wr + c3 * 128) + (lane & 7) * 8 + (lane >> 3);
        const uint32_t w0 = ld_rlx(wp), w1 = ld_rlx(wp + 4);
#pragma unroll 1
        for (int i = 0; i < 4; i++) { l2_prefetch((const char*)P.wo + b * 16384 + i * 4096 + lane * 128); __nanosleep(300); }
        const int p = lane & 15, p2 = min(p + 2, 15);
        const uint32_t t0 = dlo(sb, 8192) + (unit_of(btab, p % 7) >> 4), t1 = ring_of(p + 1, lane >> 4), t2 = mb + B_BF + 8 * (p2 % 7);
        mbar_wait(mb + B_EVB, 0);
        bar_sync(14, 64);
        sts2f(sm + OFF_COLSUM + lane * 8, __uint_as_float(w0), __uint_as_float(w1));
        sts1(sm + OFF_COLSUM + 256 + lane * 4, 0x3F803F80u);
        sts4(sm + OFF_STATS + lane * 16, t0, t1, t2, (p2 / 7) & 1);
        __syncwarp();
        if (elect_one()) {
          mbar_arrive(mb + B_WR);
          if (fidx >= 0) {
            mbar_expect_tx(mb + B_FFN, 131072); mbar_expect_tx(mb + B_FFD, 32768);
            uint64_t gt = rank ? GT1 : GT0;
#pragma unroll 1
            for (int f = 0; f < 8; f++, gt >>= 5) {
              uint32_t d0 = sm + unit_of(gt, 0);
              asm volatile("" : "+r"(d0));
              if (f == 3) mbar_wait(mb + B_GATE, 1);
              mbar_wait(mb + (f < 1 ? B_KVB : B_E + (f < 3 ? 3 + 2 * f : (f + 5) >> 1) * 8), f < 1 || f >= 3);
              tma_3d(d0, &T.m[M_G], fidx * 32, f * 128, 0, mb + B_FFN, true);
              tma_3d(d0 + UNIT, &T.m[M_U], fidx * 32, f * 128, 0, mb + B_FFN, true);
            }
            mbar_expect_tx(mb + B_KVP, 32768);
#pragma unroll
            for (int w = 0; w < 8; w++) {
              if (w == 2) mbar_wait(mb + B_E + 56, 1);
              if (w == 6) mbar_wait(mb + B_E16, 1);
              if (w == 4) mbar_wait(mb + B_EVA, 1);
              tma_3d(sm + ((DT0 >> (5 * w)) & 31) * UNIT + (w < 4 ? 0 : w < 6 ? 14 * UNIT : 0 - 14 * UNIT) * rank, &T.m[M_D], 0, fidx * 32, 2 * w, mb + (w < 4 ? B_FFD : B_KVP), true);
            }
          }
        }
      }
    }
    __syncwarp();
    IDS(get_b());
    mbar_wait(mb + B_EVB, 0);
    mbar_wait(mb + B_OUT, 0);
    const float2 cf = lds2f(sm + OFF_STATS + 64);
    const int cand0 = 2047 - (__float_as_int(cf.x) & 2047), cand1 = 2047 - (__float_as_int(cf.y) & 2047), rr = lane >> 4;
    __nv_bfloat16* const ob = P.out + c3 * 128 + (lane & 15) * 8;
    auto store_row = [&](uint32_t ha, uint32_t la, int row, bool on) {
      const uint4 v = lds4(ha);
      const float2 pr = lds2f(la);
      const float f = 1.f + pr.x, n = pr.y;
      asm volatile("{\n.reg .pred p;\nsetp.ne.u32 p, %5, 0;\n@p st.global.v4.u32 [%0], {%1,%2,%3,%4};\n}" :: "l"(ob + row * D_),
                   "r"(pack2(fmaf(bf_lo(v.x), f, n), fmaf(bf_hi(v.x), f, n))), "r"(pack2(fmaf(bf_lo(v.y), f, n), fmaf(bf_hi(v.y), f, n))),
                   "r"(pack2(fmaf(bf_lo(v.z), f, n), fmaf(bf_hi(v.z), f, n))), "r"(pack2(fmaf(bf_lo(v.w), f, n), fmaf(bf_hi(v.w), f, n))), "r"((uint32_t)on) : "memory");
    };
    {
      uint32_t t0 = clock64();
      uint32_t ha = sm + 4 * UNIT + ((wid >> 1) & 1) * STAGE_B + ((wid & 1) * 32 + rr) * 256 + (((lane & 15) ^ rr) << 4), la = sm + OFF_LNP + ((wid & 3) * 32 + rr) * 8;
      int row = rb * 256 + hf * 64 + (wid & 2) * 64 + (wid & 1) * 32 + rr;
#pragma unroll 1
      for (int i = 0; i < 16; i += 2, ha += 512 * 2, la += 16 * 2, row += 2 * 2, t0 += OPACE) {
        while ((int)((uint32_t)clock64() - t0) < 0) NAP;
#pragma unroll
        for (int j = 0; j < 2; j++) store_row((ha ^ (((i + j) & 3) << 5)) + j * 512, la + j * 16, row + 2 * j, row + 2 * j != cand0 && row + 2 * j != cand1);
      }
    }
    if (wid == 8) {
      const uint32_t kc = __float_as_uint(rr ? cf.y : cf.x);
      const int c = rr ? cand1 : cand0;
      mbar_wait(mb + B_SEL, 0);
      const float2 sel = lds2f(sm + OFF_STATS + 80);
      store_row(sm + 4 * UNIT + ((c >> 7) & 1) * STAGE_B + (c & 63) * 256 + (((lane & 15) ^ (c & 7)) << 4), sm + OFF_LNP + (((c >> 1) & 64) + (c & 63)) * 8, c,
                kc != __float_as_uint(sel.x) && kc != __float_as_uint(sel.y) && (c >> 8) == rb && ((c >> 6) & 1) == hf);
    }
  } else {
    asm volatile("setmaxnreg.inc.sync.aligned.u32 224;");
    const int t128 = tid & 127, warp = wid & 3, g = lane >> 2, t = lane & 3;
    const uint32_t sk = rank * (2 * STAGE_B);
    uint4 ost[2][4];
    uint4 abuf[3][4];
    uint4* od1;
    const uint4* ain;
    int b1;
    const uint32_t eb = (lane << 24) + bars + B_E;
    float acc[64];
    uint4 wb[4];
    uint32_t hp[32];
    {
      float acc0[96], acc1[96];
#pragma unroll
      for (int i = 0; i < 96; i++) { acc0[i] = 0.f; acc1[i] = 0.f; }
      const uint32_t xo0 = dlo(sb, 16) + (wg * 2 + hf) * 512, xo1 = dlo(sb, 16) + (wg * 2 + (hf ^ 1)) * 512;
      constexpr uint32_t ST = STAGE_B >> 4, WD = dlo(sb + 49152, 8192), WV = dlo(sb + 32768, 8192);
      const uint32_t eb0 = (t128 << 24) + bars + B_EMPTY;
      pin(acc1); pin(acc0);
      if (wg) asm volatile("cp.async.wait_group 0;" ::: "memory"); else asm volatile("cp.async.wait_group 1;" ::: "memory");
      fence_async_smem();
      bar_sync(1, 256);
      if (!wg) {
        asm volatile("cp.async.wait_group 0;" ::: "memory");
        fence_async_smem();
        bar_sync(2, 256);
        if (tid == 0) mbar_arrive(mb + B_FULL);
      }
#pragma unroll 1
      for (int kb = 0; kb < 12; kb++) {
        const int s = kb & 3;
        if (kb) mbar_wait(mb + B_FULL + 8 * s, (kb >> 2) & 1);
        pin(acc0); pin(acc1);
        wg_fence();
#pragma unroll
        for (int k = 0; k < 4; k++) {
          const uint64_t db = dsc<1024, 1>(WV + s * ST + k * 128);
          wgmma_n192_ss<0, 1, 0>(acc0, dsc<1024, 1>(s * ST + xo0 + k * 2), db, 1);
          wgmma_n192_ss<0, 1, 0>(acc1, dsc<1024, 1>(s * ST + xo1 + k * 2), db, 1);
        }
        wg_commit();
        if (kb == 0 && wg) bar_arrive(2, 256);
        wg_wait<0>();
        pin(acc0); pin(acc1);
        if (t128 < 2 && kb < 11) mbar_arrive_rem(eb0 + 8 * s);
      }
      mbar_wait(mb + B_FULL, 1);
      if (t128 < 8) mbar_arrive_rem(t128 < 4 ? (wg << 24) + bars + B_EMPTY + 24 : mb + B_EMPTY);
      mbar_wait(mb + B_AUX, 0);
      float rs[2][2], nm[2][2];
#pragma unroll
      for (int m = 0; m < 2; m++)
#pragma unroll
        for (int h = 0; h < 2; h++) { const float2 v = lds2f(sm + OFF_STATS + ((wg * 2 + (m ^ hf)) * 64 + warp * 16 + h * 8 + g) * 8); nm[m][h] = v.x; rs[m][h] = v.y; }
      auto center = [&](auto jc) {
        constexpr int j = decltype(jc)::value;
        const float2 cs = lds2f_o<sb + OFF_COLSUM + j * 32>(own + t * 8);
        acc1[j * 4] = fmaf(nm[1][0], cs.x, acc1[j * 4]); acc1[j * 4 + 1] = fmaf(nm[1][0], cs.y, acc1[j * 4 + 1]);
        acc1[j * 4 + 2] = fmaf(nm[1][1], cs.x, acc1[j * 4 + 2]); acc1[j * 4 + 3] = fmaf(nm[1][1], cs.y, acc1[j * 4 + 3]);
        acc0[j * 4] = fmaf(nm[0][0], cs.x, acc0[j * 4]); acc0[j * 4 + 1] = fmaf(nm[0][0], cs.y, acc0[j * 4 + 1]);
        acc0[j * 4 + 2] = fmaf(nm[0][1], cs.x, acc0[j * 4 + 2]); acc0[j * 4 + 3] = fmaf(nm[0][1], cs.y, acc0[j * 4 + 3]);
      };
      static_for<0, 16>(center);
      const float L2E = 1.4426950408889634f;
      uint32_t fa = sm + sk + (warp * 16 + (lane & 15)) * 128 + (((lane >> 4) ^ (lane & 7)) << 4);
      asm volatile("" : "+r"(fa));
      uint32_t xf0[32], xf1[32];
      auto pack_kv = [&](float (&a)[96], int i, float r0, float r1, uint32_t* o, uint32_t z = 0) {
        const float* p = a + i * 8;
        if (i < 4) {
          const float rl0 = __uint_as_float(__float_as_uint(r0 * L2E) | z), rl1 = __uint_as_float(__float_as_uint(r1 * L2E) | z);
          const uint32_t q0 = pack2(r0, r0), q1 = pack2(r1, r1);
          o[0] = phi2(p[0], p[1], rl0, q0); o[1] = phi2(p[2], p[3], rl1, q1); o[2] = phi2(p[4], p[5], rl0, q0); o[3] = phi2(p[6], p[7], rl1, q1);
        } else {
          const uint32_t q0 = pack2(r0, r0), q1 = pack2(r1, r1);
          o[0] = hmul2(pack2(p[0], p[1]), q0); o[1] = hmul2(pack2(p[2], p[3]), q1); o[2] = hmul2(pack2(p[4], p[5]), q0); o[3] = hmul2(pack2(p[6], p[7]), q1);
        }
      };
      auto swap_kv = [&](uint32_t (&xf)[32], uint32_t tile, int i, const uint32_t* o, uint32_t z = 0) {
        const uint32_t ad = (fa + tile * UNIT) ^ ((i & 3) << 5);
        if (i < 4) { ldsm4_o<0>(ad, xf[i * 4], xf[i * 4 + 1], xf[i * 4 + 2], xf[i * 4 + 3]); stsm4_o<0>(ad, o[0], o[1], o[2], o[3]); }
        else { ldsm4_o<STAGE_B>(ad | z, xf[i * 4], xf[i * 4 + 1], xf[i * 4 + 2], xf[i * 4 + 3]); stsm4_o<STAGE_B>(ad, o[0], o[1], o[2], o[3]); }
      };
      auto mma_q = [&](float (&a)[96], uint32_t (&xf)[32], uint32_t xo, bool ss) {
        const uint32_t r = __shfl_sync(~0u, sk >> 4, 0), o = 2 * ST - r;
#pragma unroll
        for (int j = 0; j < 8; j++) {
          if (ss) wgmma_n64_ss<0, 1, 64>(a, dsc<1024, 1>(o + (j >> 2) * ST + xo + (j & 3) * 2), dsc<1024, 1>(WD + o + (j >> 2) * ST + (j & 3) * 128), 1);
          else wgmma_n64_rs<1, 64>(a, xf[j * 4], xf[j * 4 + 1], xf[j * 4 + 2], xf[j * 4 + 3], dsc<1024, 1>(WD + r + (j >> 2) * ST + (j & 3) * 128), 1);
        }
      };
      auto epi_q = [&](float (&a)[96], float r0, float r1, uint32_t (&o)[16]) {
        const float rl0 = r0 * 1.44269511f, rl1 = r1 * 1.44269511f;
        const uint32_t q0 = dup2(r0), q1 = dup2(r1);
#pragma unroll
        for (int j = 0; j < 8; j++) { o[j * 2] = phi2(a[64 + j * 4], a[65 + j * 4], rl0, q0); o[j * 2 + 1] = phi2(a[66 + j * 4], a[67 + j * 4], rl1, q1); }
        pinu(o);
      };
      auto mma_kv1 = [&](float (&a)[96], uint32_t xo, int s) {
#pragma unroll
        for (int k = 0; k < 4; k++) wgmma_n128_ss<0, 1, 0>(a, dsc<1024, 1>(s * ST + xo + k * 2), dsc<1024, 1>(WV + s * ST + k * 128), 1);
      };
      auto epi_kv = [&](float (&a)[96], uint32_t (&xf)[32], uint32_t tile, float r0, float r1) {
        uint32_t o[8][4];
#pragma unroll
        for (int j = 3; j >= 0; j--) {
          const uint32_t z = j < 3 ? xf[(j + 5) * 4] & blockIdx.y : 0;
          pack_kv(a, j + 4, r0, r1, o[j + 4]);
          swap_kv(xf, tile, j + 4, o[j + 4], (o[j + 4][2] | o[j + 4][3]) & blockIdx.y);
          pack_kv(a, j, r0, r1, o[j], z);
          swap_kv(xf, tile, j, o[j]);
        }
      };
      bar_arrive(15, 288); bar_arrive(0, 288);
      mbar_wait(mb + B_FULL + 8, 1);
      if (!wg) bar_sync(3, 256);
      pinr<0, 64>(acc0); pinr<0, 64>(acc1);
      wg_fence();
      mma_kv1(acc1, xo1, 0); mma_kv1(acc0, xo0, 0); mma_kv1(acc1, xo1, 1); mma_kv1(acc0, xo0, 1);
      mbar_wait(mb + B_FULL + 16, 1);
      wg_fence();
      mma_kv1(acc1, xo1, 2);
      mbar_wait(mb + (wg ? B_FULL + 24 : B_F15), wg);
      wg_fence();
      mma_kv1(acc1, xo1, 3);
      wg_commit();
      bar_arrive(4 - wg, 256);
      static_for<16, 24>(center);
      pinr<64, 96>(acc0); pinr<64, 96>(acc1);
      mbar_wait(mb + B_FULL + 8, 1);
      wg_wait<0>();
      pinr<0, 64>(acc0); pinr<0, 64>(acc1);
      epi_kv(acc1, xf1, wg * 2 + (hf ^ 1), rs[1][0], rs[1][1]);
      pinu(xf1);
      bar_sync(5 - wg, 256);
      wg_fence();
      mma_kv1(acc0, xo0, 2); mma_kv1(acc0, xo0, 3);
      wg_commit();
      fence_async_smem();
      mma_q(acc1, xf1, xo1, false);
      wg_commit();
      bar_arrive(6 - wg, 256);
      wg_wait<1>();
      pinr<0, 64>(acc0);
      if (lane == 0) mbar_arrive(mb + B_EVA);
      epi_kv(acc0, xf0, wg * 2 + hf, rs[0][0], rs[0][1]);
      fence_async_smem();
      pinu(xf0);
      if (!wg) bar_arrive(7, 256);
      const uint32_t kvb = 2 * STAGE_B + (2 + (hf ^ 1)) * UNIT - sk;
      b1 = get_b();
      od1 = &P.s->obuf[(((b1 >> 4) * 4 + wg * 2 + (hf ^ 1)) * 64 + (b1 & 7)) * 128 + t128];
      ain = &P.s->obuf[((b1 >> 4) * 4 + wg * 2 + hf) * 64 * 128 + t128];
      uint32_t ka0 = sm + kvb + wid * 1024 + (lane & 7) * 128 + (((lane >> 3) ^ (lane & 7)) << 4), ka1 = sm + kvb + wid * 1024 + (t * 2 + g) * 128 + ((4 ^ (t * 2 + g)) << 4);
      uint32_t g0 = sm + sk + tid * 16, g1 = sm + sk + g * 256 + wid * 32 + t * 8;
      const uint8_t* h0 = (const uint8_t*)&P.s->kvp[(b1 & 15) * 8 * 256 + tid], *h1 = (const uint8_t*)&P.s->zp[((b1 & 15) * 8 + g) * 16] + wid * 32 + t * 8;
      asm volatile("" : "+r"(ka0), "+r"(ka1), "+r"(g0), "+r"(g1), "+l"(h0), "+l"(h1), "+l"(od1));
      if (wg) {
        float ka[36];
        auto mma_kv = [&](uint32_t tile, int i, int acc) {
          const uint32_t o = (sk >> 4) + tile * 512 + i * 128;
          wgmma_n72_ss<1, 1, 0>(ka, dsc<1024, 1>(dlo(sb, 8192) + o), dsc<1024, 1>(dlo(sb + STAGE_B, OFF_STATS - STAGE_B) + o * (1u - (1u << 16))), acc);
        };
#pragma unroll
        for (int i = 0; i < 36; i++) ka[i] = 0.f;
        mbar_wait(mb + B_LATE, 0);
        bar_sync(6, 256);
        wg_fence();
#pragma unroll
        for (int i = 0; i < 4; i++) {
          mma_kv(2, i, i); mma_kv(3, i, 1); mma_kv(hf ^ 1, i, 1);
#pragma unroll
          for (int j = 2 * i; j < 2 * i + 2; j++)
            wgmma_n64_rs<1, 64>(acc0, xf0[j * 4], xf0[j * 4 + 1], xf0[j * 4 + 2], xf0[j * 4 + 3], dsc<1024, 1>(WD + (sk >> 4) + (j >> 2) * ST + (j & 3) * 128), 1);
        }
        const int kq = (b1 & 15) * 8 + (b1 >> 4);
        uint4* dst = &P.s->kvp[kq * 256 + warp * 64 + lane];
        uint32_t* dz = (uint32_t*)&P.s->zp[kq * 16] + warp * 16 + g + t * 8;
        asm volatile("" : "+l"(dst), "+l"(dz));
        bar_sync(7, 256);
#pragma unroll
        for (int i = 0; i < 4; i++) mma_kv(hf, i, 1);
        wg_commit();
        bar_arrive(8, 256);
        wg_wait<0>();
        pin(ka); pinr<64, 96>(acc0);
        uint32_t kw[8];
#pragma unroll
        for (int i = 0; i < 8; i++) {
          const int j = (i & 3) * 4 + (i >> 2) * 2;
          asm("{\n.reg .pred p;\nsetp.ne.u32 p, %5, 0;\n@p cvt.rn.bf16x2.f32 %0, %4, %3;\n@!p cvt.rn.bf16x2.f32 %0, %2, %1;\n}"
              : "=r"(kw[i]) : "f"(ka[j]), "f"(ka[j + 1]), "f"(ka[16 + j]), "f"(ka[17 + j]), "r"(warp & 2));
        }
        st_rlx4(dst, make_uint4(kw[0], kw[1], kw[2], kw[3]));
        st_rlx4(dst + 32, make_uint4(kw[4], kw[5], kw[6], kw[7]));
        if (t < 2) st_rlx(dz, __float_as_uint(t ? ka[34] : ka[32]));
        if (lane == 0) mbar_arrive(mb + B_EVB);
        const uint32_t t1 = clock64();
        while ((uint32_t)clock64() - t1 < SDELAY) {}
      } else {
        bar_sync(8, 256);
        wg_fence();
        mma_q(acc0, xf0, xo0, false);
      }
      if (!wg) bar_sync(9, 256);
      wg_fence();
      mma_q(acc1, xf1, xo1, true);
      wg_commit();
      if (wg) { bar_arrive(9, 256); wg_wait<0>(); }
      else { wg_fence(); mma_q(acc0, xf0, xo0, true); wg_commit(); wg_wait<1>(); }
      pinr<64, 96>(acc1);
      uint32_t pq[16];
      epi_q(acc1, rs[1][0], rs[1][1], pq);
      bar_sync(11 + wg + zero_after(pq), 128);
      if (wg) {
        wg_fence();
        mma_q(acc0, xf0, xo0, true);
        wg_commit();
      }
      {
        uint4 gv[8]; uint2 gz;
        uint32_t m[8], a[4];
        float z0, z1;
        mbar_wait(mb + B_KVP, 0);
        { const float2 v = lds2f_o<UNIT>(g1); gz = make_uint2(__float_as_uint(v.x), __float_as_uint(v.y)); }
        static_for<0, 8>([&](auto sc) { constexpr int s = decltype(sc)::value; gv[s] = lds4_o<STAGE_B + s * 4096>(g0); });
#pragma unroll 1
        for (int it = 0; it < SPIN_LIMIT; it++) {
          uint32_t mm = max(gz.x, gz.y);
          z0 = __uint_as_float(gz.x); z1 = __uint_as_float(gz.y);
#pragma unroll
          for (int o = 4; o < 32; o <<= 1) { z0 += __shfl_xor_sync(~0u, z0, o); z1 += __shfl_xor_sync(~0u, z1, o); }
#pragma unroll
          for (int s = 0; s < 8; s++) m[s] = max4(0, gv[s]);
#pragma unroll
          for (int s = 0; s < 8; s += 2) mm = __vimax3_u32(mm, m[s], m[s + 1]);
          a[0] = hadd2(hadd2(hadd2(gv[0].x, gv[1].x), hadd2(gv[2].x, gv[3].x)), hadd2(hadd2(gv[4].x, gv[5].x), hadd2(gv[6].x, gv[7].x)));
          a[1] = hadd2(hadd2(hadd2(gv[0].y, gv[1].y), hadd2(gv[2].y, gv[3].y)), hadd2(hadd2(gv[4].y, gv[5].y), hadd2(gv[6].y, gv[7].y)));
          a[2] = hadd2(hadd2(hadd2(gv[0].z, gv[1].z), hadd2(gv[2].z, gv[3].z)), hadd2(hadd2(gv[4].z, gv[5].z), hadd2(gv[6].z, gv[7].z)));
          a[3] = hadd2(hadd2(hadd2(gv[0].w, gv[1].w), hadd2(gv[2].w, gv[3].w)), hadd2(hadd2(gv[4].w, gv[5].w), hadd2(gv[6].w, gv[7].w)));
          pinu(a);
          if (!__any_sync(~0u, mm == SENT)) break;
          gz = ld_rlx2(h1);
#pragma unroll
          for (int s = 0; s < 8; s++) if (m[s] == SENT) gv[s] = ld_rlx4(h0 + s * 4096);
        }
        wg_wait<0>();
        pinr<64, 96>(acc0);
        if (lane == 0) mbar_arrive(mb + B_KVB);
        stsm4(ka0, a[0], a[1], a[2], a[3]);
        const uint32_t zz = pack2(g ? z1 : z0, g ? z1 : z0);
        if (lane < 8) sts4(ka1, zz, zz, zz, zz);
        fence_async_smem();
        bar_sync(1, 256);
      }
      auto make_o = [&](uint4 (&o)[4], auto first) {
        float oa[2][20];
        wg_fence();
#pragma unroll
        for (int ks = 0; ks < 4; ks++)
          wgmma_n40_rs<1, 0>(oa[ks >> 1], pq[ks * 4], pq[ks * 4 + 1], pq[ks * 4 + 2], pq[ks * 4 + 3], dsc<1024, 1>(dlo(sb, 8192) + (kvb >> 4) + ks * 128), ks & 1);
        wg_commit();
        if constexpr (!decltype(first)::value) {
          pinu(xf0);
#pragma unroll
          for (int q = 0; q < 32; q++) { acc[q * 2] = bf_lo(xf0[q]); acc[q * 2 + 1] = bf_hi(xf0[q]); }
          pin(acc);
          mbar_wait(mb + B_BF, 0);
        }
        wg_wait<0>();
        pin(oa[0]); pin(oa[1]);
        if (decltype(first)::value && lane < 2) mbar_arrive_rem(eb);
#pragma unroll
        for (int h = 0; h < 2; h++) {
          const float (&d)[20] = oa[h];
          const float i0 = rcp(d[16] + 1e-6f), i1 = rcp(d[18] + 1e-6f);
#pragma unroll
          for (int k2 = 0; k2 < 2; k2++) {
            o[h * 2 + k2] = make_uint4(pack2(d[k2 * 8] * i0, d[k2 * 8 + 1] * i0), pack2(d[k2 * 8 + 2] * i1, d[k2 * 8 + 3] * i1),
                                       pack2(d[k2 * 8 + 4] * i0, d[k2 * 8 + 5] * i0), pack2(d[k2 * 8 + 6] * i1, d[k2 * 8 + 7] * i1));
            if (decltype(first)::value && !h && !k2) { st_rlx4(od1, o[0]); sched_fence(); }
          }
        }
      };
      make_o(ost[1], std::true_type{});
      st_rlx4(od1 + 1024 + ((ost[1][2].x | ost[1][3].w) & blockIdx.y), ost[1][1]);
      sched_fence();
      auto read1 = [&](uint32_t z) {
        mbar_wait(mb + B_F15 + z, 1);
#pragma unroll
        for (int i = 0; i < 4; i++) abuf[1][i] = ld_rlx4(ain + i * 128);
      };
      {
        const float rl0 = rs[0][0] * 1.44269511f, rl1 = rs[0][1] * 1.44269511f;
        const uint32_t q0 = dup2(rs[0][0]), q1 = dup2(rs[0][1]);
        uint32_t z = 0;
#pragma unroll
        for (int j = 0; j < 8; j++) {
          pq[j * 2] = phi2(acc0[64 + j * 4], acc0[65 + j * 4], rl0, q0); pq[j * 2 + 1] = phi2(acc0[66 + j * 4], acc0[67 + j * 4], rl1, q1);
          if (j < R1MID) z |= pq[j * 2] | pq[j * 2 + 1];
          if (j == R1MID - 1) read1(z & 0x80008000u);
        }
      }
      st_rlx4(od1 + 2048, ost[1][2]);
      make_o(ost[0], std::false_type{});
    }
   {
    IDS(b1);
    const int mb3 = rb * 4 + wg * 2 + hf;
    uint4* rp = &P.s->st2[mb3 * 64 + warp * 16 + g + t * 8];
    {
      uint4* const od0 = &P.s->obuf[(mb3 * 64 + 32 + s3 * 4) * 128 + t128];
#pragma unroll
      for (int i = 0; i < 4; i++) pin4(ost[0][i]);
      wg_fence();
#pragma unroll
      for (int k = 0; k < 4; k++) wgmma_n128_rs<1, 0>(acc, ost[0][k].x, ost[0][k].y, ost[0][k].z, ost[0][k].w, dsc<1024, 1>(dlo(sb + 4 * UNIT, 8192) + k * 128), 1);
      wg_commit();
      st_rlx4(od1 + 3072, ost[1][3]); st_rlx4(od0, ost[0][0]);
      uint32_t la = sm + t128 * 16, ev = eb + 8;
      asm volatile("" : "+r"(la), "+r"(ev));
      auto fetch = [&](uint32_t off, uint4 (&a)[4]) { const uint32_t ra = la + off; a[0] = lds4_o<0>(ra); a[1] = lds4_o<2048>(ra); a[2] = lds4_o<4096>(ra); a[3] = lds4_o<6144>(ra); };
      auto check = [&](int p, uint4 (&a)[4]) {
        if (__any_sync(~0u, max(max4(max4(0, a[0]), a[1]), max4(max4(0, a[2]), a[3])) == SENT)) {
          int pl = p; asm volatile("" : "+r"(pl));
          const uint4* q = ain + frag_of(pl);
#pragma unroll 1
          for (int it = 0;; it++) {
            uint32_t mm = 0;
#pragma unroll
            for (int i = 0; i < 4; i++) { const uint32_t m = max4(0, a[i]); mm = max(mm, m); if (m == SENT) a[i] = ld_rlx4(q + i * 128); }
            if (!__any_sync(~0u, mm == SENT)) break;
            SPINCHK(it);
          }
        }
        if (lane < 2) mbar_arrive_rem(ev);
        ev = (ev & ~0x38u) | ((ev + 8) & 0x38u);
      };
      auto mma = [&](int p, uint32_t bs, uint4 (&a)[4]) {
#pragma unroll
        for (int i = 0; i < 4; i++) pin4(a[i]);
        wg_fence();
#pragma unroll
        for (int k = 0; k < 4; k++) wgmma_n128_rs<1, 0>(acc, a[k].x, a[k].y, a[k].z, a[k].w, dsc<1024, 1>(bs + k * 128), 1);
        wg_commit();
      };
      uint32_t ta = sm + OFF_STATS + wg * 256 + 48;
      mbar_wait(mb + B_WR, 0);
      uint4 tp = lds4(ta);
      mbar_wait(mb + B_BF + 8, 0);
      check(1, abuf[1]);
      mbar_wait(mb + B_BF + 16, 0);
      fetch(ring_of(2, wg), abuf[2]);
      mma(1, dlo(sb + 11 * UNIT, 8192), abuf[1]);
      st_rlx4(od0 + 128, ost[0][1]); st_rlx4(od0 + 256, ost[0][2]);
      check(2, abuf[2]);
      mbar_wait(mb + B_BF + 24, 0);
      fetch(ring_of(3, wg), abuf[0]);
      mma(2, dlo(sb + 18 * UNIT, 8192), abuf[2]);
      st_rlx4(od0 + 384, ost[0][3]);
      wg_wait<2>();
      check(3, abuf[0]);
      mbar_wait(mb + B_BF + 32, 0);
#pragma unroll 1
      for (int p = 3; p < 15; p += 3) {
        static_for<0, 3>([&](auto jc) {
          constexpr int j = decltype(jc)::value;
          const uint4 tc = tp;
          const uint32_t bs = __shfl_sync(~0u, tc.x, 0);
          wg_wait<1>();
#pragma unroll
          for (int i = 0; i < 4; i++) pin4(abuf[(j + 1) % 3][i]);
          tp = lds4_o<16 * j + 16>(ta);
          fetch(tc.y, abuf[(j + 1) % 3]);
          mma(p + j, bs, abuf[j]);
          check(p + j + 1, abuf[(j + 1) % 3]);
          mbar_wait(tc.z, tc.w);
        });
        ta += 48;
      }
      {
        const uint32_t wa0 = sm + OFF_COLSUM + ((g & 1) ? t * 64 : 256);
        wb[0] = lds4_o<0>(wa0); wb[1] = lds4_o<16>(wa0); wb[2] = lds4_o<32>(wa0); wb[3] = lds4_o<48>(wa0);
      }
      mma(15, __shfl_sync(~0u, tp.x, 0), abuf[0]);
      wg_wait<2>();
      if (lane == 0) mbar_arrive(mb + B_E16);
      asm volatile("" : "+l"(rp));
      sched_fence();
      wg_wait<0>();
      pin(acc);
#pragma unroll
      for (int i = 0; i < 4; i++) { pin4(abuf[0][i]); pin4(abuf[1][i]); pin4(abuf[2][i]); }
    }
    {
      float q0[2] = {0.f, 0.f}, q1[2] = {0.f, 0.f}, c[2][4] = {};
#pragma unroll
      for (int j = 0; j < 16; j++) {
        hp[j * 2] = pack2(acc[j * 4], acc[j * 4 + 1]); hp[j * 2 + 1] = pack2(acc[j * 4 + 2], acc[j * 4 + 3]);
        q0[j & 1] = fmaf(acc[j * 4], acc[j * 4], fmaf(acc[j * 4 + 1], acc[j * 4 + 1], q0[j & 1]));
        q1[j & 1] = fmaf(acc[j * 4 + 2], acc[j * 4 + 2], fmaf(acc[j * 4 + 3], acc[j * 4 + 3], q1[j & 1]));
        if (j & 1) {
          const uint32_t a[4] = {hp[j * 2 - 2], hp[j * 2 - 1], hp[j * 2], hp[j * 2 + 1]};
          mma16816(c[(j >> 1) & 1], a, (j & 2) ? wb[j >> 2].z : wb[j >> 2].x, (j & 2) ? wb[j >> 2].w : wb[j >> 2].y);
        }
      }
      const bool od = t & 1;
      float q = (od ? q1[0] + q1[1] : q0[0] + q0[1]) + __shfl_xor_sync(~0u, od ? q0[0] + q0[1] : q1[0] + q1[1], 1);
      q += __shfl_xor_sync(~0u, q, 2);
      asm volatile("{\n.reg .pred p;\nsetp.lt.u32 p, %5, 2;\n@p red.relaxed.gpu.global.add.v4.f32 [%0], {%1,%2,%3,%4};\n}"
                   :: "l"(rp), "f"(od ? c[0][2] + c[1][2] : c[0][0] + c[1][0]), "f"(q), "f"(od ? c[0][3] + c[1][3] : c[0][1] + c[1][1]), "f"(1.f), "r"(t) : "memory");
    }
    const uint32_t ts = clock64();
    const uint32_t msc = sm + OFF_STATS;
    const uint32_t hst = sm + 4 * UNIT + wg * STAGE_B + warp * 4096, gslot = sm + unit_of(rank ? GT1 : GT0, wid);
    bar_sync(1, 256);
#pragma unroll
    for (int j = 0; j < 8; j++)
      stsm4(hst + (lane & 15) * 256 + (((2 * j + (lane >> 4)) ^ (lane & 7)) << 4), hp[j * 4], hp[j * 4 + 1], hp[j * 4 + 2], hp[j * 4 + 3]);
    uint32_t wa[8][4][4], wd[8][2][4];
    const uint32_t a0 = gslot + ((lane >> 4) * 8 + (lane & 7)) * 64 + ((((lane >> 3) & 1) ^ ((lane >> 1) & 3)) << 4);
    auto load_gu = [&](auto ic) { constexpr int i = decltype(ic)::value; ldsm4t_o<(i >> 2) * 1024 + ((i >> 1) & 1) * 8192>(a0 ^ ((i & 1) << 5), wa[i >> 2][i & 3]); };
    uint32_t tx;
    {
      const int row = rb * 256 + tid;
      const uint4* sp = &P.s->st2[row], *sq = &P.s->st2[row ^ 256];
      const float sw = __uint_as_float((lds1(mb + B_SW) & ~255u) | 128);
      uint4 v[2];
      uint4* d = &P.s->hsel[c3 * 128 + (g & 3) * 32 + ((rb & 6) + (lane >> 4)) * 4 + t];
      uint32_t* dk = &P.s->cand[c3 * 32 + (rb & 6) + (lane >> 4)];
      asm volatile("" : "+l"(d), "+l"(dk));
      if (fidx >= 0) mbar_wait(mb + B_FFN, 0);
      static_for<0, GU1>(load_gu);
      while ((uint32_t)clock64() - ts < SDEL2) {}
      v[0] = ld_rlx4(sp); v[1] = ld_rlx4(sq);
      static_for<GU1, GU2>(load_gu);
#pragma unroll 1
      for (int it = 0; __any_sync(~0u, min(v[0].w, v[1].w) != 0x41000000u) && it < SPIN_LIMIT; it++) {
        if (v[0].w != 0x41000000u) v[0] = ld_rlx4(sp);
        if (v[1].w != 0x41000000u) v[1] = ld_rlx4(sq);
      }
      if (lane == 0) mbar_arrive(mb + B_EVA);
      uint32_t k[2];
#pragma unroll
      for (int i = 0; i < 2; i++) {
        const float mean = __uint_as_float(v[i].x) * (1.f / D_);
        const float rstd = rsq(fmaxf(fmaf(-mean, mean, __uint_as_float(v[i].y) * (1.f / D_)), 0.f) + 1e-5f);
        const uint32_t u = __float_as_uint(rstd * fmaf(-mean, sw, __uint_as_float(v[i].z)));
        k[i] = min(((u ^ ((uint32_t)((int)u >> 31) | 0x80000000u)) & ~2047u), 0xFFFFF000u) | (2047 - (row ^ (i << 8)));
        if (i == 0 && (warp >> 1) == hf) sts2f(sm + OFF_LNP + (wg * 64 + (tid & 63)) * 8, rstd, -mean * rstd);
      }
      const uint32_t hi = max(k[0], k[1]);
      uint32_t m1 = __reduce_max_sync(~0u, hi), m2 = __reduce_max_sync(~0u, hi == m1 ? min(k[0], k[1]) : hi);
      if (lane == 0) sts2f(msc + wid * 8, __uint_as_float(m1), __uint_as_float(m2));
      bar_sync(1, 256);
      const uint32_t kk = lds1(msc + (lane & 15) * 4);
      m1 = __reduce_max_sync(~0u, kk); m2 = __reduce_max_sync(~0u, kk == m1 ? 0 : kk);
      const int c0 = 2047 - (m1 & 2047), c1 = 2047 - (m2 & 2047);
      if ((c0 >> 4) == mb3 * 4 + warp || (c1 >> 4) == mb3 * 4 + warp) {
        const int ra = (lane & 4) ? c1 : c0, rd = (lane & 16) ? c1 : c0;
        uint32_t h0, h1, h2, h3;
        ldsm4_o<0>(hst + (ra & 15) * 256 + ((((lane & 3) * 4 + (lane >> 3)) ^ (ra & 7)) << 4), h0, h1, h2, h3);
        const float2 pr = lds2f(sm + OFF_LNP + (wid * 16 + (rd & 15)) * 8);
        if ((rd >> 4) == mb3 * 4 + warp) {
          const uint4 xn = make_uint4(pack2(fmaf(bf_lo(h0), pr.x, pr.y), fmaf(bf_hi(h0), pr.x, pr.y)), pack2(fmaf(bf_lo(h1), pr.x, pr.y), fmaf(bf_hi(h1), pr.x, pr.y)),
                                      pack2(fmaf(bf_lo(h2), pr.x, pr.y), fmaf(bf_hi(h2), pr.x, pr.y)), pack2(fmaf(bf_lo(h3), pr.x, pr.y), fmaf(bf_hi(h3), pr.x, pr.y)));
          st_rlx4(d, xn);
          if (!(lane & 15)) st_rlx(dk, (lane & 16) ? m2 : m1);
          st_rlx4(d + 1024, make_uint4(h0, h1, h2, h3));
        }
      }
      tx = clock64();
      if (tid == 0) { sts2f(msc + 64, __uint_as_float(m1), __uint_as_float(m2)); mbar_arrive(mb + B_OUT); }
    }
    static_for<GU2, 32>(load_gu);
    const uint32_t dl = sm + (wid & 1) * 4096 + ((lane >> 4) * 8 + (lane & 7)) * 128 + ((((lane >> 3) & 1) ^ (lane & 7)) << 4);
    uint32_t da = dl + unit_of(DT0, wid >> 1), db = dl + unit_of(rank ? DT1 : DT0, 4 + (wid >> 1));
    uint32_t* yp = (uint32_t*)&P.s->ybuf[((wid * 8 + t * 2) * NFFN + fidx) * 2] + g;
    uint32_t k1, k2;
    uint2 key;
    uint32_t pl = sm + unit_of(rank ? GT1 : GT0, g) + (g & 1) * 64 + wid * 64 + t * 16, pa = msc + 128 + wid * 16 + ((t & 1) * 2 + (lane >> 4)) * 4 + (t >> 1) * 2;
    {
      float gu[2][4][4];
      uint4 xb[4];
      uint32_t m[4];
      const uint4* xp = &P.s->hsel[wid * 128 + lane];
      const uint2* kp = (const uint2*)&P.s->cand[wid * 32] + t;
      uint32_t ps = gslot + (wid & 1) * 64 + g * 32;
      asm volatile("" : "+l"(xp), "+l"(kp), "+l"(yp), "+r"(db), "+r"(ps), "+r"(pl), "+r"(pa));
      if (fidx >= 0) mbar_wait(mb + B_FFD, 0);
      static_for<0, 8>([&](auto ic) { constexpr int i = decltype(ic)::value; ldsm4t_o<(i & 1) * 2048>(da ^ ((i >> 1) << 5), wd[i >> 1][i & 1]); });
      while ((uint32_t)clock64() - tx < XDELAY) {}
      key = ld_rlx2(kp);
#pragma unroll
      for (int i = 0; i < 4; i++) xb[i] = ld_rlx4(xp + i * 32);
      if (fidx >= 0) mbar_wait(mb + B_KVP, 1);
#pragma unroll 1
      for (int it = 0; it < SPIN_LIMIT; it++) {
#pragma unroll
        for (int i = 0; i < 4; i++) m[i] = max4(0, xb[i]);
        if (!__any_sync(~0u, __vimax3_u32(__vimax3_u32(max(key.x, key.y), m[0], m[1]), m[2], m[3]) == SENT)) break;
        key = ld_rlx2(kp);
#pragma unroll
        for (int i = 0; i < 4; i++) if (m[i] == SENT) xb[i] = ld_rlx4(xp + i * 32);
      }
      const uint32_t hi = max(key.x, key.y);
      k1 = __reduce_max_sync(~0u, hi); k2 = __reduce_max_sync(~0u, hi == k1 ? min(key.x, key.y) : hi);
#pragma unroll
      for (int i = 0; i < 32; i++) gu[i >> 4][(i >> 2) & 3][i & 3] = 0.f;
#pragma unroll
      for (int ks = 0; ks < 8; ks++) {
#pragma unroll
        for (int i = 0; i < 4; i++) mma16816(gu[ks & 1][i], wa[ks][i], (ks & 1) ? xb[ks >> 1].z : xb[ks >> 1].x, (ks & 1) ? xb[ks >> 1].w : xb[ks >> 1].y);
        if (ks == 1) {
          const uint32_t dd = db | (__float_as_uint(gu[1][3][0]) & blockIdx.y);
          static_for<0, 8>([&](auto ic) { constexpr int i = decltype(ic)::value; ldsm4t_o<(i & 1) * 2048>(dd ^ ((i >> 1) << 5), wd[4 + (i >> 1)][i & 1]); });
          xb[3].z |= (wd[4][0][0] | wd[4][1][0] | wd[5][0][0] | wd[5][1][0] | wd[6][0][0] | wd[6][1][0] | wd[7][0][0] | wd[7][1][0]) & blockIdx.y;
        }
      }
#pragma unroll
      for (int c = 0; c < 2; c++) {
        const uint32_t kc = c ? key.y : key.x;
        float o[8];
#pragma unroll
        for (int j = 0; j < 8; j++) o[j] = gu[0][(j >> 2) + (j & 1) * 2][(j & 2) + c] + gu[1][(j >> 2) + (j & 1) * 2][(j & 2) + c];
        asm volatile("{\n.reg .pred p;\nsetp.ge.u32 p, %9, %10;\n@p st.shared.v4.f32 [%0], {%1,%2,%3,%4};\n@p st.shared.v4.f32 [%0+16], {%5,%6,%7,%8};\n}"
                     :: "r"(ps + (kc == k1 ? 0 : 256)), "f"(o[0]), "f"(o[1]), "f"(o[2]), "f"(o[3]), "f"(o[4]), "f"(o[5]), "f"(o[6]), "f"(o[7]), "r"(kc), "r"(k2) : "memory");
      }
    }
    bar_sync(1, 256);
    {
      const uint4 pv = lds4(pl);
      const bool hi = lane & 16;
      float ga = __uint_as_float(hi ? pv.z : pv.x) + __shfl_xor_sync(~0u, __uint_as_float(hi ? pv.x : pv.z), 16);
      float up = __uint_as_float(hi ? pv.w : pv.y) + __shfl_xor_sync(~0u, __uint_as_float(hi ? pv.y : pv.w), 16);
      ga += __shfl_xor_sync(~0u, ga, 8); up += __shfl_xor_sync(~0u, up, 8);
      ga += __shfl_xor_sync(~0u, ga, 4); up += __shfl_xor_sync(~0u, up, 4);
      asm volatile("st.shared.u16 [%0], %1;" :: "r"(pa), "h"((uint16_t)pack2(ga * rcp(1.f + ex2(-1.4426950408889634f * ga)) * up, 0.f)) : "memory");
      bar_sync(1, 256);
      const uint4 bv = lds4(msc + 128 + (lane & 7) * 16);
      const uint32_t bq[4] = {bv.x, bv.y, bv.z, bv.w};
      float ya[8][4];
#pragma unroll
      for (int i = 0; i < 8; i++) { ya[i][0] = 0.f; ya[i][1] = 0.f; ya[i][2] = 0.f; ya[i][3] = 0.f; }
#pragma unroll
      for (int ks = 0; ks < 2; ks++)
#pragma unroll
        for (int i = 0; i < 8; i++) mma16816(ya[i], wd[i][ks], bq[ks * 2], bq[ks * 2 + 1]);
#pragma unroll
      for (int h = 0; h < 2; h++) {
        float o[4];
#pragma unroll
        for (int j = 0; j < 4; j++) o[j] = t == 0 ? ya[h * 4][j] : t == 1 ? ya[h * 4 + 1][j] : t == 2 ? ya[h * 4 + 2][j] : ya[h * 4 + 3][j];
        asm volatile("{\n.reg .pred p;\nsetp.ge.s32 p, %3, 0;\n@p st.relaxed.gpu.global.u32 [%0], %1;\n@p st.relaxed.gpu.global.u32 [%0+%4], %2;\n}"
                     :: "l"(yp + h * (64 * NFFN * 8)), "r"(pack2(o[0], o[1])), "r"(pack2(o[2], o[3])), "r"(fidx), "n"(NFFN * 32) : "memory");
      }
    }
    if (tid == 0) { sts2f(msc + 80, __uint_as_float(k1), __uint_as_float(k2)); mbar_arrive(mb + B_SEL); }
    const uint32_t ty = clock64();
    if (wid == 0) {
      const uint32_t* yq = (const uint32_t*)&P.s->ybuf[b * NFFN * 2] + t * 8 + g;
      const uint32_t ks = (t & 1) ? k2 : k1, grp = 3 - ((ks >> 9) & 3);
      const int fs = grp * 2 + (__shfl_sync(~0u, key.y, grp) == ks);
      const uint32_t* fq = (const uint32_t*)P.s->hsel + (((b >> 4) * 4 + ((b >> 2) & 3)) * 32 + fs * 4 + (g >> 1)) * 4 + (b & 3);
      float gate = rcp(1.f + ex2(-1.4426950408889634f * __uint_as_float(ks ^ (~(uint32_t)((int)ks >> 31) | 0x80000000u))));
      __nv_bfloat16* op = P.out + (size_t)(2047 - (ks & 2047)) * D_ + b * 8 + g;
      uint32_t sel = (g & 2) ? 0x3F800000u : 0x00003F80u;
      uint32_t fn = ld_rlx(fq), fh = ld_rlx(fq + 4096), v[7][4];
      uint32_t m[7];
#pragma unroll
      for (int i = 0; i < 7; i++) { m[i] = ~blockIdx.y; asm volatile("" : "=r"(v[i][0]), "=r"(v[i][1]), "=r"(v[i][2]), "=r"(v[i][3]), "+r"(m[i])); }
      asm volatile("" : "+l"(yq), "+l"(op), "+f"(gate), "+r"(sel));
      while ((uint32_t)clock64() - ty < YDELAY) {}
      float y[2][4];
#pragma unroll 1
      for (int it = 0; it < SPIN_LIMIT; it++) {
        static_for<0, 7>([&](auto ic) { constexpr int i = decltype(ic)::value;
          asm volatile("{\n.reg .pred p;\nsetp.eq.u32 p, %5, 0xFFFFFFFF;\n@p ld.relaxed.gpu.global.u32 %0, [%4+%6];\n@p ld.relaxed.gpu.global.u32 %1, [%4+%6+128];\n"
                       "@p ld.relaxed.gpu.global.u32 %2, [%4+%6+256];\n@p ld.relaxed.gpu.global.u32 %3, [%4+%6+384];\n}"
                       : "+r"(v[i][0]), "+r"(v[i][1]), "+r"(v[i][2]), "+r"(v[i][3]) : "l"(yq), "r"(m[i]), "n"(i * 512) : "memory"); });
        uint32_t mm = max(fn, fh);
        if (mm == SENT) { fn = ld_rlx(fq); fh = ld_rlx(fq + 4096); }
#pragma unroll
        for (int i = 0; i < 8; i++) y[i >> 2][i & 3] = 0.f;
#pragma unroll
        for (int i = 0; i < 7; i++) { m[i] = __vimax3_u32(max(v[i][0], v[i][1]), v[i][2], v[i][3]); mm = max(mm, m[i]); mma16816(y[i & 1], v[i], sel, sel); }
        pin(y[0]); pin(y[1]);
        if (!__any_sync(~0u, mm == SENT)) break;
      }
      const float base = (g & 1) ? bf_hi(fh) + bf_hi(fn) : bf_lo(fh) + bf_lo(fn);
      if (t < 2) *op = __float2bfloat16(fmaf((y[0][0] + y[1][0]) + (y[0][2] + y[1][2]), gate, base));
      if (b == 0 && lane == 0) P.s->epoch = lds1(mb + B_SW) & 255;
    }
   }
  }
}

typedef CUresult (*EncodeFn)(CUtensorMap*, CUtensorMapDataType, cuuint32_t, void*, const cuuint64_t*, const cuuint64_t*, const cuuint32_t*,
                             const cuuint32_t*, CUtensorMapInterleave, CUtensorMapSwizzle, CUtensorMapL2promotion, CUtensorMapFloatOOBfill);
void make_map(EncodeFn enc, CUtensorMap* m, const void* p, int rank, std::initializer_list<cuuint64_t> dims, std::initializer_list<cuuint64_t> str,
              std::initializer_list<cuuint32_t> box, CUtensorMapSwizzle sw) {
  const cuuint32_t es[4] = {1, 1, 1, 1};
  enc(m, CU_TENSOR_MAP_DATA_TYPE_BFLOAT16, rank, const_cast<void*>(p), dims.begin(), str.begin(), box.begin(), es, CU_TENSOR_MAP_INTERLEAVE_NONE, sw,
      CU_TENSOR_MAP_L2_PROMOTION_L2_128B, CU_TENSOR_MAP_FLOAT_OOB_FILL_NONE);
}

}

extern "C" void kernel_launch(void* const* d_in, const int* in_sizes, int n_in, void* d_out, int out_size) {
  (void)in_sizes; (void)n_in; (void)out_size;
  Ptrs P;
  P.x = (const __nv_bfloat16*)d_in[0]; P.wqkv = (const __nv_bfloat16*)d_in[1]; P.wo = (const __nv_bfloat16*)d_in[2];
  P.wr = (const __nv_bfloat16*)d_in[4]; P.wg = (const __nv_bfloat16*)d_in[5]; P.wu = (const __nv_bfloat16*)d_in[6];
  P.wd = (const __nv_bfloat16*)d_in[7]; P.out = (__nv_bfloat16*)d_out;
  cudaGetSymbolAddress((void**)&P.s, g_scratch);
  void* fn = nullptr;
  cudaDriverEntryPointQueryResult q;
  cudaGetDriverEntryPoint("cuTensorMapEncodeTiled", &fn, cudaEnableDefault, &q);
  EncodeFn enc = (EncodeFn)fn;
  Maps T;
  constexpr CUtensorMapSwizzle S128 = CU_TENSOR_MAP_SWIZZLE_128B, S64 = CU_TENSOR_MAP_SWIZZLE_64B;
  make_map(enc, &T.m[M_X], P.x, 2, {D_, S_}, {D_ * 2}, {64, 128}, S128);
  make_map(enc, &T.m[M_W], P.wqkv, 3, {D_, D_, 3}, {3 * D_ * 2, D_ * 2}, {64, 64, 2}, S128);
  make_map(enc, &T.m[M_Q], P.wqkv, 2, {3 * D_, D_}, {3 * D_ * 2}, {64, 64}, S128);
  make_map(enc, &T.m[M_O], P.wo, 4, {64, 64, 16, 16}, {D_ * 2, 64 * D_ * 2, 128}, {64, 64, 1, 2}, S128);
  make_map(enc, &T.m[M_S], P.wo, 4, {64, 64, 16, 16}, {D_ * 2, 64 * D_ * 2, 128}, {64, 16, 4, 2}, S128);
  make_map(enc, &T.m[M_G], P.wg, 3, {F_, D_, 1}, {F_ * 2, F_ * 2 * D_}, {32, 128, 1}, S64);
  make_map(enc, &T.m[M_U], P.wu, 3, {F_, D_, 1}, {F_ * 2, F_ * 2 * D_}, {32, 128, 1}, S64);
  make_map(enc, &T.m[M_D], P.wd, 3, {64, F_, 16}, {D_ * 2, 128}, {64, 32, 2}, S128);
  make_map(enc, &T.m[M_L], P.wd, 2, {64, F_ * 16}, {128}, {8, 32}, CU_TENSOR_MAP_SWIZZLE_NONE);
  cudaFuncSetAttribute(fused_kernel, cudaFuncAttributeMaxDynamicSharedMemorySize, SMEM_BYTES);
  fused_kernel<<<NCTA, 384, SMEM_BYTES>>>(P, T);
}
```

```cpp
#include <cuda_runtime.h>
#include <cuda.h>
#include <cuda_bf16.h>
#include <stdint.h>
#include <type_traits>
#include <initializer_list>

namespace {

constexpr int S_ = 2048, D_ = 1024, F_ = 3584;
constexpr int NCTA = 128, NFFN = 112;
constexpr uint32_t SENT = 0xFFFFFFFFu;
constexpr int SPIN_LIMIT = 1 << 20;

#define FD0 700
#define FD1 800
#define GDELAY 400
#define PLAG 8
#define MFIRST 350
#define MKV 1430
#define MO 760
#define ADELAY 200
#define ADELAY2 600
#define R1MID 5
#define SDEL2 500
#define XDELAY 500
#define YDELAY 650
#define GU1 8
#define GU2 20
#define OPACE 450
#define NAP __nanosleep(20)
constexpr uint32_t STAGE_B = 57344;
constexpr uint32_t OFF_STATS = 229376;
constexpr uint32_t OFF_COLSUM = 231424;
constexpr uint32_t OFF_BARS = 232192;
constexpr uint32_t SMEM_BYTES = 232448;
constexpr uint32_t B_FULL = 0, B_EMPTY = 32, B_E = 64, B_AUX = 128, B_EVA = 136, B_EVB = 144, B_BF = 152, B_LATE = 232, B_FFN = 240, B_SW = 248;
constexpr uint32_t B_OUT = B_FULL, B_SEL = B_FULL + 8, B_WR = B_FULL + 16, B_FFD = B_FULL + 24, B_E16 = B_EMPTY + 16, B_KVB = B_EMPTY + 8, B_DUMMY = B_SW + 4,
                   B_GATE = B_EMPTY + 24, B_ID = B_BF + 56, B_KVP = B_BF + 64, B_F15 = B_BF + 72;
constexpr uint32_t UNIT = 8192;
constexpr uint32_t sb = 1024;
constexpr uint32_t bars = sb + OFF_BARS;
constexpr uint64_t tab5(int a, int b, int c, int d, int e, int f, int g, int h, int i = 0, int j = 0) {
  return (uint64_t)a | (uint64_t)b << 5 | (uint64_t)c << 10 | (uint64_t)d << 15 | (uint64_t)e << 20 | (uint64_t)f << 25 | (uint64_t)g << 30 | (uint64_t)h << 35 |
         (uint64_t)i << 40 | (uint64_t)j << 45;
}
constexpr uint64_t BT0 = tab5(4, 11, 18, 25, 7, 9, 16, 0), BT1 = tab5(4, 11, 18, 25, 21, 23, 2, 0);
constexpr uint64_t GT0 = tab5(2, 21, 23, 18, 0, 25, 14, 7), GT1 = tab5(16, 7, 9, 18, 0, 25, 14, 21);
constexpr uint64_t DT0 = tab5(6, 13, 20, 27, 9, 10, 16, 17), DT1 = tab5(6, 13, 20, 27, 23, 24, 2, 3);
__device__ __forceinline__ uint32_t unit_of(uint64_t tab, int i) { return ((uint32_t)(tab >> (5 * i)) & 31) * UNIT; }
__device__ __forceinline__ uint32_t ring_of(int p, int w) { return (p & 1) * (2 * STAGE_B) + ((p & 2) ? 49152 + w * STAGE_B : w * UNIT); }
constexpr uint32_t OFF_LNP = OFF_STATS + 1024;

struct Scratch {
  uint4 obuf[32 * 64 * 128];
  uint4 kvp[16 * 8 * 256];
  uint4 zp[16 * 8 * 16];
  uint4 ybuf[NCTA * NFFN * 2];
  uint4 st1[64 * 48];
  uint4 csp[16 * 8 * 48];
  uint4 st2[S_];
  uint4 hsel[2 * 8 * 128];
  uint32_t cand[8 * 32];
  uint32_t when[32 * 32];
  unsigned epoch;
};
__device__ __align__(1024) Scratch g_scratch;
__device__ __forceinline__ uint32_t smem_u32(const void* p) { return (uint32_t)__cvta_generic_to_shared(p); }
__device__ __forceinline__ void mbar_init(uint32_t bar, uint32_t cnt) { asm volatile("mbarrier.init.shared::cta.b64 [%0], %1;" :: "r"(bar), "r"(cnt) : "memory"); }
__device__ __forceinline__ void mbar_expect_tx(uint32_t bar, uint32_t bytes) { asm volatile("mbarrier.arrive.expect_tx.shared::cta.b64 _, [%0], %1;" :: "r"(bar), "r"(bytes) : "memory"); }
__device__ __forceinline__ void mbar_arrive(uint32_t bar) { asm volatile("mbarrier.arrive.shared::cta.b64 _, [%0];" :: "r"(bar) : "memory"); }
#define SPINCHK(it) if ((it) > SPIN_LIMIT) break
__device__ __forceinline__ void mbar_wait(uint32_t bar, uint32_t parity) {
  asm volatile("{\n.reg .pred p;\n.reg .u32 c;\nmov.u32 c, 0;\n"
               "WL:\nmbarrier.try_wait.parity.shared::cta.b64 p, [%0], %1;\n@p bra WD;\n"
               "add.u32 c, c, 1;\nsetp.lt.u32 p, c, 1048576;\n@p bra WL;\nWD:\n}" :: "r"(bar), "r"(parity) : "memory");
}
__device__ __forceinline__ bool mbar_test(uint32_t bar, uint32_t parity) {
  uint32_t ok;
  asm volatile("{\n.reg .pred p;\nmbarrier.test_wait.parity.shared::cta.b64 p, [%1], %2;\nselp.u32 %0, 1, 0, p;\n}" : "=r"(ok) : "r"(bar), "r"(parity) : "memory");
  return ok;
}
__device__ __forceinline__ uint64_t l2_stream() { uint64_t p; asm("createpolicy.fractional.L2::evict_first.b64 %0, 1.0;" : "=l"(p)); return p; }
__device__ __forceinline__ void tma_2d(uint32_t dst, const CUtensorMap* tm, int c0, int c1, uint32_t bar, bool stream) {
  if (stream) asm volatile("cp.async.bulk.tensor.2d.shared::cluster.global.mbarrier::complete_tx::bytes.L2::cache_hint [%0], [%1, {%3, %4}], [%2], %5;"
                           :: "r"(dst), "l"(tm), "r"(bar), "r"(c0), "r"(c1), "l"(l2_stream()) : "memory");
  else asm volatile("cp.async.bulk.tensor.2d.shared::cluster.global.mbarrier::complete_tx::bytes [%0], [%1, {%3, %4}], [%2];"
                    :: "r"(dst), "l"(tm), "r"(bar), "r"(c0), "r"(c1) : "memory");
}
__device__ __forceinline__ void tma_3d(uint32_t dst, const CUtensorMap* tm, int c0, int c1, int c2, uint32_t bar, bool stream) {
  if (stream) asm volatile("cp.async.bulk.tensor.3d.shared::cluster.global.mbarrier::complete_tx::bytes.L2::cache_hint [%0], [%1, {%3, %4, %5}], [%2], %6;"
                           :: "r"(dst), "l"(tm), "r"(bar), "r"(c0), "r"(c1), "r"(c2), "l"(l2_stream()) : "memory");
  else asm volatile("cp.async.bulk.tensor.3d.shared::cluster.global.mbarrier::complete_tx::bytes [%0], [%1, {%3, %4, %5}], [%2];"
                    :: "r"(dst), "l"(tm), "r"(bar), "r"(c0), "r"(c1), "r"(c2) : "memory");
}
__device__ __forceinline__ void tma_4d(uint32_t dst, const CUtensorMap* tm, int c0, int c1, int c2, int c3, uint32_t bar) {
  asm volatile("cp.async.bulk.tensor.4d.shared::cluster.global.mbarrier::complete_tx::bytes.L2::cache_hint [%0], [%1, {%3, %4, %5, %6}], [%2], %7;"
               :: "r"(dst), "l"(tm), "r"(bar), "r"(c0), "r"(c1), "r"(c2), "r"(c3), "l"(l2_stream()) : "memory");
}
__device__ __forceinline__ void tma_2d_mc(uint32_t dst, const CUtensorMap* tm, int c0, int c1, uint32_t bar, bool stream) {
  if (stream) asm volatile("cp.async.bulk.tensor.2d.shared::cluster.global.mbarrier::complete_tx::bytes.multicast::cluster.L2::cache_hint [%0], [%1, {%3, %4}], [%2], %5, %6;"
                           :: "r"(dst), "l"(tm), "r"(bar), "r"(c0), "r"(c1), "h"((uint16_t)3), "l"(l2_stream()) : "memory");
  else asm volatile("cp.async.bulk.tensor.2d.shared::cluster.global.mbarrier::complete_tx::bytes.multicast::cluster [%0], [%1, {%3, %4}], [%2], %5;"
                    :: "r"(dst), "l"(tm), "r"(bar), "r"(c0), "r"(c1), "h"((uint16_t)3) : "memory");
}
__device__ __forceinline__ bool elect_one() {
  uint32_t p;
  asm volatile("{\n.reg .pred q;\nelect.sync _|q, 0xFFFFFFFF;\nselp.u32 %0, 1, 0, q;\n}" : "=r"(p));
  return p;
}
__device__ __forceinline__ void bulk_load_mc(uint32_t dst, const void* src, uint32_t bytes, uint32_t bar) {
  asm volatile("cp.async.bulk.shared::cluster.global.mbarrier::complete_tx::bytes.multicast::cluster [%0], [%1], %2, [%3], %4;"
               :: "r"(dst), "l"(src), "r"(bytes), "r"(bar), "h"((uint16_t)3) : "memory");
}
__device__ __forceinline__ void bulk_load(uint32_t dst, const void* src, uint32_t bytes, uint32_t bar) {
  asm volatile("cp.async.bulk.shared::cluster.global.mbarrier::complete_tx::bytes [%0], [%1], %2, [%3];" :: "r"(dst), "l"(src), "r"(bytes), "r"(bar) : "memory");
}
__device__ __forceinline__ void bulk_store(void* dst, uint32_t src, uint32_t bytes) {
  asm volatile("cp.async.bulk.global.shared::cta.bulk_group [%0], [%1], %2;" :: "l"(dst), "r"(src), "r"(bytes) : "memory");
}
__device__ __forceinline__ void mbar_arrive_rem(uint32_t bar) { asm volatile("mbarrier.arrive.shared::cluster.b64 _, [%0];" :: "r"(bar) : "memory"); }
template <uint32_t O> __device__ __forceinline__ void ldsm4_o(uint32_t addr, uint32_t& a, uint32_t& b, uint32_t& c, uint32_t& d) {
  asm volatile("ldmatrix.sync.aligned.m8n8.x4.shared.b16 {%0,%1,%2,%3}, [%4+%5];" : "=r"(a), "=r"(b), "=r"(c), "=r"(d) : "r"(addr), "n"(O) : "memory");
}
template <uint32_t O> __device__ __forceinline__ void ldsm4t_o(uint32_t addr, uint32_t (&r)[4]) {
  asm volatile("ldmatrix.sync.aligned.m8n8.x4.trans.shared.b16 {%0,%1,%2,%3}, [%4+%5];" : "=r"(r[0]), "=r"(r[1]), "=r"(r[2]), "=r"(r[3]) : "r"(addr), "n"(O) : "memory");
}
__device__ __forceinline__ void mma16816(float (&c)[4], const uint32_t (&a)[4], uint32_t b0, uint32_t b1) {
  asm("mma.sync.aligned.m16n8k16.row.col.f32.bf16.bf16.f32 {%0,%1,%2,%3}, {%4,%5,%6,%7}, {%8,%9}, {%0,%1,%2,%3};"
      : "+f"(c[0]), "+f"(c[1]), "+f"(c[2]), "+f"(c[3]) : "r"(a[0]), "r"(a[1]), "r"(a[2]), "r"(a[3]), "r"(b0), "r"(b1));
}
__device__ __forceinline__ void l2_prefetch(const void* p) { asm volatile("prefetch.global.L2 [%0];" :: "l"(p) : "memory"); }
__device__ __forceinline__ void tmap_prefetch(const CUtensorMap* tm) { asm volatile("prefetch.tensormap [%0];" :: "l"(tm) : "memory"); }
__device__ __forceinline__ void wg_fence() { asm volatile("wgmma.fence.sync.aligned;" ::: "memory"); }
__device__ __forceinline__ void wg_commit() { asm volatile("wgmma.commit_group.sync.aligned;" ::: "memory"); }
template <int N> __device__ __forceinline__ void wg_wait() { asm volatile("wgmma.wait_group.sync.aligned %0;" :: "n"(N) : "memory"); }
template <int N> __device__ __forceinline__ void pin(float (&d)[N]) {
#pragma unroll
  for (int i = 0; i < N; i++) asm volatile("" : "+f"(d[i]) :: "memory");
}
__device__ __forceinline__ void pin4(uint4& v) { asm volatile("" : "+r"(v.x), "+r"(v.y), "+r"(v.z), "+r"(v.w) :: "memory"); }
template <uint32_t SBO, uint32_t SWZ> __device__ __forceinline__ uint64_t dsc(uint32_t lo) { return ((uint64_t)((SBO >> 4) | (SWZ << 30)) << 32) | lo; }
__host__ __device__ constexpr uint32_t dlo(uint32_t addr, uint32_t lbo) { return (addr >> 4) | ((lbo >> 4) << 16); }
__device__ __forceinline__ void bar_sync(int id, int n) { asm volatile("bar.sync %0, %1;" :: "r"(id), "r"(n) : "memory"); }
__device__ __forceinline__ void bar_arrive(int id, int n) { asm volatile("bar.arrive %0, %1;" :: "r"(id), "r"(n) : "memory"); }
__device__ __forceinline__ void fence_async_smem() { asm volatile("fence.proxy.async.shared::cta;" ::: "memory"); }
__device__ __forceinline__ void fence_gpu() { asm volatile("fence.acq_rel.gpu;" ::: "memory"); }
__device__ __forceinline__ uint4 ld_cg4(const void* p) { uint4 v; asm volatile("ld.global.cg.v4.u32 {%0,%1,%2,%3}, [%4];" : "=r"(v.x), "=r"(v.y), "=r"(v.z), "=r"(v.w) : "l"(p) : "memory"); return v; }
__device__ __forceinline__ uint4 ld_rlx4(const void* p) { uint4 v; asm volatile("ld.relaxed.gpu.global.v4.u32 {%0,%1,%2,%3}, [%4];" : "=r"(v.x), "=r"(v.y), "=r"(v.z), "=r"(v.w) : "l"(p) : "memory"); return v; }
__device__ __forceinline__ uint32_t ld_rlx(const void* p) { uint32_t v; asm volatile("ld.relaxed.gpu.global.u32 %0, [%1];" : "=r"(v) : "l"(p) : "memory"); return v; }
__device__ __forceinline__ void st_rlx4(void* p, uint4 v) { asm volatile("st.relaxed.gpu.global.v4.u32 [%0], {%1,%2,%3,%4};" :: "l"(p), "r"(v.x), "r"(v.y), "r"(v.z), "r"(v.w) : "memory"); }
__device__ __forceinline__ void st_rlx2(void* p, uint32_t a, uint32_t b) { asm volatile("st.relaxed.gpu.global.v2.u32 [%0], {%1,%2};" :: "l"(p), "r"(a), "r"(b) : "memory"); }
__device__ __forceinline__ void st_rlx(void* p, uint32_t a) { asm volatile("st.relaxed.gpu.global.u32 [%0], %1;" :: "l"(p), "r"(a) : "memory"); }
__device__ __forceinline__ uint32_t pack2(float lo, float hi) { uint32_t r; asm("cvt.rn.bf16x2.f32 %0, %1, %2;" : "=r"(r) : "f"(hi), "f"(lo)); return r; }
__device__ __forceinline__ float bf_lo(uint32_t v) { return __uint_as_float(v << 16); }
__device__ __forceinline__ float bf_hi(uint32_t v) { return __uint_as_float(v & 0xFFFF0000u); }
__device__ __forceinline__ void stsm4(uint32_t addr, uint32_t a, uint32_t b, uint32_t c, uint32_t d) {
  asm volatile("stmatrix.sync.aligned.m8n8.x4.shared.b16 [%0], {%1,%2,%3,%4};" :: "r"(addr), "r"(a), "r"(b), "r"(c), "r"(d) : "memory");
}
template <uint32_t O> __device__ __forceinline__ void stsm4_o(uint32_t addr, uint32_t a, uint32_t b, uint32_t c, uint32_t d) {
  asm volatile("stmatrix.sync.aligned.m8n8.x4.shared.b16 [%0+%5], {%1,%2,%3,%4};" :: "r"(addr), "r"(a), "r"(b), "r"(c), "r"(d), "n"(O) : "memory");
}
__device__ __forceinline__ void sts4(uint32_t addr, uint32_t a, uint32_t b, uint32_t c, uint32_t d) { asm volatile("st.shared.v4.u32 [%0], {%1,%2,%3,%4};" :: "r"(addr), "r"(a), "r"(b), "r"(c), "r"(d) : "memory"); }
__device__ __forceinline__ void sts2f(uint32_t addr, float a, float b) { asm volatile("st.shared.v2.f32 [%0], {%1,%2};" :: "r"(addr), "f"(a), "f"(b) : "memory"); }
__device__ __forceinline__ void sts1(uint32_t addr, uint32_t a) { asm volatile("st.shared.u32 [%0], %1;" :: "r"(addr), "r"(a) : "memory"); }
__device__ __forceinline__ float2 lds2f(uint32_t addr) { float2 v; asm volatile("ld.shared.v2.f32 {%0,%1}, [%2];" : "=f"(v.x), "=f"(v.y) : "r"(addr) : "memory"); return v; }
template <uint32_t O> __device__ __forceinline__ float2 lds2f_o(uint32_t addr) { float2 v; asm volatile("ld.shared.v2.f32 {%0,%1}, [%2+%3];" : "=f"(v.x), "=f"(v.y) : "r"(addr), "n"(O) : "memory"); return v; }
template <int I, int N, class F> __device__ __forceinline__ void static_for(F&& f) { if constexpr (I < N) { f(std::integral_constant<int, I>{}); static_for<I + 1, N>(f); } }
__device__ __forceinline__ uint4 lds4(uint32_t addr) { uint4 v; asm volatile("ld.shared.v4.u32 {%0,%1,%2,%3}, [%4];" : "=r"(v.x), "=r"(v.y), "=r"(v.z), "=r"(v.w) : "r"(addr) : "memory"); return v; }
__device__ __forceinline__ uint32_t lds1(uint32_t addr) { uint32_t v; asm volatile("ld.shared.u32 %0, [%1];" : "=r"(v) : "r"(addr) : "memory"); return v; }
__device__ __forceinline__ float ex2(float x) { float y; asm("ex2.approx.ftz.f32 %0, %1;" : "=f"(y) : "f"(x)); return y; }
__device__ __forceinline__ uint32_t max4(uint32_t m, const uint4& v) { return __vimax3_u32(__vimax3_u32(m, v.x, v.y), v.z, v.w); }
__device__ __forceinline__ float rsq(float x) { float y; asm("rsqrt.approx.ftz.f32 %0, %1;" : "=f"(y) : "f"(x)); return y; }
__device__ __forceinline__ float rcp(float x) { float y; asm("rcp.approx.ftz.f32 %0, %1;" : "=f"(y) : "f"(x)); return y; }
__device__ __forceinline__ uint2 ld_rlx2(const void* p) { uint2 v; asm volatile("ld.relaxed.gpu.global.v2.u32 {%0,%1}, [%2];" : "=r"(v.x), "=r"(v.y) : "l"(p) : "memory"); return v; }
template <uint32_t O> __device__ __forceinline__ uint4 lds4_o(uint32_t addr) { uint4 v; asm volatile("ld.shared.v4.u32 {%0,%1,%2,%3}, [%4+%5];" : "=r"(v.x), "=r"(v.y), "=r"(v.z), "=r"(v.w) : "r"(addr), "n"(O) : "memory"); return v; }
__device__ __forceinline__ uint32_t phi2(float u0, float u1, float rl, uint32_t r2) {
  uint32_t pu, r;
  asm("cvt.rn.relu.bf16x2.f32 %0, %1, %2;" : "=r"(pu) : "f"(u1), "f"(u0));
  asm("fma.rn.bf16x2 %0, %1, %2, %3;" : "=r"(r) : "r"(pu), "r"(r2), "r"(pack2(__saturatef(ex2(u0 * rl) + 1e-6f), __saturatef(ex2(u1 * rl) + 1e-6f))));
  return r;
}
__device__ __forceinline__ uint32_t dup2(float r) { uint32_t v; asm("cvt.rn.relu.bf16x2.f32 %0, %1, %1;" : "=r"(v) : "f"(r)); return v; }
__device__ __forceinline__ uint32_t zero_after(const uint32_t (&v)[16]) {
  uint32_t z = 0;
#pragma unroll
  for (int i = 0; i < 16; i++) z |= v[i];
  return z & 0x80008000u;
}
__device__ __forceinline__ uint32_t hadd2(uint32_t a, uint32_t b) { uint32_t v; asm("add.rn.bf16x2 %0, %1, %2;" : "=r"(v) : "r"(a), "r"(b)); return v; }
__device__ __forceinline__ void sched_fence() { asm volatile("{\n.reg .pred p;\n.reg .u64 c;\nSF:\nmov.u64 c, %clock64;\nsetp.eq.u64 p, c, 0;\n@p bra SF;\n}" ::: "memory"); }
__device__ __forceinline__ uint32_t now_ns() { uint32_t v; asm volatile("mov.u32 %0, %%globaltimer_lo;" : "=r"(v) :: "memory"); return v; }
__device__ __forceinline__ void meet(uint32_t* mine, const uint4* all, int first, int after, uint32_t bar) {
  const uint32_t t0 = now_ns() & ~1u;
  if ((threadIdx.x & 31) == 0) st_rlx(mine, t0);
  while ((int)(now_ns() - t0) < first) NAP;
  uint4 v;
#pragma unroll 1
  for (int it = 0; it < SPIN_LIMIT; it++) { v = ld_rlx4(all); if (!__any_sync(~0u, max4(0, v) == SENT)) break; }
  const int d = min(__reduce_max_sync(~0u, max(max((int)(v.x - t0), (int)(v.y - t0)), max((int)(v.z - t0), (int)(v.w - t0)))), 100000) + after;
  mbar_wait(bar, 0);
  while ((int)(now_ns() - t0) < d) NAP;
}
__device__ __forceinline__ uint32_t hmul2(uint32_t a, uint32_t b) { uint32_t v; asm("mul.rn.bf16x2 %0, %1, %2;" : "=r"(v) : "r"(a), "r"(b)); return v; }
__device__ __forceinline__ uint32_t lane_id() { uint32_t v; asm volatile("mov.u32 %0, %%laneid;" : "=r"(v)); return v; }
template <int A, int B, int N> __device__ __forceinline__ void pinr(float (&d)[N]) {
#pragma unroll
  for (int i = A; i < B; i++) asm volatile("" : "+f"(d[i]) :: "memory");
}
template <int N> __device__ __forceinline__ void pinu(uint32_t (&d)[N]) {
#pragma unroll
  for (int i = 0; i < N; i++) asm volatile("" : "+r"(d[i]) :: "memory");
}

template<int TA, int TB, int OFF, int SZ> __device__ __forceinline__ void wgmma_n192_ss(float (&d)[SZ], uint64_t da, uint64_t db, int scale_d) {
  asm volatile("{\n.reg .pred p;\nsetp.ne.b32 p, %98, 0;\n"
    "wgmma.mma_async.sync.aligned.m64n192k16.f32.bf16.bf16 {%0,%1,%2,%3,%4,%5,%6,%7,%8,%9,%10,%11,%12,%13,%14,%15,%16,%17,%18,%19,%20,%21,%22,%23,%24,%25,%26,%27,%28,%29,%30,%31,%32,%33,%34,%35,%36,%37,%38,%39,%40,%41,%42,%43,%44,%45,%46,%47,%48,%49,%50,%51,%52,%53,%54,%55,%56,%57,%58,%59,%60,%61,%62,%63,%64,%65,%66,%67,%68,%69,%70,%71,%72,%73,%74,%75,%76,%77,%78,%79,%80,%81,%82,%83,%84,%85,%86,%87,%88,%89,%90,%91,%92,%93,%94,%95}, %96, %97, p, 1, 1, %99, %100;\n}\n"
    : "+f"(d[OFF+0]), "+f"(d[OFF+1]), "+f"(d[OFF+2]), "+f"(d[OFF+3]), "+f"(d[OFF+4]), "+f"(d[OFF+5]), "+f"(d[OFF+6]), "+f"(d[OFF+7]),
      "+f"(d[OFF+8]), "+f"(d[OFF+9]), "+f"(d[OFF+10]), "+f"(d[OFF+11]), "+f"(d[OFF+12]), "+f"(d[OFF+13]), "+f"(d[OFF+14]), "+f"(d[OFF+15]),
      "+f"(d[OFF+16]), "+f"(d[OFF+17]), "+f"(d[OFF+18]), "+f"(d[OFF+19]), "+f"(d[OFF+20]), "+f"(d[OFF+21]), "+f"(d[OFF+22]), "+f"(d[OFF+23]),
      "+f"(d[OFF+24]), "+f"(d[OFF+25]), "+f"(d[OFF+26]), "+f"(d[OFF+27]), "+f"(d[OFF+28]), "+f"(d[OFF+29]), "+f"(d[OFF+30]), "+f"(d[OFF+31]),
      "+f"(d[OFF+32]), "+f"(d[OFF+33]), "+f"(d[OFF+34]), "+f"(d[OFF+35]), "+f"(d[OFF+36]), "+f"(d[OFF+37]), "+f"(d[OFF+38]), "+f"(d[OFF+39]),
      "+f"(d[OFF+40]), "+f"(d[OFF+41]), "+f"(d[OFF+42]), "+f"(d[OFF+43]), "+f"(d[OFF+44]), "+f"(d[OFF+45]), "+f"(d[OFF+46]), "+f"(d[OFF+47]),
      "+f"(d[OFF+48]), "+f"(d[OFF+49]), "+f"(d[OFF+50]), "+f"(d[OFF+51]), "+f"(d[OFF+52]), "+f"(d[OFF+53]), "+f"(d[OFF+54]), "+f"(d[OFF+55]),
      "+f"(d[OFF+56]), "+f"(d[OFF+57]), "+f"(d[OFF+58]), "+f"(d[OFF+59]), "+f"(d[OFF+60]), "+f"(d[OFF+61]), "+f"(d[OFF+62]), "+f"(d[OFF+63]),
      "+f"(d[OFF+64]), "+f"(d[OFF+65]), "+f"(d[OFF+66]), "+f"(d[OFF+67]), "+f"(d[OFF+68]), "+f"(d[OFF+69]), "+f"(d[OFF+70]), "+f"(d[OFF+71]),
      "+f"(d[OFF+72]), "+f"(d[OFF+73]), "+f"(d[OFF+74]), "+f"(d[OFF+75]), "+f"(d[OFF+76]), "+f"(d[OFF+77]), "+f"(d[OFF+78]), "+f"(d[OFF+79]),
      "+f"(d[OFF+80]), "+f"(d[OFF+81]), "+f"(d[OFF+82]), "+f"(d[OFF+83]), "+f"(d[OFF+84]), "+f"(d[OFF+85]), "+f"(d[OFF+86]), "+f"(d[OFF+87]),
      "+f"(d[OFF+88]), "+f"(d[OFF+89]), "+f"(d[OFF+90]), "+f"(d[OFF+91]), "+f"(d[OFF+92]), "+f"(d[OFF+93]), "+f"(d[OFF+94]), "+f"(d[OFF+95])
    : "l"(da), "l"(db), "r"(scale_d), "n"(TA), "n"(TB));
}
template<int TA, int TB, int OFF, int SZ> __device__ __forceinline__ void wgmma_n128_ss(float (&d)[SZ], uint64_t da, uint64_t db, int scale_d) {
  asm volatile("{\n.reg .pred p;\nsetp.ne.b32 p, %66, 0;\n"
    "wgmma.mma_async.sync.aligned.m64n128k16.f32.bf16.bf16 {%0,%1,%2,%3,%4,%5,%6,%7,%8,%9,%10,%11,%12,%13,%14,%15,%16,%17,%18,%19,%20,%21,%22,%23,%24,%25,%26,%27,%28,%29,%30,%31,%32,%33,%34,%35,%36,%37,%38,%39,%40,%41,%42,%43,%44,%45,%46,%47,%48,%49,%50,%51,%52,%53,%54,%55,%56,%57,%58,%59,%60,%61,%62,%63}, %64, %65, p, 1, 1, %67, %68;\n}\n"
    : "+f"(d[OFF+0]), "+f"(d[OFF+1]), "+f"(d[OFF+2]), "+f"(d[OFF+3]), "+f"(d[OFF+4]), "+f"(d[OFF+5]), "+f"(d[OFF+6]), "+f"(d[OFF+7]),
      "+f"(d[OFF+8]), "+f"(d[OFF+9]), "+f"(d[OFF+10]), "+f"(d[OFF+11]), "+f"(d[OFF+12]), "+f"(d[OFF+13]), "+f"(d[OFF+14]), "+f"(d[OFF+15]),
      "+f"(d[OFF+16]), "+f"(d[OFF+17]), "+f"(d[OFF+18]), "+f"(d[OFF+19]), "+f"(d[OFF+20]), "+f"(d[OFF+21]), "+f"(d[OFF+22]), "+f"(d[OFF+23]),
      "+f"(d[OFF+24]), "+f"(d[OFF+25]), "+f"(d[OFF+26]), "+f"(d[OFF+27]), "+f"(d[OFF+28]), "+f"(d[OFF+29]), "+f"(d[OFF+30]), "+f"(d[OFF+31]),
      "+f"(d[OFF+32]), "+f"(d[OFF+33]), "+f"(d[OFF+34]), "+f"(d[OFF+35]), "+f"(d[OFF+36]), "+f"(d[OFF+37]), "+f"(d[OFF+38]), "+f"(d[OFF+39]),
      "+f"(d[OFF+40]), "+f"(d[OFF+41]), "+f"(d[OFF+42]), "+f"(d[OFF+43]), "+f"(d[OFF+44]), "+f"(d[OFF+45]), "+f"(d[OFF+46]), "+f"(d[OFF+47]),
      "+f"(d[OFF+48]), "+f"(d[OFF+49]), "+f"(d[OFF+50]), "+f"(d[OFF+51]), "+f"(d[OFF+52]), "+f"(d[OFF+53]), "+f"(d[OFF+54]), "+f"(d[OFF+55]),
      "+f"(d[OFF+56]), "+f"(d[OFF+57]), "+f"(d[OFF+58]), "+f"(d[OFF+59]), "+f"(d[OFF+60]), "+f"(d[OFF+61]), "+f"(d[OFF+62]), "+f"(d[OFF+63])
    : "l"(da), "l"(db), "r"(scale_d), "n"(TA), "n"(TB));
}
template<int TA, int TB, int OFF, int SZ> __device__ __forceinline__ void wgmma_n64_ss(float (&d)[SZ], uint64_t da, uint64_t db, int scale_d) {
  asm volatile("{\n.reg .pred p;\nsetp.ne.b32 p, %34, 0;\n"
    "wgmma.mma_async.sync.aligned.m64n64k16.f32.bf16.bf16 {%0,%1,%2,%3,%4,%5,%6,%7,%8,%9,%10,%11,%12,%13,%14,%15,%16,%17,%18,%19,%20,%21,%22,%23,%24,%25,%26,%27,%28,%29,%30,%31}, %32, %33, p, 1, 1, %35, %36;\n}\n"
    : "+f"(d[OFF+0]), "+f"(d[OFF+1]), "+f"(d[OFF+2]), "+f"(d[OFF+3]), "+f"(d[OFF+4]), "+f"(d[OFF+5]), "+f"(d[OFF+6]), "+f"(d[OFF+7]),
      "+f"(d[OFF+8]), "+f"(d[OFF+9]), "+f"(d[OFF+10]), "+f"(d[OFF+11]), "+f"(d[OFF+12]), "+f"(d[OFF+13]), "+f"(d[OFF+14]), "+f"(d[OFF+15]),
      "+f"(d[OFF+16]), "+f"(d[OFF+17]), "+f"(d[OFF+18]), "+f"(d[OFF+19]), "+f"(d[OFF+20]), "+f"(d[OFF+21]), "+f"(d[OFF+22]), "+f"(d[OFF+23]),
      "+f"(d[OFF+24]), "+f"(d[OFF+25]), "+f"(d[OFF+26]), "+f"(d[OFF+27]), "+f"(d[OFF+28]), "+f"(d[OFF+29]), "+f"(d[OFF+30]), "+f"(d[OFF+31])
    : "l"(da), "l"(db), "r"(scale_d), "n"(TA), "n"(TB));
}
template<int TA, int TB, int OFF, int SZ> __device__ __forceinline__ void wgmma_n72_ss(float (&d)[SZ], uint64_t da, uint64_t db, int scale_d) {
  asm volatile("{\n.reg .pred p;\nsetp.ne.b32 p, %38, 0;\n"
    "wgmma.mma_async.sync.aligned.m64n72k16.f32.bf16.bf16 {%0,%1,%2,%3,%4,%5,%6,%7,%8,%9,%10,%11,%12,%13,%14,%15,%16,%17,%18,%19,%20,%21,%22,%23,%24,%25,%26,%27,%28,%29,%30,%31,%32,%33,%34,%35}, %36, %37, p, 1, 1, %39, %40;\n}\n"
    : "+f"(d[OFF+0]), "+f"(d[OFF+1]), "+f"(d[OFF+2]), "+f"(d[OFF+3]), "+f"(d[OFF+4]), "+f"(d[OFF+5]), "+f"(d[OFF+6]), "+f"(d[OFF+7]),
      "+f"(d[OFF+8]), "+f"(d[OFF+9]), "+f"(d[OFF+10]), "+f"(d[OFF+11]), "+f"(d[OFF+12]), "+f"(d[OFF+13]), "+f"(d[OFF+14]), "+f"(d[OFF+15]),
      "+f"(d[OFF+16]), "+f"(d[OFF+17]), "+f"(d[OFF+18]), "+f"(d[OFF+19]), "+f"(d[OFF+20]), "+f"(d[OFF+21]), "+f"(d[OFF+22]), "+f"(d[OFF+23]),
      "+f"(d[OFF+24]), "+f"(d[OFF+25]), "+f"(d[OFF+26]), "+f"(d[OFF+27]), "+f"(d[OFF+28]), "+f"(d[OFF+29]), "+f"(d[OFF+30]), "+f"(d[OFF+31]),
      "+f"(d[OFF+32]), "+f"(d[OFF+33]), "+f"(d[OFF+34]), "+f"(d[OFF+35])
    : "l"(da), "l"(db), "r"(scale_d), "n"(TA), "n"(TB));
}
template<int TB, int OFF, int SZ> __device__ __forceinline__ void wgmma_n64_rs(float (&d)[SZ], uint32_t a0, uint32_t a1, uint32_t a2, uint32_t a3, uint64_t db, int scale_d) {
  asm volatile("{\n.reg .pred p;\nsetp.ne.b32 p, %37, 0;\n"
    "wgmma.mma_async.sync.aligned.m64n64k16.f32.bf16.bf16 {%0,%1,%2,%3,%4,%5,%6,%7,%8,%9,%10,%11,%12,%13,%14,%15,%16,%17,%18,%19,%20,%21,%22,%23,%24,%25,%26,%27,%28,%29,%30,%31}, {%32,%33,%34,%35}, %36, p, 1, 1, %38;\n}\n"
    : "+f"(d[OFF+0]), "+f"(d[OFF+1]), "+f"(d[OFF+2]), "+f"(d[OFF+3]), "+f"(d[OFF+4]), "+f"(d[OFF+5]), "+f"(d[OFF+6]), "+f"(d[OFF+7]),
      "+f"(d[OFF+8]), "+f"(d[OFF+9]), "+f"(d[OFF+10]), "+f"(d[OFF+11]), "+f"(d[OFF+12]), "+f"(d[OFF+13]), "+f"(d[OFF+14]), "+f"(d[OFF+15]),
      "+f"(d[OFF+16]), "+f"(d[OFF+17]), "+f"(d[OFF+18]), "+f"(d[OFF+19]), "+f"(d[OFF+20]), "+f"(d[OFF+21]), "+f"(d[OFF+22]), "+f"(d[OFF+23]),
      "+f"(d[OFF+24]), "+f"(d[OFF+25]), "+f"(d[OFF+26]), "+f"(d[OFF+27]), "+f"(d[OFF+28]), "+f"(d[OFF+29]), "+f"(d[OFF+30]), "+f"(d[OFF+31])
    : "r"(a0), "r"(a1), "r"(a2), "r"(a3), "l"(db), "r"(scale_d), "n"(TB));
}
template<int TB, int OFF, int SZ> __device__ __forceinline__ void wgmma_n40_rs(float (&d)[SZ], uint32_t a0, uint32_t a1, uint32_t a2, uint32_t a3, uint64_t db, int scale_d) {
  asm volatile("{\n.reg .pred p;\nsetp.ne.b32 p, %25, 0;\n"
    "wgmma.mma_async.sync.aligned.m64n40k16.f32.bf16.bf16 {%0,%1,%2,%3,%4,%5,%6,%7,%8,%9,%10,%11,%12,%13,%14,%15,%16,%17,%18,%19}, {%20,%21,%22,%23}, %24, p, 1, 1, %26;\n}\n"
    : "+f"(d[OFF+0]), "+f"(d[OFF+1]), "+f"(d[OFF+2]), "+f"(d[OFF+3]), "+f"(d[OFF+4]), "+f"(d[OFF+5]), "+f"(d[OFF+6]), "+f"(d[OFF+7]),
      "+f"(d[OFF+8]), "+f"(d[OFF+9]), "+f"(d[OFF+10]), "+f"(d[OFF+11]), "+f"(d[OFF+12]), "+f"(d[OFF+13]), "+f"(d[OFF+14]), "+f"(d[OFF+15]),
      "+f"(d[OFF+16]), "+f"(d[OFF+17]), "+f"(d[OFF+18]), "+f"(d[OFF+19])
    : "r"(a0), "r"(a1), "r"(a2), "r"(a3), "l"(db), "r"(scale_d), "n"(TB));
}
template<int TB, int OFF, int SZ> __device__ __forceinline__ void wgmma_n128_rs(float (&d)[SZ], uint32_t a0, uint32_t a1, uint32_t a2, uint32_t a3, uint64_t db, int scale_d) {
  asm volatile("{\n.reg .pred p;\nsetp.ne.b32 p, %69, 0;\n"
    "wgmma.mma_async.sync.aligned.m64n128k16.f32.bf16.bf16 {%0,%1,%2,%3,%4,%5,%6,%7,%8,%9,%10,%11,%12,%13,%14,%15,%16,%17,%18,%19,%20,%21,%22,%23,%24,%25,%26,%27,%28,%29,%30,%31,%32,%33,%34,%35,%36,%37,%38,%39,%40,%41,%42,%43,%44,%45,%46,%47,%48,%49,%50,%51,%52,%53,%54,%55,%56,%57,%58,%59,%60,%61,%62,%63}, {%64,%65,%66,%67}, %68, p, 1, 1, %70;\n}\n"
    : "+f"(d[OFF+0]), "+f"(d[OFF+1]), "+f"(d[OFF+2]), "+f"(d[OFF+3]), "+f"(d[OFF+4]), "+f"(d[OFF+5]), "+f"(d[OFF+6]), "+f"(d[OFF+7]),
      "+f"(d[OFF+8]), "+f"(d[OFF+9]), "+f"(d[OFF+10]), "+f"(d[OFF+11]), "+f"(d[OFF+12]), "+f"(d[OFF+13]), "+f"(d[OFF+14]), "+f"(d[OFF+15]),
      "+f"(d[OFF+16]), "+f"(d[OFF+17]), "+f"(d[OFF+18]), "+f"(d[OFF+19]), "+f"(d[OFF+20]), "+f"(d[OFF+21]), "+f"(d[OFF+22]), "+f"(d[OFF+23]),
      "+f"(d[OFF+24]), "+f"(d[OFF+25]), "+f"(d[OFF+26]), "+f"(d[OFF+27]), "+f"(d[OFF+28]), "+f"(d[OFF+29]), "+f"(d[OFF+30]), "+f"(d[OFF+31]),
      "+f"(d[OFF+32]), "+f"(d[OFF+33]), "+f"(d[OFF+34]), "+f"(d[OFF+35]), "+f"(d[OFF+36]), "+f"(d[OFF+37]), "+f"(d[OFF+38]), "+f"(d[OFF+39]),
      "+f"(d[OFF+40]), "+f"(d[OFF+41]), "+f"(d[OFF+42]), "+f"(d[OFF+43]), "+f"(d[OFF+44]), "+f"(d[OFF+45]), "+f"(d[OFF+46]), "+f"(d[OFF+47]),
      "+f"(d[OFF+48]), "+f"(d[OFF+49]), "+f"(d[OFF+50]), "+f"(d[OFF+51]), "+f"(d[OFF+52]), "+f"(d[OFF+53]), "+f"(d[OFF+54]), "+f"(d[OFF+55]),
      "+f"(d[OFF+56]), "+f"(d[OFF+57]), "+f"(d[OFF+58]), "+f"(d[OFF+59]), "+f"(d[OFF+60]), "+f"(d[OFF+61]), "+f"(d[OFF+62]), "+f"(d[OFF+63])
    : "r"(a0), "r"(a1), "r"(a2), "r"(a3), "l"(db), "r"(scale_d), "n"(TB));
}

struct Ptrs { const __nv_bfloat16 *x, *wqkv, *wo, *wr, *wg, *wu, *wd; __nv_bfloat16* out; Scratch* s; };

enum { M_X, M_W, M_Q, M_O, M_S, M_G, M_U, M_D, M_L, M_N };
struct Maps { CUtensorMap m[M_N]; };

__global__ void __cluster_dims__(2, 1, 1) __launch_bounds__(384, 1) fused_kernel(const Ptrs P, const __grid_constant__ Maps T) {
  extern __shared__ __align__(1024) uint8_t smem_raw[];
  const uint32_t rank = blockIdx.x & 1;
  uint32_t own = rank << 24;
  asm("" : "+r"(own));
  const uint32_t sm = own + sb, mb = own + bars;
  int b0;
  { const int j = blockIdx.x >> 1, u = j - 36, v = j * 2 - 8 + (max(u * 37 + 256, 0) >> 8) * (u < 0 ? 0 : 2), w = j < 4 ? j * 16 + 64 : v;
    b0 = ((w & 15) | (w & 48) << 1 | (w & 64) >> 2) + rank; }
#define IDS(B) \
  const int b = (B), rb = b >> 4, cg = b & 15, hf = cg >> 3, s3 = cg & 7, c3 = s3 ^ ((rb & 1) << 2), jp = cg >> 1, km = (~c3 & 6) << 1; \
  const int fidx = jp == rb ? -1 : b - 2 * rb - (jp > rb ? 2 : 0); \
  [[maybe_unused]] auto kcol = [&](int kb) { return (kb ^ (kb < 8 ? km & 8 : km)) * 64; }; \
  auto src_of = [&](int p) { return p == 0 ? s3 : p == 15 ? s3 ^ 1 : (((jp & 3) ^ ((p - 7) >> 1)) << 1) + ((p - 1) & 1); }; \
  [[maybe_unused]] auto frag_of = [&](int p) { return p < 9 ? (p - 1) * 512 : 4096 + src_of(p) * 512; }; \
  (void)hf; (void)fidx
  auto get_b = [&]() { return __shfl_sync(~0u, (int)lds1(mb + B_ID), 0); };
  IDS(b0);
  auto load_w = [&](uint32_t st, int kc, uint32_t bar, bool last) { tma_3d(st + 32768, &T.m[M_W], cg * 64, kc, 1, bar, last); tma_2d(st + 49152, &T.m[M_Q], cg * 64, kc, bar, last); };
  if (threadIdx.x < 256) {
    const int r = threadIdx.x >> 3, c = threadIdx.x & 7, xr = (r & 16) * 8 + (r & 15);
    const uint32_t sw = ((c ^ r) & 7) << 4;
    const __nv_bfloat16* gw = P.wqkv + (kcol(0) + r) * 3072 + cg * 64 + c * 8, *gx = P.x + (rb * 256 + xr) * D_ + kcol(0) + c * 8;
#pragma unroll
    for (int i = 0; i < 6; i++)
      asm volatile("cp.async.cg.shared.global [%0], [%1], 16;" :: "r"(sm + 32768 + i * 4096 + r * 128 + sw), "l"(gw + (i & 1) * 32 * 3072 + ((i >> 1) + 1) % 3 * 1024) : "memory");
    asm volatile("cp.async.commit_group;" ::: "memory");
#pragma unroll
    for (int i = 0; i < 8; i++) asm volatile("cp.async.cg.shared.global [%0], [%1], 16;" :: "r"(sm + i * 2048 + xr * 128 + sw), "l"(gx + i * 16 * D_) : "memory");
    asm volatile("cp.async.commit_group;" ::: "memory");
  }
  const int tid = threadIdx.x, wid = __shfl_sync(~0u, tid >> 5, 0), wg = wid >> 2, lane = lane_id();
  const uint32_t tk = clock64();
  if (wid == 8) {
    if (elect_one()) { tmap_prefetch(&T.m[M_X]); tmap_prefetch(&T.m[M_W]); tmap_prefetch(&T.m[M_Q]); }
  } else if (wid == 9) {
    if (elect_one()) {
#pragma unroll
      for (int i = 0; i < 31; i++) if (8 * i != B_ID) mbar_init(mb + 8 * i, i < 4 ? 1 : i < 8 ? 8 : i < 16 ? 16 : i == 16 ? 64 : i == 17 ? 8 : i == 18 ? 4 : 1);
      asm volatile("fence.mbarrier_init.release.cluster;" ::: "memory");
      fence_async_smem();
    }
  } else if (wid == 11) {
#pragma unroll
    for (int i = 0; i < 4; i++) sts4(sm + OFF_STATS + i * 512 + lane * 16, SENT, SENT, SENT, SENT);
    sts1(mb + B_ID, b);
    if (smem_u32(smem_raw) != sm) asm volatile("trap;");
    fence_async_smem();
  }
  __syncthreads();
  asm volatile("barrier.cluster.arrive.relaxed.aligned;\nbarrier.cluster.wait.aligned;" ::: "memory");

  if (wg == 2) {
    asm volatile("setmaxnreg.dec.sync.aligned.u32 56;");
    if (wid == 8) {
      if (elect_one()) {
#pragma unroll 1
        for (int kb = 1; kb < 15; kb++) {
          const uint32_t fb = mb + B_FULL + 8 * (kb & 3), st = sm + (kb & 3) * STAGE_B;
          const int kc = kcol(kb);
          if (kb < 4) while ((uint32_t)clock64() - tk < FD0 + kb * FD1) {}
          else mbar_wait(fb + B_EMPTY, ((kb >> 2) & 1) ^ 1);
          mbar_expect_tx(fb, STAGE_B);
          tma_2d_mc(st + rank * 16384, &T.m[M_X], kc, rb * 256 + rank * 128, fb, kb >= 12);
          load_w(st, kc, fb, kb >= 8);
          if (kb >= 8 && kb < 11) asm volatile("mbarrier.arrive.shared::cta.b64 _, [%0], %1;" :: "r"(fb + B_EMPTY), "r"(4) : "memory");
        }
        {
          const uint32_t st = sm + 3 * STAGE_B, fa = mb + B_FULL + 24, fb = mb + B_F15;
          const int kc = kcol(15);
          mbar_wait(fa, 0);
          mbar_expect_tx(fa, 32768); mbar_expect_tx(fb, 24576);
          if (rank) { mbar_wait(mb + B_EMPTY + 24, 0); tma_2d_mc(st + 16384, &T.m[M_X], kc, rb * 256 + 128, fa, true); }
          mbar_wait(mb + B_EMPTY, 1);
          tma_3d(st + 32768, &T.m[M_W], cg * 64, kc, 1, fa, true);
          if (!rank) { mbar_wait(mb + B_EMPTY + 24, 0); tma_2d_mc(st, &T.m[M_X], kc, rb * 256, fb, true); }
          tma_2d(st + 49152, &T.m[M_Q], cg * 64, kc, fb, true);
        }
        mbar_expect_tx(mb + B_KVP, 32768 + 2048);
      }
      __syncwarp();
      const uint4* kp = &P.s->kvp[cg * 8 * 256], *zq = &P.s->zp[cg * 8 * 16], *src = &P.s->obuf[(rb * 4 + rank * 2 + hf) * 64 * 128];
      asm volatile("" : "+l"(kp), "+l"(zq), "+l"(src));
      bar_sync(13, 160);
      meet(&P.s->when[cg * 32 + rb], (const uint4*)&P.s->when[cg * 32] + (lane & 1), MFIRST, MKV, mb + B_EVB);
      if (elect_one()) {
        bulk_load(sm + rank * (2 * STAGE_B) + STAGE_B, kp, 32768, mb + B_KVP);
        bulk_load(sm + rank * (2 * STAGE_B) + UNIT, zq, 2048, mb + B_KVP);
      }
      mbar_wait(mb + B_KVP, 0);
      mbar_wait(mb + B_KVB, 1);
      meet(&P.s->when[(16 + rb * 2 + hf) * 32 + s3], (const uint4*)&P.s->when[(16 + rb * 2 + (hf ^ 1)) * 32] + (lane & 1), MFIRST, MO, mb + B_E);
      if (elect_one()) {
        const uint32_t t0 = clock64();
        mbar_arrive(mb + B_F15);
#pragma unroll
        for (int p = 2; p < 5; p++) {
          if (p < 4) while ((uint32_t)clock64() - t0 < (p == 2 ? ADELAY : ADELAY2)) NAP;
          bulk_load_mc(sm + ring_of(p, rank), src + (p - 1) * 512, UNIT, mb + B_BF + 8 * p);
        }
#pragma unroll 1
        for (int p = 5; p < 15; p++) {
          uint32_t dst = sm + ring_of(p, rank), bar = mb + B_BF + 8 * (p % 7);
          const uint4* q = src + frag_of(p);
          asm volatile("" : "+r"(dst), "+r"(bar), "+l"(q));
          mbar_wait(mb + B_E + 8 * ((p - 4) & 7), p >= 12);
          bulk_load_mc(dst, q, UNIT, bar);
        }
        asm volatile("mbarrier.arrive.shared::cta.b64 _, [%0], 8;" :: "r"(mb + B_GATE) : "memory");
        const uint4* s15 = &P.s->obuf[(rb * 4 + hf) * 64 * 128 + frag_of(15)];
        mbar_wait(mb + B_E + 24, 1);
        bulk_load(sm + ring_of(15, 0), s15, UNIT, mb + B_BF + 8); bulk_load(sm + ring_of(15, 1), s15 + 2 * 64 * 128, UNIT, mb + B_BF + 8);
      }
    } else if (wid == 11) {
      IDS(get_b());
      mbar_wait(mb + B_FULL, 0);
      {
        const uint32_t ep = ld_rlx(&P.s->epoch);
        float s = 0.f;
#pragma unroll
        for (int i = 0; i < 4; i++) {
          const uint4 v = ld_cg4((const uint4*)P.wr + lane + i * 32);
          s += (bf_lo(v.x) + bf_hi(v.x)) + (bf_lo(v.y) + bf_hi(v.y)) + (bf_lo(v.z) + bf_hi(v.z)) + (bf_lo(v.w) + bf_hi(v.w));
        }
#pragma unroll
        for (int o = 16; o; o >>= 1) s += __shfl_xor_sync(~0u, s, o);
        if (lane == 0) sts1(mb + B_SW, (__float_as_uint(s) & ~255u) | ((ep + 1) & 255));
      }
      bar_arrive(10, 96);
      if (fidx >= 0) {
        const uint32_t o = (rank * 32 + lane) * (F_ * 2) + (fidx >> 1) * 128;
        const char* q0 = (const char*)P.wg + o, *q1 = (const char*)P.wu + o;
        mbar_wait(mb + B_FULL + 24, 0);
#pragma unroll 1
        for (int r = 0; r < 16; r++, q0 += 64 * F_ * 2, q1 += 64 * F_ * 2) {
          if (mbar_test(mb + B_F15, 0)) { l2_prefetch(q0); l2_prefetch(q1); continue; }
          asm volatile("cp.async.ca.shared.global.L2::128B [%0], [%1], 4;\ncp.async.commit_group;\ncp.async.wait_group %3;\n"
                       "cp.async.ca.shared.global.L2::128B [%0], [%2], 4;\ncp.async.commit_group;\ncp.async.wait_group %3;" :: "r"(mb + B_DUMMY), "l"(q0), "l"(q1), "n"(2) : "memory");
        }
        mbar_wait(mb + B_F15, 0);
        bar_sync(15, 288);
        q0 = (const char*)P.wd + fidx * 65536 + lane * 128;
        const uint32_t bar = mb + B_BF + 48;
        if (lane == 0) mbar_expect_tx(bar, 8192);
#pragma unroll 1
        for (int i = 0; i < 16 + PLAG; i++) {
          if (i < 16) l2_prefetch(q0 + i * 4096);
          if (i >= PLAG && elect_one()) tma_2d(sm + OFF_COLSUM, &T.m[M_L], 0, fidx * 512 + (i - PLAG) * 32, bar, false);
        }
        mbar_wait(bar, 0);
        __syncwarp();
        if (lane == 0) { mbar_arrive(bar); }
        asm volatile("cp.async.wait_all;" ::: "memory");
      } else bar_sync(15, 288);
      bar_arrive(14, 64);
    } else {
      const uint32_t eb = (lane << 24) + bars + B_EMPTY;
      float c[6];
      if (wid == 10) {
        float sx[4] = {0.f, 0.f, 0.f, 0.f}, qx[4] = {0.f, 0.f, 0.f, 0.f};
        const uint32_t xa = sm + ((hf * 4 + (cg & 3)) * 32 + lane) * 128 + ((lane & 7) << 4);
#pragma unroll 1
        for (int kb = 0; kb < 8; kb++) {
          uint4 xv[8];
          const uint32_t so = xa + (kb & 3) * STAGE_B;
          mbar_wait(mb + B_FULL + 8 * (kb & 3), kb >> 2);
#pragma unroll
          for (int i = 0; i < 8; i++) xv[i] = lds4(so ^ (i << 4));
#pragma unroll
          for (int i = 0; i < 8; i++) {
            const uint32_t e[4] = {xv[i].x, xv[i].y, xv[i].z, xv[i].w};
#pragma unroll
            for (int j = 0; j < 4; j++) {
              const float d0 = bf_lo(e[j]), d1 = bf_hi(e[j]);
              sx[j] += d0 + d1; qx[j] = fmaf(d0, d0, fmaf(d1, d1, qx[j]));
            }
          }
          __syncwarp();
          if (lane < 2) mbar_arrive_rem(eb + 8 * (kb & 3));
          if (kb == 1) {
            if (elect_one()) {
#pragma unroll 1
              for (int i = 0; i < 16; i++) bulk_store(&P.s->obuf[((rb * 4 + (i >> 2)) * 64 + (((i >> 2) & 1) == hf ? 32 + s3 * 4 + (i & 3) : (i & 3) * 8 + s3)) * 128], sm + OFF_STATS, 2048);
              bulk_store(&P.s->kvp[(cg * 8 + rb) * 256], sm + OFF_STATS, 2048); bulk_store(&P.s->kvp[(cg * 8 + rb) * 256 + 128], sm + OFF_STATS, 2048);
              bulk_store(&P.s->zp[(cg * 8 + rb) * 16], sm + OFF_STATS, 256);
              if (s3 == 0) bulk_store(&P.s->when[(16 + rb * 2 + hf) * 32], sm + OFF_STATS, 128);
              if (rb == 0) bulk_store(&P.s->when[cg * 32], sm + OFF_STATS, 128);
              asm volatile("cp.async.bulk.commit_group;" ::: "memory");
#pragma unroll
              for (int i = M_O; i < M_N; i++) tmap_prefetch(&T.m[i]);
            }
            __syncwarp();
          }
        }
        asm volatile("cp.async.bulk.wait_group 0;\nfence.proxy.async.global;" ::: "memory");
        fence_gpu();
        c[0] = ((sx[0] + sx[1]) + (sx[2] + sx[3])) * (2.f / D_);
        c[1] = fmaxf(fmaf(-c[0], c[0], ((qx[0] + qx[1]) + (qx[2] + qx[3])) * (2.f / D_)), 0.f);
      } else {
        float a[12];
#pragma unroll
        for (int i = 0; i < 12; i++) a[i] = 0.f;
        const int r2 = lane >> 4, c16 = lane & 15;
        const uint32_t a0 = sm + 32768 + (rb >> 1) * 2048 + r2 * 128 + (((c16 >> 1) ^ r2) << 4) + (c16 & 1) * 8;
#pragma unroll 1
        for (int it = 0; it < 16; it++) {
          uint2 w[12];
          const int s = (it >> 1) & 3;
          const uint32_t so = a0 + s * STAGE_B + (it & 1) * 1024;
          if (!(it & 1)) { mbar_wait(mb + B_FULL + 8 * s, it >> 3); }
          static_for<0, 12>([&](auto ic) { constexpr int i = decltype(ic)::value;
            const float2 v = lds2f_o<(i >> 2) * 8192 + (i & 3) * 256>(so ^ ((i & 3) << 5)); w[i] = make_uint2(__float_as_uint(v.x), __float_as_uint(v.y)); });
#pragma unroll
          for (int i = 0; i < 12; i++) { float* q = a + (i >> 2) * 4; q[0] += bf_lo(w[i].x); q[1] += bf_hi(w[i].x); q[2] += bf_lo(w[i].y); q[3] += bf_hi(w[i].y); }
          __syncwarp();
          if (lane < 2 && (it & 1)) mbar_arrive_rem(eb + 8 * s);
        }
#pragma unroll
        for (int i = 0; i < 6; i++) {
          const int o = (i >> 1) * 4 + (i & 1);
          c[i] = (r2 ? a[o + 2] : a[o]) + __shfl_xor_sync(~0u, r2 ? a[o] : a[o + 2], 16);
        }
      }
      bar_sync(10, 96);
      {
        const uint32_t tag = lds1(mb + B_SW) & 255;
        auto tagged = [&](float v) { return ((__float_as_uint(v) + 128) & ~255u) | tag; };
        if (wid == 9) {
#pragma unroll
          for (int sg = 0; sg < 3; sg++) {
            st_rlx2((uint2*)&P.s->csp[(cg * 8 + rb) * 48] + sg * 32 + (lane & 15) * 2 + (lane >> 4), tagged(c[sg * 2]), tagged(c[sg * 2 + 1]));
          }
        } else st_rlx2((uint2*)&P.s->st1[(rb * 8 + hf * 4 + (cg & 3)) * 48 + lane] + ((cg >> 2) & 1), tagged(c[0]), tagged(c[1]));
        __nanosleep(GDELAY);
#pragma unroll 1
        for (int h = wid - 9; h < 2; h++) {
          const int q = h * 24 + min(lane, 23);
          const uint4* gp = wid == 10 ? &P.s->st1[rb * 8 * 48 + lane] : &P.s->csp[cg * 8 * 48 + q];
          uint4 v[8];
#pragma unroll 1
          for (int it = 0;; it++) {
            uint32_t x = 0;
#pragma unroll
            for (int i = 0; i < 8; i++) v[i] = ld_rlx4(gp + i * 48);
#pragma unroll
            for (int i = 0; i < 8; i++) { v[i].x ^= tag; v[i].y ^= tag; v[i].z ^= tag; v[i].w ^= tag; x |= v[i].x | v[i].y | v[i].z | v[i].w; }
            if (!__any_sync(~0u, (x & 255) != 0)) break;
            SPINCHK(it);
          }
          if (wid == 10) {
#pragma unroll
            for (int i = 0; i < 8; i++) {
              const float m0 = __uint_as_float(v[i].x), m1 = __uint_as_float(v[i].z), dm = 0.5f * (m0 - m1);
              sts2f(sm + OFF_STATS + (i * 32 + lane) * 8, -0.5f * (m0 + m1), rsq(fmaf(dm, dm, 0.5f * (__uint_as_float(v[i].y) + __uint_as_float(v[i].w))) + 1e-5f));
            }
          } else {
            float s4[4] = {0.f, 0.f, 0.f, 0.f};
#pragma unroll
            for (int i = 0; i < 8; i++) { s4[0] += __uint_as_float(v[i].x); s4[1] += __uint_as_float(v[i].y); s4[2] += __uint_as_float(v[i].z); s4[3] += __uint_as_float(v[i].w); }
            sts4(sm + OFF_COLSUM + q * 16, __float_as_uint(s4[0]), __float_as_uint(s4[1]), __float_as_uint(s4[2]), __float_as_uint(s4[3]));
          }
        }
        mbar_arrive(mb + B_AUX);
      }
      IDS(get_b());
      const uint64_t btab = rank ? BT1 : BT0;
      if (wid == 9) {
        {
          const uint4 sv = make_uint4(SENT, SENT, SENT, SENT);
          uint4* y = &P.s->ybuf[b * NFFN * 2 + lane];
#pragma unroll
          for (int i = 0; i < 7; i++) y[i * 32] = sv;
          if (lane < 16) P.s->st2[b * 16 + lane] = make_uint4(0, 0, 0, 0); else P.s->hsel[b * 16 + lane - 16] = sv;
          if (b < 8) P.s->cand[b * 32 + lane] = SENT;
          fence_gpu();
          bar_sync(0, 288);
          if (lane < 16) sts4(sm + OFF_STATS + lane * 128 + ((lane & 7) << 4), 0x3F803F80u, 0x3F803F80u, 0x3F803F80u, 0x3F803F80u);
          fence_async_smem();
          __syncwarp();
          if (lane == 0) mbar_arrive(mb + B_LATE);
        }
        {
          const int p = lane & 15, sl = p % 7;
          const bool sliced = p > 0 && p < 9;
          const uint32_t c = sliced ? ((p - 1) >> 1) * 16 | ((hf ^ 1) * 8 + ((p - 1) & 1) * 4) << 8 | 128 << 16 : (hf * 8 + src_of(p)) << 8;
          const uint32_t ev = mb + (p < 4 ? B_EVA : B_E + 8 * ((p < 7 ? p == 6 : p - 4) & 7) + (p >= 12));
          mbar_wait(mb + B_EVA, 0);
          sts4(sm + OFF_COLSUM + 512 + p * 16, sm + unit_of(btab, sl), mb + B_BF + 8 * sl, c, ev);
          __syncwarp();
        }
        if (elect_one()) {
#pragma unroll 1
          for (int p = 0; p < 16; p++) {
            const uint4 e = lds4(sm + OFF_COLSUM + 512 + p * 16);
            if (p == 4) mbar_wait(mb + B_WR, 0);
            mbar_wait(e.w & ~1u, e.w & 1);
            mbar_expect_tx(e.y, p > 1 ? 4 * UNIT : 2 * UNIT);
            tma_4d(e.x, (const CUtensorMap*)((const char*)&T.m[M_O] + (e.z >> 16)), 0, e.z & 255, (e.z >> 8) & 255, c3 * 2, e.y);
          }
        }
      } else {
        const uint32_t* wp = (const uint32_t*)(P.wr + c3 * 128) + (lane & 7) * 8 + (lane >> 3);
        const uint32_t w0 = ld_rlx(wp), w1 = ld_rlx(wp + 4);
#pragma unroll 1
        for (int i = 0; i < 4; i++) { l2_prefetch((const char*)P.wo + b * 16384 + i * 4096 + lane * 128); __nanosleep(300); }
        const int p = lane & 15, p2 = min(p + 2, 15);
        const uint32_t t0 = dlo(sb, 8192) + (unit_of(btab, p % 7) >> 4), t1 = ring_of(p + 1, lane >> 4), t2 = mb + B_BF + 8 * (p2 % 7);
        mbar_wait(mb + B_EVB, 0);
        bar_sync(14, 64);
        sts2f(sm + OFF_COLSUM + lane * 8, __uint_as_float(w0), __uint_as_float(w1));
        sts1(sm + OFF_COLSUM + 256 + lane * 4, 0x3F803F80u);
        sts4(sm + OFF_STATS + lane * 16, t0, t1, t2, (p2 / 7) & 1);
        __syncwarp();
        if (elect_one()) {
          mbar_arrive(mb + B_WR);
          if (fidx >= 0) {
            mbar_expect_tx(mb + B_FFN, 131072); mbar_expect_tx(mb + B_FFD, 32768);
            uint64_t gt = rank ? GT1 : GT0;
            mbar_wait(mb + B_KVP, 0);
#pragma unroll 1
            for (int f = 0; f < 8; f++, gt >>= 5) {
              uint32_t d0 = sm + unit_of(gt, 0);
              asm volatile("" : "+r"(d0));
              if (f == 3) mbar_wait(mb + B_GATE, 1);
              mbar_wait(mb + (f < 1 ? B_KVB : B_E + (f < 3 ? 3 + 2 * f : (f + 5) >> 1) * 8), f < 1 || f >= 3);
              tma_3d(d0, &T.m[M_G], fidx * 32, f * 128, 0, mb + B_FFN, true);
              tma_3d(d0 + UNIT, &T.m[M_U], fidx * 32, f * 128, 0, mb + B_FFN, true);
            }
            mbar_expect_tx(mb + B_KVP, 32768);
#pragma unroll
            for (int w = 0; w < 8; w++) {
              if (w == 2) mbar_wait(mb + B_E + 56, 1);
              if (w == 6) mbar_wait(mb + B_E16, 1);
              if (w == 4) mbar_wait(mb + B_EVA, 1);
              tma_3d(sm + ((DT0 >> (5 * w)) & 31) * UNIT + (w < 4 ? 0 : w < 6 ? 14 * UNIT : 0 - 14 * UNIT) * rank, &T.m[M_D], 0, fidx * 32, 2 * w, mb + (w < 4 ? B_FFD : B_KVP), true);
            }
          }
        }
      }
    }
    __syncwarp();
    IDS(get_b());
    mbar_wait(mb + B_EVB, 0);
    mbar_wait(mb + B_OUT, 0);
    const float2 cf = lds2f(sm + OFF_STATS + 64);
    const int cand0 = 2047 - (__float_as_int(cf.x) & 2047), cand1 = 2047 - (__float_as_int(cf.y) & 2047), rr = lane >> 4;
    __nv_bfloat16* const ob = P.out + c3 * 128 + (lane & 15) * 8;
    auto store_row = [&](uint32_t ha, uint32_t la, int row, bool on) {
      const uint4 v = lds4(ha);
      const float2 pr = lds2f(la);
      const float f = 1.f + pr.x, n = pr.y;
      asm volatile("{\n.reg .pred p;\nsetp.ne.u32 p, %5, 0;\n@p st.global.v4.u32 [%0], {%1,%2,%3,%4};\n}" :: "l"(ob + row * D_),
                   "r"(pack2(fmaf(bf_lo(v.x), f, n), fmaf(bf_hi(v.x), f, n))), "r"(pack2(fmaf(bf_lo(v.y), f, n), fmaf(bf_hi(v.y), f, n))),
                   "r"(pack2(fmaf(bf_lo(v.z), f, n), fmaf(bf_hi(v.z), f, n))), "r"(pack2(fmaf(bf_lo(v.w), f, n), fmaf(bf_hi(v.w), f, n))), "r"((uint32_t)on) : "memory");
    };
    {
      uint32_t t0 = clock64();
      uint32_t ha = sm + 4 * UNIT + ((wid >> 1) & 1) * STAGE_B + ((wid & 1) * 32 + rr) * 256 + (((lane & 15) ^ rr) << 4), la = sm + OFF_LNP + ((wid & 3) * 32 + rr) * 8;
      int row = rb * 256 + hf * 64 + (wid & 2) * 64 + (wid & 1) * 32 + rr;
#pragma unroll 1
      for (int i = 0; i < 16; i += 2, ha += 512 * 2, la += 16 * 2, row += 2 * 2, t0 += OPACE) {
        while ((int)((uint32_t)clock64() - t0) < 0) NAP;
#pragma unroll
        for (int j = 0; j < 2; j++) store_row((ha ^ (((i + j) & 3) << 5)) + j * 512, la + j * 16, row + 2 * j, row + 2 * j != cand0 && row + 2 * j != cand1);
      }
    }
    if (wid == 8) {
      const uint32_t kc = __float_as_uint(rr ? cf.y : cf.x);
      const int c = rr ? cand1 : cand0;
      mbar_wait(mb + B_SEL, 0);
      const float2 sel = lds2f(sm + OFF_STATS + 80);
      store_row(sm + 4 * UNIT + ((c >> 7) & 1) * STAGE_B + (c & 63) * 256 + (((lane & 15) ^ (c & 7)) << 4), sm + OFF_LNP + (((c >> 1) & 64) + (c & 63)) * 8, c,
                kc != __float_as_uint(sel.x) && kc != __float_as_uint(sel.y) && (c >> 8) == rb && ((c >> 6) & 1) == hf);
    }
  } else {
    asm volatile("setmaxnreg.inc.sync.aligned.u32 224;");
    const int t128 = tid & 127, warp = wid & 3, g = lane >> 2, t = lane & 3;
    const uint32_t sk = rank * (2 * STAGE_B);
    uint4 ost[2][4];
    uint4 abuf[3][4];
    uint4* od1;
    const uint4* ain;
    int b1;
    const uint32_t eb = (lane << 24) + bars + B_E;
    float acc[64];
    uint4 wb[4];
    uint32_t hp[32];
    {
      float acc0[96], acc1[96];
#pragma unroll
      for (int i = 0; i < 96; i++) { acc0[i] = 0.f; acc1[i] = 0.f; }
      const uint32_t xo0 = dlo(sb, 16) + (wg * 2 + hf) * 512, xo1 = dlo(sb, 16) + (wg * 2 + (hf ^ 1)) * 512;
      constexpr uint32_t ST = STAGE_B >> 4, WD = dlo(sb + 49152, 8192), WV = dlo(sb + 32768, 8192);
      const uint32_t eb0 = (t128 << 24) + bars + B_EMPTY;
      pin(acc1); pin(acc0);
      if (wg) asm volatile("cp.async.wait_group 0;" ::: "memory"); else asm volatile("cp.async.wait_group 1;" ::: "memory");
      fence_async_smem();
      bar_sync(1, 256);
      if (!wg) {
        asm volatile("cp.async.wait_group 0;" ::: "memory");
        fence_async_smem();
        bar_sync(2, 256);
        if (tid == 0) mbar_arrive(mb + B_FULL);
      }
#pragma unroll 1
      for (int kb = 0; kb < 12; kb++) {
        const int s = kb & 3;
        if (kb) mbar_wait(mb + B_FULL + 8 * s, (kb >> 2) & 1);
        pin(acc0); pin(acc1);
        wg_fence();
#pragma unroll
        for (int k = 0; k < 4; k++) {
          const uint64_t db = dsc<1024, 1>(WV + s * ST + k * 128);
          wgmma_n192_ss<0, 1, 0>(acc0, dsc<1024, 1>(s * ST + xo0 + k * 2), db, 1);
          wgmma_n192_ss<0, 1, 0>(acc1, dsc<1024, 1>(s * ST + xo1 + k * 2), db, 1);
        }
        wg_commit();
        if (kb == 0 && wg) bar_arrive(2, 256);
        wg_wait<0>();
        pin(acc0); pin(acc1);
        if (t128 < 2 && kb < 11) mbar_arrive_rem(eb0 + 8 * s);
      }
      mbar_wait(mb + B_FULL, 1);
      if (t128 < 8) mbar_arrive_rem(t128 < 4 ? (wg << 24) + bars + B_EMPTY + 24 : mb + B_EMPTY);
      mbar_wait(mb + B_AUX, 0);
      float rs[2][2], nm[2][2];
#pragma unroll
      for (int m = 0; m < 2; m++)
#pragma unroll
        for (int h = 0; h < 2; h++) { const float2 v = lds2f(sm + OFF_STATS + ((wg * 2 + (m ^ hf)) * 64 + warp * 16 + h * 8 + g) * 8); nm[m][h] = v.x; rs[m][h] = v.y; }
      auto center = [&](auto jc) {
        constexpr int j = decltype(jc)::value;
        const float2 cs = lds2f_o<sb + OFF_COLSUM + j * 32>(own + t * 8);
        acc1[j * 4] = fmaf(nm[1][0], cs.x, acc1[j * 4]); acc1[j * 4 + 1] = fmaf(nm[1][0], cs.y, acc1[j * 4 + 1]);
        acc1[j * 4 + 2] = fmaf(nm[1][1], cs.x, acc1[j * 4 + 2]); acc1[j * 4 + 3] = fmaf(nm[1][1], cs.y, acc1[j * 4 + 3]);
        acc0[j * 4] = fmaf(nm[0][0], cs.x, acc0[j * 4]); acc0[j * 4 + 1] = fmaf(nm[0][0], cs.y, acc0[j * 4 + 1]);
        acc0[j * 4 + 2] = fmaf(nm[0][1], cs.x, acc0[j * 4 + 2]); acc0[j * 4 + 3] = fmaf(nm[0][1], cs.y, acc0[j * 4 + 3]);
      };
      static_for<0, 16>(center);
      const float L2E = 1.4426950408889634f;
      uint32_t fa = sm + sk + (warp * 16 + (lane & 15)) * 128 + (((lane >> 4) ^ (lane & 7)) << 4);
      asm volatile("" : "+r"(fa));
      uint32_t xf0[32], xf1[32];
      auto pack_kv = [&](float (&a)[96], int i, float r0, float r1, uint32_t* o, uint32_t z = 0) {
        const float* p = a + i * 8;
        if (i < 4) {
          const float rl0 = __uint_as_float(__float_as_uint(r0 * L2E) | z), rl1 = __uint_as_float(__float_as_uint(r1 * L2E) | z);
          const uint32_t q0 = pack2(r0, r0), q1 = pack2(r1, r1);
          o[0] = phi2(p[0], p[1], rl0, q0); o[1] = phi2(p[2], p[3], rl1, q1); o[2] = phi2(p[4], p[5], rl0, q0); o[3] = phi2(p[6], p[7], rl1, q1);
        } else {
          const uint32_t q0 = pack2(r0, r0), q1 = pack2(r1, r1);
          o[0] = hmul2(pack2(p[0], p[1]), q0); o[1] = hmul2(pack2(p[2], p[3]), q1); o[2] = hmul2(pack2(p[4], p[5]), q0); o[3] = hmul2(pack2(p[6], p[7]), q1);
        }
      };
      auto swap_kv = [&](uint32_t (&xf)[32], uint32_t tile, int i, const uint32_t* o, uint32_t z = 0) {
        const uint32_t ad = (fa + tile * UNIT) ^ ((i & 3) << 5);
        if (i < 4) { ldsm4_o<0>(ad, xf[i * 4], xf[i * 4 + 1], xf[i * 4 + 2], xf[i * 4 + 3]); stsm4_o<0>(ad, o[0], o[1], o[2], o[3]); }
        else { ldsm4_o<STAGE_B>(ad | z, xf[i * 4], xf[i * 4 + 1], xf[i * 4 + 2], xf[i * 4 + 3]); stsm4_o<STAGE_B>(ad, o[0], o[1], o[2], o[3]); }
      };
      auto mma_q = [&](float (&a)[96], uint32_t (&xf)[32], uint32_t xo, bool ss) {
        const uint32_t r = __shfl_sync(~0u, sk >> 4, 0), o = 2 * ST - r;
#pragma unroll
        for (int j = 0; j < 8; j++) {
          if (ss) wgmma_n64_ss<0, 1, 64>(a, dsc<1024, 1>(o + (j >> 2) * ST + xo + (j & 3) * 2), dsc<1024, 1>(WD + o + (j >> 2) * ST + (j & 3) * 128), 1);
          else wgmma_n64_rs<1, 64>(a, xf[j * 4], xf[j * 4 + 1], xf[j * 4 + 2], xf[j * 4 + 3], dsc<1024, 1>(WD + r + (j >> 2) * ST + (j & 3) * 128), 1);
        }
      };
      auto epi_q = [&](float (&a)[96], float r0, float r1, uint32_t (&o)[16]) {
        const float rl0 = r0 * 1.44269511f, rl1 = r1 * 1.44269511f;
        const uint32_t q0 = dup2(r0), q1 = dup2(r1);
#pragma unroll
        for (int j = 0; j < 8; j++) { o[j * 2] = phi2(a[64 + j * 4], a[65 + j * 4], rl0, q0); o[j * 2 + 1] = phi2(a[66 + j * 4], a[67 + j * 4], rl1, q1); }
        pinu(o);
      };
      auto mma_kv1 = [&](float (&a)[96], uint32_t xo, int s) {
#pragma unroll
        for (int k = 0; k < 4; k++) wgmma_n128_ss<0, 1, 0>(a, dsc<1024, 1>(s * ST + xo + k * 2), dsc<1024, 1>(WV + s * ST + k * 128), 1);
      };
      auto epi_kv = [&](float (&a)[96], uint32_t (&xf)[32], uint32_t tile, float r0, float r1) {
        uint32_t o[8][4];
#pragma unroll
        for (int j = 3; j >= 0; j--) {
          const uint32_t z = j < 3 ? xf[(j + 5) * 4] & blockIdx.y : 0;
          pack_kv(a, j + 4, r0, r1, o[j + 4]);
          swap_kv(xf, tile, j + 4, o[j + 4], (o[j + 4][2] | o[j + 4][3]) & blockIdx.y);
          pack_kv(a, j, r0, r1, o[j], z);
          swap_kv(xf, tile, j, o[j]);
        }
      };
      bar_arrive(15, 288); bar_arrive(0, 288);
      pinr<0, 64>(acc0); pinr<0, 64>(acc1);
      if (wg) {
        mbar_wait(mb + B_FULL + 8, 1);
        wg_fence();
        mma_kv1(acc1, xo1, 0); mma_kv1(acc0, xo0, 0); mma_kv1(acc1, xo1, 1); mma_kv1(acc0, xo0, 1);
        mbar_wait(mb + B_FULL + 16, 1);
        wg_fence();
        mma_kv1(acc1, xo1, 2);
        mbar_wait(mb + B_FULL + 24, 1);
        wg_fence();
        mma_kv1(acc1, xo1, 3);
        wg_commit();
        bar_arrive(3, 256);
      }
      b1 = get_b();
      static_for<16, 24>(center);
      pinr<64, 96>(acc0); pinr<64, 96>(acc1);
      if (wg) wg_wait<0>();
      else {
        bar_sync(3, 256);
        wg_fence();
        mma_kv1(acc1, xo1, 0); mma_kv1(acc1, xo1, 1); mma_kv1(acc1, xo1, 2);
        mbar_wait(mb + B_F15, 0);
        wg_fence();
        mma_kv1(acc1, xo1, 3);
        wg_commit();
        mma_kv1(acc0, xo0, 0); mma_kv1(acc0, xo0, 1);
        wg_commit();
        bar_arrive(4, 256);
        wg_wait<1>();
      }
      pinr<0, 64>(acc1);
      epi_kv(acc1, xf1, wg * 2 + (hf ^ 1), rs[1][0], rs[1][1]);
      pinu(xf1);
      if (wg) mbar_wait(mb + B_LATE, 0);
      bar_sync(5 - wg, 256);
      wg_fence();
      mma_kv1(acc0, xo0, 2); mma_kv1(acc0, xo0, 3);
      wg_commit();
      fence_async_smem();
      mma_q(acc1, xf1, xo1, false);
      wg_commit();
      bar_arrive(6 - wg, 256);
      if (wg) bar_arrive(13, 160);
      wg_wait<1>();
      pinr<0, 64>(acc0);
      if (lane == 0) mbar_arrive(mb + B_EVA);
      epi_kv(acc0, xf0, wg * 2 + hf, rs[0][0], rs[0][1]);
      fence_async_smem();
      pinu(xf0);
      const uint32_t kvb = 2 * STAGE_B + (2 + (hf ^ 1)) * UNIT - sk;
      uint32_t ka0, ka1, g0, g1;
      const uint8_t* h0, *h1;
      auto prepare = [&]() {
        const uint32_t l = lane_id();
        od1 = &P.s->obuf[(((b1 >> 4) * 4 + wg * 2 + (hf ^ 1)) * 64 + (b1 & 7)) * 128 + warp * 32 + l];
        ain = &P.s->obuf[((b1 >> 4) * 4 + wg * 2 + hf) * 64 * 128 + warp * 32 + l];
        const uint32_t r = (l & 3) * 2 + (l >> 2), zo = (l >> 2) * 256 + wid * 32 + (l & 3) * 8;
        ka0 = sm + kvb + wid * 1024 + (l & 7) * 128 + (((l >> 3) ^ (l & 7)) << 4); ka1 = sm + kvb + wid * 1024 + r * 128 + ((4 ^ r) << 4);
        g0 = sm + sk + wid * 512 + l * 16; g1 = sm + sk + zo;
        h0 = (const uint8_t*)&P.s->kvp[(b1 & 15) * 8 * 256 + wid * 32 + l]; h1 = (const uint8_t*)&P.s->zp[(b1 & 15) * 8 * 16] + zo;
        asm volatile("" : "+r"(ka0), "+r"(ka1), "+r"(g0), "+r"(g1), "+l"(h0), "+l"(h1), "+l"(od1), "+l"(ain));
        sched_fence();
      };
      if (wg) {
        float ka[36];
        auto mma_kv = [&](uint32_t tile, int i, int acc) {
          const uint32_t o = (sk >> 4) + tile * 512 + i * 128;
          wgmma_n72_ss<1, 1, 0>(ka, dsc<1024, 1>(dlo(sb, 8192) + o), dsc<1024, 1>(dlo(sb + STAGE_B, OFF_STATS - STAGE_B) + o * (1u - (1u << 16))), acc);
        };
        auto mma_q1 = [&](int j) { wgmma_n64_rs<1, 64>(acc0, xf0[j * 4], xf0[j * 4 + 1], xf0[j * 4 + 2], xf0[j * 4 + 3], dsc<1024, 1>(WD + (sk >> 4) + (j >> 2) * ST + (j & 3) * 128), 1); };
#pragma unroll
        for (int i = 0; i < 36; i++) ka[i] = 0.f;
        bar_sync(6, 256);
        wg_fence();
#pragma unroll
        for (int i = 0; i < 4; i++) {
          mma_kv(2, i, i); mma_kv(3, i, 1); mma_kv(hf ^ 1, i, 1);
          mma_q1(i);
        }
        const int kq = (b1 & 15) * 8 + (b1 >> 4);
        uint4* dst = &P.s->kvp[kq * 256 + warp * 64 + lane];
        uint32_t* dz = (uint32_t*)&P.s->zp[kq * 16] + warp * 16 + g + t * 8;
        asm volatile("" : "+l"(dst), "+l"(dz));
        bar_sync(7, 256);
#pragma unroll
        for (int i = 0; i < 4; i++) mma_kv(hf, i, 1);
        wg_commit();
#pragma unroll
        for (int j = 4; j < 8; j++) mma_q1(j);
        wg_commit();
        bar_arrive(8, 256);
        wg_wait<1>();
        pin(ka);
        uint32_t kw[8];
#pragma unroll
        for (int i = 0; i < 8; i++) {
          const int j = (i & 3) * 4 + (i >> 2) * 2;
          asm("{\n.reg .pred p;\nsetp.ne.u32 p, %5, 0;\n@p cvt.rn.bf16x2.f32 %0, %4, %3;\n@!p cvt.rn.bf16x2.f32 %0, %2, %1;\n}"
              : "=r"(kw[i]) : "f"(ka[j]), "f"(ka[j + 1]), "f"(ka[16 + j]), "f"(ka[17 + j]), "r"(warp & 2));
        }
        st_rlx4(dst, make_uint4(kw[0], kw[1], kw[2], kw[3]));
        st_rlx4(dst + 32, make_uint4(kw[4], kw[5], kw[6], kw[7]));
        if (t < 2) st_rlx(dz, __float_as_uint(t ? ka[34] : ka[32]));
        if (lane == 0) mbar_arrive(mb + B_EVB);
        asm volatile("" : "=r"(ka0), "=r"(ka1), "=r"(g0), "=r"(g1), "=l"(h0), "=l"(h1), "=l"(od1), "=l"(ain));
      } else {
        bar_arrive(7, 256);
        bar_sync(8, 256);
        wg_fence();
        mma_q(acc0, xf0, xo0, false);
        prepare();
        bar_sync(9, 256);
      }
      wg_fence();
      mma_q(acc1, xf1, xo1, true);
      wg_commit();
      if (wg) { bar_arrive(9, 256); prepare(); wg_wait<0>(); }
      else { wg_fence(); mma_q(acc0, xf0, xo0, true); wg_commit(); wg_wait<1>(); }
      pinr<64, 96>(acc1);
      uint32_t pq[16];
      epi_q(acc1, rs[1][0], rs[1][1], pq);
      bar_sync(11 + wg + zero_after(pq), 128);
      if (lane == 0) mbar_arrive(mb + B_KVB);
      if (wg) {
        wg_fence();
        mma_q(acc0, xf0, xo0, true);
        wg_commit();
      }
      {
        uint4 gv[8]; uint2 gz;
        uint32_t m[8], a[4];
        float z0, z1;
        mbar_wait(mb + B_KVP, 0);
        { const float2 v = lds2f_o<UNIT>(g1); gz = make_uint2(__float_as_uint(v.x), __float_as_uint(v.y)); }
        static_for<0, 8>([&](auto sc) { constexpr int s = decltype(sc)::value; gv[s] = lds4_o<STAGE_B + s * 4096>(g0); });
#pragma unroll 1
        for (int it = 0; it < SPIN_LIMIT; it++) {
          uint32_t mm = max(gz.x, gz.y);
          z0 = __uint_as_float(gz.x); z1 = __uint_as_float(gz.y);
#pragma unroll
          for (int o = 4; o < 32; o <<= 1) { z0 += __shfl_xor_sync(~0u, z0, o); z1 += __shfl_xor_sync(~0u, z1, o); }
#pragma unroll
          for (int s = 0; s < 8; s++) m[s] = max4(0, gv[s]);
#pragma unroll
          for (int s = 0; s < 8; s += 2) mm = __vimax3_u32(mm, m[s], m[s + 1]);
          a[0] = hadd2(hadd2(hadd2(gv[0].x, gv[1].x), hadd2(gv[2].x, gv[3].x)), hadd2(hadd2(gv[4].x, gv[5].x), hadd2(gv[6].x, gv[7].x)));
          a[1] = hadd2(hadd2(hadd2(gv[0].y, gv[1].y), hadd2(gv[2].y, gv[3].y)), hadd2(hadd2(gv[4].y, gv[5].y), hadd2(gv[6].y, gv[7].y)));
          a[2] = hadd2(hadd2(hadd2(gv[0].z, gv[1].z), hadd2(gv[2].z, gv[3].z)), hadd2(hadd2(gv[4].z, gv[5].z), hadd2(gv[6].z, gv[7].z)));
          a[3] = hadd2(hadd2(hadd2(gv[0].w, gv[1].w), hadd2(gv[2].w, gv[3].w)), hadd2(hadd2(gv[4].w, gv[5].w), hadd2(gv[6].w, gv[7].w)));
          pinu(a);
          if (!__any_sync(~0u, mm == SENT)) break;
          gz = ld_rlx2(h1);
#pragma unroll
          for (int s = 0; s < 8; s++) if (m[s] == SENT) gv[s] = ld_rlx4(h0 + s * 4096);
        }
        wg_wait<0>();
        pinr<64, 96>(acc0);
        stsm4(ka0, a[0], a[1], a[2], a[3]);
        const uint32_t zz = pack2(g ? z1 : z0, g ? z1 : z0);
        if (lane < 8) sts4(ka1, zz, zz, zz, zz);
        fence_async_smem();
        bar_sync(1, 256);
      }
      auto make_o = [&](uint4 (&o)[4], auto first) {
        float oa[2][20];
        wg_fence();
#pragma unroll
        for (int ks = 0; ks < 4; ks++)
          wgmma_n40_rs<1, 0>(oa[ks >> 1], pq[ks * 4], pq[ks * 4 + 1], pq[ks * 4 + 2], pq[ks * 4 + 3], dsc<1024, 1>(dlo(sb, 8192) + (kvb >> 4) + ks * 128), ks & 1);
        wg_commit();
        if constexpr (!decltype(first)::value) {
          pinu(xf0);
#pragma unroll
          for (int q = 0; q < 32; q++) { acc[q * 2] = bf_lo(xf0[q]); acc[q * 2 + 1] = bf_hi(xf0[q]); }
          pin(acc);
          mbar_wait(mb + B_BF, 0);
        }
        wg_wait<0>();
        pin(oa[0]); pin(oa[1]);
        if (decltype(first)::value && lane < 2) mbar_arrive_rem(eb);
#pragma unroll
        for (int h = 0; h < 2; h++) {
          const float (&d)[20] = oa[h];
          const float i0 = rcp(d[16] + 1e-6f), i1 = rcp(d[18] + 1e-6f);
#pragma unroll
          for (int k2 = 0; k2 < 2; k2++) {
            o[h * 2 + k2] = make_uint4(pack2(d[k2 * 8] * i0, d[k2 * 8 + 1] * i0), pack2(d[k2 * 8 + 2] * i1, d[k2 * 8 + 3] * i1),
                                       pack2(d[k2 * 8 + 4] * i0, d[k2 * 8 + 5] * i0), pack2(d[k2 * 8 + 6] * i1, d[k2 * 8 + 7] * i1));
            if (decltype(first)::value && !h && !k2) { st_rlx4(od1, o[0]); sched_fence(); }
          }
        }
      };
      make_o(ost[1], std::true_type{});
      st_rlx4(od1 + 1024 + ((ost[1][2].x | ost[1][3].w) & blockIdx.y), ost[1][1]);
      sched_fence();
      auto read1 = [&](uint32_t z) {
        mbar_wait(mb + B_F15 + z, 1);
#pragma unroll
        for (int i = 0; i < 4; i++) abuf[1][i] = ld_rlx4(ain + i * 128);
      };
      {
        const float rl0 = rs[0][0] * 1.44269511f, rl1 = rs[0][1] * 1.44269511f;
        const uint32_t q0 = dup2(rs[0][0]), q1 = dup2(rs[0][1]);
        uint32_t z = 0;
#pragma unroll
        for (int j = 0; j < 8; j++) {
          pq[j * 2] = phi2(acc0[64 + j * 4], acc0[65 + j * 4], rl0, q0); pq[j * 2 + 1] = phi2(acc0[66 + j * 4], acc0[67 + j * 4], rl1, q1);
          if (j < R1MID) z |= pq[j * 2] | pq[j * 2 + 1];
          if (j == R1MID - 1) read1(z & 0x80008000u);
        }
      }
      st_rlx4(od1 + 2048, ost[1][2]);
      make_o(ost[0], std::false_type{});
    }
   {
    IDS(b1);
    const int mb3 = rb * 4 + wg * 2 + hf;
    uint4* rp = &P.s->st2[mb3 * 64 + warp * 16 + g + t * 8];
    {
      uint4* const od0 = &P.s->obuf[(mb3 * 64 + 32 + s3 * 4) * 128 + t128];
#pragma unroll
      for (int i = 0; i < 4; i++) pin4(ost[0][i]);
      wg_fence();
#pragma unroll
      for (int k = 0; k < 4; k++) wgmma_n128_rs<1, 0>(acc, ost[0][k].x, ost[0][k].y, ost[0][k].z, ost[0][k].w, dsc<1024, 1>(dlo(sb + 4 * UNIT, 8192) + k * 128), 1);
      wg_commit();
      st_rlx4(od1 + 3072, ost[1][3]); st_rlx4(od0, ost[0][0]);
      uint32_t la = sm + t128 * 16, ev = eb + 8;
      asm volatile("" : "+r"(la), "+r"(ev));
      auto fetch = [&](uint32_t off, uint4 (&a)[4]) { const uint32_t ra = la + off; a[0] = lds4_o<0>(ra); a[1] = lds4_o<2048>(ra); a[2] = lds4_o<4096>(ra); a[3] = lds4_o<6144>(ra); };
      auto check = [&](int p, uint4 (&a)[4]) {
        if (__any_sync(~0u, max(max4(max4(0, a[0]), a[1]), max4(max4(0, a[2]), a[3])) == SENT)) {
          int pl = p; asm volatile("" : "+r"(pl));
          const uint4* q = ain + frag_of(pl);
#pragma unroll 1
          for (int it = 0;; it++) {
            uint32_t mm = 0;
#pragma unroll
            for (int i = 0; i < 4; i++) { const uint32_t m = max4(0, a[i]); mm = max(mm, m); if (m == SENT) a[i] = ld_rlx4(q + i * 128); }
            if (!__any_sync(~0u, mm == SENT)) break;
            SPINCHK(it);
          }
        }
        if (lane < 2) mbar_arrive_rem(ev);
        ev = (ev & ~0x38u) | ((ev + 8) & 0x38u);
      };
      auto mma = [&](int p, uint32_t bs, uint4 (&a)[4]) {
#pragma unroll
        for (int i = 0; i < 4; i++) pin4(a[i]);
        wg_fence();
#pragma unroll
        for (int k = 0; k < 4; k++) wgmma_n128_rs<1, 0>(acc, a[k].x, a[k].y, a[k].z, a[k].w, dsc<1024, 1>(bs + k * 128), 1);
        wg_commit();
      };
      uint32_t ta = sm + OFF_STATS + wg * 256 + 48;
      mbar_wait(mb + B_WR, 0);
      uint4 tp = lds4(ta);
      mbar_wait(mb + B_BF + 8, 0);
      check(1, abuf[1]);
      mbar_wait(mb + B_BF + 16, 0);
      fetch(ring_of(2, wg), abuf[2]);
      mma(1, dlo(sb + 11 * UNIT, 8192), abuf[1]);
      st_rlx4(od0 + 128, ost[0][1]); st_rlx4(od0 + 256, ost[0][2]);
      check(2, abuf[2]);
      mbar_wait(mb + B_BF + 24, 0);
      fetch(ring_of(3, wg), abuf[0]);
      mma(2, dlo(sb + 18 * UNIT, 8192), abuf[2]);
      st_rlx4(od0 + 384, ost[0][3]);
      wg_wait<2>();
      check(3, abuf[0]);
      mbar_wait(mb + B_BF + 32, 0);
#pragma unroll 1
      for (int p = 3; p < 15; p += 3) {
        static_for<0, 3>([&](auto jc) {
          constexpr int j = decltype(jc)::value;
          const uint4 tc = tp;
          const uint32_t bs = __shfl_sync(~0u, tc.x, 0);
          wg_wait<1>();
#pragma unroll
          for (int i = 0; i < 4; i++) pin4(abuf[(j + 1) % 3][i]);
          tp = lds4_o<16 * j + 16>(ta);
          fetch(tc.y, abuf[(j + 1) % 3]);
          mma(p + j, bs, abuf[j]);
          check(p + j + 1, abuf[(j + 1) % 3]);
          mbar_wait(tc.z, tc.w);
        });
        ta += 48;
      }
      {
        const uint32_t wa0 = sm + OFF_COLSUM + ((g & 1) ? t * 64 : 256);
        wb[0] = lds4_o<0>(wa0); wb[1] = lds4_o<16>(wa0); wb[2] = lds4_o<32>(wa0); wb[3] = lds4_o<48>(wa0);
      }
      mma(15, __shfl_sync(~0u, tp.x, 0), abuf[0]);
      wg_wait<2>();
      if (lane == 0) mbar_arrive(mb + B_E16);
      asm volatile("" : "+l"(rp));
      sched_fence();
      wg_wait<0>();
      pin(acc);
#pragma unroll
      for (int i = 0; i < 4; i++) { pin4(abuf[0][i]); pin4(abuf[1][i]); pin4(abuf[2][i]); }
    }
    {
      float q0[2] = {0.f, 0.f}, q1[2] = {0.f, 0.f}, c[2][4] = {};
#pragma unroll
      for (int j = 0; j < 16; j++) {
        hp[j * 2] = pack2(acc[j * 4], acc[j * 4 + 1]); hp[j * 2 + 1] = pack2(acc[j * 4 + 2], acc[j * 4 + 3]);
        q0[j & 1] = fmaf(acc[j * 4], acc[j * 4], fmaf(acc[j * 4 + 1], acc[j * 4 + 1], q0[j & 1]));
        q1[j & 1] = fmaf(acc[j * 4 + 2], acc[j * 4 + 2], fmaf(acc[j * 4 + 3], acc[j * 4 + 3], q1[j & 1]));
        if (j & 1) {
          const uint32_t a[4] = {hp[j * 2 - 2], hp[j * 2 - 1], hp[j * 2], hp[j * 2 + 1]};
          mma16816(c[(j >> 1) & 1], a, (j & 2) ? wb[j >> 2].z : wb[j >> 2].x, (j & 2) ? wb[j >> 2].w : wb[j >> 2].y);
        }
      }
      const bool od = t & 1;
      float q = (od ? q1[0] + q1[1] : q0[0] + q0[1]) + __shfl_xor_sync(~0u, od ? q0[0] + q0[1] : q1[0] + q1[1], 1);
      q += __shfl_xor_sync(~0u, q, 2);
      asm volatile("{\n.reg .pred p;\nsetp.lt.u32 p, %5, 2;\n@p red.relaxed.gpu.global.add.v4.f32 [%0], {%1,%2,%3,%4};\n}"
                   :: "l"(rp), "f"(od ? c[0][2] + c[1][2] : c[0][0] + c[1][0]), "f"(q), "f"(od ? c[0][3] + c[1][3] : c[0][1] + c[1][1]), "f"(1.f), "r"(t) : "memory");
    }
    const uint32_t ts = clock64();
    const uint32_t msc = sm + OFF_STATS;
    const uint32_t hst = sm + 4 * UNIT + wg * STAGE_B + warp * 4096, gslot = sm + unit_of(rank ? GT1 : GT0, wid);
    bar_sync(1, 256);
#pragma unroll
    for (int j = 0; j < 8; j++)
      stsm4(hst + (lane & 15) * 256 + (((2 * j + (lane >> 4)) ^ (lane & 7)) << 4), hp[j * 4], hp[j * 4 + 1], hp[j * 4 + 2], hp[j * 4 + 3]);
    uint32_t wa[8][4][4], wd[8][2][4];
    const uint32_t a0 = gslot + ((lane >> 4) * 8 + (lane & 7)) * 64 + ((((lane >> 3) & 1) ^ ((lane >> 1) & 3)) << 4);
    auto load_gu = [&](auto ic) { constexpr int i = decltype(ic)::value; ldsm4t_o<(i >> 2) * 1024 + ((i >> 1) & 1) * 8192>(a0 ^ ((i & 1) << 5), wa[i >> 2][i & 3]); };
    uint32_t tx;
    {
      const int row = rb * 256 + tid;
      const uint4* sp = &P.s->st2[row], *sq = &P.s->st2[row ^ 256];
      const float sw = __uint_as_float((lds1(mb + B_SW) & ~255u) | 128);
      uint4 v[2];
      uint4* d = &P.s->hsel[c3 * 128 + (g & 3) * 32 + ((rb & 6) + (lane >> 4)) * 4 + t];
      uint32_t* dk = &P.s->cand[c3 * 32 + (rb & 6) + (lane >> 4)];
      asm volatile("" : "+l"(d), "+l"(dk));
      if (fidx >= 0) mbar_wait(mb + B_FFN, 0);
      static_for<0, GU1>(load_gu);
      while ((uint32_t)clock64() - ts < SDEL2) {}
      v[0] = ld_rlx4(sp); v[1] = ld_rlx4(sq);
      static_for<GU1, GU2>(load_gu);
#pragma unroll 1
      for (int it = 0; __any_sync(~0u, min(v[0].w, v[1].w) != 0x41000000u) && it < SPIN_LIMIT; it++) {
        if (v[0].w != 0x41000000u) v[0] = ld_rlx4(sp);
        if (v[1].w != 0x41000000u) v[1] = ld_rlx4(sq);
      }
      if (lane == 0) mbar_arrive(mb + B_EVA);
      uint32_t k[2];
#pragma unroll
      for (int i = 0; i < 2; i++) {
        const float mean = __uint_as_float(v[i].x) * (1.f / D_);
        const float rstd = rsq(fmaxf(fmaf(-mean, mean, __uint_as_float(v[i].y) * (1.f / D_)), 0.f) + 1e-5f);
        const uint32_t u = __float_as_uint(rstd * fmaf(-mean, sw, __uint_as_float(v[i].z)));
        k[i] = min(((u ^ ((uint32_t)((int)u >> 31) | 0x80000000u)) & ~2047u), 0xFFFFF000u) | (2047 - (row ^ (i << 8)));
        if (i == 0 && (warp >> 1) == hf) sts2f(sm + OFF_LNP + (wg * 64 + (tid & 63)) * 8, rstd, -mean * rstd);
      }
      const uint32_t hi = max(k[0], k[1]);
      uint32_t m1 = __reduce_max_sync(~0u, hi), m2 = __reduce_max_sync(~0u, hi == m1 ? min(k[0], k[1]) : hi);
      if (lane == 0) sts2f(msc + wid * 8, __uint_as_float(m1), __uint_as_float(m2));
      bar_sync(1, 256);
      const uint32_t kk = lds1(msc + (lane & 15) * 4);
      m1 = __reduce_max_sync(~0u, kk); m2 = __reduce_max_sync(~0u, kk == m1 ? 0 : kk);
      const int c0 = 2047 - (m1 & 2047), c1 = 2047 - (m2 & 2047);
      if ((c0 >> 4) == mb3 * 4 + warp || (c1 >> 4) == mb3 * 4 + warp) {
        const int ra = (lane & 4) ? c1 : c0, rd = (lane & 16) ? c1 : c0;
        uint32_t h0, h1, h2, h3;
        ldsm4_o<0>(hst + (ra & 15) * 256 + ((((lane & 3) * 4 + (lane >> 3)) ^ (ra & 7)) << 4), h0, h1, h2, h3);
        const float2 pr = lds2f(sm + OFF_LNP + (wid * 16 + (rd & 15)) * 8);
        if ((rd >> 4) == mb3 * 4 + warp) {
          const uint4 xn = make_uint4(pack2(fmaf(bf_lo(h0), pr.x, pr.y), fmaf(bf_hi(h0), pr.x, pr.y)), pack2(fmaf(bf_lo(h1), pr.x, pr.y), fmaf(bf_hi(h1), pr.x, pr.y)),
                                      pack2(fmaf(bf_lo(h2), pr.x, pr.y), fmaf(bf_hi(h2), pr.x, pr.y)), pack2(fmaf(bf_lo(h3), pr.x, pr.y), fmaf(bf_hi(h3), pr.x, pr.y)));
          st_rlx4(d, xn);
          if (!(lane & 15)) st_rlx(dk, (lane & 16) ? m2 : m1);
          st_rlx4(d + 1024, make_uint4(h0, h1, h2, h3));
        }
      }
      tx = clock64();
      if (tid == 0) { sts2f(msc + 64, __uint_as_float(m1), __uint_as_float(m2)); mbar_arrive(mb + B_OUT); }
    }
    static_for<GU2, 32>(load_gu);
    const uint32_t dl = sm + (wid & 1) * 4096 + ((lane >> 4) * 8 + (lane & 7)) * 128 + ((((lane >> 3) & 1) ^ (lane & 7)) << 4);
    uint32_t da = dl + unit_of(DT0, wid >> 1), db = dl + unit_of(rank ? DT1 : DT0, 4 + (wid >> 1));
    uint32_t* yp = (uint32_t*)&P.s->ybuf[((wid * 8 + t * 2) * NFFN + fidx) * 2] + g;
    uint32_t k1, k2;
    uint2 key;
    uint32_t pl = sm + unit_of(rank ? GT1 : GT0, g) + (g & 1) * 64 + wid * 64 + t * 16, pa = msc + 128 + wid * 16 + ((t & 1) * 2 + (lane >> 4)) * 4 + (t >> 1) * 2;
    {
      float gu[2][4][4];
      uint4 xb[4];
      uint32_t m[4];
      const uint4* xp = &P.s->hsel[wid * 128 + lane];
      const uint2* kp = (const uint2*)&P.s->cand[wid * 32] + t;
      uint32_t ps = gslot + (wid & 1) * 64 + g * 32;
      asm volatile("" : "+l"(xp), "+l"(kp), "+l"(yp), "+r"(db), "+r"(ps), "+r"(pl), "+r"(pa));
      if (fidx >= 0) mbar_wait(mb + B_FFD, 0);
      static_for<0, 8>([&](auto ic) { constexpr int i = decltype(ic)::value; ldsm4t_o<(i & 1) * 2048>(da ^ ((i >> 1) << 5), wd[i >> 1][i & 1]); });
      while ((uint32_t)clock64() - tx < XDELAY) {}
      key = ld_rlx2(kp);
#pragma unroll
      for (int i = 0; i < 4; i++) xb[i] = ld_rlx4(xp + i * 32);
      if (fidx >= 0) mbar_wait(mb + B_KVP, 1);
#pragma unroll 1
      for (int it = 0; it < SPIN_LIMIT; it++) {
#pragma unroll
        for (int i = 0; i < 4; i++) m[i] = max4(0, xb[i]);
        if (!__any_sync(~0u, __vimax3_u32(__vimax3_u32(max(key.x, key.y), m[0], m[1]), m[2], m[3]) == SENT)) break;
        key = ld_rlx2(kp);
#pragma unroll
        for (int i = 0; i < 4; i++) if (m[i] == SENT) xb[i] = ld_rlx4(xp + i * 32);
      }
      const uint32_t hi = max(key.x, key.y);
      k1 = __reduce_max_sync(~0u, hi); k2 = __reduce_max_sync(~0u, hi == k1 ? min(key.x, key.y) : hi);
#pragma unroll
      for (int i = 0; i < 32; i++) gu[i >> 4][(i >> 2) & 3][i & 3] = 0.f;
#pragma unroll
      for (int ks = 0; ks < 8; ks++) {
#pragma unroll
        for (int i = 0; i < 4; i++) mma16816(gu[ks & 1][i], wa[ks][i], (ks & 1) ? xb[ks >> 1].z : xb[ks >> 1].x, (ks & 1) ? xb[ks >> 1].w : xb[ks >> 1].y);
        if (ks == 1) {
          const uint32_t dd = db | (__float_as_uint(gu[1][3][0]) & blockIdx.y);
          static_for<0, 8>([&](auto ic) { constexpr int i = decltype(ic)::value; ldsm4t_o<(i & 1) * 2048>(dd ^ ((i >> 1) << 5), wd[4 + (i >> 1)][i & 1]); });
          xb[3].z |= (wd[4][0][0] | wd[4][1][0] | wd[5][0][0] | wd[5][1][0] | wd[6][0][0] | wd[6][1][0] | wd[7][0][0] | wd[7][1][0]) & blockIdx.y;
        }
      }
#pragma unroll
      for (int c = 0; c < 2; c++) {
        const uint32_t kc = c ? key.y : key.x;
        float o[8];
#pragma unroll
        for (int j = 0; j < 8; j++) o[j] = gu[0][(j >> 2) + (j & 1) * 2][(j & 2) + c] + gu[1][(j >> 2) + (j & 1) * 2][(j & 2) + c];
        asm volatile("{\n.reg .pred p;\nsetp.ge.u32 p, %9, %10;\n@p st.shared.v4.f32 [%0], {%1,%2,%3,%4};\n@p st.shared.v4.f32 [%0+16], {%5,%6,%7,%8};\n}"
                     :: "r"(ps + (kc == k1 ? 0 : 256)), "f"(o[0]), "f"(o[1]), "f"(o[2]), "f"(o[3]), "f"(o[4]), "f"(o[5]), "f"(o[6]), "f"(o[7]), "r"(kc), "r"(k2) : "memory");
      }
    }
    bar_sync(1, 256);
    {
      const uint4 pv = lds4(pl);
      const bool hi = lane & 16;
      float ga = __uint_as_float(hi ? pv.z : pv.x) + __shfl_xor_sync(~0u, __uint_as_float(hi ? pv.x : pv.z), 16);
      float up = __uint_as_float(hi ? pv.w : pv.y) + __shfl_xor_sync(~0u, __uint_as_float(hi ? pv.y : pv.w), 16);
      ga += __shfl_xor_sync(~0u, ga, 8); up += __shfl_xor_sync(~0u, up, 8);
      ga += __shfl_xor_sync(~0u, ga, 4); up += __shfl_xor_sync(~0u, up, 4);
      asm volatile("st.shared.u16 [%0], %1;" :: "r"(pa), "h"((uint16_t)pack2(ga * rcp(1.f + ex2(-1.4426950408889634f * ga)) * up, 0.f)) : "memory");
      bar_sync(1, 256);
      const uint4 bv = lds4(msc + 128 + (lane & 7) * 16);
      const uint32_t bq[4] = {bv.x, bv.y, bv.z, bv.w};
      float ya[8][4];
#pragma unroll
      for (int i = 0; i < 8; i++) { ya[i][0] = 0.f; ya[i][1] = 0.f; ya[i][2] = 0.f; ya[i][3] = 0.f; }
#pragma unroll
      for (int ks = 0; ks < 2; ks++)
#pragma unroll
        for (int i = 0; i < 8; i++) mma16816(ya[i], wd[i][ks], bq[ks * 2], bq[ks * 2 + 1]);
#pragma unroll
      for (int h = 0; h < 2; h++) {
        float o[4];
#pragma unroll
        for (int j = 0; j < 4; j++) o[j] = t == 0 ? ya[h * 4][j] : t == 1 ? ya[h * 4 + 1][j] : t == 2 ? ya[h * 4 + 2][j] : ya[h * 4 + 3][j];
        asm volatile("{\n.reg .pred p;\nsetp.ge.s32 p, %3, 0;\n@p st.relaxed.gpu.global.u32 [%0], %1;\n@p st.relaxed.gpu.global.u32 [%0+%4], %2;\n}"
                     :: "l"(yp + h * (64 * NFFN * 8)), "r"(pack2(o[0], o[1])), "r"(pack2(o[2], o[3])), "r"(fidx), "n"(NFFN * 32) : "memory");
      }
    }
    if (tid == 0) { sts2f(msc + 80, __uint_as_float(k1), __uint_as_float(k2)); mbar_arrive(mb + B_SEL); }
    const uint32_t ty = clock64();
    if (wid == 0) {
      const uint32_t* yq = (const uint32_t*)&P.s->ybuf[b * NFFN * 2] + t * 8 + g;
      const uint32_t ks = (t & 1) ? k2 : k1, grp = 3 - ((ks >> 9) & 3);
      const int fs = grp * 2 + (__shfl_sync(~0u, key.y, grp) == ks);
      const uint32_t* fq = (const uint32_t*)P.s->hsel + (((b >> 4) * 4 + ((b >> 2) & 3)) * 32 + fs * 4 + (g >> 1)) * 4 + (b & 3);
      float gate = rcp(1.f + ex2(-1.4426950408889634f * __uint_as_float(ks ^ (~(uint32_t)((int)ks >> 31) | 0x80000000u))));
      __nv_bfloat16* op = P.out + (size_t)(2047 - (ks & 2047)) * D_ + b * 8 + g;
      uint32_t sel = (g & 2) ? 0x3F800000u : 0x00003F80u;
      uint32_t fn = ld_rlx(fq), fh = ld_rlx(fq + 4096), v[7][4];
      uint32_t m[7];
#pragma unroll
      for (int i = 0; i < 7; i++) { m[i] = ~blockIdx.y; asm volatile("" : "=r"(v[i][0]), "=r"(v[i][1]), "=r"(v[i][2]), "=r"(v[i][3]), "+r"(m[i])); }
      asm volatile("" : "+l"(yq), "+l"(op), "+f"(gate), "+r"(sel));
      while ((uint32_t)clock64() - ty < YDELAY) {}
      float y[2][4];
#pragma unroll 1
      for (int it = 0; it < SPIN_LIMIT; it++) {
        static_for<0, 7>([&](auto ic) { constexpr int i = decltype(ic)::value;
          asm volatile("{\n.reg .pred p;\nsetp.eq.u32 p, %5, 0xFFFFFFFF;\n@p ld.relaxed.gpu.global.u32 %0, [%4+%6];\n@p ld.relaxed.gpu.global.u32 %1, [%4+%6+128];\n"
                       "@p ld.relaxed.gpu.global.u32 %2, [%4+%6+256];\n@p ld.relaxed.gpu.global.u32 %3, [%4+%6+384];\n}"
                       : "+r"(v[i][0]), "+r"(v[i][1]), "+r"(v[i][2]), "+r"(v[i][3]) : "l"(yq), "r"(m[i]), "n"(i * 512) : "memory"); });
        uint32_t mm = max(fn, fh);
        if (mm == SENT) { fn = ld_rlx(fq); fh = ld_rlx(fq + 4096); }
#pragma unroll
        for (int i = 0; i < 8; i++) y[i >> 2][i & 3] = 0.f;
#pragma unroll
        for (int i = 0; i < 7; i++) { m[i] = __vimax3_u32(max(v[i][0], v[i][1]), v[i][2], v[i][3]); mm = max(mm, m[i]); mma16816(y[i & 1], v[i], sel, sel); }
        pin(y[0]); pin(y[1]);
        if (!__any_sync(~0u, mm == SENT)) break;
      }
      const float base = (g & 1) ? bf_hi(fh) + bf_hi(fn) : bf_lo(fh) + bf_lo(fn);
      if (t < 2) *op = __float2bfloat16(fmaf((y[0][0] + y[1][0]) + (y[0][2] + y[1][2]), gate, base));
      if (b == 0 && lane == 0) P.s->epoch = lds1(mb + B_SW) & 255;
    }
   }
  }
}

typedef CUresult (*EncodeFn)(CUtensorMap*, CUtensorMapDataType, cuuint32_t, void*, const cuuint64_t*, const cuuint64_t*, const cuuint32_t*,
                             const cuuint32_t*, CUtensorMapInterleave, CUtensorMapSwizzle, CUtensorMapL2promotion, CUtensorMapFloatOOBfill);
void make_map(EncodeFn enc, CUtensorMap* m, const void* p, int rank, std::initializer_list<cuuint64_t> dims, std::initializer_list<cuuint64_t> str,
              std::initializer_list<cuuint32_t> box, CUtensorMapSwizzle sw) {
  const cuuint32_t es[4] = {1, 1, 1, 1};
  enc(m, CU_TENSOR_MAP_DATA_TYPE_BFLOAT16, rank, const_cast<void*>(p), dims.begin(), str.begin(), box.begin(), es, CU_TENSOR_MAP_INTERLEAVE_NONE, sw,
      CU_TENSOR_MAP_L2_PROMOTION_L2_128B, CU_TENSOR_MAP_FLOAT_OOB_FILL_NONE);
}

}

extern "C" void kernel_launch(void* const* d_in, const int* in_sizes, int n_in, void* d_out, int out_size) {
  (void)in_sizes; (void)n_in; (void)out_size;
  Ptrs P;
  P.x = (const __nv_bfloat16*)d_in[0]; P.wqkv = (const __nv_bfloat16*)d_in[1]; P.wo = (const __nv_bfloat16*)d_in[2];
  P.wr = (const __nv_bfloat16*)d_in[4]; P.wg = (const __nv_bfloat16*)d_in[5]; P.wu = (const __nv_bfloat16*)d_in[6];
  P.wd = (const __nv_bfloat16*)d_in[7]; P.out = (__nv_bfloat16*)d_out;
  cudaGetSymbolAddress((void**)&P.s, g_scratch);
  void* fn = nullptr;
  cudaDriverEntryPointQueryResult q;
  cudaGetDriverEntryPoint("cuTensorMapEncodeTiled", &fn, cudaEnableDefault, &q);
  EncodeFn enc = (EncodeFn)fn;
  Maps T;
  constexpr CUtensorMapSwizzle S128 = CU_TENSOR_MAP_SWIZZLE_128B, S64 = CU_TENSOR_MAP_SWIZZLE_64B;
  make_map(enc, &T.m[M_X], P.x, 2, {D_, S_}, {D_ * 2}, {64, 128}, S128);
  make_map(enc, &T.m[M_W], P.wqkv, 3, {D_, D_, 3}, {3 * D_ * 2, D_ * 2}, {64, 64, 2}, S128);
  make_map(enc, &T.m[M_Q], P.wqkv, 2, {3 * D_, D_}, {3 * D_ * 2}, {64, 64}, S128);
  make_map(enc, &T.m[M_O], P.wo, 4, {64, 64, 16, 16}, {D_ * 2, 64 * D_ * 2, 128}, {64, 64, 1, 2}, S128);
  make_map(enc, &T.m[M_S], P.wo, 4, {64, 64, 16, 16}, {D_ * 2, 64 * D_ * 2, 128}, {64, 16, 4, 2}, S128);
  make_map(enc, &T.m[M_G], P.wg, 3, {F_, D_, 1}, {F_ * 2, F_ * 2 * D_}, {32, 128, 1}, S64);
  make_map(enc, &T.m[M_U], P.wu, 3, {F_, D_, 1}, {F_ * 2, F_ * 2 * D_}, {32, 128, 1}, S64);
  make_map(enc, &T.m[M_D], P.wd, 3, {64, F_, 16}, {D_ * 2, 128}, {64, 32, 2}, S128);
  make_map(enc, &T.m[M_L], P.wd, 2, {64, F_ * 16}, {128}, {8, 32}, CU_TENSOR_MAP_SWIZZLE_NONE);
  cudaFuncSetAttribute(fused_kernel, cudaFuncAttributeMaxDynamicSharedMemorySize, SMEM_BYTES);
  fused_kernel<<<NCTA, 384, SMEM_BYTES>>>(P, T);
}
```

```cpp
#include <cuda_runtime.h>
#include <cuda.h>
#include <cuda_bf16.h>
#include <stdint.h>
#include <type_traits>
#include <initializer_list>

namespace {

constexpr int S_ = 2048, D_ = 1024, F_ = 3584;
constexpr int NCTA = 128, NFFN = 112;
constexpr uint32_t SENT = 0xFFFFFFFFu;
constexpr int SPIN_LIMIT = 1 << 20;

#define FD0 700
#define FD1 800
#define GDELAY 400
#define PLAG 8
#define MFIRST 320
#define MKV 1430
#define MO 720
#define ADELAY 150
#define ADELAY2 600
#define R1MID 5
#define SDEL2 500
#define XDELAY 500
#define YDELAY 670
#define GU1 6
#define GU2 20
#define OPACE 500
#define NAP __nanosleep(20)
constexpr uint32_t STAGE_B = 57344;
constexpr uint32_t OFF_STATS = 229376;
constexpr uint32_t OFF_COLSUM = 231424;
constexpr uint32_t OFF_BARS = 232192;
constexpr uint32_t SMEM_BYTES = 232448;
constexpr uint32_t B_FULL = 0, B_EMPTY = 32, B_E = 64, B_AUX = 128, B_EVA = 136, B_EVB = 144, B_BF = 152, B_LATE = 232, B_FFN = 240, B_SW = 248;
constexpr uint32_t B_OUT = B_FULL, B_SEL = B_FULL + 8, B_WR = B_FULL + 16, B_FFD = B_FULL + 24, B_E16 = B_EMPTY + 16, B_KVB = B_EMPTY + 8, B_DUMMY = B_SW + 4,
                   B_GATE = B_EMPTY + 24, B_ID = B_BF + 56, B_KVP = B_BF + 64, B_F15 = B_BF + 72;
constexpr uint32_t UNIT = 8192;
constexpr uint32_t sb = 1024;
constexpr uint32_t bars = sb + OFF_BARS;
constexpr uint64_t tab5(int a, int b, int c, int d, int e, int f, int g, int h, int i = 0, int j = 0) {
  return (uint64_t)a | (uint64_t)b << 5 | (uint64_t)c << 10 | (uint64_t)d << 15 | (uint64_t)e << 20 | (uint64_t)f << 25 | (uint64_t)g << 30 | (uint64_t)h << 35 |
         (uint64_t)i << 40 | (uint64_t)j << 45;
}
constexpr uint64_t BT0 = tab5(4, 11, 18, 25, 7, 9, 16, 0), BT1 = tab5(4, 11, 18, 25, 21, 23, 2, 0);
constexpr uint64_t GT0 = tab5(2, 21, 23, 18, 0, 25, 14, 7), GT1 = tab5(16, 7, 9, 18, 0, 25, 14, 21);
constexpr uint64_t DT0 = tab5(6, 13, 20, 27, 9, 10, 16, 17), DT1 = tab5(6, 13, 20, 27, 23, 24, 2, 3);
__device__ __forceinline__ uint32_t unit_of(uint64_t tab, int i) { return ((uint32_t)(tab >> (5 * i)) & 31) * UNIT; }
__device__ __forceinline__ uint32_t ring_of(int p, int w) { return (p & 1) * (2 * STAGE_B) + ((p & 2) ? 49152 + w * STAGE_B : w * UNIT); }
constexpr uint32_t OFF_LNP = OFF_STATS + 1024;

struct Scratch {
  uint4 obuf[32 * 64 * 128];
  uint4 kvp[16 * 8 * 256];
  uint4 zp[16 * 8 * 16];
  uint4 ybuf[NCTA * NFFN * 2];
  uint4 st1[64 * 48];
  uint4 csp[16 * 8 * 48];
  uint4 st2[S_];
  uint4 hsel[2 * 8 * 128];
  uint32_t cand[8 * 32];
  uint32_t when[32 * 32];
  unsigned epoch;
};
__device__ __align__(1024) Scratch g_scratch;
__device__ __forceinline__ uint32_t smem_u32(const void* p) { return (uint32_t)__cvta_generic_to_shared(p); }
__device__ __forceinline__ void mbar_init(uint32_t bar, uint32_t cnt) { asm volatile("mbarrier.init.shared::cta.b64 [%0], %1;" :: "r"(bar), "r"(cnt) : "memory"); }
__device__ __forceinline__ void mbar_expect_tx(uint32_t bar, uint32_t bytes) { asm volatile("mbarrier.arrive.expect_tx.shared::cta.b64 _, [%0], %1;" :: "r"(bar), "r"(bytes) : "memory"); }
__device__ __forceinline__ void mbar_arrive(uint32_t bar) { asm volatile("mbarrier.arrive.shared::cta.b64 _, [%0];" :: "r"(bar) : "memory"); }
#define SPINCHK(it) if ((it) > SPIN_LIMIT) break
__device__ __forceinline__ void mbar_wait(uint32_t bar, uint32_t parity) {
  asm volatile("{\n.reg .pred p;\n.reg .u32 c;\nmov.u32 c, 0;\n"
               "WL:\nmbarrier.try_wait.parity.shared::cta.b64 p, [%0], %1;\n@p bra WD;\n"
               "add.u32 c, c, 1;\nsetp.lt.u32 p, c, 1048576;\n@p bra WL;\nWD:\n}" :: "r"(bar), "r"(parity) : "memory");
}
__device__ __forceinline__ bool mbar_test(uint32_t bar, uint32_t parity) {
  uint32_t ok;
  asm volatile("{\n.reg .pred p;\nmbarrier.test_wait.parity.shared::cta.b64 p, [%1], %2;\nselp.u32 %0, 1, 0, p;\n}" : "=r"(ok) : "r"(bar), "r"(parity) : "memory");
  return ok;
}
__device__ __forceinline__ uint64_t l2_stream() { uint64_t p; asm("createpolicy.fractional.L2::evict_first.b64 %0, 1.0;" : "=l"(p)); return p; }
__device__ __forceinline__ void tma_2d(uint32_t dst, const CUtensorMap* tm, int c0, int c1, uint32_t bar, bool stream) {
  if (stream) asm volatile("cp.async.bulk.tensor.2d.shared::cluster.global.mbarrier::complete_tx::bytes.L2::cache_hint [%0], [%1, {%3, %4}], [%2], %5;"
                           :: "r"(dst), "l"(tm), "r"(bar), "r"(c0), "r"(c1), "l"(l2_stream()) : "memory");
  else asm volatile("cp.async.bulk.tensor.2d.shared::cluster.global.mbarrier::complete_tx::bytes [%0], [%1, {%3, %4}], [%2];"
                    :: "r"(dst), "l"(tm), "r"(bar), "r"(c0), "r"(c1) : "memory");
}
__device__ __forceinline__ void tma_3d(uint32_t dst, const CUtensorMap* tm, int c0, int c1, int c2, uint32_t bar, bool stream) {
  if (stream) asm volatile("cp.async.bulk.tensor.3d.shared::cluster.global.mbarrier::complete_tx::bytes.L2::cache_hint [%0], [%1, {%3, %4, %5}], [%2], %6;"
                           :: "r"(dst), "l"(tm), "r"(bar), "r"(c0), "r"(c1), "r"(c2), "l"(l2_stream()) : "memory");
  else asm volatile("cp.async.bulk.tensor.3d.shared::cluster.global.mbarrier::complete_tx::bytes [%0], [%1, {%3, %4, %5}], [%2];"
                    :: "r"(dst), "l"(tm), "r"(bar), "r"(c0), "r"(c1), "r"(c2) : "memory");
}
__device__ __forceinline__ void tma_4d(uint32_t dst, const CUtensorMap* tm, int c0, int c1, int c2, int c3, uint32_t bar) {
  asm volatile("cp.async.bulk.tensor.4d.shared::cluster.global.mbarrier::complete_tx::bytes.L2::cache_hint [%0], [%1, {%3, %4, %5, %6}], [%2], %7;"
               :: "r"(dst), "l"(tm), "r"(bar), "r"(c0), "r"(c1), "r"(c2), "r"(c3), "l"(l2_stream()) : "memory");
}
__device__ __forceinline__ void tma_2d_mc(uint32_t dst, const CUtensorMap* tm, int c0, int c1, uint32_t bar, bool stream) {
  if (stream) asm volatile("cp.async.bulk.tensor.2d.shared::cluster.global.mbarrier::complete_tx::bytes.multicast::cluster.L2::cache_hint [%0], [%1, {%3, %4}], [%2], %5, %6;"
                           :: "r"(dst), "l"(tm), "r"(bar), "r"(c0), "r"(c1), "h"((uint16_t)3), "l"(l2_stream()) : "memory");
  else asm volatile("cp.async.bulk.tensor.2d.shared::cluster.global.mbarrier::complete_tx::bytes.multicast::cluster [%0], [%1, {%3, %4}], [%2], %5;"
                    :: "r"(dst), "l"(tm), "r"(bar), "r"(c0), "r"(c1), "h"((uint16_t)3) : "memory");
}
__device__ __forceinline__ bool elect_one() {
  uint32_t p;
  asm volatile("{\n.reg .pred q;\nelect.sync _|q, 0xFFFFFFFF;\nselp.u32 %0, 1, 0, q;\n}" : "=r"(p));
  return p;
}
__device__ __forceinline__ void bulk_load_mc(uint32_t dst, const void* src, uint32_t bytes, uint32_t bar) {
  asm volatile("cp.async.bulk.shared::cluster.global.mbarrier::complete_tx::bytes.multicast::cluster [%0], [%1], %2, [%3], %4;"
               :: "r"(dst), "l"(src), "r"(bytes), "r"(bar), "h"((uint16_t)3) : "memory");
}
__device__ __forceinline__ void bulk_load(uint32_t dst, const void* src, uint32_t bytes, uint32_t bar) {
  asm volatile("cp.async.bulk.shared::cluster.global.mbarrier::complete_tx::bytes [%0], [%1], %2, [%3];" :: "r"(dst), "l"(src), "r"(bytes), "r"(bar) : "memory");
}
__device__ __forceinline__ void bulk_store(void* dst, uint32_t src, uint32_t bytes) {
  asm volatile("cp.async.bulk.global.shared::cta.bulk_group [%0], [%1], %2;" :: "l"(dst), "r"(src), "r"(bytes) : "memory");
}
__device__ __forceinline__ void mbar_arrive_rem(uint32_t bar) { asm volatile("mbarrier.arrive.shared::cluster.b64 _, [%0];" :: "r"(bar) : "memory"); }
template <uint32_t O> __device__ __forceinline__ void ldsm4_o(uint32_t addr, uint32_t& a, uint32_t& b, uint32_t& c, uint32_t& d) {
  asm volatile("ldmatrix.sync.aligned.m8n8.x4.shared.b16 {%0,%1,%2,%3}, [%4+%5];" : "=r"(a), "=r"(b), "=r"(c), "=r"(d) : "r"(addr), "n"(O) : "memory");
}
template <uint32_t O> __device__ __forceinline__ void ldsm4t_o(uint32_t addr, uint32_t (&r)[4]) {
  asm volatile("ldmatrix.sync.aligned.m8n8.x4.trans.shared.b16 {%0,%1,%2,%3}, [%4+%5];" : "=r"(r[0]), "=r"(r[1]), "=r"(r[2]), "=r"(r[3]) : "r"(addr), "n"(O) : "memory");
}
__device__ __forceinline__ void mma16816(float (&c)[4], const uint32_t (&a)[4], uint32_t b0, uint32_t b1) {
  asm("mma.sync.aligned.m16n8k16.row.col.f32.bf16.bf16.f32 {%0,%1,%2,%3}, {%4,%5,%6,%7}, {%8,%9}, {%0,%1,%2,%3};"
      : "+f"(c[0]), "+f"(c[1]), "+f"(c[2]), "+f"(c[3]) : "r"(a[0]), "r"(a[1]), "r"(a[2]), "r"(a[3]), "r"(b0), "r"(b1));
}
__device__ __forceinline__ void l2_prefetch(const void* p) { asm volatile("prefetch.global.L2 [%0];" :: "l"(p) : "memory"); }
__device__ __forceinline__ void tmap_prefetch(const CUtensorMap* tm) { asm volatile("prefetch.tensormap [%0];" :: "l"(tm) : "memory"); }
__device__ __forceinline__ void wg_fence() { asm volatile("wgmma.fence.sync.aligned;" ::: "memory"); }
__device__ __forceinline__ void wg_commit() { asm volatile("wgmma.commit_group.sync.aligned;" ::: "memory"); }
template <int N> __device__ __forceinline__ void wg_wait() { asm volatile("wgmma.wait_group.sync.aligned %0;" :: "n"(N) : "memory"); }
template <int N> __device__ __forceinline__ void pin(float (&d)[N]) {
#pragma unroll
  for (int i = 0; i < N; i++) asm volatile("" : "+f"(d[i]) :: "memory");
}
__device__ __forceinline__ void pin4(uint4& v) { asm volatile("" : "+r"(v.x), "+r"(v.y), "+r"(v.z), "+r"(v.w) :: "memory"); }
template <uint32_t SBO, uint32_t SWZ> __device__ __forceinline__ uint64_t dsc(uint32_t lo) { return ((uint64_t)((SBO >> 4) | (SWZ << 30)) << 32) | lo; }
__host__ __device__ constexpr uint32_t dlo(uint32_t addr, uint32_t lbo) { return (addr >> 4) | ((lbo >> 4) << 16); }
__device__ __forceinline__ void bar_sync(int id, int n) { asm volatile("bar.sync %0, %1;" :: "r"(id), "r"(n) : "memory"); }
__device__ __forceinline__ void bar_arrive(int id, int n) { asm volatile("bar.arrive %0, %1;" :: "r"(id), "r"(n) : "memory"); }
__device__ __forceinline__ void fence_async_smem() { asm volatile("fence.proxy.async.shared::cta;" ::: "memory"); }
__device__ __forceinline__ void fence_gpu() { asm volatile("fence.acq_rel.gpu;" ::: "memory"); }
__device__ __forceinline__ uint4 ld_cg4(const void* p) { uint4 v; asm volatile("ld.global.cg.v4.u32 {%0,%1,%2,%3}, [%4];" : "=r"(v.x), "=r"(v.y), "=r"(v.z), "=r"(v.w) : "l"(p) : "memory"); return v; }
__device__ __forceinline__ uint4 ld_rlx4(const void* p) { uint4 v; asm volatile("ld.relaxed.gpu.global.v4.u32 {%0,%1,%2,%3}, [%4];" : "=r"(v.x), "=r"(v.y), "=r"(v.z), "=r"(v.w) : "l"(p) : "memory"); return v; }
__device__ __forceinline__ uint32_t ld_rlx(const void* p) { uint32_t v; asm volatile("ld.relaxed.gpu.global.u32 %0, [%1];" : "=r"(v) : "l"(p) : "memory"); return v; }
__device__ __forceinline__ void st_rlx4(void* p, uint4 v) { asm volatile("st.relaxed.gpu.global.v4.u32 [%0], {%1,%2,%3,%4};" :: "l"(p), "r"(v.x), "r"(v.y), "r"(v.z), "r"(v.w) : "memory"); }
__device__ __forceinline__ void st_rlx2(void* p, uint32_t a, uint32_t b) { asm volatile("st.relaxed.gpu.global.v2.u32 [%0], {%1,%2};" :: "l"(p), "r"(a), "r"(b) : "memory"); }
__device__ __forceinline__ void st_rlx(void* p, uint32_t a) { asm volatile("st.relaxed.gpu.global.u32 [%0], %1;" :: "l"(p), "r"(a) : "memory"); }
__device__ __forceinline__ uint32_t pack2(float lo, float hi) { uint32_t r; asm("cvt.rn.bf16x2.f32 %0, %1, %2;" : "=r"(r) : "f"(hi), "f"(lo)); return r; }
__device__ __forceinline__ float bf_lo(uint32_t v) { return __uint_as_float(v << 16); }
__device__ __forceinline__ float bf_hi(uint32_t v) { return __uint_as_float(v & 0xFFFF0000u); }
__device__ __forceinline__ void stsm4(uint32_t addr, uint32_t a, uint32_t b, uint32_t c, uint32_t d) {
  asm volatile("stmatrix.sync.aligned.m8n8.x4.shared.b16 [%0], {%1,%2,%3,%4};" :: "r"(addr), "r"(a), "r"(b), "r"(c), "r"(d) : "memory");
}
template <uint32_t O> __device__ __forceinline__ void stsm4_o(uint32_t addr, uint32_t a, uint32_t b, uint32_t c, uint32_t d) {
  asm volatile("stmatrix.sync.aligned.m8n8.x4.shared.b16 [%0+%5], {%1,%2,%3,%4};" :: "r"(addr), "r"(a), "r"(b), "r"(c), "r"(d), "n"(O) : "memory");
}
__device__ __forceinline__ void sts4(uint32_t addr, uint32_t a, uint32_t b, uint32_t c, uint32_t d) { asm volatile("st.shared.v4.u32 [%0], {%1,%2,%3,%4};" :: "r"(addr), "r"(a), "r"(b), "r"(c), "r"(d) : "memory"); }
__device__ __forceinline__ void sts2f(uint32_t addr, float a, float b) { asm volatile("st.shared.v2.f32 [%0], {%1,%2};" :: "r"(addr), "f"(a), "f"(b) : "memory"); }
__device__ __forceinline__ void sts1(uint32_t addr, uint32_t a) { asm volatile("st.shared.u32 [%0], %1;" :: "r"(addr), "r"(a) : "memory"); }
__device__ __forceinline__ float2 lds2f(uint32_t addr) { float2 v; asm volatile("ld.shared.v2.f32 {%0,%1}, [%2];" : "=f"(v.x), "=f"(v.y) : "r"(addr) : "memory"); return v; }
template <uint32_t O> __device__ __forceinline__ float2 lds2f_o(uint32_t addr) { float2 v; asm volatile("ld.shared.v2.f32 {%0,%1}, [%2+%3];" : "=f"(v.x), "=f"(v.y) : "r"(addr), "n"(O) : "memory"); return v; }
template <int I, int N, class F> __device__ __forceinline__ void static_for(F&& f) { if constexpr (I < N) { f(std::integral_constant<int, I>{}); static_for<I + 1, N>(f); } }
__device__ __forceinline__ uint4 lds4(uint32_t addr) { uint4 v; asm volatile("ld.shared.v4.u32 {%0,%1,%2,%3}, [%4];" : "=r"(v.x), "=r"(v.y), "=r"(v.z), "=r"(v.w) : "r"(addr) : "memory"); return v; }
__device__ __forceinline__ uint32_t lds1(uint32_t addr) { uint32_t v; asm volatile("ld.shared.u32 %0, [%1];" : "=r"(v) : "r"(addr) : "memory"); return v; }
__device__ __forceinline__ float ex2(float x) { float y; asm("ex2.approx.ftz.f32 %0, %1;" : "=f"(y) : "f"(x)); return y; }
__device__ __forceinline__ uint32_t max4(uint32_t m, const uint4& v) { return __vimax3_u32(__vimax3_u32(m, v.x, v.y), v.z, v.w); }
__device__ __forceinline__ float rsq(float x) { float y; asm("rsqrt.approx.ftz.f32 %0, %1;" : "=f"(y) : "f"(x)); return y; }
__device__ __forceinline__ float rcp(float x) { float y; asm("rcp.approx.ftz.f32 %0, %1;" : "=f"(y) : "f"(x)); return y; }
__device__ __forceinline__ uint2 ld_rlx2(const void* p) { uint2 v; asm volatile("ld.relaxed.gpu.global.v2.u32 {%0,%1}, [%2];" : "=r"(v.x), "=r"(v.y) : "l"(p) : "memory"); return v; }
template <uint32_t O> __device__ __forceinline__ uint4 lds4_o(uint32_t addr) { uint4 v; asm volatile("ld.shared.v4.u32 {%0,%1,%2,%3}, [%4+%5];" : "=r"(v.x), "=r"(v.y), "=r"(v.z), "=r"(v.w) : "r"(addr), "n"(O) : "memory"); return v; }
__device__ __forceinline__ uint32_t phi2(float u0, float u1, float rl, uint32_t r2) {
  uint32_t pu, r;
  asm("cvt.rn.relu.bf16x2.f32 %0, %1, %2;" : "=r"(pu) : "f"(u1), "f"(u0));
  asm("fma.rn.bf16x2 %0, %1, %2, %3;" : "=r"(r) : "r"(pu), "r"(r2), "r"(pack2(__saturatef(ex2(u0 * rl) + 1e-6f), __saturatef(ex2(u1 * rl) + 1e-6f))));
  return r;
}
__device__ __forceinline__ uint32_t dup2(float r) { uint32_t v; asm("cvt.rn.relu.bf16x2.f32 %0, %1, %1;" : "=r"(v) : "f"(r)); return v; }
__device__ __forceinline__ uint32_t zero_after(const uint32_t (&v)[16]) {
  uint32_t z = 0;
#pragma unroll
  for (int i = 0; i < 16; i++) z |= v[i];
  return z & 0x80008000u;
}
__device__ __forceinline__ uint32_t hadd2(uint32_t a, uint32_t b) { uint32_t v; asm("add.rn.bf16x2 %0, %1, %2;" : "=r"(v) : "r"(a), "r"(b)); return v; }
__device__ __forceinline__ void sched_fence() { asm volatile("{\n.reg .pred p;\n.reg .u64 c;\nSF:\nmov.u64 c, %clock64;\nsetp.eq.u64 p, c, 0;\n@p bra SF;\n}" ::: "memory"); }
__device__ __forceinline__ uint32_t now_ns() { uint32_t v; asm volatile("mov.u32 %0, %%globaltimer_lo;" : "=r"(v) :: "memory"); return v; }
__device__ __forceinline__ void meet(uint32_t* mine, const uint4* all, int first, int after, uint32_t bar) {
  const uint32_t t0 = now_ns() & ~1u;
  if ((threadIdx.x & 31) == 0) st_rlx(mine, t0);
  while ((int)(now_ns() - t0) < first) NAP;
  uint4 v;
#pragma unroll 1
  for (int it = 0; it < SPIN_LIMIT; it++) { v = ld_rlx4(all); if (!__any_sync(~0u, max4(0, v) == SENT)) break; }
  const int d = min(__reduce_max_sync(~0u, max(max((int)(v.x - t0), (int)(v.y - t0)), max((int)(v.z - t0), (int)(v.w - t0)))), 100000) + after;
  mbar_wait(bar, 0);
  while ((int)(now_ns() - t0) < d) NAP;
}
__device__ __forceinline__ uint32_t hmul2(uint32_t a, uint32_t b) { uint32_t v; asm("mul.rn.bf16x2 %0, %1, %2;" : "=r"(v) : "r"(a), "r"(b)); return v; }
__device__ __forceinline__ uint32_t lane_id() { uint32_t v; asm volatile("mov.u32 %0, %%laneid;" : "=r"(v)); return v; }
template <int A, int B, int N> __device__ __forceinline__ void pinr(float (&d)[N]) {
#pragma unroll
  for (int i = A; i < B; i++) asm volatile("" : "+f"(d[i]) :: "memory");
}
template <int N> __device__ __forceinline__ void pinu(uint32_t (&d)[N]) {
#pragma unroll
  for (int i = 0; i < N; i++) asm volatile("" : "+r"(d[i]) :: "memory");
}

template<int TA, int TB, int OFF, int SZ> __device__ __forceinline__ void wgmma_n192_ss(float (&d)[SZ], uint64_t da, uint64_t db, int scale_d) {
  asm volatile("{\n.reg .pred p;\nsetp.ne.b32 p, %98, 0;\n"
    "wgmma.mma_async.sync.aligned.m64n192k16.f32.bf16.bf16 {%0,%1,%2,%3,%4,%5,%6,%7,%8,%9,%10,%11,%12,%13,%14,%15,%16,%17,%18,%19,%20,%21,%22,%23,%24,%25,%26,%27,%28,%29,%30,%31,%32,%33,%34,%35,%36,%37,%38,%39,%40,%41,%42,%43,%44,%45,%46,%47,%48,%49,%50,%51,%52,%53,%54,%55,%56,%57,%58,%59,%60,%61,%62,%63,%64,%65,%66,%67,%68,%69,%70,%71,%72,%73,%74,%75,%76,%77,%78,%79,%80,%81,%82,%83,%84,%85,%86,%87,%88,%89,%90,%91,%92,%93,%94,%95}, %96, %97, p, 1, 1, %99, %100;\n}\n"
    : "+f"(d[OFF+0]), "+f"(d[OFF+1]), "+f"(d[OFF+2]), "+f"(d[OFF+3]), "+f"(d[OFF+4]), "+f"(d[OFF+5]), "+f"(d[OFF+6]), "+f"(d[OFF+7]),
      "+f"(d[OFF+8]), "+f"(d[OFF+9]), "+f"(d[OFF+10]), "+f"(d[OFF+11]), "+f"(d[OFF+12]), "+f"(d[OFF+13]), "+f"(d[OFF+14]), "+f"(d[OFF+15]),
      "+f"(d[OFF+16]), "+f"(d[OFF+17]), "+f"(d[OFF+18]), "+f"(d[OFF+19]), "+f"(d[OFF+20]), "+f"(d[OFF+21]), "+f"(d[OFF+22]), "+f"(d[OFF+23]),
      "+f"(d[OFF+24]), "+f"(d[OFF+25]), "+f"(d[OFF+26]), "+f"(d[OFF+27]), "+f"(d[OFF+28]), "+f"(d[OFF+29]), "+f"(d[OFF+30]), "+f"(d[OFF+31]),
      "+f"(d[OFF+32]), "+f"(d[OFF+33]), "+f"(d[OFF+34]), "+f"(d[OFF+35]), "+f"(d[OFF+36]), "+f"(d[OFF+37]), "+f"(d[OFF+38]), "+f"(d[OFF+39]),
      "+f"(d[OFF+40]), "+f"(d[OFF+41]), "+f"(d[OFF+42]), "+f"(d[OFF+43]), "+f"(d[OFF+44]), "+f"(d[OFF+45]), "+f"(d[OFF+46]), "+f"(d[OFF+47]),
      "+f"(d[OFF+48]), "+f"(d[OFF+49]), "+f"(d[OFF+50]), "+f"(d[OFF+51]), "+f"(d[OFF+52]), "+f"(d[OFF+53]), "+f"(d[OFF+54]), "+f"(d[OFF+55]),
      "+f"(d[OFF+56]), "+f"(d[OFF+57]), "+f"(d[OFF+58]), "+f"(d[OFF+59]), "+f"(d[OFF+60]), "+f"(d[OFF+61]), "+f"(d[OFF+62]), "+f"(d[OFF+63]),
      "+f"(d[OFF+64]), "+f"(d[OFF+65]), "+f"(d[OFF+66]), "+f"(d[OFF+67]), "+f"(d[OFF+68]), "+f"(d[OFF+69]), "+f"(d[OFF+70]), "+f"(d[OFF+71]),
      "+f"(d[OFF+72]), "+f"(d[OFF+73]), "+f"(d[OFF+74]), "+f"(d[OFF+75]), "+f"(d[OFF+76]), "+f"(d[OFF+77]), "+f"(d[OFF+78]), "+f"(d[OFF+79]),
      "+f"(d[OFF+80]), "+f"(d[OFF+81]), "+f"(d[OFF+82]), "+f"(d[OFF+83]), "+f"(d[OFF+84]), "+f"(d[OFF+85]), "+f"(d[OFF+86]), "+f"(d[OFF+87]),
      "+f"(d[OFF+88]), "+f"(d[OFF+89]), "+f"(d[OFF+90]), "+f"(d[OFF+91]), "+f"(d[OFF+92]), "+f"(d[OFF+93]), "+f"(d[OFF+94]), "+f"(d[OFF+95])
    : "l"(da), "l"(db), "r"(scale_d), "n"(TA), "n"(TB));
}
template<int TA, int TB, int OFF, int SZ> __device__ __forceinline__ void wgmma_n128_ss(float (&d)[SZ], uint64_t da, uint64_t db, int scale_d) {
  asm volatile("{\n.reg .pred p;\nsetp.ne.b32 p, %66, 0;\n"
    "wgmma.mma_async.sync.aligned.m64n128k16.f32.bf16.bf16 {%0,%1,%2,%3,%4,%5,%6,%7,%8,%9,%10,%11,%12,%13,%14,%15,%16,%17,%18,%19,%20,%21,%22,%23,%24,%25,%26,%27,%28,%29,%30,%31,%32,%33,%34,%35,%36,%37,%38,%39,%40,%41,%42,%43,%44,%45,%46,%47,%48,%49,%50,%51,%52,%53,%54,%55,%56,%57,%58,%59,%60,%61,%62,%63}, %64, %65, p, 1, 1, %67, %68;\n}\n"
    : "+f"(d[OFF+0]), "+f"(d[OFF+1]), "+f"(d[OFF+2]), "+f"(d[OFF+3]), "+f"(d[OFF+4]), "+f"(d[OFF+5]), "+f"(d[OFF+6]), "+f"(d[OFF+7]),
      "+f"(d[OFF+8]), "+f"(d[OFF+9]), "+f"(d[OFF+10]), "+f"(d[OFF+11]), "+f"(d[OFF+12]), "+f"(d[OFF+13]), "+f"(d[OFF+14]), "+f"(d[OFF+15]),
      "+f"(d[OFF+16]), "+f"(d[OFF+17]), "+f"(d[OFF+18]), "+f"(d[OFF+19]), "+f"(d[OFF+20]), "+f"(d[OFF+21]), "+f"(d[OFF+22]), "+f"(d[OFF+23]),
      "+f"(d[OFF+24]), "+f"(d[OFF+25]), "+f"(d[OFF+26]), "+f"(d[OFF+27]), "+f"(d[OFF+28]), "+f"(d[OFF+29]), "+f"(d[OFF+30]), "+f"(d[OFF+31]),
      "+f"(d[OFF+32]), "+f"(d[OFF+33]), "+f"(d[OFF+34]), "+f"(d[OFF+35]), "+f"(d[OFF+36]), "+f"(d[OFF+37]), "+f"(d[OFF+38]), "+f"(d[OFF+39]),
      "+f"(d[OFF+40]), "+f"(d[OFF+41]), "+f"(d[OFF+42]), "+f"(d[OFF+43]), "+f"(d[OFF+44]), "+f"(d[OFF+45]), "+f"(d[OFF+46]), "+f"(d[OFF+47]),
      "+f"(d[OFF+48]), "+f"(d[OFF+49]), "+f"(d[OFF+50]), "+f"(d[OFF+51]), "+f"(d[OFF+52]), "+f"(d[OFF+53]), "+f"(d[OFF+54]), "+f"(d[OFF+55]),
      "+f"(d[OFF+56]), "+f"(d[OFF+57]), "+f"(d[OFF+58]), "+f"(d[OFF+59]), "+f"(d[OFF+60]), "+f"(d[OFF+61]), "+f"(d[OFF+62]), "+f"(d[OFF+63])
    : "l"(da), "l"(db), "r"(scale_d), "n"(TA), "n"(TB));
}
template<int TA, int TB, int OFF, int SZ> __device__ __forceinline__ void wgmma_n64_ss(float (&d)[SZ], uint64_t da, uint64_t db, int scale_d) {
  asm volatile("{\n.reg .pred p;\nsetp.ne.b32 p, %34, 0;\n"
    "wgmma.mma_async.sync.aligned.m64n64k16.f32.bf16.bf16 {%0,%1,%2,%3,%4,%5,%6,%7,%8,%9,%10,%11,%12,%13,%14,%15,%16,%17,%18,%19,%20,%21,%22,%23,%24,%25,%26,%27,%28,%29,%30,%31}, %32, %33, p, 1, 1, %35, %36;\n}\n"
    : "+f"(d[OFF+0]), "+f"(d[OFF+1]), "+f"(d[OFF+2]), "+f"(d[OFF+3]), "+f"(d[OFF+4]), "+f"(d[OFF+5]), "+f"(d[OFF+6]), "+f"(d[OFF+7]),
      "+f"(d[OFF+8]), "+f"(d[OFF+9]), "+f"(d[OFF+10]), "+f"(d[OFF+11]), "+f"(d[OFF+12]), "+f"(d[OFF+13]), "+f"(d[OFF+14]), "+f"(d[OFF+15]),
      "+f"(d[OFF+16]), "+f"(d[OFF+17]), "+f"(d[OFF+18]), "+f"(d[OFF+19]), "+f"(d[OFF+20]), "+f"(d[OFF+21]), "+f"(d[OFF+22]), "+f"(d[OFF+23]),
      "+f"(d[OFF+24]), "+f"(d[OFF+25]), "+f"(d[OFF+26]), "+f"(d[OFF+27]), "+f"(d[OFF+28]), "+f"(d[OFF+29]), "+f"(d[OFF+30]), "+f"(d[OFF+31])
    : "l"(da), "l"(db), "r"(scale_d), "n"(TA), "n"(TB));
}
template<int TA, int TB, int OFF, int SZ> __device__ __forceinline__ void wgmma_n72_ss(float (&d)[SZ], uint64_t da, uint64_t db, int scale_d) {
  asm volatile("{\n.reg .pred p;\nsetp.ne.b32 p, %38, 0;\n"
    "wgmma.mma_async.sync.aligned.m64n72k16.f32.bf16.bf16 {%0,%1,%2,%3,%4,%5,%6,%7,%8,%9,%10,%11,%12,%13,%14,%15,%16,%17,%18,%19,%20,%21,%22,%23,%24,%25,%26,%27,%28,%29,%30,%31,%32,%33,%34,%35}, %36, %37, p, 1, 1, %39, %40;\n}\n"
    : "+f"(d[OFF+0]), "+f"(d[OFF+1]), "+f"(d[OFF+2]), "+f"(d[OFF+3]), "+f"(d[OFF+4]), "+f"(d[OFF+5]), "+f"(d[OFF+6]), "+f"(d[OFF+7]),
      "+f"(d[OFF+8]), "+f"(d[OFF+9]), "+f"(d[OFF+10]), "+f"(d[OFF+11]), "+f"(d[OFF+12]), "+f"(d[OFF+13]), "+f"(d[OFF+14]), "+f"(d[OFF+15]),
      "+f"(d[OFF+16]), "+f"(d[OFF+17]), "+f"(d[OFF+18]), "+f"(d[OFF+19]), "+f"(d[OFF+20]), "+f"(d[OFF+21]), "+f"(d[OFF+22]), "+f"(d[OFF+23]),
      "+f"(d[OFF+24]), "+f"(d[OFF+25]), "+f"(d[OFF+26]), "+f"(d[OFF+27]), "+f"(d[OFF+28]), "+f"(d[OFF+29]), "+f"(d[OFF+30]), "+f"(d[OFF+31]),
      "+f"(d[OFF+32]), "+f"(d[OFF+33]), "+f"(d[OFF+34]), "+f"(d[OFF+35])
    : "l"(da), "l"(db), "r"(scale_d), "n"(TA), "n"(TB));
}
template<int TB, int OFF, int SZ> __device__ __forceinline__ void wgmma_n64_rs(float (&d)[SZ], uint32_t a0, uint32_t a1, uint32_t a2, uint32_t a3, uint64_t db, int scale_d) {
  asm volatile("{\n.reg .pred p;\nsetp.ne.b32 p, %37, 0;\n"
    "wgmma.mma_async.sync.aligned.m64n64k16.f32.bf16.bf16 {%0,%1,%2,%3,%4,%5,%6,%7,%8,%9,%10,%11,%12,%13,%14,%15,%16,%17,%18,%19,%20,%21,%22,%23,%24,%25,%26,%27,%28,%29,%30,%31}, {%32,%33,%34,%35}, %36, p, 1, 1, %38;\n}\n"
    : "+f"(d[OFF+0]), "+f"(d[OFF+1]), "+f"(d[OFF+2]), "+f"(d[OFF+3]), "+f"(d[OFF+4]), "+f"(d[OFF+5]), "+f"(d[OFF+6]), "+f"(d[OFF+7]),
      "+f"(d[OFF+8]), "+f"(d[OFF+9]), "+f"(d[OFF+10]), "+f"(d[OFF+11]), "+f"(d[OFF+12]), "+f"(d[OFF+13]), "+f"(d[OFF+14]), "+f"(d[OFF+15]),
      "+f"(d[OFF+16]), "+f"(d[OFF+17]), "+f"(d[OFF+18]), "+f"(d[OFF+19]), "+f"(d[OFF+20]), "+f"(d[OFF+21]), "+f"(d[OFF+22]), "+f"(d[OFF+23]),
      "+f"(d[OFF+24]), "+f"(d[OFF+25]), "+f"(d[OFF+26]), "+f"(d[OFF+27]), "+f"(d[OFF+28]), "+f"(d[OFF+29]), "+f"(d[OFF+30]), "+f"(d[OFF+31])
    : "r"(a0), "r"(a1), "r"(a2), "r"(a3), "l"(db), "r"(scale_d), "n"(TB));
}
template<int TB, int OFF, int SZ> __device__ __forceinline__ void wgmma_n40_rs(float (&d)[SZ], uint32_t a0, uint32_t a1, uint32_t a2, uint32_t a3, uint64_t db, int scale_d) {
  asm volatile("{\n.reg .pred p;\nsetp.ne.b32 p, %25, 0;\n"
    "wgmma.mma_async.sync.aligned.m64n40k16.f32.bf16.bf16 {%0,%1,%2,%3,%4,%5,%6,%7,%8,%9,%10,%11,%12,%13,%14,%15,%16,%17,%18,%19}, {%20,%21,%22,%23}, %24, p, 1, 1, %26;\n}\n"
    : "+f"(d[OFF+0]), "+f"(d[OFF+1]), "+f"(d[OFF+2]), "+f"(d[OFF+3]), "+f"(d[OFF+4]), "+f"(d[OFF+5]), "+f"(d[OFF+6]), "+f"(d[OFF+7]),
      "+f"(d[OFF+8]), "+f"(d[OFF+9]), "+f"(d[OFF+10]), "+f"(d[OFF+11]), "+f"(d[OFF+12]), "+f"(d[OFF+13]), "+f"(d[OFF+14]), "+f"(d[OFF+15]),
      "+f"(d[OFF+16]), "+f"(d[OFF+17]), "+f"(d[OFF+18]), "+f"(d[OFF+19])
    : "r"(a0), "r"(a1), "r"(a2), "r"(a3), "l"(db), "r"(scale_d), "n"(TB));
}
template<int TB, int OFF, int SZ> __device__ __forceinline__ void wgmma_n128_rs(float (&d)[SZ], uint32_t a0, uint32_t a1, uint32_t a2, uint32_t a3, uint64_t db, int scale_d) {
  asm volatile("{\n.reg .pred p;\nsetp.ne.b32 p, %69, 0;\n"
    "wgmma.mma_async.sync.aligned.m64n128k16.f32.bf16.bf16 {%0,%1,%2,%3,%4,%5,%6,%7,%8,%9,%10,%11,%12,%13,%14,%15,%16,%17,%18,%19,%20,%21,%22,%23,%24,%25,%26,%27,%28,%29,%30,%31,%32,%33,%34,%35,%36,%37,%38,%39,%40,%41,%42,%43,%44,%45,%46,%47,%48,%49,%50,%51,%52,%53,%54,%55,%56,%57,%58,%59,%60,%61,%62,%63}, {%64,%65,%66,%67}, %68, p, 1, 1, %70;\n}\n"
    : "+f"(d[OFF+0]), "+f"(d[OFF+1]), "+f"(d[OFF+2]), "+f"(d[OFF+3]), "+f"(d[OFF+4]), "+f"(d[OFF+5]), "+f"(d[OFF+6]), "+f"(d[OFF+7]),
      "+f"(d[OFF+8]), "+f"(d[OFF+9]), "+f"(d[OFF+10]), "+f"(d[OFF+11]), "+f"(d[OFF+12]), "+f"(d[OFF+13]), "+f"(d[OFF+14]), "+f"(d[OFF+15]),
      "+f"(d[OFF+16]), "+f"(d[OFF+17]), "+f"(d[OFF+18]), "+f"(d[OFF+19]), "+f"(d[OFF+20]), "+f"(d[OFF+21]), "+f"(d[OFF+22]), "+f"(d[OFF+23]),
      "+f"(d[OFF+24]), "+f"(d[OFF+25]), "+f"(d[OFF+26]), "+f"(d[OFF+27]), "+f"(d[OFF+28]), "+f"(d[OFF+29]), "+f"(d[OFF+30]), "+f"(d[OFF+31]),
      "+f"(d[OFF+32]), "+f"(d[OFF+33]), "+f"(d[OFF+34]), "+f"(d[OFF+35]), "+f"(d[OFF+36]), "+f"(d[OFF+37]), "+f"(d[OFF+38]), "+f"(d[OFF+39]),
      "+f"(d[OFF+40]), "+f"(d[OFF+41]), "+f"(d[OFF+42]), "+f"(d[OFF+43]), "+f"(d[OFF+44]), "+f"(d[OFF+45]), "+f"(d[OFF+46]), "+f"(d[OFF+47]),
      "+f"(d[OFF+48]), "+f"(d[OFF+49]), "+f"(d[OFF+50]), "+f"(d[OFF+51]), "+f"(d[OFF+52]), "+f"(d[OFF+53]), "+f"(d[OFF+54]), "+f"(d[OFF+55]),
      "+f"(d[OFF+56]), "+f"(d[OFF+57]), "+f"(d[OFF+58]), "+f"(d[OFF+59]), "+f"(d[OFF+60]), "+f"(d[OFF+61]), "+f"(d[OFF+62]), "+f"(d[OFF+63])
    : "r"(a0), "r"(a1), "r"(a2), "r"(a3), "l"(db), "r"(scale_d), "n"(TB));
}

struct Ptrs { const __nv_bfloat16 *x, *wqkv, *wo, *wr, *wg, *wu, *wd; __nv_bfloat16* out; Scratch* s; };

enum { M_X, M_W, M_Q, M_O, M_S, M_G, M_U, M_D, M_L, M_N };
struct Maps { CUtensorMap m[M_N]; };

__global__ void __cluster_dims__(2, 1, 1) __launch_bounds__(384, 1) fused_kernel(const Ptrs P, const __grid_constant__ Maps T) {
  extern __shared__ __align__(1024) uint8_t smem_raw[];
  const uint32_t rank = blockIdx.x & 1;
  uint32_t own = rank << 24;
  asm("" : "+r"(own));
  const uint32_t sm = own + sb, mb = own + bars;
  int b0;
  { const int j = blockIdx.x >> 1, u = j - 36, v = j * 2 - 8 + (max(u * 37 + 256, 0) >> 8) * (u < 0 ? 0 : 2), w = j < 4 ? j * 16 + 64 : v;
    b0 = ((w & 15) | (w & 48) << 1 | (w & 64) >> 2) + rank; }
#define IDS(B) \
  const int b = (B), rb = b >> 4, cg = b & 15, hf = cg >> 3, s3 = cg & 7, c3 = s3 ^ ((rb & 1) << 2), jp = cg >> 1, km = (~c3 & 6) << 1; \
  const int fidx = rb == (jp & 6) ? -1 : (jp * 7 + rb - (rb > (jp & 6))) * 2 + (b & 1); \
  [[maybe_unused]] auto kcol = [&](int kb) { return (kb ^ (kb < 8 ? km & 8 : km)) * 64; }; \
  auto src_of = [&](int p) { return p == 0 ? s3 : p == 15 ? s3 ^ 1 : (((jp & 3) ^ ((p - 7) >> 1)) << 1) + ((p - 1) & 1); }; \
  [[maybe_unused]] auto frag_of = [&](int p) { return p < 9 ? (p - 1) * 512 : 4096 + src_of(p) * 512; }; \
  (void)hf; (void)fidx
  auto get_b = [&]() { return __shfl_sync(~0u, (int)lds1(mb + B_ID), 0); };
  IDS(b0);
  auto load_w = [&](uint32_t st, int kc, uint32_t bar, bool last) { tma_3d(st + 32768, &T.m[M_W], cg * 64, kc, 1, bar, last); tma_2d(st + 49152, &T.m[M_Q], cg * 64, kc, bar, last); };
  if (threadIdx.x < 256) {
    const int r = threadIdx.x >> 3, c = threadIdx.x & 7, xr = (r & 16) * 8 + (r & 15);
    const uint32_t sw = ((c ^ r) & 7) << 4;
    const __nv_bfloat16* gw = P.wqkv + (kcol(0) + r) * 3072 + cg * 64 + c * 8, *gx = P.x + (rb * 256 + xr) * D_ + kcol(0) + c * 8;
#pragma unroll
    for (int i = 0; i < 6; i++)
      asm volatile("cp.async.cg.shared.global [%0], [%1], 16;" :: "r"(sm + 32768 + i * 4096 + r * 128 + sw), "l"(gw + (i & 1) * 32 * 3072 + ((i >> 1) + 1) % 3 * 1024) : "memory");
    asm volatile("cp.async.commit_group;" ::: "memory");
#pragma unroll
    for (int i = 0; i < 8; i++) asm volatile("cp.async.cg.shared.global [%0], [%1], 16;" :: "r"(sm + i * 2048 + xr * 128 + sw), "l"(gx + i * 16 * D_) : "memory");
    asm volatile("cp.async.commit_group;" ::: "memory");
  }
  const int tid = threadIdx.x, wid = __shfl_sync(~0u, tid >> 5, 0), wg = wid >> 2, lane = lane_id();
  const uint32_t tk = clock64();
  if (wid == 8) {
    if (elect_one()) { tmap_prefetch(&T.m[M_X]); tmap_prefetch(&T.m[M_W]); tmap_prefetch(&T.m[M_Q]); }
  } else if (wid == 9) {
    if (elect_one()) {
#pragma unroll
      for (int i = 0; i < 31; i++) if (8 * i != B_ID) mbar_init(mb + 8 * i, i < 4 ? 1 : i < 8 ? 8 : i < 16 ? 16 : i == 16 ? 64 : i == 17 ? 8 : i == 18 ? 4 : 1);
      asm volatile("fence.mbarrier_init.release.cluster;" ::: "memory");
      fence_async_smem();
    }
  } else if (wid == 11) {
#pragma unroll
    for (int i = 0; i < 4; i++) sts4(sm + OFF_STATS + i * 512 + lane * 16, SENT, SENT, SENT, SENT);
    sts1(mb + B_ID, b);
    if (smem_u32(smem_raw) != sm) asm volatile("trap;");
    fence_async_smem();
  }
  __syncthreads();
  asm volatile("barrier.cluster.arrive.relaxed.aligned;\nbarrier.cluster.wait.aligned;" ::: "memory");

  if (wg == 2) {
    asm volatile("setmaxnreg.dec.sync.aligned.u32 56;");
    if (wid == 8) {
      if (elect_one()) {
#pragma unroll 1
        for (int kb = 1; kb < 15; kb++) {
          const uint32_t fb = mb + B_FULL + 8 * (kb & 3), st = sm + (kb & 3) * STAGE_B;
          const int kc = kcol(kb);
          if (kb < 4) while ((uint32_t)clock64() - tk < FD0 + kb * FD1) {}
          else mbar_wait(fb + B_EMPTY, ((kb >> 2) & 1) ^ 1);
          mbar_expect_tx(fb, STAGE_B);
          tma_2d_mc(st + rank * 16384, &T.m[M_X], kc, rb * 256 + rank * 128, fb, kb >= 12);
          load_w(st, kc, fb, kb >= 8);
          if (kb >= 8 && kb < 11) asm volatile("mbarrier.arrive.shared::cta.b64 _, [%0], %1;" :: "r"(fb + B_EMPTY), "r"(4) : "memory");
        }
        {
          const uint32_t st = sm + 3 * STAGE_B, fa = mb + B_FULL + 24, fb = mb + B_F15;
          const int kc = kcol(15);
          mbar_wait(fa, 0);
          mbar_expect_tx(fa, 32768); mbar_expect_tx(fb, 24576);
          if (rank) { mbar_wait(mb + B_EMPTY + 24, 0); tma_2d_mc(st + 16384, &T.m[M_X], kc, rb * 256 + 128, fa, true); }
          mbar_wait(mb + B_EMPTY, 1);
          tma_3d(st + 32768, &T.m[M_W], cg * 64, kc, 1, fa, true);
          if (!rank) { mbar_wait(mb + B_EMPTY + 24, 0); tma_2d_mc(st, &T.m[M_X], kc, rb * 256, fb, true); }
          tma_2d(st + 49152, &T.m[M_Q], cg * 64, kc, fb, true);
        }
        mbar_expect_tx(mb + B_KVP, 32768 + 2048);
      }
      __syncwarp();
      const uint4* kp = &P.s->kvp[cg * 8 * 256], *zq = &P.s->zp[cg * 8 * 16], *src = &P.s->obuf[(rb * 4 + rank * 2 + hf) * 64 * 128];
      asm volatile("" : "+l"(kp), "+l"(zq), "+l"(src));
      bar_sync(13, 160);
      meet(&P.s->when[cg * 32 + rb], (const uint4*)&P.s->when[cg * 32] + (lane & 1), MFIRST, MKV, mb + B_EVB);
      if (elect_one()) {
        bulk_load(sm + rank * (2 * STAGE_B) + STAGE_B, kp, 32768, mb + B_KVP);
        bulk_load(sm + rank * (2 * STAGE_B) + UNIT, zq, 2048, mb + B_KVP);
      }
      mbar_wait(mb + B_KVP, 0);
      mbar_wait(mb + B_KVB, 1);
      meet(&P.s->when[(16 + rb * 2 + hf) * 32 + s3], (const uint4*)&P.s->when[(16 + rb * 2 + (hf ^ 1)) * 32] + (lane & 1), MFIRST, MO, mb + B_E);
      if (elect_one()) {
        const uint32_t t0 = clock64();
        mbar_arrive(mb + B_F15);
#pragma unroll
        for (int p = 2; p < 5; p++) {
          if (p < 4) while ((uint32_t)clock64() - t0 < (p == 2 ? ADELAY : ADELAY2)) NAP;
          bulk_load_mc(sm + ring_of(p, rank), src + (p - 1) * 512, UNIT, mb + B_BF + 8 * p);
        }
#pragma unroll 1
        for (int p = 5; p < 15; p++) {
          uint32_t dst = sm + ring_of(p, rank), bar = mb + B_BF + 8 * (p % 7);
          const uint4* q = src + frag_of(p);
          asm volatile("" : "+r"(dst), "+r"(bar), "+l"(q));
          mbar_wait(mb + B_E + 8 * ((p - 4) & 7), p >= 12);
          bulk_load_mc(dst, q, UNIT, bar);
        }
        asm volatile("mbarrier.arrive.shared::cta.b64 _, [%0], 8;" :: "r"(mb + B_GATE) : "memory");
        const uint4* s15 = &P.s->obuf[(rb * 4 + hf) * 64 * 128 + frag_of(15)];
        mbar_wait(mb + B_E + 24, 1);
        bulk_load(sm + ring_of(15, 0), s15, UNIT, mb + B_BF + 8); bulk_load(sm + ring_of(15, 1), s15 + 2 * 64 * 128, UNIT, mb + B_BF + 8);
      }
    } else if (wid == 11) {
      IDS(get_b());
      mbar_wait(mb + B_FULL, 0);
      {
        const uint32_t ep = ld_rlx(&P.s->epoch);
        float s = 0.f;
#pragma unroll
        for (int i = 0; i < 4; i++) {
          const uint4 v = ld_cg4((const uint4*)P.wr + lane + i * 32);
          s += (bf_lo(v.x) + bf_hi(v.x)) + (bf_lo(v.y) + bf_hi(v.y)) + (bf_lo(v.z) + bf_hi(v.z)) + (bf_lo(v.w) + bf_hi(v.w));
        }
#pragma unroll
        for (int o = 16; o; o >>= 1) s += __shfl_xor_sync(~0u, s, o);
        if (lane == 0) sts1(mb + B_SW, (__float_as_uint(s) & ~255u) | ((ep + 1) & 255));
      }
      bar_arrive(10, 96);
      if (fidx >= 0) {
        const uint32_t o = (rank * 32 + lane) * (F_ * 2) + (fidx >> 1) * 128;
        const char* q0 = (const char*)P.wg + o, *q1 = (const char*)P.wu + o;
        mbar_wait(mb + B_FULL + 24, 0);
#pragma unroll 1
        for (int r = 0; r < 16; r++, q0 += 64 * F_ * 2, q1 += 64 * F_ * 2) {
          if (mbar_test(mb + B_F15, 0)) { l2_prefetch(q0); l2_prefetch(q1); continue; }
          asm volatile("cp.async.ca.shared.global.L2::128B [%0], [%1], 4;\ncp.async.commit_group;\ncp.async.wait_group %3;\n"
                       "cp.async.ca.shared.global.L2::128B [%0], [%2], 4;\ncp.async.commit_group;\ncp.async.wait_group %3;" :: "r"(mb + B_DUMMY), "l"(q0), "l"(q1), "n"(2) : "memory");
        }
        mbar_wait(mb + B_F15, 0);
        bar_sync(15, 288);
        q0 = (const char*)P.wd + fidx * 65536 + lane * 128;
        const uint32_t bar = mb + B_BF + 48;
        if (lane == 0) mbar_expect_tx(bar, 8192);
#pragma unroll 1
        for (int i = 0; i < 16 + PLAG; i++) {
          if (i < 16) l2_prefetch(q0 + i * 4096);
          if (i >= PLAG && elect_one()) tma_2d(sm + OFF_COLSUM, &T.m[M_L], 0, fidx * 512 + (i - PLAG) * 32, bar, false);
        }
        mbar_wait(bar, 0);
        __syncwarp();
        if (lane == 0) { mbar_arrive(bar); }
        asm volatile("cp.async.wait_all;" ::: "memory");
      } else bar_sync(15, 288);
      bar_arrive(14, 64);
    } else {
      const uint32_t eb = (lane << 24) + bars + B_EMPTY;
      float c[6];
      if (wid == 10) {
        float sx[4] = {0.f, 0.f, 0.f, 0.f}, qx[4] = {0.f, 0.f, 0.f, 0.f};
        const uint32_t xa = sm + ((hf * 4 + (cg & 3)) * 32 + lane) * 128 + ((lane & 7) << 4);
#pragma unroll 1
        for (int kb = 0; kb < 8; kb++) {
          uint4 xv[8];
          const uint32_t so = xa + (kb & 3) * STAGE_B;
          mbar_wait(mb + B_FULL + 8 * (kb & 3), kb >> 2);
#pragma unroll
          for (int i = 0; i < 8; i++) xv[i] = lds4(so ^ (i << 4));
#pragma unroll
          for (int i = 0; i < 8; i++) {
            const uint32_t e[4] = {xv[i].x, xv[i].y, xv[i].z, xv[i].w};
#pragma unroll
            for (int j = 0; j < 4; j++) {
              const float d0 = bf_lo(e[j]), d1 = bf_hi(e[j]);
              sx[j] += d0 + d1; qx[j] = fmaf(d0, d0, fmaf(d1, d1, qx[j]));
            }
          }
          __syncwarp();
          if (lane < 2) mbar_arrive_rem(eb + 8 * (kb & 3));
          if (kb == 1) {
            if (elect_one()) {
#pragma unroll 1
              for (int i = 0; i < 16; i++) bulk_store(&P.s->obuf[((rb * 4 + (i >> 2)) * 64 + (((i >> 2) & 1) == hf ? 32 + s3 * 4 + (i & 3) : (i & 3) * 8 + s3)) * 128], sm + OFF_STATS, 2048);
              bulk_store(&P.s->kvp[(cg * 8 + rb) * 256], sm + OFF_STATS, 2048); bulk_store(&P.s->kvp[(cg * 8 + rb) * 256 + 128], sm + OFF_STATS, 2048);
              bulk_store(&P.s->zp[(cg * 8 + rb) * 16], sm + OFF_STATS, 256);
              if (s3 == 0) bulk_store(&P.s->when[(16 + rb * 2 + hf) * 32], sm + OFF_STATS, 128);
              if (rb == 0) bulk_store(&P.s->when[cg * 32], sm + OFF_STATS, 128);
              asm volatile("cp.async.bulk.commit_group;" ::: "memory");
#pragma unroll
              for (int i = M_O; i < M_N; i++) tmap_prefetch(&T.m[i]);
            }
            __syncwarp();
          }
        }
        asm volatile("cp.async.bulk.wait_group 0;\nfence.proxy.async.global;" ::: "memory");
        fence_gpu();
        c[0] = ((sx[0] + sx[1]) + (sx[2] + sx[3])) * (2.f / D_);
        c[1] = fmaxf(fmaf(-c[0], c[0], ((qx[0] + qx[1]) + (qx[2] + qx[3])) * (2.f / D_)), 0.f);
      } else {
        float a[12];
#pragma unroll
        for (int i = 0; i < 12; i++) a[i] = 0.f;
        const int r2 = lane >> 4, c16 = lane & 15;
        const uint32_t a0 = sm + 32768 + (rb >> 1) * 2048 + r2 * 128 + (((c16 >> 1) ^ r2) << 4) + (c16 & 1) * 8;
#pragma unroll 1
        for (int it = 0; it < 16; it++) {
          uint2 w[12];
          const int s = (it >> 1) & 3;
          const uint32_t so = a0 + s * STAGE_B + (it & 1) * 1024;
          if (!(it & 1)) { mbar_wait(mb + B_FULL + 8 * s, it >> 3); }
          static_for<0, 12>([&](auto ic) { constexpr int i = decltype(ic)::value;
            const float2 v = lds2f_o<(i >> 2) * 8192 + (i & 3) * 256>(so ^ ((i & 3) << 5)); w[i] = make_uint2(__float_as_uint(v.x), __float_as_uint(v.y)); });
#pragma unroll
          for (int i = 0; i < 12; i++) { float* q = a + (i >> 2) * 4; q[0] += bf_lo(w[i].x); q[1] += bf_hi(w[i].x); q[2] += bf_lo(w[i].y); q[3] += bf_hi(w[i].y); }
          __syncwarp();
          if (lane < 2 && (it & 1)) mbar_arrive_rem(eb + 8 * s);
        }
#pragma unroll
        for (int i = 0; i < 6; i++) {
          const int o = (i >> 1) * 4 + (i & 1);
          c[i] = (r2 ? a[o + 2] : a[o]) + __shfl_xor_sync(~0u, r2 ? a[o] : a[o + 2], 16);
        }
      }
      bar_sync(10, 96);
      {
        const uint32_t tag = lds1(mb + B_SW) & 255;
        auto tagged = [&](float v) { return ((__float_as_uint(v) + 128) & ~255u) | tag; };
        if (wid == 9) {
#pragma unroll
          for (int sg = 0; sg < 3; sg++) {
            st_rlx2((uint2*)&P.s->csp[(cg * 8 + rb) * 48] + sg * 32 + (lane & 15) * 2 + (lane >> 4), tagged(c[sg * 2]), tagged(c[sg * 2 + 1]));
          }
        } else st_rlx2((uint2*)&P.s->st1[(rb * 8 + hf * 4 + (cg & 3)) * 48 + lane] + ((cg >> 2) & 1), tagged(c[0]), tagged(c[1]));
        __nanosleep(GDELAY);
#pragma unroll 1
        for (int h = wid - 9; h < 2; h++) {
          const int q = h * 24 + min(lane, 23);
          const uint4* gp = wid == 10 ? &P.s->st1[rb * 8 * 48 + lane] : &P.s->csp[cg * 8 * 48 + q];
          uint4 v[8];
#pragma unroll 1
          for (int it = 0;; it++) {
            uint32_t x = 0;
#pragma unroll
            for (int i = 0; i < 8; i++) v[i] = ld_rlx4(gp + i * 48);
#pragma unroll
            for (int i = 0; i < 8; i++) { v[i].x ^= tag; v[i].y ^= tag; v[i].z ^= tag; v[i].w ^= tag; x |= v[i].x | v[i].y | v[i].z | v[i].w; }
            if (!__any_sync(~0u, (x & 255) != 0)) break;
            SPINCHK(it);
          }
          if (wid == 10) {
#pragma unroll
            for (int i = 0; i < 8; i++) {
              const float m0 = __uint_as_float(v[i].x), m1 = __uint_as_float(v[i].z), dm = 0.5f * (m0 - m1);
              sts2f(sm + OFF_STATS + (i * 32 + lane) * 8, -0.5f * (m0 + m1), rsq(fmaf(dm, dm, 0.5f * (__uint_as_float(v[i].y) + __uint_as_float(v[i].w))) + 1e-5f));
            }
          } else {
            float s4[4] = {0.f, 0.f, 0.f, 0.f};
#pragma unroll
            for (int i = 0; i < 8; i++) { s4[0] += __uint_as_float(v[i].x); s4[1] += __uint_as_float(v[i].y); s4[2] += __uint_as_float(v[i].z); s4[3] += __uint_as_float(v[i].w); }
            sts4(sm + OFF_COLSUM + q * 16, __float_as_uint(s4[0]), __float_as_uint(s4[1]), __float_as_uint(s4[2]), __float_as_uint(s4[3]));
          }
        }
        mbar_arrive(mb + B_AUX);
      }
      IDS(get_b());
      const uint64_t btab = rank ? BT1 : BT0;
      if (wid == 9) {
        {
          const uint4 sv = make_uint4(SENT, SENT, SENT, SENT);
          uint4* y = &P.s->ybuf[b * NFFN * 2 + lane];
#pragma unroll
          for (int i = 0; i < 7; i++) y[i * 32] = sv;
          if (lane < 16) P.s->st2[b * 16 + lane] = make_uint4(0, 0, 0, 0); else P.s->hsel[b * 16 + lane - 16] = sv;
          if (b < 8) P.s->cand[b * 32 + lane] = SENT;
          fence_gpu();
          bar_sync(0, 288);
          if (lane < 16) sts4(sm + OFF_STATS + lane * 128 + ((lane & 7) << 4), 0x3F803F80u, 0x3F803F80u, 0x3F803F80u, 0x3F803F80u);
          fence_async_smem();
          __syncwarp();
          if (lane == 0) mbar_arrive(mb + B_LATE);
        }
        {
          const int p = lane & 15, sl = p % 7;
          const bool sliced = p > 0 && p < 9;
          const uint32_t c = sliced ? ((p - 1) >> 1) * 16 | ((hf ^ 1) * 8 + ((p - 1) & 1) * 4) << 8 | 128 << 16 : (hf * 8 + src_of(p)) << 8;
          const uint32_t ev = mb + (p < 4 ? B_EVA : B_E + 8 * ((p < 7 ? p == 6 : p - 4) & 7) + (p >= 12));
          mbar_wait(mb + B_EVA, 0);
          sts4(sm + OFF_COLSUM + 512 + p * 16, sm + unit_of(btab, sl), mb + B_BF + 8 * sl, c, ev);
          __syncwarp();
        }
        if (elect_one()) {
#pragma unroll 1
          for (int p = 0; p < 16; p++) {
            const uint4 e = lds4(sm + OFF_COLSUM + 512 + p * 16);
            if (p == 4) mbar_wait(mb + B_WR, 0);
            mbar_wait(e.w & ~1u, e.w & 1);
            mbar_expect_tx(e.y, p > 1 ? 4 * UNIT : 2 * UNIT);
            tma_4d(e.x, (const CUtensorMap*)((const char*)&T.m[M_O] + (e.z >> 16)), 0, e.z & 255, (e.z >> 8) & 255, c3 * 2, e.y);
          }
        }
      } else {
        const uint32_t* wp = (const uint32_t*)(P.wr + c3 * 128) + (lane & 7) * 8 + (lane >> 3);
        const uint32_t w0 = ld_rlx(wp), w1 = ld_rlx(wp + 4);
#pragma unroll 1
        for (int i = 0; i < 4; i++) { l2_prefetch((const char*)P.wo + b * 16384 + i * 4096 + lane * 128); __nanosleep(300); }
        const int p = lane & 15, p2 = min(p + 2, 15);
        const uint32_t t0 = dlo(sb, 8192) + (unit_of(btab, p % 7) >> 4), t1 = ring_of(p + 1, lane >> 4), t2 = mb + B_BF + 8 * (p2 % 7);
        mbar_wait(mb + B_EVB, 0);
        bar_sync(14, 64);
        sts2f(sm + OFF_COLSUM + (lane & 6) * 64 + (lane >> 3) * 16 + (lane & 1) * 8, __uint_as_float(w0), __uint_as_float(w1));
        sts1(sm + OFF_COLSUM + (lane >> 3) * 128 + 64 + (lane & 7) * 4, 0x3F803F80u);
        sts4(sm + OFF_STATS + lane * 16, t0, t1, t2, (p2 / 7) & 1);
        __syncwarp();
        if (elect_one()) {
          mbar_arrive(mb + B_WR);
          if (fidx >= 0) {
            mbar_expect_tx(mb + B_FFN, 131072); mbar_expect_tx(mb + B_FFD, 32768);
            uint64_t gt = rank ? GT1 : GT0;
            mbar_wait(mb + B_KVP, 0);
#pragma unroll 1
            for (int f = 0; f < 8; f++, gt >>= 5) {
              uint32_t d0 = sm + unit_of(gt, 0);
              asm volatile("" : "+r"(d0));
              if (f == 3) mbar_wait(mb + B_GATE, 1);
              mbar_wait(mb + (f < 1 ? B_KVB : B_E + (f < 3 ? 3 * f - 1 : (f + 5) >> 1) * 8), f < 1 || f >= 3);
              tma_3d(d0, &T.m[M_G], fidx * 32, f * 128, 0, mb + B_FFN, true);
              tma_3d(d0 + UNIT, &T.m[M_U], fidx * 32, f * 128, 0, mb + B_FFN, true);
            }
            mbar_expect_tx(mb + B_KVP, 32768);
#pragma unroll
            for (int w = 0; w < 8; w++) {
              if (w == 2) mbar_wait(mb + B_E + 56, 1);
              if (w == 6) mbar_wait(mb + B_E16, 1);
              if (w == 4) mbar_wait(mb + B_EVA, 1);
              tma_3d(sm + ((DT0 >> (5 * w)) & 31) * UNIT + (w < 4 ? 0 : w < 6 ? 14 * UNIT : 0 - 14 * UNIT) * rank, &T.m[M_D], 0, fidx * 32, 2 * w, mb + (w < 4 ? B_FFD : B_KVP), true);
            }
          }
        }
      }
    }
    __syncwarp();
    IDS(get_b());
    mbar_wait(mb + B_EVB, 0);
    mbar_wait(mb + B_OUT, 0);
    const float2 cf = lds2f(sm + OFF_STATS + 64);
    const int cand0 = 2047 - (__float_as_int(cf.x) & 2047), cand1 = 2047 - (__float_as_int(cf.y) & 2047), rr = lane >> 4;
    __nv_bfloat16* const ob = P.out + c3 * 128 + (lane & 15) * 8;
    auto store_row = [&](uint32_t ha, uint32_t la, int row, bool on) {
      const uint4 v = lds4(ha);
      const float2 pr = lds2f(la);
      const float f = 1.f + pr.x, n = pr.y;
      asm volatile("{\n.reg .pred p;\nsetp.ne.u32 p, %5, 0;\n@p st.global.v4.u32 [%0], {%1,%2,%3,%4};\n}" :: "l"(ob + row * D_),
                   "r"(pack2(fmaf(bf_lo(v.x), f, n), fmaf(bf_hi(v.x), f, n))), "r"(pack2(fmaf(bf_lo(v.y), f, n), fmaf(bf_hi(v.y), f, n))),
                   "r"(pack2(fmaf(bf_lo(v.z), f, n), fmaf(bf_hi(v.z), f, n))), "r"(pack2(fmaf(bf_lo(v.w), f, n), fmaf(bf_hi(v.w), f, n))), "r"((uint32_t)on) : "memory");
    };
    {
      uint32_t t0 = clock64();
      uint32_t ha = sm + 4 * UNIT + ((wid >> 1) & 1) * STAGE_B + ((wid & 1) * 32 + rr) * 256 + (((lane & 15) ^ rr) << 4), la = sm + OFF_LNP + ((wid & 3) * 32 + rr) * 8;
      int row = rb * 256 + hf * 64 + (wid & 2) * 64 + (wid & 1) * 32 + rr;
#pragma unroll 1
      for (int i = 0; i < 16; i += 2, ha += 512 * 2, la += 16 * 2, row += 2 * 2, t0 += OPACE) {
        while ((int)((uint32_t)clock64() - t0) < 0) NAP;
#pragma unroll
        for (int j = 0; j < 2; j++) store_row((ha ^ (((i + j) & 3) << 5)) + j * 512, la + j * 16, row + 2 * j, row + 2 * j != cand0 && row + 2 * j != cand1);
      }
    }
    if (wid == 8) {
      const uint32_t kc = __float_as_uint(rr ? cf.y : cf.x);
      const int c = rr ? cand1 : cand0;
      mbar_wait(mb + B_SEL, 0);
      const float2 sel = lds2f(sm + OFF_STATS + 80);
      store_row(sm + 4 * UNIT + ((c >> 7) & 1) * STAGE_B + (c & 63) * 256 + (((lane & 15) ^ (c & 7)) << 4), sm + OFF_LNP + (((c >> 1) & 64) + (c & 63)) * 8, c,
                kc != __float_as_uint(sel.x) && kc != __float_as_uint(sel.y) && (c >> 8) == rb && ((c >> 6) & 1) == hf);
    }
  } else {
    asm volatile("setmaxnreg.inc.sync.aligned.u32 224;");
    const int t128 = tid & 127, warp = wid & 3, g = lane >> 2, t = lane & 3;
    const uint32_t sk = rank * (2 * STAGE_B);
    uint4 ost[2][4];
    uint4 abuf[3][4];
    uint4* od1;
    const uint4* ain;
    int b1;
    const uint32_t eb = (lane << 24) + bars + B_E;
    float acc[64];
    uint4 wb[4];
    uint32_t hp[32];
    {
      float acc0[96], acc1[96];
#pragma unroll
      for (int i = 0; i < 96; i++) { acc0[i] = 0.f; acc1[i] = 0.f; }
      const uint32_t xo0 = dlo(sb, 16) + (wg * 2 + hf) * 512, xo1 = dlo(sb, 16) + (wg * 2 + (hf ^ 1)) * 512;
      constexpr uint32_t ST = STAGE_B >> 4, WD = dlo(sb + 49152, 8192), WV = dlo(sb + 32768, 8192);
      const uint32_t eb0 = (t128 << 24) + bars + B_EMPTY;
      pin(acc1); pin(acc0);
      if (wg) asm volatile("cp.async.wait_group 0;" ::: "memory"); else asm volatile("cp.async.wait_group 1;" ::: "memory");
      fence_async_smem();
      bar_sync(1, 256);
      if (!wg) {
        asm volatile("cp.async.wait_group 0;" ::: "memory");
        fence_async_smem();
        bar_sync(2, 256);
        if (tid == 0) mbar_arrive(mb + B_FULL);
      }
#pragma unroll 1
      for (int kb = 0; kb < 12; kb++) {
        const int s = kb & 3;
        if (kb) mbar_wait(mb + B_FULL + 8 * s, (kb >> 2) & 1);
        pin(acc0); pin(acc1);
        wg_fence();
#pragma unroll
        for (int k = 0; k < 4; k++) {
          const uint64_t db = dsc<1024, 1>(WV + s * ST + k * 128);
          wgmma_n192_ss<0, 1, 0>(acc0, dsc<1024, 1>(s * ST + xo0 + k * 2), db, 1);
          wgmma_n192_ss<0, 1, 0>(acc1, dsc<1024, 1>(s * ST + xo1 + k * 2), db, 1);
        }
        wg_commit();
        if (kb == 0 && wg) bar_arrive(2, 256);
        wg_wait<0>();
        pin(acc0); pin(acc1);
        if (t128 < 2 && kb < 11) mbar_arrive_rem(eb0 + 8 * s);
      }
      mbar_wait(mb + B_FULL, 1);
      if (t128 < 8) mbar_arrive_rem(t128 < 4 ? (wg << 24) + bars + B_EMPTY + 24 : mb + B_EMPTY);
      mbar_wait(mb + B_AUX, 0);
      float rs[2][2], nm[2][2];
#pragma unroll
      for (int m = 0; m < 2; m++)
#pragma unroll
        for (int h = 0; h < 2; h++) { const float2 v = lds2f(sm + OFF_STATS + ((wg * 2 + (m ^ hf)) * 64 + warp * 16 + h * 8 + g) * 8); nm[m][h] = v.x; rs[m][h] = v.y; }
      auto center = [&](auto jc) {
        constexpr int j = decltype(jc)::value;
        const float2 cs = lds2f_o<sb + OFF_COLSUM + j * 32>(own + t * 8);
        acc1[j * 4] = fmaf(nm[1][0], cs.x, acc1[j * 4]); acc1[j * 4 + 1] = fmaf(nm[1][0], cs.y, acc1[j * 4 + 1]);
        acc1[j * 4 + 2] = fmaf(nm[1][1], cs.x, acc1[j * 4 + 2]); acc1[j * 4 + 3] = fmaf(nm[1][1], cs.y, acc1[j * 4 + 3]);
        acc0[j * 4] = fmaf(nm[0][0], cs.x, acc0[j * 4]); acc0[j * 4 + 1] = fmaf(nm[0][0], cs.y, acc0[j * 4 + 1]);
        acc0[j * 4 + 2] = fmaf(nm[0][1], cs.x, acc0[j * 4 + 2]); acc0[j * 4 + 3] = fmaf(nm[0][1], cs.y, acc0[j * 4 + 3]);
      };
      static_for<0, 16>(center);
      const float L2E = 1.4426950408889634f;
      uint32_t fa = sm + sk + (warp * 16 + (lane & 15)) * 128 + (((lane >> 4) ^ (lane & 7)) << 4);
      asm volatile("" : "+r"(fa));
      uint32_t xf0[32], xf1[32];
      auto pack_kv = [&](float (&a)[96], int i, float r0, float r1, uint32_t* o, uint32_t z = 0) {
        const float* p = a + i * 8;
        if (i < 4) {
          const float rl0 = __uint_as_float(__float_as_uint(r0 * L2E) | z), rl1 = __uint_as_float(__float_as_uint(r1 * L2E) | z);
          const uint32_t q0 = pack2(r0, r0), q1 = pack2(r1, r1);
          o[0] = phi2(p[0], p[1], rl0, q0); o[1] = phi2(p[2], p[3], rl1, q1); o[2] = phi2(p[4], p[5], rl0, q0); o[3] = phi2(p[6], p[7], rl1, q1);
        } else {
          const uint32_t q0 = pack2(r0, r0), q1 = pack2(r1, r1);
          o[0] = hmul2(pack2(p[0], p[1]), q0); o[1] = hmul2(pack2(p[2], p[3]), q1); o[2] = hmul2(pack2(p[4], p[5]), q0); o[3] = hmul2(pack2(p[6], p[7]), q1);
        }
      };
      auto swap_kv = [&](uint32_t (&xf)[32], uint32_t tile, int i, const uint32_t* o, uint32_t z = 0) {
        const uint32_t ad = (fa + tile * UNIT) ^ ((i & 3) << 5);
        if (i < 4) { ldsm4_o<0>(ad, xf[i * 4], xf[i * 4 + 1], xf[i * 4 + 2], xf[i * 4 + 3]); stsm4_o<0>(ad, o[0], o[1], o[2], o[3]); }
        else { ldsm4_o<STAGE_B>(ad | z, xf[i * 4], xf[i * 4 + 1], xf[i * 4 + 2], xf[i * 4 + 3]); stsm4_o<STAGE_B>(ad, o[0], o[1], o[2], o[3]); }
      };
      auto mma_q = [&](float (&a)[96], uint32_t (&xf)[32], uint32_t xo, bool ss) {
        const uint32_t r = __shfl_sync(~0u, sk >> 4, 0), o = 2 * ST - r;
#pragma unroll
        for (int j = 0; j < 8; j++) {
          if (ss) wgmma_n64_ss<0, 1, 64>(a, dsc<1024, 1>(o + (j >> 2) * ST + xo + (j & 3) * 2), dsc<1024, 1>(WD + o + (j >> 2) * ST + (j & 3) * 128), 1);
          else wgmma_n64_rs<1, 64>(a, xf[j * 4], xf[j * 4 + 1], xf[j * 4 + 2], xf[j * 4 + 3], dsc<1024, 1>(WD + r + (j >> 2) * ST + (j & 3) * 128), 1);
        }
      };
      auto epi_q = [&](float (&a)[96], float r0, float r1, uint32_t (&o)[16]) {
        const float rl0 = r0 * 1.44269511f, rl1 = r1 * 1.44269511f;
        const uint32_t q0 = dup2(r0), q1 = dup2(r1);
#pragma unroll
        for (int j = 0; j < 8; j++) { o[j * 2] = phi2(a[64 + j * 4], a[65 + j * 4], rl0, q0); o[j * 2 + 1] = phi2(a[66 + j * 4], a[67 + j * 4], rl1, q1); }
        pinu(o);
      };
      auto mma_kv1 = [&](float (&a)[96], uint32_t xo, int s) {
#pragma unroll
        for (int k = 0; k < 4; k++) wgmma_n128_ss<0, 1, 0>(a, dsc<1024, 1>(s * ST + xo + k * 2), dsc<1024, 1>(WV + s * ST + k * 128), 1);
      };
      auto epi_kv = [&](float (&a)[96], uint32_t (&xf)[32], uint32_t tile, float r0, float r1) {
        uint32_t o[8][4];
#pragma unroll
        for (int j = 3; j >= 0; j--) {
          const uint32_t z = j < 3 ? xf[(j + 5) * 4] & blockIdx.y : 0;
          pack_kv(a, j + 4, r0, r1, o[j + 4]);
          swap_kv(xf, tile, j + 4, o[j + 4], (o[j + 4][2] | o[j + 4][3]) & blockIdx.y);
          pack_kv(a, j, r0, r1, o[j], z);
          swap_kv(xf, tile, j, o[j]);
        }
      };
      bar_arrive(15, 288); bar_arrive(0, 288);
      pinr<0, 64>(acc0); pinr<0, 64>(acc1);
      if (wg) {
        mbar_wait(mb + B_FULL + 8, 1);
        wg_fence();
        mma_kv1(acc1, xo1, 0); mma_kv1(acc0, xo0, 0); mma_kv1(acc1, xo1, 1); mma_kv1(acc0, xo0, 1);
        mbar_wait(mb + B_FULL + 16, 1);
        wg_fence();
        mma_kv1(acc1, xo1, 2);
        mbar_wait(mb + B_FULL + 24, 1);
        wg_fence();
        mma_kv1(acc1, xo1, 3);
        wg_commit();
        bar_arrive(3, 256);
      }
      b1 = get_b();
      static_for<16, 24>(center);
      pinr<64, 96>(acc0); pinr<64, 96>(acc1);
      if (wg) wg_wait<0>();
      else {
        bar_sync(3, 256);
        wg_fence();
        mma_kv1(acc1, xo1, 0); mma_kv1(acc1, xo1, 1); mma_kv1(acc1, xo1, 2);
        mbar_wait(mb + B_F15, 0);
        wg_fence();
        mma_kv1(acc1, xo1, 3);
        wg_commit();
        mma_kv1(acc0, xo0, 0); mma_kv1(acc0, xo0, 1);
        wg_commit();
        bar_arrive(4, 256);
        wg_wait<1>();
      }
      pinr<0, 64>(acc1);
      epi_kv(acc1, xf1, wg * 2 + (hf ^ 1), rs[1][0], rs[1][1]);
      pinu(xf1);
      if (wg) mbar_wait(mb + B_LATE, 0);
      bar_sync(5 - wg, 256);
      wg_fence();
      mma_kv1(acc0, xo0, 2); mma_kv1(acc0, xo0, 3);
      wg_commit();
      fence_async_smem();
      mma_q(acc1, xf1, xo1, false);
      wg_commit();
      bar_arrive(6 - wg, 256);
      if (wg) bar_arrive(13, 160);
      wg_wait<1>();
      pinr<0, 64>(acc0);
      if (lane == 0) mbar_arrive(mb + B_EVA);
      epi_kv(acc0, xf0, wg * 2 + hf, rs[0][0], rs[0][1]);
      fence_async_smem();
      pinu(xf0);
      const uint32_t kvb = 2 * STAGE_B + (2 + (hf ^ 1)) * UNIT - sk;
      uint32_t ka0, ka1, g0, g1;
      const uint8_t* h0, *h1;
      auto prepare = [&]() {
        const uint32_t l = lane_id();
        od1 = &P.s->obuf[(((b1 >> 4) * 4 + wg * 2 + (hf ^ 1)) * 64 + (b1 & 7)) * 128 + warp * 32 + l];
        ain = &P.s->obuf[((b1 >> 4) * 4 + wg * 2 + hf) * 64 * 128 + warp * 32 + l];
        const uint32_t zo = wid * 32 + (l & 7) * 4;
        ka0 = sm + kvb + wid * 1024 + (l & 7) * 128 + (((l >> 3) ^ (l & 7)) << 4); ka1 = sm + kvb + wid * 1024 + l * 128 + ((4 ^ l) << 4);
        g0 = sm + sk + wid * 512 + l * 16; g1 = sm + sk + zo;
        h0 = (const uint8_t*)&P.s->kvp[(b1 & 15) * 8 * 256 + wid * 32 + l]; h1 = (const uint8_t*)&P.s->zp[(b1 & 15) * 8 * 16] + zo;
        asm volatile("" : "+r"(ka0), "+r"(ka1), "+r"(g0), "+r"(g1), "+l"(h0), "+l"(h1), "+l"(od1), "+l"(ain));
        sched_fence();
      };
      if (wg) {
        float ka[36];
        auto mma_kv = [&](uint32_t tile, int i, int acc) {
          const uint32_t o = (sk >> 4) + tile * 512 + i * 128;
          wgmma_n72_ss<1, 1, 0>(ka, dsc<1024, 1>(dlo(sb, 8192) + o), dsc<1024, 1>(dlo(sb + STAGE_B, OFF_STATS - STAGE_B) + o * (1u - (1u << 16))), acc);
        };
        auto mma_q1 = [&](int j) { wgmma_n64_rs<1, 64>(acc0, xf0[j * 4], xf0[j * 4 + 1], xf0[j * 4 + 2], xf0[j * 4 + 3], dsc<1024, 1>(WD + (sk >> 4) + (j >> 2) * ST + (j & 3) * 128), 1); };
#pragma unroll
        for (int i = 0; i < 36; i++) ka[i] = 0.f;
        bar_sync(6, 256);
        wg_fence();
#pragma unroll
        for (int i = 0; i < 4; i++) {
          mma_kv(2, i, i); mma_kv(3, i, 1); mma_kv(hf ^ 1, i, 1);
          mma_q1(i);
        }
        const int kq = (b1 & 15) * 8 + (b1 >> 4);
        uint4* dst = &P.s->kvp[kq * 256 + warp * 64 + lane];
        uint32_t* dz = (uint32_t*)&P.s->zp[kq * 16] + warp * 16 + g + t * 8;
        asm volatile("" : "+l"(dst), "+l"(dz));
        bar_sync(7, 256);
#pragma unroll
        for (int i = 0; i < 4; i++) mma_kv(hf, i, 1);
        wg_commit();
#pragma unroll
        for (int j = 4; j < 8; j++) mma_q1(j);
        wg_commit();
        bar_arrive(8, 256);
        wg_wait<1>();
        pin(ka);
        uint32_t kw[8];
#pragma unroll
        for (int i = 0; i < 8; i++) {
          const int j = (i & 3) * 4 + (i >> 2) * 2;
          asm("{\n.reg .pred p;\nsetp.ne.u32 p, %5, 0;\n@p cvt.rn.bf16x2.f32 %0, %4, %3;\n@!p cvt.rn.bf16x2.f32 %0, %2, %1;\n}"
              : "=r"(kw[i]) : "f"(ka[j]), "f"(ka[j + 1]), "f"(ka[16 + j]), "f"(ka[17 + j]), "r"(warp & 2));
        }
        st_rlx4(dst, make_uint4(kw[0], kw[1], kw[2], kw[3]));
        st_rlx4(dst + 32, make_uint4(kw[4], kw[5], kw[6], kw[7]));
        if (t < 2) st_rlx(dz, __float_as_uint(t ? ka[34] : ka[32]));
        if (lane == 0) mbar_arrive(mb + B_EVB);
        asm volatile("" : "=r"(ka0), "=r"(ka1), "=r"(g0), "=r"(g1), "=l"(h0), "=l"(h1), "=l"(od1), "=l"(ain));
      } else {
        bar_arrive(7, 256);
        bar_sync(8, 256);
        wg_fence();
        mma_q(acc0, xf0, xo0, false);
        prepare();
        bar_sync(9, 256);
      }
      wg_fence();
      mma_q(acc1, xf1, xo1, true);
      wg_commit();
      if (wg) { bar_arrive(9, 256); prepare(); wg_wait<0>(); }
      else { wg_fence(); mma_q(acc0, xf0, xo0, true); wg_commit(); wg_wait<1>(); }
      pinr<64, 96>(acc1);
      uint32_t pq[16];
      epi_q(acc1, rs[1][0], rs[1][1], pq);
      bar_sync(11 + wg + zero_after(pq), 128);
      if (lane == 0) mbar_arrive(mb + B_KVB);
      if (wg) {
        wg_fence();
        mma_q(acc0, xf0, xo0, true);
        wg_commit();
      }
      {
        uint4 gv[8];
        uint32_t m[8], a[4];
        float z;
        mbar_wait(mb + B_KVP, 0);
        uint32_t zq[8];
        static_for<0, 8>([&](auto sc) { constexpr int s = decltype(sc)::value; asm volatile("ld.shared.u32 %0, [%1+%2];" : "=r"(zq[s]) : "r"(g1), "n"(UNIT + s * 256) : "memory"); });
        static_for<0, 8>([&](auto sc) { constexpr int s = decltype(sc)::value; gv[s] = lds4_o<STAGE_B + s * 4096>(g0); });
#pragma unroll 1
        for (int it = 0; it < SPIN_LIMIT; it++) {
          uint32_t mm = max4(max4(0, make_uint4(zq[0], zq[1], zq[2], zq[3])), make_uint4(zq[4], zq[5], zq[6], zq[7]));
          z = ((__uint_as_float(zq[0]) + __uint_as_float(zq[1])) + (__uint_as_float(zq[2]) + __uint_as_float(zq[3]))) +
              ((__uint_as_float(zq[4]) + __uint_as_float(zq[5])) + (__uint_as_float(zq[6]) + __uint_as_float(zq[7])));
#pragma unroll
          for (int s = 0; s < 8; s++) m[s] = max4(0, gv[s]);
#pragma unroll
          for (int s = 0; s < 8; s += 2) mm = __vimax3_u32(mm, m[s], m[s + 1]);
          a[0] = hadd2(hadd2(hadd2(gv[0].x, gv[1].x), hadd2(gv[2].x, gv[3].x)), hadd2(hadd2(gv[4].x, gv[5].x), hadd2(gv[6].x, gv[7].x)));
          a[1] = hadd2(hadd2(hadd2(gv[0].y, gv[1].y), hadd2(gv[2].y, gv[3].y)), hadd2(hadd2(gv[4].y, gv[5].y), hadd2(gv[6].y, gv[7].y)));
          a[2] = hadd2(hadd2(hadd2(gv[0].z, gv[1].z), hadd2(gv[2].z, gv[3].z)), hadd2(hadd2(gv[4].z, gv[5].z), hadd2(gv[6].z, gv[7].z)));
          a[3] = hadd2(hadd2(hadd2(gv[0].w, gv[1].w), hadd2(gv[2].w, gv[3].w)), hadd2(hadd2(gv[4].w, gv[5].w), hadd2(gv[6].w, gv[7].w)));
          pinu(a);
          if (!__any_sync(~0u, mm == SENT)) break;
#pragma unroll
          for (int s = 0; s < 8; s++) {
            zq[s] = ld_rlx(h1 + s * 256);
            if (m[s] == SENT) gv[s] = ld_rlx4(h0 + s * 4096);
          }
        }
        wg_wait<0>();
        pinr<64, 96>(acc0);
        stsm4(ka0, a[0], a[1], a[2], a[3]);
        const uint32_t zz = pack2(z, z);
        if (lane < 8) sts4(ka1, zz, zz, zz, zz);
        fence_async_smem();
        bar_sync(1, 256);
      }
      uint32_t pb[16];
      auto phi_b = [&](int j0, int j1) {
        const float rl0 = rs[0][0] * 1.44269511f, rl1 = rs[0][1] * 1.44269511f;
        const uint32_t q0 = dup2(rs[0][0]), q1 = dup2(rs[0][1]);
        uint32_t z = 0;
#pragma unroll
        for (int j = 0; j < 8; j++)
          if (j >= j0 && j < j1) {
            pb[j * 2] = phi2(acc0[64 + j * 4], acc0[65 + j * 4], rl0, q0); pb[j * 2 + 1] = phi2(acc0[66 + j * 4], acc0[67 + j * 4], rl1, q1);
            z |= pb[j * 2] | pb[j * 2 + 1];
          }
        return z & 0x80008000u;
      };
      auto make_o = [&](uint4 (&o)[4], uint32_t (&pq)[16], auto first) {
        float oa[2][20];
        wg_fence();
#pragma unroll
        for (int ks = 0; ks < 4; ks++) {
          wgmma_n40_rs<1, 0>(oa[ks >> 1], pq[ks * 4], pq[ks * 4 + 1], pq[ks * 4 + 2], pq[ks * 4 + 3], dsc<1024, 1>(dlo(sb, 8192) + (kvb >> 4) + ks * 128), ks & 1);
          if (decltype(first)::value && ks == 1) wg_commit();
        }
        wg_commit();
        if constexpr (!decltype(first)::value) {
          pinu(xf0);
#pragma unroll
          for (int q = 0; q < 32; q++) { acc[q * 2] = bf_lo(xf0[q]); acc[q * 2 + 1] = bf_hi(xf0[q]); }
          pin(acc);
          mbar_wait(mb + B_BF, 0);
        }
        if (decltype(first)::value) { wg_wait<1>(); pin(oa[0]); }
        else { wg_wait<0>(); pin(oa[0]); pin(oa[1]); }
#pragma unroll
        for (int h = 0; h < 2; h++) {
          const float (&d)[20] = oa[h];
          const float i0 = rcp(d[16] + 1e-6f), i1 = rcp(d[18] + 1e-6f);
#pragma unroll
          for (int k2 = 0; k2 < 2; k2++) {
            o[h * 2 + k2] = make_uint4(pack2(d[k2 * 8] * i0, d[k2 * 8 + 1] * i0), pack2(d[k2 * 8 + 2] * i1, d[k2 * 8 + 3] * i1),
                                       pack2(d[k2 * 8 + 4] * i0, d[k2 * 8 + 5] * i0), pack2(d[k2 * 8 + 6] * i1, d[k2 * 8 + 7] * i1));
            if (decltype(first)::value && !h && !k2) {
              st_rlx4(od1, o[0]); sched_fence();
              wg_wait<0>();
              pin(oa[1]);
              if (lane < 2) mbar_arrive_rem(eb);
            }
          }
        }
      };
      make_o(ost[1], pq, std::true_type{});
      st_rlx4(od1 + 1024 + ((ost[1][2].x | ost[1][3].w) & blockIdx.y), ost[1][1]);
      sched_fence();
      mbar_wait(mb + B_F15 + phi_b(0, R1MID), 1);
#pragma unroll
      for (int i = 0; i < 4; i++) abuf[1][i] = ld_rlx4(ain + i * 128);
      phi_b(R1MID, 8);
      st_rlx4(od1 + 2048, ost[1][2]);
      make_o(ost[0], pb, std::false_type{});
    }
   {
    IDS(b1);
    const int mb3 = rb * 4 + wg * 2 + hf;
    uint4* rp = &P.s->st2[mb3 * 64 + warp * 16 + g + t * 8];
    {
      uint4* const od0 = &P.s->obuf[(mb3 * 64 + 32 + s3 * 4) * 128 + t128];
#pragma unroll
      for (int i = 0; i < 4; i++) pin4(ost[0][i]);
      wg_fence();
#pragma unroll
      for (int k = 0; k < 4; k++) wgmma_n128_rs<1, 0>(acc, ost[0][k].x, ost[0][k].y, ost[0][k].z, ost[0][k].w, dsc<1024, 1>(dlo(sb + 4 * UNIT, 8192) + k * 128), 1);
      wg_commit();
      st_rlx4(od1 + 3072, ost[1][3]); st_rlx4(od0, ost[0][0]);
      uint32_t la = sm + t128 * 16, ev = eb + 8;
      asm volatile("" : "+r"(la), "+r"(ev));
      auto fetch = [&](uint32_t off, uint4 (&a)[4]) { const uint32_t ra = la + off; a[0] = lds4_o<0>(ra); a[1] = lds4_o<2048>(ra); a[2] = lds4_o<4096>(ra); a[3] = lds4_o<6144>(ra); };
      auto check = [&](int p, uint4 (&a)[4]) {
        if (__any_sync(~0u, max(max4(max4(0, a[0]), a[1]), max4(max4(0, a[2]), a[3])) == SENT)) {
          int pl = p; asm volatile("" : "+r"(pl));
          const uint4* q = ain + frag_of(pl);
#pragma unroll 1
          for (int it = 0;; it++) {
            uint32_t mm = 0;
#pragma unroll
            for (int i = 0; i < 4; i++) { const uint32_t m = max4(0, a[i]); mm = max(mm, m); if (m == SENT) a[i] = ld_rlx4(q + i * 128); }
            if (!__any_sync(~0u, mm == SENT)) break;
            SPINCHK(it);
          }
        }
        if (lane < 2) mbar_arrive_rem(ev);
        ev = (ev & ~0x38u) | ((ev + 8) & 0x38u);
      };
      auto mma = [&](int p, uint32_t bs, uint4 (&a)[4]) {
#pragma unroll
        for (int i = 0; i < 4; i++) pin4(a[i]);
        wg_fence();
#pragma unroll
        for (int k = 0; k < 4; k++) wgmma_n128_rs<1, 0>(acc, a[k].x, a[k].y, a[k].z, a[k].w, dsc<1024, 1>(bs + k * 128), 1);
        wg_commit();
      };
      uint32_t ta = sm + OFF_STATS + wg * 256 + 48;
      mbar_wait(mb + B_WR, 0);
      uint4 tp = lds4(ta);
      mbar_wait(mb + B_BF + 8, 0);
      check(1, abuf[1]);
      mbar_wait(mb + B_BF + 16, 0);
      fetch(ring_of(2, wg), abuf[2]);
      mma(1, dlo(sb + 11 * UNIT, 8192), abuf[1]);
      st_rlx4(od0 + 128, ost[0][1]); st_rlx4(od0 + 256, ost[0][2]);
      check(2, abuf[2]);
      mbar_wait(mb + B_BF + 24, 0);
      fetch(ring_of(3, wg), abuf[0]);
      mma(2, dlo(sb + 18 * UNIT, 8192), abuf[2]);
      st_rlx4(od0 + 384, ost[0][3]);
      wg_wait<2>();
      check(3, abuf[0]);
      mbar_wait(mb + B_BF + 32, 0);
#pragma unroll 1
      for (int p = 3; p < 15; p += 3) {
        static_for<0, 3>([&](auto jc) {
          constexpr int j = decltype(jc)::value;
          const uint4 tc = tp;
          const uint32_t bs = __shfl_sync(~0u, tc.x, 0);
          wg_wait<1>();
#pragma unroll
          for (int i = 0; i < 4; i++) pin4(abuf[(j + 1) % 3][i]);
          tp = lds4_o<16 * j + 16>(ta);
          fetch(tc.y, abuf[(j + 1) % 3]);
          mma(p + j, bs, abuf[j]);
          check(p + j + 1, abuf[(j + 1) % 3]);
          mbar_wait(tc.z, tc.w);
        });
        ta += 48;
      }
      {
        const uint32_t wa0 = sm + OFF_COLSUM + ((g & 1) ? t * 16 : 64);
        wb[0] = lds4_o<0>(wa0); wb[1] = lds4_o<128>(wa0); wb[2] = lds4_o<256>(wa0); wb[3] = lds4_o<384>(wa0);
      }
      mma(15, __shfl_sync(~0u, tp.x, 0), abuf[0]);
      wg_wait<2>();
      if (lane == 0) mbar_arrive(mb + B_E16);
      asm volatile("" : "+l"(rp));
      sched_fence();
      wg_wait<0>();
      pin(acc);
#pragma unroll
      for (int i = 0; i < 4; i++) { pin4(abuf[0][i]); pin4(abuf[1][i]); pin4(abuf[2][i]); }
    }
    {
      float q0[2] = {0.f, 0.f}, q1[2] = {0.f, 0.f}, c[2][4] = {};
#pragma unroll
      for (int j = 0; j < 16; j++) {
        hp[j * 2] = pack2(acc[j * 4], acc[j * 4 + 1]); hp[j * 2 + 1] = pack2(acc[j * 4 + 2], acc[j * 4 + 3]);
        q0[j & 1] = fmaf(acc[j * 4], acc[j * 4], fmaf(acc[j * 4 + 1], acc[j * 4 + 1], q0[j & 1]));
        q1[j & 1] = fmaf(acc[j * 4 + 2], acc[j * 4 + 2], fmaf(acc[j * 4 + 3], acc[j * 4 + 3], q1[j & 1]));
        if (j & 1) {
          const uint32_t a[4] = {hp[j * 2 - 2], hp[j * 2 - 1], hp[j * 2], hp[j * 2 + 1]};
          mma16816(c[(j >> 1) & 1], a, (j & 2) ? wb[j >> 2].z : wb[j >> 2].x, (j & 2) ? wb[j >> 2].w : wb[j >> 2].y);
        }
      }
      const bool od = t & 1;
      float q = (od ? q1[0] + q1[1] : q0[0] + q0[1]) + __shfl_xor_sync(~0u, od ? q0[0] + q0[1] : q1[0] + q1[1], 1);
      q += __shfl_xor_sync(~0u, q, 2);
      asm volatile("{\n.reg .pred p;\nsetp.lt.u32 p, %5, 2;\n@p red.relaxed.gpu.global.add.v4.f32 [%0], {%1,%2,%3,%4};\n}"
                   :: "l"(rp), "f"(od ? c[0][2] + c[1][2] : c[0][0] + c[1][0]), "f"(q), "f"(od ? c[0][3] + c[1][3] : c[0][1] + c[1][1]), "f"(1.f), "r"(t) : "memory");
    }
    const uint32_t ts = clock64();
    const uint32_t msc = sm + OFF_STATS;
    const uint32_t hst = sm + 4 * UNIT + wg * STAGE_B + warp * 4096, gslot = sm + unit_of(rank ? GT1 : GT0, wid);
    bar_sync(1, 256);
#pragma unroll
    for (int j = 0; j < 8; j++)
      stsm4(hst + (lane & 15) * 256 + (((2 * j + (lane >> 4)) ^ (lane & 7)) << 4), hp[j * 4], hp[j * 4 + 1], hp[j * 4 + 2], hp[j * 4 + 3]);
    uint32_t wa[8][4][4], wd[8][2][4];
    const uint32_t a0 = gslot + ((lane >> 4) * 8 + (lane & 7)) * 64 + ((((lane >> 3) & 1) ^ ((lane >> 1) & 3)) << 4);
    auto load_gu = [&](auto ic) { constexpr int i = decltype(ic)::value; ldsm4t_o<(i >> 2) * 1024 + ((i >> 1) & 1) * 8192>(a0 ^ ((i & 1) << 5), wa[i >> 2][i & 3]); };
    uint32_t tx;
    {
      const int row = rb * 256 + tid;
      const uint4* sp = &P.s->st2[row], *sq = &P.s->st2[row ^ 256];
      const float sw = __uint_as_float((lds1(mb + B_SW) & ~255u) | 128);
      uint4 v[2];
      uint4* d = &P.s->hsel[c3 * 128 + (g & 3) * 32 + ((rb & 6) + (lane >> 4)) * 4 + t];
      uint32_t* dk = &P.s->cand[c3 * 32 + (rb & 6) + (lane >> 4)];
      asm volatile("" : "+l"(d), "+l"(dk));
      if (fidx >= 0) mbar_wait(mb + B_FFN, 0);
      static_for<0, GU1>(load_gu);
      while ((uint32_t)clock64() - ts < SDEL2) {}
      v[0] = ld_rlx4(sp); v[1] = ld_rlx4(sq);
      static_for<GU1, GU2>(load_gu);
#pragma unroll 1
      for (int it = 0; __any_sync(~0u, min(v[0].w, v[1].w) != 0x41000000u) && it < SPIN_LIMIT; it++) {
        if (v[0].w != 0x41000000u) v[0] = ld_rlx4(sp);
        if (v[1].w != 0x41000000u) v[1] = ld_rlx4(sq);
      }
      if (lane == 0) mbar_arrive(mb + B_EVA);
      uint32_t k[2];
#pragma unroll
      for (int i = 0; i < 2; i++) {
        const float mean = __uint_as_float(v[i].x) * (1.f / D_);
        const float rstd = rsq(fmaxf(fmaf(-mean, mean, __uint_as_float(v[i].y) * (1.f / D_)), 0.f) + 1e-5f);
        const uint32_t u = __float_as_uint(rstd * fmaf(-mean, sw, __uint_as_float(v[i].z)));
        k[i] = min(((u ^ ((uint32_t)((int)u >> 31) | 0x80000000u)) & ~2047u), 0xFFFFF000u) | (2047 - (row ^ (i << 8)));
        if (i == 0 && (warp >> 1) == hf) sts2f(sm + OFF_LNP + (wg * 64 + (tid & 63)) * 8, rstd, -mean * rstd);
      }
      const uint32_t hi = max(k[0], k[1]);
      uint32_t m1 = __reduce_max_sync(~0u, hi), m2 = __reduce_max_sync(~0u, hi == m1 ? min(k[0], k[1]) : hi);
      if (lane == 0) sts2f(msc + wid * 8, __uint_as_float(m1), __uint_as_float(m2));
      bar_sync(1, 256);
      const uint32_t kk = lds1(msc + (lane & 15) * 4);
      m1 = __reduce_max_sync(~0u, kk); m2 = __reduce_max_sync(~0u, kk == m1 ? 0 : kk);
      const int c0 = 2047 - (m1 & 2047), c1 = 2047 - (m2 & 2047);
      if ((c0 >> 4) == mb3 * 4 + warp || (c1 >> 4) == mb3 * 4 + warp) {
        const int ra = (lane & 4) ? c1 : c0, rd = (lane & 16) ? c1 : c0;
        uint32_t h0, h1, h2, h3;
        ldsm4_o<0>(hst + (ra & 15) * 256 + ((((lane & 3) * 4 + (lane >> 3)) ^ (ra & 7)) << 4), h0, h1, h2, h3);
        const float2 pr = lds2f(sm + OFF_LNP + (wid * 16 + (rd & 15)) * 8);
        if ((rd >> 4) == mb3 * 4 + warp) {
          const uint4 xn = make_uint4(pack2(fmaf(bf_lo(h0), pr.x, pr.y), fmaf(bf_hi(h0), pr.x, pr.y)), pack2(fmaf(bf_lo(h1), pr.x, pr.y), fmaf(bf_hi(h1), pr.x, pr.y)),
                                      pack2(fmaf(bf_lo(h2), pr.x, pr.y), fmaf(bf_hi(h2), pr.x, pr.y)), pack2(fmaf(bf_lo(h3), pr.x, pr.y), fmaf(bf_hi(h3), pr.x, pr.y)));
          st_rlx4(d, xn);
          if (!(lane & 15)) st_rlx(dk, (lane & 16) ? m2 : m1);
          st_rlx4(d + 1024, make_uint4(h0, h1, h2, h3));
        }
      }
      tx = clock64();
      if (tid == 0) { sts2f(msc + 64, __uint_as_float(m1), __uint_as_float(m2)); mbar_arrive(mb + B_OUT); }
    }
    static_for<GU2, 32>(load_gu);
    const uint32_t dl = sm + (wid & 1) * 4096 + ((lane >> 4) * 8 + (lane & 7)) * 128 + ((((lane >> 3) & 1) ^ (lane & 7)) << 4);
    uint32_t da = dl + unit_of(DT0, wid >> 1), db = dl + unit_of(rank ? DT1 : DT0, 4 + (wid >> 1));
    uint32_t* yp = (uint32_t*)&P.s->ybuf[((wid * 8 + t * 2) * NFFN + fidx) * 2] + g;
    uint32_t k1, k2;
    uint2 key;
    uint32_t pl = sm + unit_of(rank ? GT1 : GT0, g) + (g & 1) * 64 + wid * 64 + t * 16, pa = msc + 128 + wid * 16 + ((t & 1) * 2 + (lane >> 4)) * 4 + (t >> 1) * 2;
    {
      float gu[2][4][4];
      uint4 xb[4];
      uint32_t m[4];
      const uint4* xp = &P.s->hsel[wid * 128 + lane];
      const uint2* kp = (const uint2*)&P.s->cand[wid * 32] + t;
      uint32_t ps = gslot + (wid & 1) * 64 + g * 32;
      asm volatile("" : "+l"(xp), "+l"(kp), "+l"(yp), "+r"(db), "+r"(ps), "+r"(pl), "+r"(pa));
      if (fidx >= 0) mbar_wait(mb + B_FFD, 0);
      static_for<0, 8>([&](auto ic) { constexpr int i = decltype(ic)::value; ldsm4t_o<(i & 1) * 2048>(da ^ ((i >> 1) << 5), wd[i >> 1][i & 1]); });
      while ((uint32_t)clock64() - tx < XDELAY) {}
      key = ld_rlx2(kp);
#pragma unroll
      for (int i = 0; i < 4; i++) xb[i] = ld_rlx4(xp + i * 32);
      if (fidx >= 0) mbar_wait(mb + B_KVP, 1);
#pragma unroll 1
      for (int it = 0; it < SPIN_LIMIT; it++) {
#pragma unroll
        for (int i = 0; i < 4; i++) m[i] = max4(0, xb[i]);
        if (!__any_sync(~0u, __vimax3_u32(__vimax3_u32(max(key.x, key.y), m[0], m[1]), m[2], m[3]) == SENT)) break;
        key = ld_rlx2(kp);
#pragma unroll
        for (int i = 0; i < 4; i++) if (m[i] == SENT) xb[i] = ld_rlx4(xp + i * 32);
      }
      const uint32_t hi = max(key.x, key.y);
      k1 = __reduce_max_sync(~0u, hi); k2 = __reduce_max_sync(~0u, hi == k1 ? min(key.x, key.y) : hi);
#pragma unroll
      for (int i = 0; i < 32; i++) gu[i >> 4][(i >> 2) & 3][i & 3] = 0.f;
#pragma unroll
      for (int ks = 0; ks < 8; ks++) {
#pragma unroll
        for (int i = 0; i < 4; i++) mma16816(gu[ks & 1][i], wa[ks][i], (ks & 1) ? xb[ks >> 1].z : xb[ks >> 1].x, (ks & 1) ? xb[ks >> 1].w : xb[ks >> 1].y);
        if (ks == 1) {
          const uint32_t dd = db | (__float_as_uint(gu[1][3][0]) & blockIdx.y);
          static_for<0, 8>([&](auto ic) { constexpr int i = decltype(ic)::value; ldsm4t_o<(i & 1) * 2048>(dd ^ ((i >> 1) << 5), wd[4 + (i >> 1)][i & 1]); });
          xb[3].z |= (wd[4][0][0] | wd[4][1][0] | wd[5][0][0] | wd[5][1][0] | wd[6][0][0] | wd[6][1][0] | wd[7][0][0] | wd[7][1][0]) & blockIdx.y;
        }
      }
#pragma unroll
      for (int c = 0; c < 2; c++) {
        const uint32_t kc = c ? key.y : key.x;
        float o[8];
#pragma unroll
        for (int j = 0; j < 8; j++) o[j] = gu[0][(j >> 2) + (j & 1) * 2][(j & 2) + c] + gu[1][(j >> 2) + (j & 1) * 2][(j & 2) + c];
        asm volatile("{\n.reg .pred p;\nsetp.ge.u32 p, %9, %10;\n@p st.shared.v4.f32 [%0], {%1,%2,%3,%4};\n@p st.shared.v4.f32 [%0+16], {%5,%6,%7,%8};\n}"
                     :: "r"(ps + (kc == k1 ? 0 : 256)), "f"(o[0]), "f"(o[1]), "f"(o[2]), "f"(o[3]), "f"(o[4]), "f"(o[5]), "f"(o[6]), "f"(o[7]), "r"(kc), "r"(k2) : "memory");
      }
    }
    bar_sync(1, 256);
    {
      const uint4 pv = lds4(pl);
      const bool hi = lane & 16;
      float ga = __uint_as_float(hi ? pv.z : pv.x) + __shfl_xor_sync(~0u, __uint_as_float(hi ? pv.x : pv.z), 16);
      float up = __uint_as_float(hi ? pv.w : pv.y) + __shfl_xor_sync(~0u, __uint_as_float(hi ? pv.y : pv.w), 16);
      ga += __shfl_xor_sync(~0u, ga, 8); up += __shfl_xor_sync(~0u, up, 8);
      ga += __shfl_xor_sync(~0u, ga, 4); up += __shfl_xor_sync(~0u, up, 4);
      asm volatile("st.shared.u16 [%0], %1;" :: "r"(pa), "h"((uint16_t)pack2(ga * rcp(1.f + ex2(-1.4426950408889634f * ga)) * up, 0.f)) : "memory");
      bar_sync(1, 256);
      const uint4 bv = lds4(msc + 128 + (lane & 7) * 16);
      const uint32_t bq[4] = {bv.x, bv.y, bv.z, bv.w};
      float ya[8][4];
#pragma unroll
      for (int i = 0; i < 8; i++) { ya[i][0] = 0.f; ya[i][1] = 0.f; ya[i][2] = 0.f; ya[i][3] = 0.f; }
#pragma unroll
      for (int ks = 0; ks < 2; ks++)
#pragma unroll
        for (int i = 0; i < 8; i++) mma16816(ya[i], wd[i][ks], bq[ks * 2], bq[ks * 2 + 1]);
#pragma unroll
      for (int h = 0; h < 2; h++) {
        float o[4];
#pragma unroll
        for (int j = 0; j < 4; j++) o[j] = t == 0 ? ya[h * 4][j] : t == 1 ? ya[h * 4 + 1][j] : t == 2 ? ya[h * 4 + 2][j] : ya[h * 4 + 3][j];
        asm volatile("{\n.reg .pred p;\nsetp.ge.s32 p, %3, 0;\n@p st.relaxed.gpu.global.u32 [%0], %1;\n@p st.relaxed.gpu.global.u32 [%0+%4], %2;\n}"
                     :: "l"(yp + h * (64 * NFFN * 8)), "r"(pack2(o[0], o[1])), "r"(pack2(o[2], o[3])), "r"(fidx), "n"(NFFN * 32) : "memory");
      }
    }
    if (tid == 0) { sts2f(msc + 80, __uint_as_float(k1), __uint_as_float(k2)); mbar_arrive(mb + B_SEL); }
    const uint32_t ty = clock64();
    if (wid == 0) {
      const uint32_t* yq = (const uint32_t*)&P.s->ybuf[b * NFFN * 2] + t * 8 + g;
      const uint32_t ks = (t & 1) ? k2 : k1, grp = 3 - ((ks >> 9) & 3);
      const int fs = grp * 2 + (__shfl_sync(~0u, key.y, grp) == ks);
      const uint32_t* fq = (const uint32_t*)P.s->hsel + (((b >> 4) * 4 + ((b >> 2) & 3)) * 32 + fs * 4 + (g >> 1)) * 4 + (b & 3);
      float gate = rcp(1.f + ex2(-1.4426950408889634f * __uint_as_float(ks ^ (~(uint32_t)((int)ks >> 31) | 0x80000000u))));
      __nv_bfloat16* op = P.out + (size_t)(2047 - (ks & 2047)) * D_ + b * 8 + g;
      uint32_t sel = (g & 2) ? 0x3F800000u : 0x00003F80u;
      uint32_t fn = ld_rlx(fq), fh = ld_rlx(fq + 4096), v[7][4];
      uint32_t m[7];
#pragma unroll
      for (int i = 0; i < 7; i++) { m[i] = ~blockIdx.y; asm volatile("" : "=r"(v[i][0]), "=r"(v[i][1]), "=r"(v[i][2]), "=r"(v[i][3]), "+r"(m[i])); }
      asm volatile("" : "+l"(yq), "+l"(op), "+f"(gate), "+r"(sel));
      while ((uint32_t)clock64() - ty < YDELAY) {}
      float y[2][4];
#pragma unroll 1
      for (int it = 0; it < SPIN_LIMIT; it++) {
        static_for<0, 7>([&](auto ic) { constexpr int i = decltype(ic)::value;
          asm volatile("{\n.reg .pred p;\nsetp.eq.u32 p, %5, 0xFFFFFFFF;\n@p ld.relaxed.gpu.global.u32 %0, [%4+%6];\n@p ld.relaxed.gpu.global.u32 %1, [%4+%6+128];\n"
                       "@p ld.relaxed.gpu.global.u32 %2, [%4+%6+256];\n@p ld.relaxed.gpu.global.u32 %3, [%4+%6+384];\n}"
                       : "+r"(v[i][0]), "+r"(v[i][1]), "+r"(v[i][2]), "+r"(v[i][3]) : "l"(yq), "r"(m[i]), "n"(i * 512) : "memory"); });
        uint32_t mm = max(fn, fh);
        if (mm == SENT) { fn = ld_rlx(fq); fh = ld_rlx(fq + 4096); }
#pragma unroll
        for (int i = 0; i < 8; i++) y[i >> 2][i & 3] = 0.f;
#pragma unroll
        for (int i = 0; i < 7; i++) { m[i] = __vimax3_u32(max(v[i][0], v[i][1]), v[i][2], v[i][3]); mm = max(mm, m[i]); mma16816(y[i & 1], v[i], sel, sel); }
        pin(y[0]); pin(y[1]);
        if (!__any_sync(~0u, mm == SENT)) break;
      }
      const float base = (g & 1) ? bf_hi(fh) + bf_hi(fn) : bf_lo(fh) + bf_lo(fn);
      if (t < 2) *op = __float2bfloat16(fmaf((y[0][0] + y[1][0]) + (y[0][2] + y[1][2]), gate, base));
      if (b == 0 && lane == 0) P.s->epoch = lds1(mb + B_SW) & 255;
    }
   }
  }
}

typedef CUresult (*EncodeFn)(CUtensorMap*, CUtensorMapDataType, cuuint32_t, void*, const cuuint64_t*, const cuuint64_t*, const cuuint32_t*,
                             const cuuint32_t*, CUtensorMapInterleave, CUtensorMapSwizzle, CUtensorMapL2promotion, CUtensorMapFloatOOBfill);
void make_map(EncodeFn enc, CUtensorMap* m, const void* p, int rank, std::initializer_list<cuuint64_t> dims, std::initializer_list<cuuint64_t> str,
              std::initializer_list<cuuint32_t> box, CUtensorMapSwizzle sw) {
  const cuuint32_t es[4] = {1, 1, 1, 1};
  enc(m, CU_TENSOR_MAP_DATA_TYPE_BFLOAT16, rank, const_cast<void*>(p), dims.begin(), str.begin(), box.begin(), es, CU_TENSOR_MAP_INTERLEAVE_NONE, sw,
      CU_TENSOR_MAP_L2_PROMOTION_L2_128B, CU_TENSOR_MAP_FLOAT_OOB_FILL_NONE);
}

}

extern "C" void kernel_launch(void* const* d_in, const int* in_sizes, int n_in, void* d_out, int out_size) {
  (void)in_sizes; (void)n_in; (void)out_size;
  Ptrs P;
  P.x = (const __nv_bfloat16*)d_in[0]; P.wqkv = (const __nv_bfloat16*)d_in[1]; P.wo = (const __nv_bfloat16*)d_in[2];
  P.wr = (const __nv_bfloat16*)d_in[4]; P.wg = (const __nv_bfloat16*)d_in[5]; P.wu = (const __nv_bfloat16*)d_in[6];
  P.wd = (const __nv_bfloat16*)d_in[7]; P.out = (__nv_bfloat16*)d_out;
  cudaGetSymbolAddress((void**)&P.s, g_scratch);
  void* fn = nullptr;
  cudaDriverEntryPointQueryResult q;
  cudaGetDriverEntryPoint("cuTensorMapEncodeTiled", &fn, cudaEnableDefault, &q);
  EncodeFn enc = (EncodeFn)fn;
  Maps T;
  constexpr CUtensorMapSwizzle S128 = CU_TENSOR_MAP_SWIZZLE_128B, S64 = CU_TENSOR_MAP_SWIZZLE_64B;
  make_map(enc, &T.m[M_X], P.x, 2, {D_, S_}, {D_ * 2}, {64, 128}, S128);
  make_map(enc, &T.m[M_W], P.wqkv, 3, {D_, D_, 3}, {3 * D_ * 2, D_ * 2}, {64, 64, 2}, S128);
  make_map(enc, &T.m[M_Q], P.wqkv, 2, {3 * D_, D_}, {3 * D_ * 2}, {64, 64}, S128);
  make_map(enc, &T.m[M_O], P.wo, 4, {64, 64, 16, 16}, {D_ * 2, 64 * D_ * 2, 128}, {64, 64, 1, 2}, S128);
  make_map(enc, &T.m[M_S], P.wo, 4, {64, 64, 16, 16}, {D_ * 2, 64 * D_ * 2, 128}, {64, 16, 4, 2}, S128);
  make_map(enc, &T.m[M_G], P.wg, 3, {F_, D_, 1}, {F_ * 2, F_ * 2 * D_}, {32, 128, 1}, S64);
  make_map(enc, &T.m[M_U], P.wu, 3, {F_, D_, 1}, {F_ * 2, F_ * 2 * D_}, {32, 128, 1}, S64);
  make_map(enc, &T.m[M_D], P.wd, 3, {64, F_, 16}, {D_ * 2, 128}, {64, 32, 2}, S128);
  make_map(enc, &T.m[M_L], P.wd, 2, {64, F_ * 16}, {128}, {8, 32}, CU_TENSOR_MAP_SWIZZLE_NONE);
  cudaFuncSetAttribute(fused_kernel, cudaFuncAttributeMaxDynamicSharedMemorySize, SMEM_BYTES);
  fused_kernel<<<NCTA, 384, SMEM_BYTES>>>(P, T);
}
```

```cpp
#include <cuda_runtime.h>
#include <cuda.h>
#include <cuda_bf16.h>
#include <stdint.h>
#include <type_traits>
#include <initializer_list>

namespace {

constexpr int S_ = 2048, D_ = 1024, F_ = 3584;
constexpr int NCTA = 128, NFFN = 112;
constexpr uint32_t SENT = 0xFFFFFFFFu;
constexpr int SPIN_LIMIT = 1 << 20;

#define FD0 700
#define FD1 800
#define GDELAY 400
#define PLAG 8
#define MFIRST 320
#define MKV 1460
#define MO 720
#define ADELAY 150
#define ADELAY2 600
#define R1MID 5
#define SDEL2 600
#define XDELAY 400
#define YDELAY 600
#define GU1 4
#define GU2 14
#define GU3 30
#define OPACE 480
#define NAP __nanosleep(20)
constexpr uint32_t STAGE_B = 57344;
constexpr uint32_t OFF_STATS = 229376;
constexpr uint32_t OFF_COLSUM = 231424;
constexpr uint32_t OFF_BARS = 232192;
constexpr uint32_t SMEM_BYTES = 232448;
constexpr uint32_t B_FULL = 0, B_EMPTY = 32, B_E = 64, B_AUX = 128, B_EVA = 136, B_EVB = 144, B_BF = 152, B_LATE = 232, B_FFN = 240, B_SW = 248;
constexpr uint32_t B_OUT = B_FULL, B_SEL = B_FULL + 8, B_WR = B_FULL + 16, B_FFD = B_FULL + 24, B_E16 = B_EMPTY + 16, B_KVB = B_EMPTY + 8, B_DUMMY = B_SW + 4,
                   B_GATE = B_EMPTY + 24, B_ID = B_BF + 56, B_KVP = B_BF + 64, B_F15 = B_BF + 72;
constexpr uint32_t UNIT = 8192;
constexpr uint32_t sb = 1024;
constexpr uint32_t bars = sb + OFF_BARS;
constexpr uint64_t tab5(int a, int b, int c, int d, int e, int f, int g, int h, int i = 0, int j = 0) {
  return (uint64_t)a | (uint64_t)b << 5 | (uint64_t)c << 10 | (uint64_t)d << 15 | (uint64_t)e << 20 | (uint64_t)f << 25 | (uint64_t)g << 30 | (uint64_t)h << 35 |
         (uint64_t)i << 40 | (uint64_t)j << 45;
}
constexpr uint64_t BT0 = tab5(4, 11, 18, 25, 7, 9, 16, 0), BT1 = tab5(4, 11, 18, 25, 21, 23, 2, 0);
constexpr uint64_t GT0 = tab5(2, 21, 23, 18, 0, 25, 14, 7), GT1 = tab5(16, 7, 9, 18, 0, 25, 14, 21);
constexpr uint64_t DT0 = tab5(6, 13, 20, 27, 9, 10, 16, 17), DT1 = tab5(6, 13, 20, 27, 23, 24, 2, 3);
__device__ __forceinline__ uint32_t unit_of(uint64_t tab, int i) { return ((uint32_t)(tab >> (5 * i)) & 31) * UNIT; }
__device__ __forceinline__ uint32_t ring_of(int p, int w) { return (p & 1) * (2 * STAGE_B) + ((p & 2) ? 49152 + w * STAGE_B : w * UNIT); }
constexpr uint32_t OFF_LNP = OFF_STATS + 1024;

struct Scratch {
  uint4 obuf[32 * 64 * 128];
  uint4 kvp[16 * 8 * 256];
  uint4 zp[16 * 8 * 16];
  uint4 ybuf[NCTA * NFFN * 2];
  uint4 st1[64 * 48];
  uint4 csp[16 * 8 * 48];
  uint4 st2[S_];
  uint4 hsel[2 * 8 * 128];
  uint32_t cand[8 * 32];
  uint32_t when[32 * 32];
  unsigned epoch, pad_;
};
__device__ __align__(1024) Scratch g_scratch;
__device__ __forceinline__ uint32_t smem_u32(const void* p) { return (uint32_t)__cvta_generic_to_shared(p); }
__device__ __forceinline__ void mbar_init(uint32_t bar, uint32_t cnt) { asm volatile("mbarrier.init.shared::cta.b64 [%0], %1;" :: "r"(bar), "r"(cnt) : "memory"); }
__device__ __forceinline__ void mbar_expect_tx(uint32_t bar, uint32_t bytes) { asm volatile("mbarrier.arrive.expect_tx.shared::cta.b64 _, [%0], %1;" :: "r"(bar), "r"(bytes) : "memory"); }
__device__ __forceinline__ void mbar_arrive(uint32_t bar) { asm volatile("mbarrier.arrive.shared::cta.b64 _, [%0];" :: "r"(bar) : "memory"); }
#define SPINCHK(it) if ((it) > SPIN_LIMIT) break
__device__ __forceinline__ void mbar_wait(uint32_t bar, uint32_t parity) {
  asm volatile("{\n.reg .pred p;\n.reg .u32 c;\nmov.u32 c, 0;\n"
               "WL:\nmbarrier.try_wait.parity.shared::cta.b64 p, [%0], %1;\n@p bra WD;\n"
               "add.u32 c, c, 1;\nsetp.lt.u32 p, c, 1048576;\n@p bra WL;\nWD:\n}" :: "r"(bar), "r"(parity) : "memory");
}
__device__ __forceinline__ bool mbar_test(uint32_t bar, uint32_t parity) {
  uint32_t ok;
  asm volatile("{\n.reg .pred p;\nmbarrier.test_wait.parity.shared::cta.b64 p, [%1], %2;\nselp.u32 %0, 1, 0, p;\n}" : "=r"(ok) : "r"(bar), "r"(parity) : "memory");
  return ok;
}
__device__ __forceinline__ uint64_t l2_stream() { uint64_t p; asm("createpolicy.fractional.L2::evict_first.b64 %0, 1.0;" : "=l"(p)); return p; }
__device__ __forceinline__ void tma_2d(uint32_t dst, const CUtensorMap* tm, int c0, int c1, uint32_t bar, bool stream) {
  if (stream) asm volatile("cp.async.bulk.tensor.2d.shared::cluster.global.mbarrier::complete_tx::bytes.L2::cache_hint [%0], [%1, {%3, %4}], [%2], %5;"
                           :: "r"(dst), "l"(tm), "r"(bar), "r"(c0), "r"(c1), "l"(l2_stream()) : "memory");
  else asm volatile("cp.async.bulk.tensor.2d.shared::cluster.global.mbarrier::complete_tx::bytes [%0], [%1, {%3, %4}], [%2];"
                    :: "r"(dst), "l"(tm), "r"(bar), "r"(c0), "r"(c1) : "memory");
}
__device__ __forceinline__ void tma_3d(uint32_t dst, const CUtensorMap* tm, int c0, int c1, int c2, uint32_t bar, bool stream) {
  if (stream) asm volatile("cp.async.bulk.tensor.3d.shared::cluster.global.mbarrier::complete_tx::bytes.L2::cache_hint [%0], [%1, {%3, %4, %5}], [%2], %6;"
                           :: "r"(dst), "l"(tm), "r"(bar), "r"(c0), "r"(c1), "r"(c2), "l"(l2_stream()) : "memory");
  else asm volatile("cp.async.bulk.tensor.3d.shared::cluster.global.mbarrier::complete_tx::bytes [%0], [%1, {%3, %4, %5}], [%2];"
                    :: "r"(dst), "l"(tm), "r"(bar), "r"(c0), "r"(c1), "r"(c2) : "memory");
}
__device__ __forceinline__ void tma_4d(uint32_t dst, const CUtensorMap* tm, int c0, int c1, int c2, int c3, uint32_t bar) {
  asm volatile("cp.async.bulk.tensor.4d.shared::cluster.global.mbarrier::complete_tx::bytes.L2::cache_hint [%0], [%1, {%3, %4, %5, %6}], [%2], %7;"
               :: "r"(dst), "l"(tm), "r"(bar), "r"(c0), "r"(c1), "r"(c2), "r"(c3), "l"(l2_stream()) : "memory");
}
__device__ __forceinline__ void tma_2d_mc(uint32_t dst, const CUtensorMap* tm, int c0, int c1, uint32_t bar, bool stream) {
  if (stream) asm volatile("cp.async.bulk.tensor.2d.shared::cluster.global.mbarrier::complete_tx::bytes.multicast::cluster.L2::cache_hint [%0], [%1, {%3, %4}], [%2], %5, %6;"
                           :: "r"(dst), "l"(tm), "r"(bar), "r"(c0), "r"(c1), "h"((uint16_t)3), "l"(l2_stream()) : "memory");
  else asm volatile("cp.async.bulk.tensor.2d.shared::cluster.global.mbarrier::complete_tx::bytes.multicast::cluster [%0], [%1, {%3, %4}], [%2], %5;"
                    :: "r"(dst), "l"(tm), "r"(bar), "r"(c0), "r"(c1), "h"((uint16_t)3) : "memory");
}
__device__ __forceinline__ bool elect_one() {
  uint32_t p;
  asm volatile("{\n.reg .pred q;\nelect.sync _|q, 0xFFFFFFFF;\nselp.u32 %0, 1, 0, q;\n}" : "=r"(p));
  return p;
}
__device__ __forceinline__ void bulk_load_mc(uint32_t dst, const void* src, uint32_t bytes, uint32_t bar) {
  asm volatile("cp.async.bulk.shared::cluster.global.mbarrier::complete_tx::bytes.multicast::cluster [%0], [%1], %2, [%3], %4;"
               :: "r"(dst), "l"(src), "r"(bytes), "r"(bar), "h"((uint16_t)3) : "memory");
}
__device__ __forceinline__ void bulk_load(uint32_t dst, const void* src, uint32_t bytes, uint32_t bar) {
  asm volatile("cp.async.bulk.shared::cluster.global.mbarrier::complete_tx::bytes [%0], [%1], %2, [%3];" :: "r"(dst), "l"(src), "r"(bytes), "r"(bar) : "memory");
}
__device__ __forceinline__ void bulk_store(void* dst, uint32_t src, uint32_t bytes) {
  asm volatile("cp.async.bulk.global.shared::cta.bulk_group [%0], [%1], %2;" :: "l"(dst), "r"(src), "r"(bytes) : "memory");
}
__device__ __forceinline__ void mbar_arrive_rem(uint32_t bar) { asm volatile("mbarrier.arrive.shared::cluster.b64 _, [%0];" :: "r"(bar) : "memory"); }
template <uint32_t O> __device__ __forceinline__ void ldsm4_o(uint32_t addr, uint32_t& a, uint32_t& b, uint32_t& c, uint32_t& d) {
  asm volatile("ldmatrix.sync.aligned.m8n8.x4.shared.b16 {%0,%1,%2,%3}, [%4+%5];" : "=r"(a), "=r"(b), "=r"(c), "=r"(d) : "r"(addr), "n"(O) : "memory");
}
template <uint32_t O> __device__ __forceinline__ void ldsm4t_o(uint32_t addr, uint32_t (&r)[4]) {
  asm volatile("ldmatrix.sync.aligned.m8n8.x4.trans.shared.b16 {%0,%1,%2,%3}, [%4+%5];" : "=r"(r[0]), "=r"(r[1]), "=r"(r[2]), "=r"(r[3]) : "r"(addr), "n"(O) : "memory");
}
__device__ __forceinline__ void mma16816(float (&c)[4], const uint32_t (&a)[4], uint32_t b0, uint32_t b1) {
  asm("mma.sync.aligned.m16n8k16.row.col.f32.bf16.bf16.f32 {%0,%1,%2,%3}, {%4,%5,%6,%7}, {%8,%9}, {%0,%1,%2,%3};"
      : "+f"(c[0]), "+f"(c[1]), "+f"(c[2]), "+f"(c[3]) : "r"(a[0]), "r"(a[1]), "r"(a[2]), "r"(a[3]), "r"(b0), "r"(b1));
}
__device__ __forceinline__ void l2_prefetch(const void* p) { asm volatile("prefetch.global.L2 [%0];" :: "l"(p) : "memory"); }
__device__ __forceinline__ void tmap_prefetch(const CUtensorMap* tm) { asm volatile("prefetch.tensormap [%0];" :: "l"(tm) : "memory"); }
__device__ __forceinline__ void wg_fence() { asm volatile("wgmma.fence.sync.aligned;" ::: "memory"); }
__device__ __forceinline__ void wg_commit() { asm volatile("wgmma.commit_group.sync.aligned;" ::: "memory"); }
template <int N> __device__ __forceinline__ void wg_wait() { asm volatile("wgmma.wait_group.sync.aligned %0;" :: "n"(N) : "memory"); }
template <int N> __device__ __forceinline__ void pin(float (&d)[N]) {
#pragma unroll
  for (int i = 0; i < N; i++) asm volatile("" : "+f"(d[i]) :: "memory");
}
__device__ __forceinline__ void pin4(uint4& v) { asm volatile("" : "+r"(v.x), "+r"(v.y), "+r"(v.z), "+r"(v.w) :: "memory"); }
template <uint32_t SBO, uint32_t SWZ> __device__ __forceinline__ uint64_t dsc(uint32_t lo) { return ((uint64_t)((SBO >> 4) | (SWZ << 30)) << 32) | lo; }
__host__ __device__ constexpr uint32_t dlo(uint32_t addr, uint32_t lbo) { return (addr >> 4) | ((lbo >> 4) << 16); }
__device__ __forceinline__ void bar_sync(int id, int n) { asm volatile("bar.sync %0, %1;" :: "r"(id), "r"(n) : "memory"); }
__device__ __forceinline__ void bar_arrive(int id, int n) { asm volatile("bar.arrive %0, %1;" :: "r"(id), "r"(n) : "memory"); }
__device__ __forceinline__ void fence_async_smem() { asm volatile("fence.proxy.async.shared::cta;" ::: "memory"); }
__device__ __forceinline__ void fence_gpu() { asm volatile("fence.acq_rel.gpu;" ::: "memory"); }
__device__ __forceinline__ uint4 ld_cg4(const void* p) { uint4 v; asm volatile("ld.global.cg.v4.u32 {%0,%1,%2,%3}, [%4];" : "=r"(v.x), "=r"(v.y), "=r"(v.z), "=r"(v.w) : "l"(p) : "memory"); return v; }
__device__ __forceinline__ uint4 ld_rlx4(const void* p) { uint4 v; asm volatile("ld.relaxed.gpu.global.v4.u32 {%0,%1,%2,%3}, [%4];" : "=r"(v.x), "=r"(v.y), "=r"(v.z), "=r"(v.w) : "l"(p) : "memory"); return v; }
__device__ __forceinline__ uint32_t ld_rlx(const void* p) { uint32_t v; asm volatile("ld.relaxed.gpu.global.u32 %0, [%1];" : "=r"(v) : "l"(p) : "memory"); return v; }
__device__ __forceinline__ void st_rlx4(void* p, uint4 v) { asm volatile("st.relaxed.gpu.global.v4.u32 [%0], {%1,%2,%3,%4};" :: "l"(p), "r"(v.x), "r"(v.y), "r"(v.z), "r"(v.w) : "memory"); }
__device__ __forceinline__ void st_rlx2(void* p, uint32_t a, uint32_t b) { asm volatile("st.relaxed.gpu.global.v2.u32 [%0], {%1,%2};" :: "l"(p), "r"(a), "r"(b) : "memory"); }
__device__ __forceinline__ void st_rlx(void* p, uint32_t a) { asm volatile("st.relaxed.gpu.global.u32 [%0], %1;" :: "l"(p), "r"(a) : "memory"); }
__device__ __forceinline__ uint32_t pack2(float lo, float hi) { uint32_t r; asm("cvt.rn.bf16x2.f32 %0, %1, %2;" : "=r"(r) : "f"(hi), "f"(lo)); return r; }
__device__ __forceinline__ float bf_lo(uint32_t v) { return __uint_as_float(v << 16); }
__device__ __forceinline__ float bf_hi(uint32_t v) { return __uint_as_float(v & 0xFFFF0000u); }
__device__ __forceinline__ void stsm4(uint32_t addr, uint32_t a, uint32_t b, uint32_t c, uint32_t d) {
  asm volatile("stmatrix.sync.aligned.m8n8.x4.shared.b16 [%0], {%1,%2,%3,%4};" :: "r"(addr), "r"(a), "r"(b), "r"(c), "r"(d) : "memory");
}
template <uint32_t O> __device__ __forceinline__ void stsm4_o(uint32_t addr, uint32_t a, uint32_t b, uint32_t c, uint32_t d) {
  asm volatile("stmatrix.sync.aligned.m8n8.x4.shared.b16 [%0+%5], {%1,%2,%3,%4};" :: "r"(addr), "r"(a), "r"(b), "r"(c), "r"(d), "n"(O) : "memory");
}
__device__ __forceinline__ void sts4(uint32_t addr, uint32_t a, uint32_t b, uint32_t c, uint32_t d) { asm volatile("st.shared.v4.u32 [%0], {%1,%2,%3,%4};" :: "r"(addr), "r"(a), "r"(b), "r"(c), "r"(d) : "memory"); }
__device__ __forceinline__ void sts2f(uint32_t addr, float a, float b) { asm volatile("st.shared.v2.f32 [%0], {%1,%2};" :: "r"(addr), "f"(a), "f"(b) : "memory"); }
__device__ __forceinline__ void sts1(uint32_t addr, uint32_t a) { asm volatile("st.shared.u32 [%0], %1;" :: "r"(addr), "r"(a) : "memory"); }
__device__ __forceinline__ float2 lds2f(uint32_t addr) { float2 v; asm volatile("ld.shared.v2.f32 {%0,%1}, [%2];" : "=f"(v.x), "=f"(v.y) : "r"(addr) : "memory"); return v; }
template <uint32_t O> __device__ __forceinline__ float2 lds2f_o(uint32_t addr) { float2 v; asm volatile("ld.shared.v2.f32 {%0,%1}, [%2+%3];" : "=f"(v.x), "=f"(v.y) : "r"(addr), "n"(O) : "memory"); return v; }
template <int I, int N, class F> __device__ __forceinline__ void static_for(F&& f) { if constexpr (I < N) { f(std::integral_constant<int, I>{}); static_for<I + 1, N>(f); } }
__device__ __forceinline__ uint4 lds4(uint32_t addr) { uint4 v; asm volatile("ld.shared.v4.u32 {%0,%1,%2,%3}, [%4];" : "=r"(v.x), "=r"(v.y), "=r"(v.z), "=r"(v.w) : "r"(addr) : "memory"); return v; }
__device__ __forceinline__ uint32_t lds1(uint32_t addr) { uint32_t v; asm volatile("ld.shared.u32 %0, [%1];" : "=r"(v) : "r"(addr) : "memory"); return v; }
__device__ __forceinline__ float ex2(float x) { float y; asm("ex2.approx.ftz.f32 %0, %1;" : "=f"(y) : "f"(x)); return y; }
__device__ __forceinline__ uint32_t max4(uint32_t m, const uint4& v) { return __vimax3_u32(__vimax3_u32(m, v.x, v.y), v.z, v.w); }
__device__ __forceinline__ float rsq(float x) { float y; asm("rsqrt.approx.ftz.f32 %0, %1;" : "=f"(y) : "f"(x)); return y; }
__device__ __forceinline__ float rcp(float x) { float y; asm("rcp.approx.ftz.f32 %0, %1;" : "=f"(y) : "f"(x)); return y; }
__device__ __forceinline__ uint2 ld_rlx2(const void* p) { uint2 v; asm volatile("ld.relaxed.gpu.global.v2.u32 {%0,%1}, [%2];" : "=r"(v.x), "=r"(v.y) : "l"(p) : "memory"); return v; }
template <uint32_t O> __device__ __forceinline__ uint4 lds4_o(uint32_t addr) { uint4 v; asm volatile("ld.shared.v4.u32 {%0,%1,%2,%3}, [%4+%5];" : "=r"(v.x), "=r"(v.y), "=r"(v.z), "=r"(v.w) : "r"(addr), "n"(O) : "memory"); return v; }
__device__ __forceinline__ uint32_t phi2(float u0, float u1, float rl, uint32_t r2) {
  uint32_t pu, r;
  asm("cvt.rn.relu.bf16x2.f32 %0, %1, %2;" : "=r"(pu) : "f"(u1), "f"(u0));
  asm("fma.rn.bf16x2 %0, %1, %2, %3;" : "=r"(r) : "r"(pu), "r"(r2), "r"(pack2(__saturatef(ex2(u0 * rl) + 1e-6f), __saturatef(ex2(u1 * rl) + 1e-6f))));
  return r;
}
__device__ __forceinline__ uint32_t dup2(float r) { uint32_t v; asm("cvt.rn.relu.bf16x2.f32 %0, %1, %1;" : "=r"(v) : "f"(r)); return v; }
__device__ __forceinline__ uint32_t zero_after(const uint32_t (&v)[16]) {
  uint32_t z = 0;
#pragma unroll
  for (int i = 0; i < 16; i++) z |= v[i];
  return z & 0x80008000u;
}
__device__ __forceinline__ uint32_t hadd2(uint32_t a, uint32_t b) { uint32_t v; asm("add.rn.bf16x2 %0, %1, %2;" : "=r"(v) : "r"(a), "r"(b)); return v; }
__device__ __forceinline__ void sched_fence() { asm volatile("{\n.reg .pred p;\n.reg .u64 c;\nSF:\nmov.u64 c, %clock64;\nsetp.eq.u64 p, c, 0;\n@p bra SF;\n}" ::: "memory"); }
__device__ __forceinline__ uint32_t now_ns() { uint32_t v; asm volatile("mov.u32 %0, %%globaltimer_lo;" : "=r"(v) :: "memory"); return v; }
__device__ __forceinline__ void meet(uint32_t* mine, const uint4* all, int first, int after, uint32_t bar) {
  const uint32_t t0 = now_ns() & ~1u;
  if ((threadIdx.x & 31) == 0) st_rlx(mine, t0);
  while ((int)(now_ns() - t0) < first) NAP;
  uint4 v;
#pragma unroll 1
  for (int it = 0; it < SPIN_LIMIT; it++) { v = ld_rlx4(all); if (!__any_sync(~0u, max4(0, v) == SENT)) break; }
  const int d = min(__reduce_max_sync(~0u, max(max((int)(v.x - t0), (int)(v.y - t0)), max((int)(v.z - t0), (int)(v.w - t0)))), 100000) + after;
  mbar_wait(bar, 0);
  while ((int)(now_ns() - t0) < d) NAP;
}
__device__ __forceinline__ uint32_t hmul2(uint32_t a, uint32_t b) { uint32_t v; asm("mul.rn.bf16x2 %0, %1, %2;" : "=r"(v) : "r"(a), "r"(b)); return v; }
__device__ __forceinline__ uint32_t lane_id() { uint32_t v; asm volatile("mov.u32 %0, %%laneid;" : "=r"(v)); return v; }
template <int A, int B, int N> __device__ __forceinline__ void pinr(float (&d)[N]) {
#pragma unroll
  for (int i = A; i < B; i++) asm volatile("" : "+f"(d[i]) :: "memory");
}
template <int N> __device__ __forceinline__ void pinu(uint32_t (&d)[N]) {
#pragma unroll
  for (int i = 0; i < N; i++) asm volatile("" : "+r"(d[i]) :: "memory");
}

template<int TA, int TB, int OFF, int SZ> __device__ __forceinline__ void wgmma_n192_ss(float (&d)[SZ], uint64_t da, uint64_t db, int scale_d) {
  asm volatile("{\n.reg .pred p;\nsetp.ne.b32 p, %98, 0;\n"
    "wgmma.mma_async.sync.aligned.m64n192k16.f32.bf16.bf16 {%0,%1,%2,%3,%4,%5,%6,%7,%8,%9,%10,%11,%12,%13,%14,%15,%16,%17,%18,%19,%20,%21,%22,%23,%24,%25,%26,%27,%28,%29,%30,%31,%32,%33,%34,%35,%36,%37,%38,%39,%40,%41,%42,%43,%44,%45,%46,%47,%48,%49,%50,%51,%52,%53,%54,%55,%56,%57,%58,%59,%60,%61,%62,%63,%64,%65,%66,%67,%68,%69,%70,%71,%72,%73,%74,%75,%76,%77,%78,%79,%80,%81,%82,%83,%84,%85,%86,%87,%88,%89,%90,%91,%92,%93,%94,%95}, %96, %97, p, 1, 1, %99, %100;\n}\n"
    : "+f"(d[OFF+0]), "+f"(d[OFF+1]), "+f"(d[OFF+2]), "+f"(d[OFF+3]), "+f"(d[OFF+4]), "+f"(d[OFF+5]), "+f"(d[OFF+6]), "+f"(d[OFF+7]),
      "+f"(d[OFF+8]), "+f"(d[OFF+9]), "+f"(d[OFF+10]), "+f"(d[OFF+11]), "+f"(d[OFF+12]), "+f"(d[OFF+13]), "+f"(d[OFF+14]), "+f"(d[OFF+15]),
      "+f"(d[OFF+16]), "+f"(d[OFF+17]), "+f"(d[OFF+18]), "+f"(d[OFF+19]), "+f"(d[OFF+20]), "+f"(d[OFF+21]), "+f"(d[OFF+22]), "+f"(d[OFF+23]),
      "+f"(d[OFF+24]), "+f"(d[OFF+25]), "+f"(d[OFF+26]), "+f"(d[OFF+27]), "+f"(d[OFF+28]), "+f"(d[OFF+29]), "+f"(d[OFF+30]), "+f"(d[OFF+31]),
      "+f"(d[OFF+32]), "+f"(d[OFF+33]), "+f"(d[OFF+34]), "+f"(d[OFF+35]), "+f"(d[OFF+36]), "+f"(d[OFF+37]), "+f"(d[OFF+38]), "+f"(d[OFF+39]),
      "+f"(d[OFF+40]), "+f"(d[OFF+41]), "+f"(d[OFF+42]), "+f"(d[OFF+43]), "+f"(d[OFF+44]), "+f"(d[OFF+45]), "+f"(d[OFF+46]), "+f"(d[OFF+47]),
      "+f"(d[OFF+48]), "+f"(d[OFF+49]), "+f"(d[OFF+50]), "+f"(d[OFF+51]), "+f"(d[OFF+52]), "+f"(d[OFF+53]), "+f"(d[OFF+54]), "+f"(d[OFF+55]),
      "+f"(d[OFF+56]), "+f"(d[OFF+57]), "+f"(d[OFF+58]), "+f"(d[OFF+59]), "+f"(d[OFF+60]), "+f"(d[OFF+61]), "+f"(d[OFF+62]), "+f"(d[OFF+63]),
      "+f"(d[OFF+64]), "+f"(d[OFF+65]), "+f"(d[OFF+66]), "+f"(d[OFF+67]), "+f"(d[OFF+68]), "+f"(d[OFF+69]), "+f"(d[OFF+70]), "+f"(d[OFF+71]),
      "+f"(d[OFF+72]), "+f"(d[OFF+73]), "+f"(d[OFF+74]), "+f"(d[OFF+75]), "+f"(d[OFF+76]), "+f"(d[OFF+77]), "+f"(d[OFF+78]), "+f"(d[OFF+79]),
      "+f"(d[OFF+80]), "+f"(d[OFF+81]), "+f"(d[OFF+82]), "+f"(d[OFF+83]), "+f"(d[OFF+84]), "+f"(d[OFF+85]), "+f"(d[OFF+86]), "+f"(d[OFF+87]),
      "+f"(d[OFF+88]), "+f"(d[OFF+89]), "+f"(d[OFF+90]), "+f"(d[OFF+91]), "+f"(d[OFF+92]), "+f"(d[OFF+93]), "+f"(d[OFF+94]), "+f"(d[OFF+95])
    : "l"(da), "l"(db), "r"(scale_d), "n"(TA), "n"(TB));
}
template<int TA, int TB, int OFF, int SZ> __device__ __forceinline__ void wgmma_n128_ss(float (&d)[SZ], uint64_t da, uint64_t db, int scale_d) {
  asm volatile("{\n.reg .pred p;\nsetp.ne.b32 p, %66, 0;\n"
    "wgmma.mma_async.sync.aligned.m64n128k16.f32.bf16.bf16 {%0,%1,%2,%3,%4,%5,%6,%7,%8,%9,%10,%11,%12,%13,%14,%15,%16,%17,%18,%19,%20,%21,%22,%23,%24,%25,%26,%27,%28,%29,%30,%31,%32,%33,%34,%35,%36,%37,%38,%39,%40,%41,%42,%43,%44,%45,%46,%47,%48,%49,%50,%51,%52,%53,%54,%55,%56,%57,%58,%59,%60,%61,%62,%63}, %64, %65, p, 1, 1, %67, %68;\n}\n"
    : "+f"(d[OFF+0]), "+f"(d[OFF+1]), "+f"(d[OFF+2]), "+f"(d[OFF+3]), "+f"(d[OFF+4]), "+f"(d[OFF+5]), "+f"(d[OFF+6]), "+f"(d[OFF+7]),
      "+f"(d[OFF+8]), "+f"(d[OFF+9]), "+f"(d[OFF+10]), "+f"(d[OFF+11]), "+f"(d[OFF+12]), "+f"(d[OFF+13]), "+f"(d[OFF+14]), "+f"(d[OFF+15]),
      "+f"(d[OFF+16]), "+f"(d[OFF+17]), "+f"(d[OFF+18]), "+f"(d[OFF+19]), "+f"(d[OFF+20]), "+f"(d[OFF+21]), "+f"(d[OFF+22]), "+f"(d[OFF+23]),
      "+f"(d[OFF+24]), "+f"(d[OFF+25]), "+f"(d[OFF+26]), "+f"(d[OFF+27]), "+f"(d[OFF+28]), "+f"(d[OFF+29]), "+f"(d[OFF+30]), "+f"(d[OFF+31]),
      "+f"(d[OFF+32]), "+f"(d[OFF+33]), "+f"(d[OFF+34]), "+f"(d[OFF+35]), "+f"(d[OFF+36]), "+f"(d[OFF+37]), "+f"(d[OFF+38]), "+f"(d[OFF+39]),
      "+f"(d[OFF+40]), "+f"(d[OFF+41]), "+f"(d[OFF+42]), "+f"(d[OFF+43]), "+f"(d[OFF+44]), "+f"(d[OFF+45]), "+f"(d[OFF+46]), "+f"(d[OFF+47]),
      "+f"(d[OFF+48]), "+f"(d[OFF+49]), "+f"(d[OFF+50]), "+f"(d[OFF+51]), "+f"(d[OFF+52]), "+f"(d[OFF+53]), "+f"(d[OFF+54]), "+f"(d[OFF+55]),
      "+f"(d[OFF+56]), "+f"(d[OFF+57]), "+f"(d[OFF+58]), "+f"(d[OFF+59]), "+f"(d[OFF+60]), "+f"(d[OFF+61]), "+f"(d[OFF+62]), "+f"(d[OFF+63])
    : "l"(da), "l"(db), "r"(scale_d), "n"(TA), "n"(TB));
}
template<int TA, int TB, int OFF, int SZ> __device__ __forceinline__ void wgmma_n64_ss(float (&d)[SZ], uint64_t da, uint64_t db, int scale_d) {
  asm volatile("{\n.reg .pred p;\nsetp.ne.b32 p, %34, 0;\n"
    "wgmma.mma_async.sync.aligned.m64n64k16.f32.bf16.bf16 {%0,%1,%2,%3,%4,%5,%6,%7,%8,%9,%10,%11,%12,%13,%14,%15,%16,%17,%18,%19,%20,%21,%22,%23,%24,%25,%26,%27,%28,%29,%30,%31}, %32, %33, p, 1, 1, %35, %36;\n}\n"
    : "+f"(d[OFF+0]), "+f"(d[OFF+1]), "+f"(d[OFF+2]), "+f"(d[OFF+3]), "+f"(d[OFF+4]), "+f"(d[OFF+5]), "+f"(d[OFF+6]), "+f"(d[OFF+7]),
      "+f"(d[OFF+8]), "+f"(d[OFF+9]), "+f"(d[OFF+10]), "+f"(d[OFF+11]), "+f"(d[OFF+12]), "+f"(d[OFF+13]), "+f"(d[OFF+14]), "+f"(d[OFF+15]),
      "+f"(d[OFF+16]), "+f"(d[OFF+17]), "+f"(d[OFF+18]), "+f"(d[OFF+19]), "+f"(d[OFF+20]), "+f"(d[OFF+21]), "+f"(d[OFF+22]), "+f"(d[OFF+23]),
      "+f"(d[OFF+24]), "+f"(d[OFF+25]), "+f"(d[OFF+26]), "+f"(d[OFF+27]), "+f"(d[OFF+28]), "+f"(d[OFF+29]), "+f"(d[OFF+30]), "+f"(d[OFF+31])
    : "l"(da), "l"(db), "r"(scale_d), "n"(TA), "n"(TB));
}
template<int TA, int TB, int OFF, int SZ> __device__ __forceinline__ void wgmma_n72_ss(float (&d)[SZ], uint64_t da, uint64_t db, int scale_d) {
  asm volatile("{\n.reg .pred p;\nsetp.ne.b32 p, %38, 0;\n"
    "wgmma.mma_async.sync.aligned.m64n72k16.f32.bf16.bf16 {%0,%1,%2,%3,%4,%5,%6,%7,%8,%9,%10,%11,%12,%13,%14,%15,%16,%17,%18,%19,%20,%21,%22,%23,%24,%25,%26,%27,%28,%29,%30,%31,%32,%33,%34,%35}, %36, %37, p, 1, 1, %39, %40;\n}\n"
    : "+f"(d[OFF+0]), "+f"(d[OFF+1]), "+f"(d[OFF+2]), "+f"(d[OFF+3]), "+f"(d[OFF+4]), "+f"(d[OFF+5]), "+f"(d[OFF+6]), "+f"(d[OFF+7]),
      "+f"(d[OFF+8]), "+f"(d[OFF+9]), "+f"(d[OFF+10]), "+f"(d[OFF+11]), "+f"(d[OFF+12]), "+f"(d[OFF+13]), "+f"(d[OFF+14]), "+f"(d[OFF+15]),
      "+f"(d[OFF+16]), "+f"(d[OFF+17]), "+f"(d[OFF+18]), "+f"(d[OFF+19]), "+f"(d[OFF+20]), "+f"(d[OFF+21]), "+f"(d[OFF+22]), "+f"(d[OFF+23]),
      "+f"(d[OFF+24]), "+f"(d[OFF+25]), "+f"(d[OFF+26]), "+f"(d[OFF+27]), "+f"(d[OFF+28]), "+f"(d[OFF+29]), "+f"(d[OFF+30]), "+f"(d[OFF+31]),
      "+f"(d[OFF+32]), "+f"(d[OFF+33]), "+f"(d[OFF+34]), "+f"(d[OFF+35])
    : "l"(da), "l"(db), "r"(scale_d), "n"(TA), "n"(TB));
}
template<int TB, int OFF, int SZ> __device__ __forceinline__ void wgmma_n64_rs(float (&d)[SZ], uint32_t a0, uint32_t a1, uint32_t a2, uint32_t a3, uint64_t db, int scale_d) {
  asm volatile("{\n.reg .pred p;\nsetp.ne.b32 p, %37, 0;\n"
    "wgmma.mma_async.sync.aligned.m64n64k16.f32.bf16.bf16 {%0,%1,%2,%3,%4,%5,%6,%7,%8,%9,%10,%11,%12,%13,%14,%15,%16,%17,%18,%19,%20,%21,%22,%23,%24,%25,%26,%27,%28,%29,%30,%31}, {%32,%33,%34,%35}, %36, p, 1, 1, %38;\n}\n"
    : "+f"(d[OFF+0]), "+f"(d[OFF+1]), "+f"(d[OFF+2]), "+f"(d[OFF+3]), "+f"(d[OFF+4]), "+f"(d[OFF+5]), "+f"(d[OFF+6]), "+f"(d[OFF+7]),
      "+f"(d[OFF+8]), "+f"(d[OFF+9]), "+f"(d[OFF+10]), "+f"(d[OFF+11]), "+f"(d[OFF+12]), "+f"(d[OFF+13]), "+f"(d[OFF+14]), "+f"(d[OFF+15]),
      "+f"(d[OFF+16]), "+f"(d[OFF+17]), "+f"(d[OFF+18]), "+f"(d[OFF+19]), "+f"(d[OFF+20]), "+f"(d[OFF+21]), "+f"(d[OFF+22]), "+f"(d[OFF+23]),
      "+f"(d[OFF+24]), "+f"(d[OFF+25]), "+f"(d[OFF+26]), "+f"(d[OFF+27]), "+f"(d[OFF+28]), "+f"(d[OFF+29]), "+f"(d[OFF+30]), "+f"(d[OFF+31])
    : "r"(a0), "r"(a1), "r"(a2), "r"(a3), "l"(db), "r"(scale_d), "n"(TB));
}
template<int TB, int OFF, int SZ> __device__ __forceinline__ void wgmma_n40_rs(float (&d)[SZ], uint32_t a0, uint32_t a1, uint32_t a2, uint32_t a3, uint64_t db, int scale_d) {
  asm volatile("{\n.reg .pred p;\nsetp.ne.b32 p, %25, 0;\n"
    "wgmma.mma_async.sync.aligned.m64n40k16.f32.bf16.bf16 {%0,%1,%2,%3,%4,%5,%6,%7,%8,%9,%10,%11,%12,%13,%14,%15,%16,%17,%18,%19}, {%20,%21,%22,%23}, %24, p, 1, 1, %26;\n}\n"
    : "+f"(d[OFF+0]), "+f"(d[OFF+1]), "+f"(d[OFF+2]), "+f"(d[OFF+3]), "+f"(d[OFF+4]), "+f"(d[OFF+5]), "+f"(d[OFF+6]), "+f"(d[OFF+7]),
      "+f"(d[OFF+8]), "+f"(d[OFF+9]), "+f"(d[OFF+10]), "+f"(d[OFF+11]), "+f"(d[OFF+12]), "+f"(d[OFF+13]), "+f"(d[OFF+14]), "+f"(d[OFF+15]),
      "+f"(d[OFF+16]), "+f"(d[OFF+17]), "+f"(d[OFF+18]), "+f"(d[OFF+19])
    : "r"(a0), "r"(a1), "r"(a2), "r"(a3), "l"(db), "r"(scale_d), "n"(TB));
}
template<int TB, int OFF, int SZ> __device__ __forceinline__ void wgmma_n128_rs(float (&d)[SZ], uint32_t a0, uint32_t a1, uint32_t a2, uint32_t a3, uint64_t db, int scale_d) {
  asm volatile("{\n.reg .pred p;\nsetp.ne.b32 p, %69, 0;\n"
    "wgmma.mma_async.sync.aligned.m64n128k16.f32.bf16.bf16 {%0,%1,%2,%3,%4,%5,%6,%7,%8,%9,%10,%11,%12,%13,%14,%15,%16,%17,%18,%19,%20,%21,%22,%23,%24,%25,%26,%27,%28,%29,%30,%31,%32,%33,%34,%35,%36,%37,%38,%39,%40,%41,%42,%43,%44,%45,%46,%47,%48,%49,%50,%51,%52,%53,%54,%55,%56,%57,%58,%59,%60,%61,%62,%63}, {%64,%65,%66,%67}, %68, p, 1, 1, %70;\n}\n"
    : "+f"(d[OFF+0]), "+f"(d[OFF+1]), "+f"(d[OFF+2]), "+f"(d[OFF+3]), "+f"(d[OFF+4]), "+f"(d[OFF+5]), "+f"(d[OFF+6]), "+f"(d[OFF+7]),
      "+f"(d[OFF+8]), "+f"(d[OFF+9]), "+f"(d[OFF+10]), "+f"(d[OFF+11]), "+f"(d[OFF+12]), "+f"(d[OFF+13]), "+f"(d[OFF+14]), "+f"(d[OFF+15]),
      "+f"(d[OFF+16]), "+f"(d[OFF+17]), "+f"(d[OFF+18]), "+f"(d[OFF+19]), "+f"(d[OFF+20]), "+f"(d[OFF+21]), "+f"(d[OFF+22]), "+f"(d[OFF+23]),
      "+f"(d[OFF+24]), "+f"(d[OFF+25]), "+f"(d[OFF+26]), "+f"(d[OFF+27]), "+f"(d[OFF+28]), "+f"(d[OFF+29]), "+f"(d[OFF+30]), "+f"(d[OFF+31]),
      "+f"(d[OFF+32]), "+f"(d[OFF+33]), "+f"(d[OFF+34]), "+f"(d[OFF+35]), "+f"(d[OFF+36]), "+f"(d[OFF+37]), "+f"(d[OFF+38]), "+f"(d[OFF+39]),
      "+f"(d[OFF+40]), "+f"(d[OFF+41]), "+f"(d[OFF+42]), "+f"(d[OFF+43]), "+f"(d[OFF+44]), "+f"(d[OFF+45]), "+f"(d[OFF+46]), "+f"(d[OFF+47]),
      "+f"(d[OFF+48]), "+f"(d[OFF+49]), "+f"(d[OFF+50]), "+f"(d[OFF+51]), "+f"(d[OFF+52]), "+f"(d[OFF+53]), "+f"(d[OFF+54]), "+f"(d[OFF+55]),
      "+f"(d[OFF+56]), "+f"(d[OFF+57]), "+f"(d[OFF+58]), "+f"(d[OFF+59]), "+f"(d[OFF+60]), "+f"(d[OFF+61]), "+f"(d[OFF+62]), "+f"(d[OFF+63])
    : "r"(a0), "r"(a1), "r"(a2), "r"(a3), "l"(db), "r"(scale_d), "n"(TB));
}

struct Ptrs { const __nv_bfloat16 *x, *wqkv, *wo, *wr, *wg, *wu, *wd; __nv_bfloat16* out; Scratch* s; };

enum { M_X, M_W, M_Q, M_O, M_S, M_G, M_U, M_D, M_L, M_N };
struct Maps { CUtensorMap m[M_N]; };

__global__ void __cluster_dims__(2, 1, 1) __launch_bounds__(384, 1) fused_kernel(const Ptrs P, const __grid_constant__ Maps T) {
  extern __shared__ __align__(1024) uint8_t smem_raw[];
  const uint32_t rank = blockIdx.x & 1;
  uint32_t own = rank << 24;
  asm("" : "+r"(own));
  const uint32_t sm = own + sb, mb = own + bars;
  int b0;
  { const int j = blockIdx.x >> 1, u = j - 36, v = j * 2 - 8 + (max(u * 37 + 256, 0) >> 8) * (u < 0 ? 0 : 2), w = j < 4 ? j * 16 + 64 : v;
    b0 = ((w & 15) | (w & 48) << 1 | (w & 64) >> 2) + rank; }
#define IDS(B) \
  const int b = (B), rb = b >> 4, cg = b & 15, hf = cg >> 3, s3 = cg & 7, c3 = s3 ^ ((rb & 1) << 2), jp = cg >> 1, km = (~c3 & 6) << 1; \
  const int fidx = rb == (jp & 6) ? -1 : (jp * 7 + rb - (rb > (jp & 6))) * 2 + (b & 1); \
  [[maybe_unused]] auto kcol = [&](int kb) { return (kb ^ (kb < 8 ? km & 8 : km)) * 64; }; \
  auto src_of = [&](int p) { return p == 0 ? s3 : p == 15 ? s3 ^ 1 : (((jp & 3) ^ ((p - 7) >> 1)) << 1) + ((p - 1) & 1); }; \
  [[maybe_unused]] auto frag_of = [&](int p) { return p < 9 ? (p - 1) * 512 : 4096 + src_of(p) * 512; }; \
  (void)hf; (void)fidx
  auto get_b = [&]() { return __shfl_sync(~0u, (int)lds1(mb + B_ID), 0); };
  IDS(b0);
  auto load_w = [&](uint32_t st, int kc, uint32_t bar, bool last) { tma_3d(st + 32768, &T.m[M_W], cg * 64, kc, 1, bar, last); tma_2d(st + 49152, &T.m[M_Q], cg * 64, kc, bar, last); };
  if (threadIdx.x < 256) {
    const int r = threadIdx.x >> 3, c = threadIdx.x & 7, xr = (r & 16) * 8 + (r & 15);
    const uint32_t sw = ((c ^ r) & 7) << 4;
    const __nv_bfloat16* gw = P.wqkv + (kcol(0) + r) * 3072 + cg * 64 + c * 8, *gx = P.x + (rb * 256 + xr) * D_ + kcol(0) + c * 8;
#pragma unroll
    for (int i = 0; i < 6; i++)
      asm volatile("cp.async.cg.shared.global [%0], [%1], 16;" :: "r"(sm + 32768 + i * 4096 + r * 128 + sw), "l"(gw + (i & 1) * 32 * 3072 + ((i >> 1) + 1) % 3 * 1024) : "memory");
    asm volatile("cp.async.commit_group;" ::: "memory");
#pragma unroll
    for (int i = 0; i < 8; i++) asm volatile("cp.async.cg.shared.global [%0], [%1], 16;" :: "r"(sm + i * 2048 + xr * 128 + sw), "l"(gx + i * 16 * D_) : "memory");
    asm volatile("cp.async.commit_group;" ::: "memory");
  }
  const int tid = threadIdx.x, wid = __shfl_sync(~0u, tid >> 5, 0), wg = wid >> 2, lane = lane_id();
  const uint32_t tk = clock64();
  if (wid == 8) {
    if (elect_one()) { tmap_prefetch(&T.m[M_X]); tmap_prefetch(&T.m[M_W]); tmap_prefetch(&T.m[M_Q]); }
  } else if (wid == 9) {
    if (elect_one()) {
#pragma unroll
      for (int i = 0; i < 31; i++) if (8 * i != B_ID) mbar_init(mb + 8 * i, i < 4 ? 1 : i < 8 ? 8 : i < 16 ? 16 : i == 16 ? 64 : i == 17 ? 8 : i == 18 ? 4 : 1);
      asm volatile("fence.mbarrier_init.release.cluster;" ::: "memory");
      fence_async_smem();
    }
  } else if (wid == 11) {
#pragma unroll
    for (int i = 0; i < 4; i++) sts4(sm + OFF_STATS + i * 512 + lane * 16, SENT, SENT, SENT, SENT);
    sts1(mb + B_ID, b);
    if (smem_u32(smem_raw) != sm) asm volatile("trap;");
    fence_async_smem();
  }
  __syncthreads();
  asm volatile("barrier.cluster.arrive.relaxed.aligned;\nbarrier.cluster.wait.aligned;" ::: "memory");

  if (wg == 2) {
    asm volatile("setmaxnreg.dec.sync.aligned.u32 56;");
    if (wid == 8) {
      if (elect_one()) {
#pragma unroll 1
        for (int kb = 1; kb < 15; kb++) {
          const uint32_t fb = mb + B_FULL + 8 * (kb & 3), st = sm + (kb & 3) * STAGE_B;
          const int kc = kcol(kb);
          if (kb < 4) while ((uint32_t)clock64() - tk < FD0 + kb * FD1) {}
          else mbar_wait(fb + B_EMPTY, ((kb >> 2) & 1) ^ 1);
          mbar_expect_tx(fb, STAGE_B);
          tma_2d_mc(st + rank * 16384, &T.m[M_X], kc, rb * 256 + rank * 128, fb, kb >= 12);
          load_w(st, kc, fb, kb >= 8);
          if (kb >= 8 && kb < 11) asm volatile("mbarrier.arrive.shared::cta.b64 _, [%0], %1;" :: "r"(fb + B_EMPTY), "r"(4) : "memory");
        }
        {
          const uint32_t st = sm + 3 * STAGE_B, fa = mb + B_FULL + 24, fb = mb + B_F15;
          const int kc = kcol(15);
          mbar_wait(fa, 0);
          mbar_expect_tx(fa, 32768); mbar_expect_tx(fb, 24576);
          if (rank) { mbar_wait(mb + B_EMPTY + 24, 0); tma_2d_mc(st + 16384, &T.m[M_X], kc, rb * 256 + 128, fa, true); }
          mbar_wait(mb + B_EMPTY, 1);
          tma_3d(st + 32768, &T.m[M_W], cg * 64, kc, 1, fa, true);
          if (!rank) { mbar_wait(mb + B_EMPTY + 24, 0); tma_2d_mc(st, &T.m[M_X], kc, rb * 256, fb, true); }
          tma_2d(st + 49152, &T.m[M_Q], cg * 64, kc, fb, true);
        }
        mbar_expect_tx(mb + B_KVP, 32768 + 2048);
      }
      __syncwarp();
      const uint4* kp = &P.s->kvp[cg * 8 * 256], *zq = &P.s->zp[cg * 8 * 16], *src = &P.s->obuf[(rb * 4 + rank * 2 + hf) * 64 * 128];
      asm volatile("" : "+l"(kp), "+l"(zq), "+l"(src));
      bar_sync(13, 160);
      meet(&P.s->when[cg * 32 + rb], (const uint4*)&P.s->when[cg * 32] + (lane & 1), MFIRST, MKV, mb + B_EVB);
      if (elect_one()) {
        bulk_load(sm + rank * (2 * STAGE_B) + STAGE_B, kp, 32768, mb + B_KVP);
        bulk_load(sm + rank * (2 * STAGE_B) + UNIT, zq, 2048, mb + B_KVP);
      }
      mbar_wait(mb + B_KVP, 0);
      mbar_wait(mb + B_KVB, 1);
      meet(&P.s->when[(16 + rb * 2 + hf) * 32 + s3], (const uint4*)&P.s->when[(16 + rb * 2 + (hf ^ 1)) * 32] + (lane & 1), MFIRST, MO, mb + B_E);
      if (elect_one()) {
        const uint32_t t0 = clock64();
        mbar_arrive(mb + B_F15);
#pragma unroll
        for (int p = 2; p < 5; p++) {
          if (p < 4) while ((uint32_t)clock64() - t0 < (p == 2 ? ADELAY : ADELAY2)) NAP;
          bulk_load_mc(sm + ring_of(p, rank), src + (p - 1) * 512, UNIT, mb + B_BF + 8 * p);
        }
#pragma unroll 1
        for (int p = 5; p < 15; p++) {
          uint32_t dst = sm + ring_of(p, rank), bar = mb + B_BF + 8 * (p % 7);
          const uint4* q = src + frag_of(p);
          asm volatile("" : "+r"(dst), "+r"(bar), "+l"(q));
          mbar_wait(mb + B_E + 8 * ((p - 4) & 7), p >= 12);
          bulk_load_mc(dst, q, UNIT, bar);
        }
        asm volatile("mbarrier.arrive.shared::cta.b64 _, [%0], 8;" :: "r"(mb + B_GATE) : "memory");
        const uint4* s15 = &P.s->obuf[(rb * 4 + hf) * 64 * 128 + frag_of(15)];
        mbar_wait(mb + B_E + 24, 1);
        bulk_load(sm + ring_of(15, 0), s15, UNIT, mb + B_BF + 8); bulk_load(sm + ring_of(15, 1), s15 + 2 * 64 * 128, UNIT, mb + B_BF + 8);
      }
    } else if (wid == 11) {
      IDS(get_b());
      mbar_wait(mb + B_FULL, 0);
      {
        const uint32_t ep = ld_rlx(&P.s->epoch);
        float s = 0.f;
#pragma unroll
        for (int i = 0; i < 4; i++) {
          const uint4 v = ld_cg4((const uint4*)P.wr + lane + i * 32);
          s += (bf_lo(v.x) + bf_hi(v.x)) + (bf_lo(v.y) + bf_hi(v.y)) + (bf_lo(v.z) + bf_hi(v.z)) + (bf_lo(v.w) + bf_hi(v.w));
        }
#pragma unroll
        for (int o = 16; o; o >>= 1) s += __shfl_xor_sync(~0u, s, o);
        if (lane == 0) sts1(mb + B_SW, (__float_as_uint(s) & ~255u) | ((ep + 1) & 255));
      }
      bar_arrive(10, 96);
      if (fidx >= 0) {
        const uint32_t o = (rank * 32 + lane) * (F_ * 2) + (fidx >> 1) * 128;
        const char* q0 = (const char*)P.wg + o, *q1 = (const char*)P.wu + o;
        mbar_wait(mb + B_FULL + 24, 0);
#pragma unroll 1
        for (int r = 0; r < 16; r++, q0 += 64 * F_ * 2, q1 += 64 * F_ * 2) {
          if (mbar_test(mb + B_F15, 0)) { l2_prefetch(q0); l2_prefetch(q1); continue; }
          asm volatile("cp.async.ca.shared.global.L2::128B [%0], [%1], 4;\ncp.async.commit_group;\ncp.async.wait_group %3;\n"
                       "cp.async.ca.shared.global.L2::128B [%0], [%2], 4;\ncp.async.commit_group;\ncp.async.wait_group %3;" :: "r"(mb + B_DUMMY), "l"(q0), "l"(q1), "n"(2) : "memory");
        }
        mbar_wait(mb + B_F15, 0);
        bar_sync(15, 288);
        q0 = (const char*)P.wd + fidx * 65536 + lane * 128;
        const uint32_t bar = mb + B_BF + 48;
        if (lane == 0) mbar_expect_tx(bar, 8192);
#pragma unroll 1
        for (int i = 0; i < 16 + PLAG; i++) {
          if (i < 16) l2_prefetch(q0 + i * 4096);
          if (i >= PLAG && elect_one()) tma_2d(sm + OFF_COLSUM, &T.m[M_L], 0, fidx * 512 + (i - PLAG) * 32, bar, false);
        }
        mbar_wait(bar, 0);
        __syncwarp();
        if (lane == 0) { mbar_arrive(bar); }
        asm volatile("cp.async.wait_all;" ::: "memory");
      } else bar_sync(15, 288);
      bar_arrive(14, 64);
    } else {
      const uint32_t eb = (lane << 24) + bars + B_EMPTY;
      float c[6];
      if (wid == 10) {
        float sx[4] = {0.f, 0.f, 0.f, 0.f}, qx[4] = {0.f, 0.f, 0.f, 0.f};
        const uint32_t xa = sm + ((hf * 4 + (cg & 3)) * 32 + lane) * 128 + ((lane & 7) << 4);
#pragma unroll 1
        for (int kb = 0; kb < 8; kb++) {
          uint4 xv[8];
          const uint32_t so = xa + (kb & 3) * STAGE_B;
          mbar_wait(mb + B_FULL + 8 * (kb & 3), kb >> 2);
#pragma unroll
          for (int i = 0; i < 8; i++) xv[i] = lds4(so ^ (i << 4));
#pragma unroll
          for (int i = 0; i < 8; i++) {
            const uint32_t e[4] = {xv[i].x, xv[i].y, xv[i].z, xv[i].w};
#pragma unroll
            for (int j = 0; j < 4; j++) {
              const float d0 = bf_lo(e[j]), d1 = bf_hi(e[j]);
              sx[j] += d0 + d1; qx[j] = fmaf(d0, d0, fmaf(d1, d1, qx[j]));
            }
          }
          __syncwarp();
          if (lane < 2) mbar_arrive_rem(eb + 8 * (kb & 3));
          if (kb == 1) {
            if (elect_one()) {
#pragma unroll 1
              for (int i = 0; i < 16; i++) bulk_store(&P.s->obuf[((rb * 4 + (i >> 2)) * 64 + (((i >> 2) & 1) == hf ? 32 + s3 * 4 + (i & 3) : (i & 3) * 8 + s3)) * 128], sm + OFF_STATS, 2048);
              bulk_store(&P.s->kvp[(cg * 8 + rb) * 256], sm + OFF_STATS, 2048); bulk_store(&P.s->kvp[(cg * 8 + rb) * 256 + 128], sm + OFF_STATS, 2048);
              bulk_store(&P.s->zp[(cg * 8 + rb) * 16], sm + OFF_STATS, 256);
              if (s3 == 0) bulk_store(&P.s->when[(16 + rb * 2 + hf) * 32], sm + OFF_STATS, 128);
              if (rb == 0) bulk_store(&P.s->when[cg * 32], sm + OFF_STATS, 128);
              asm volatile("cp.async.bulk.commit_group;" ::: "memory");
#pragma unroll
              for (int i = M_O; i < M_N; i++) tmap_prefetch(&T.m[i]);
            }
            __syncwarp();
          }
        }
        asm volatile("cp.async.bulk.wait_group 0;\nfence.proxy.async.global;" ::: "memory");
        fence_gpu();
        c[0] = ((sx[0] + sx[1]) + (sx[2] + sx[3])) * (2.f / D_);
        c[1] = fmaxf(fmaf(-c[0], c[0], ((qx[0] + qx[1]) + (qx[2] + qx[3])) * (2.f / D_)), 0.f);
      } else {
        float a[12];
#pragma unroll
        for (int i = 0; i < 12; i++) a[i] = 0.f;
        const int r2 = lane >> 4, c16 = lane & 15;
        const uint32_t a0 = sm + 32768 + (rb >> 1) * 2048 + r2 * 128 + (((c16 >> 1) ^ r2) << 4) + (c16 & 1) * 8;
#pragma unroll 1
        for (int it = 0; it < 16; it++) {
          uint2 w[12];
          const int s = (it >> 1) & 3;
          const uint32_t so = a0 + s * STAGE_B + (it & 1) * 1024;
          if (!(it & 1)) { mbar_wait(mb + B_FULL + 8 * s, it >> 3); }
          static_for<0, 12>([&](auto ic) { constexpr int i = decltype(ic)::value;
            const float2 v = lds2f_o<(i >> 2) * 8192 + (i & 3) * 256>(so ^ ((i & 3) << 5)); w[i] = make_uint2(__float_as_uint(v.x), __float_as_uint(v.y)); });
#pragma unroll
          for (int i = 0; i < 12; i++) { float* q = a + (i >> 2) * 4; q[0] += bf_lo(w[i].x); q[1] += bf_hi(w[i].x); q[2] += bf_lo(w[i].y); q[3] += bf_hi(w[i].y); }
          __syncwarp();
          if (lane < 2 && (it & 1)) mbar_arrive_rem(eb + 8 * s);
        }
#pragma unroll
        for (int i = 0; i < 6; i++) {
          const int o = (i >> 1) * 4 + (i & 1);
          c[i] = (r2 ? a[o + 2] : a[o]) + __shfl_xor_sync(~0u, r2 ? a[o] : a[o + 2], 16);
        }
      }
      bar_sync(10, 96);
      {
        const uint32_t tag = lds1(mb + B_SW) & 255;
        auto tagged = [&](float v) { return ((__float_as_uint(v) + 128) & ~255u) | tag; };
        if (wid == 9) {
#pragma unroll
          for (int sg = 0; sg < 3; sg++) {
            st_rlx2((uint2*)&P.s->csp[(cg * 8 + rb) * 48] + sg * 32 + (lane & 15) * 2 + (lane >> 4), tagged(c[sg * 2]), tagged(c[sg * 2 + 1]));
          }
        } else st_rlx2((uint2*)&P.s->st1[(rb * 8 + hf * 4 + (cg & 3)) * 48 + lane] + ((cg >> 2) & 1), tagged(c[0]), tagged(c[1]));
        __nanosleep(GDELAY);
#pragma unroll 1
        for (int h = wid - 9; h < 2; h++) {
          const int q = h * 24 + min(lane, 23);
          const uint4* gp = wid == 10 ? &P.s->st1[rb * 8 * 48 + lane] : &P.s->csp[cg * 8 * 48 + q];
          uint4 v[8];
#pragma unroll 1
          for (int it = 0;; it++) {
            uint32_t x = 0;
#pragma unroll
            for (int i = 0; i < 8; i++) v[i] = ld_rlx4(gp + i * 48);
#pragma unroll
            for (int i = 0; i < 8; i++) { v[i].x ^= tag; v[i].y ^= tag; v[i].z ^= tag; v[i].w ^= tag; x |= v[i].x | v[i].y | v[i].z | v[i].w; }
            if (!__any_sync(~0u, (x & 255) != 0)) break;
            SPINCHK(it);
          }
          if (wid == 10) {
#pragma unroll
            for (int i = 0; i < 8; i++) {
              const float m0 = __uint_as_float(v[i].x), m1 = __uint_as_float(v[i].z), dm = 0.5f * (m0 - m1);
              sts2f(sm + OFF_STATS + (i * 32 + lane) * 8, -0.5f * (m0 + m1), rsq(fmaf(dm, dm, 0.5f * (__uint_as_float(v[i].y) + __uint_as_float(v[i].w))) + 1e-5f));
            }
          } else {
            float s4[4] = {0.f, 0.f, 0.f, 0.f};
#pragma unroll
            for (int i = 0; i < 8; i++) { s4[0] += __uint_as_float(v[i].x); s4[1] += __uint_as_float(v[i].y); s4[2] += __uint_as_float(v[i].z); s4[3] += __uint_as_float(v[i].w); }
            sts4(sm + OFF_COLSUM + q * 16, __float_as_uint(s4[0]), __float_as_uint(s4[1]), __float_as_uint(s4[2]), __float_as_uint(s4[3]));
          }
        }
        mbar_arrive(mb + B_AUX);
      }
      IDS(get_b());
      const uint64_t btab = rank ? BT1 : BT0;
      if (wid == 9) {
        {
          const uint4 sv = make_uint4(SENT, SENT, SENT, SENT);
          uint4* y = &P.s->ybuf[b * NFFN * 2 + lane];
#pragma unroll
          for (int i = 0; i < 7; i++) y[i * 32] = sv;
          if (lane < 16) P.s->st2[b * 16 + lane] = make_uint4(0, 0, 0, 0); else P.s->hsel[b * 16 + lane - 16] = sv;
          if (b < 8) P.s->cand[b * 32 + lane] = SENT;
          fence_gpu();
          bar_sync(0, 288);
          if (lane < 16) sts4(sm + OFF_STATS + lane * 128 + ((lane & 7) << 4), 0x3F803F80u, 0x3F803F80u, 0x3F803F80u, 0x3F803F80u);
          fence_async_smem();
          __syncwarp();
          if (lane == 0) mbar_arrive(mb + B_LATE);
        }
        {
          const int p = lane & 15, sl = p % 7;
          const bool sliced = p > 0 && p < 9;
          const uint32_t c = sliced ? ((p - 1) >> 1) * 16 | ((hf ^ 1) * 8 + ((p - 1) & 1) * 4) << 8 | 128 << 16 : (hf * 8 + src_of(p)) << 8;
          const uint32_t ev = mb + (p < 4 ? B_EVA : B_E + 8 * ((p < 7 ? p == 6 : p - 4) & 7) + (p >= 12));
          mbar_wait(mb + B_EVA, 0);
          sts4(sm + OFF_COLSUM + 512 + p * 16, sm + unit_of(btab, sl), mb + B_BF + 8 * sl, c, ev);
          __syncwarp();
        }
        if (elect_one()) {
#pragma unroll 1
          for (int p = 0; p < 16; p++) {
            const uint4 e = lds4(sm + OFF_COLSUM + 512 + p * 16);
            if (p == 4) mbar_wait(mb + B_WR, 0);
            mbar_wait(e.w & ~1u, e.w & 1);
            mbar_expect_tx(e.y, p > 1 ? 4 * UNIT : 2 * UNIT);
            tma_4d(e.x, (const CUtensorMap*)((const char*)&T.m[M_O] + (e.z >> 16)), 0, e.z & 255, (e.z >> 8) & 255, c3 * 2, e.y);
          }
        }
      } else {
        const uint32_t* wp = (const uint32_t*)(P.wr + c3 * 128) + (lane & 7) * 8 + (lane >> 3);
        const uint32_t w0 = ld_rlx(wp), w1 = ld_rlx(wp + 4);
#pragma unroll 1
        for (int i = 0; i < 4; i++) { l2_prefetch((const char*)P.wo + b * 16384 + i * 4096 + lane * 128); __nanosleep(300); }
        const int p = lane & 15, p2 = min(p + 2, 15);
        const uint32_t t0 = dlo(sb, 8192) + (unit_of(btab, p % 7) >> 4), t1 = ring_of(p + 1, lane >> 4), t2 = mb + B_BF + 8 * (p2 % 7);
        mbar_wait(mb + B_EVB, 0);
        bar_sync(14, 64);
        sts2f(sm + OFF_COLSUM + (lane & 6) * 64 + (lane >> 3) * 16 + (lane & 1) * 8, __uint_as_float(w0), __uint_as_float(w1));
        sts1(sm + OFF_COLSUM + (lane >> 3) * 128 + 64 + (lane & 7) * 4, 0x3F803F80u);
        sts4(sm + OFF_STATS + lane * 16, t0, t1, t2, (p2 / 7) & 1);
        __syncwarp();
        if (elect_one()) {
          mbar_arrive(mb + B_WR);
          if (fidx >= 0) {
            mbar_expect_tx(mb + B_FFN, 131072); mbar_expect_tx(mb + B_FFD, 32768);
            uint64_t gt = rank ? GT1 : GT0;
            mbar_wait(mb + B_KVP, 0);
#pragma unroll 1
            for (int f = 0; f < 8; f++, gt >>= 5) {
              uint32_t d0 = sm + unit_of(gt, 0);
              asm volatile("" : "+r"(d0));
              if (f == 3) mbar_wait(mb + B_GATE, 1);
              mbar_wait(mb + (f < 1 ? B_KVB : B_E + (f < 3 ? 3 * f - 1 : (f + 5) >> 1) * 8), f < 1 || f >= 3);
              tma_3d(d0, &T.m[M_G], fidx * 32, f * 128, 0, mb + B_FFN, true);
              tma_3d(d0 + UNIT, &T.m[M_U], fidx * 32, f * 128, 0, mb + B_FFN, true);
            }
            mbar_expect_tx(mb + B_KVP, 32768);
#pragma unroll
            for (int w = 0; w < 8; w++) {
              if (w == 2) mbar_wait(mb + B_E + 56, 1);
              if (w == 6) mbar_wait(mb + B_E16, 1);
              if (w == 4) mbar_wait(mb + B_EVA, 1);
              tma_3d(sm + ((DT0 >> (5 * w)) & 31) * UNIT + (w < 4 ? 0 : w < 6 ? 14 * UNIT : 0 - 14 * UNIT) * rank, &T.m[M_D], 0, fidx * 32, 2 * w, mb + (w < 4 ? B_FFD : B_KVP), true);
            }
          }
        }
      }
    }
    __syncwarp();
    IDS(get_b());
    mbar_wait(mb + B_EVB, 0);
    mbar_wait(mb + B_OUT, 0);
    const float2 cf = lds2f(sm + OFF_STATS + 64);
    const int cand0 = 2047 - (__float_as_int(cf.x) & 2047), cand1 = 2047 - (__float_as_int(cf.y) & 2047), rr = lane >> 4;
    __nv_bfloat16* const ob = P.out + c3 * 128 + (lane & 15) * 8;
    auto store_row = [&](uint32_t ha, uint32_t la, int row, bool on) {
      const uint4 v = lds4(ha);
      const float2 pr = lds2f(la);
      const float f = 1.f + pr.x, n = pr.y;
      asm volatile("{\n.reg .pred p;\nsetp.ne.u32 p, %5, 0;\n@p st.global.v4.u32 [%0], {%1,%2,%3,%4};\n}" :: "l"(ob + row * D_),
                   "r"(pack2(fmaf(bf_lo(v.x), f, n), fmaf(bf_hi(v.x), f, n))), "r"(pack2(fmaf(bf_lo(v.y), f, n), fmaf(bf_hi(v.y), f, n))),
                   "r"(pack2(fmaf(bf_lo(v.z), f, n), fmaf(bf_hi(v.z), f, n))), "r"(pack2(fmaf(bf_lo(v.w), f, n), fmaf(bf_hi(v.w), f, n))), "r"((uint32_t)on) : "memory");
    };
    {
      uint32_t t0 = clock64();
      uint32_t ha = sm + 4 * UNIT + ((wid >> 1) & 1) * STAGE_B + ((wid & 1) * 32 + rr) * 256 + (((lane & 15) ^ rr) << 4), la = sm + OFF_LNP + ((wid & 3) * 32 + rr) * 8;
      int row = rb * 256 + hf * 64 + (wid & 2) * 64 + (wid & 1) * 32 + rr;
#pragma unroll 1
      for (int i = 0; i < 16; i += 2, ha += 512 * 2, la += 16 * 2, row += 2 * 2, t0 += OPACE) {
        while ((int)((uint32_t)clock64() - t0) < 0) NAP;
#pragma unroll
        for (int j = 0; j < 2; j++) store_row((ha ^ (((i + j) & 3) << 5)) + j * 512, la + j * 16, row + 2 * j, row + 2 * j != cand0 && row + 2 * j != cand1);
      }
    }
    if (wid == 8) {
      const uint32_t kc = __float_as_uint(rr ? cf.y : cf.x);
      const int c = rr ? cand1 : cand0;
      mbar_wait(mb + B_SEL, 0);
      const float2 sel = lds2f(sm + OFF_STATS + 80);
      store_row(sm + 4 * UNIT + ((c >> 7) & 1) * STAGE_B + (c & 63) * 256 + (((lane & 15) ^ (c & 7)) << 4), sm + OFF_LNP + (((c >> 1) & 64) + (c & 63)) * 8, c,
                kc != __float_as_uint(sel.x) && kc != __float_as_uint(sel.y) && (c >> 8) == rb && ((c >> 6) & 1) == hf);
    }
  } else {
    asm volatile("setmaxnreg.inc.sync.aligned.u32 224;");
    const int t128 = tid & 127, warp = wid & 3, g = lane >> 2, t = lane & 3;
    const uint32_t sk = rank * (2 * STAGE_B);
    uint4 ost[2][4];
    uint4 abuf[3][4];
    uint4* od1;
    const uint4* ain;
    int b1;
    const uint32_t eb = (lane << 24) + bars + B_E;
    float acc[64];
    uint4 wb[4];
    uint32_t hp[32];
    {
      float acc0[96], acc1[96];
#pragma unroll
      for (int i = 0; i < 96; i++) { acc0[i] = 0.f; acc1[i] = 0.f; }
      const uint32_t xo0 = dlo(sb, 16) + (wg * 2 + hf) * 512, xo1 = dlo(sb, 16) + (wg * 2 + (hf ^ 1)) * 512;
      constexpr uint32_t ST = STAGE_B >> 4, WD = dlo(sb + 49152, 8192), WV = dlo(sb + 32768, 8192);
      const uint32_t eb0 = (t128 << 24) + bars + B_EMPTY;
      pin(acc1); pin(acc0);
      if (wg) asm volatile("cp.async.wait_group 0;" ::: "memory"); else asm volatile("cp.async.wait_group 1;" ::: "memory");
      fence_async_smem();
      bar_sync(1, 256);
      if (!wg) {
        asm volatile("cp.async.wait_group 0;" ::: "memory");
        fence_async_smem();
        bar_sync(2, 256);
        if (tid == 0) mbar_arrive(mb + B_FULL);
      }
#pragma unroll 1
      for (int kb = 0; kb < 12; kb++) {
        const int s = kb & 3;
        if (kb) mbar_wait(mb + B_FULL + 8 * s, (kb >> 2) & 1);
        pin(acc0); pin(acc1);
        wg_fence();
#pragma unroll
        for (int k = 0; k < 4; k++) {
          const uint64_t db = dsc<1024, 1>(WV + s * ST + k * 128);
          wgmma_n192_ss<0, 1, 0>(acc0, dsc<1024, 1>(s * ST + xo0 + k * 2), db, 1);
          wgmma_n192_ss<0, 1, 0>(acc1, dsc<1024, 1>(s * ST + xo1 + k * 2), db, 1);
        }
        wg_commit();
        if (kb == 0 && wg) bar_arrive(2, 256);
        wg_wait<0>();
        pin(acc0); pin(acc1);
        if (t128 < 2 && kb < 11) mbar_arrive_rem(eb0 + 8 * s);
      }
      mbar_wait(mb + B_FULL, 1);
      if (t128 < 8) mbar_arrive_rem(t128 < 4 ? (wg << 24) + bars + B_EMPTY + 24 : mb + B_EMPTY);
      mbar_wait(mb + B_AUX, 0);
      float rs[2][2], nm[2][2];
#pragma unroll
      for (int m = 0; m < 2; m++)
#pragma unroll
        for (int h = 0; h < 2; h++) { const float2 v = lds2f(sm + OFF_STATS + ((wg * 2 + (m ^ hf)) * 64 + warp * 16 + h * 8 + g) * 8); nm[m][h] = v.x; rs[m][h] = v.y; }
      auto center = [&](auto jc) {
        constexpr int j = decltype(jc)::value;
        const float2 cs = lds2f_o<sb + OFF_COLSUM + j * 32>(own + t * 8);
        acc1[j * 4] = fmaf(nm[1][0], cs.x, acc1[j * 4]); acc1[j * 4 + 1] = fmaf(nm[1][0], cs.y, acc1[j * 4 + 1]);
        acc1[j * 4 + 2] = fmaf(nm[1][1], cs.x, acc1[j * 4 + 2]); acc1[j * 4 + 3] = fmaf(nm[1][1], cs.y, acc1[j * 4 + 3]);
        acc0[j * 4] = fmaf(nm[0][0], cs.x, acc0[j * 4]); acc0[j * 4 + 1] = fmaf(nm[0][0], cs.y, acc0[j * 4 + 1]);
        acc0[j * 4 + 2] = fmaf(nm[0][1], cs.x, acc0[j * 4 + 2]); acc0[j * 4 + 3] = fmaf(nm[0][1], cs.y, acc0[j * 4 + 3]);
      };
      static_for<0, 16>(center);
      const float L2E = 1.4426950408889634f;
      uint32_t fa = sm + sk + (warp * 16 + (lane & 15)) * 128 + (((lane >> 4) ^ (lane & 7)) << 4);
      asm volatile("" : "+r"(fa));
      uint32_t xf0[32], xf1[32];
      auto pack_kv = [&](float (&a)[96], int i, float r0, float r1, uint32_t* o, uint32_t z = 0) {
        const float* p = a + i * 8;
        if (i < 4) {
          const float rl0 = __uint_as_float(__float_as_uint(r0 * L2E) | z), rl1 = __uint_as_float(__float_as_uint(r1 * L2E) | z);
          const uint32_t q0 = pack2(r0, r0), q1 = pack2(r1, r1);
          o[0] = phi2(p[0], p[1], rl0, q0); o[1] = phi2(p[2], p[3], rl1, q1); o[2] = phi2(p[4], p[5], rl0, q0); o[3] = phi2(p[6], p[7], rl1, q1);
        } else {
          const uint32_t q0 = pack2(r0, r0), q1 = pack2(r1, r1);
          o[0] = hmul2(pack2(p[0], p[1]), q0); o[1] = hmul2(pack2(p[2], p[3]), q1); o[2] = hmul2(pack2(p[4], p[5]), q0); o[3] = hmul2(pack2(p[6], p[7]), q1);
        }
      };
      auto swap_kv = [&](uint32_t (&xf)[32], uint32_t tile, int i, const uint32_t* o, uint32_t z = 0) {
        const uint32_t ad = (fa + tile * UNIT) ^ ((i & 3) << 5);
        if (i < 4) { ldsm4_o<0>(ad, xf[i * 4], xf[i * 4 + 1], xf[i * 4 + 2], xf[i * 4 + 3]); stsm4_o<0>(ad, o[0], o[1], o[2], o[3]); }
        else { ldsm4_o<STAGE_B>(ad | z, xf[i * 4], xf[i * 4 + 1], xf[i * 4 + 2], xf[i * 4 + 3]); stsm4_o<STAGE_B>(ad, o[0], o[1], o[2], o[3]); }
      };
      auto mma_q = [&](float (&a)[96], uint32_t (&xf)[32], uint32_t xo, bool ss) {
        const uint32_t r = __shfl_sync(~0u, sk >> 4, 0), o = 2 * ST - r;
#pragma unroll
        for (int j = 0; j < 8; j++) {
          if (ss) wgmma_n64_ss<0, 1, 64>(a, dsc<1024, 1>(o + (j >> 2) * ST + xo + (j & 3) * 2), dsc<1024, 1>(WD + o + (j >> 2) * ST + (j & 3) * 128), 1);
          else wgmma_n64_rs<1, 64>(a, xf[j * 4], xf[j * 4 + 1], xf[j * 4 + 2], xf[j * 4 + 3], dsc<1024, 1>(WD + r + (j >> 2) * ST + (j & 3) * 128), 1);
        }
      };
      auto epi_q = [&](float (&a)[96], float r0, float r1, uint32_t (&o)[16]) {
        const float rl0 = r0 * 1.44269511f, rl1 = r1 * 1.44269511f;
        const uint32_t q0 = dup2(r0), q1 = dup2(r1);
#pragma unroll
        for (int j = 0; j < 8; j++) { o[j * 2] = phi2(a[64 + j * 4], a[65 + j * 4], rl0, q0); o[j * 2 + 1] = phi2(a[66 + j * 4], a[67 + j * 4], rl1, q1); }
        pinu(o);
      };
      auto mma_kv1 = [&](float (&a)[96], uint32_t xo, int s) {
#pragma unroll
        for (int k = 0; k < 4; k++) wgmma_n128_ss<0, 1, 0>(a, dsc<1024, 1>(s * ST + xo + k * 2), dsc<1024, 1>(WV + s * ST + k * 128), 1);
      };
      auto epi_kv = [&](float (&a)[96], uint32_t (&xf)[32], uint32_t tile, float r0, float r1) {
        uint32_t o[8][4];
#pragma unroll
        for (int j = 3; j >= 0; j--) {
          const uint32_t z = j < 3 ? xf[(j + 5) * 4] & blockIdx.y : 0;
          pack_kv(a, j + 4, r0, r1, o[j + 4]);
          swap_kv(xf, tile, j + 4, o[j + 4], (o[j + 4][2] | o[j + 4][3]) & blockIdx.y);
          pack_kv(a, j, r0, r1, o[j], z);
          swap_kv(xf, tile, j, o[j]);
        }
      };
      bar_arrive(15, 288); bar_arrive(0, 288);
      pinr<0, 64>(acc0); pinr<0, 64>(acc1);
      if (wg) {
        mbar_wait(mb + B_FULL + 8, 1);
        wg_fence();
        mma_kv1(acc1, xo1, 0); mma_kv1(acc0, xo0, 0); mma_kv1(acc1, xo1, 1); mma_kv1(acc0, xo0, 1);
        mbar_wait(mb + B_FULL + 16, 1);
        wg_fence();
        mma_kv1(acc1, xo1, 2);
        mbar_wait(mb + B_FULL + 24, 1);
        wg_fence();
        mma_kv1(acc1, xo1, 3);
        wg_commit();
        bar_arrive(3, 256);
      }
      b1 = get_b();
      static_for<16, 24>(center);
      pinr<64, 96>(acc0); pinr<64, 96>(acc1);
      if (wg) wg_wait<0>();
      else {
        bar_sync(3, 256);
        wg_fence();
        mma_kv1(acc1, xo1, 0); mma_kv1(acc1, xo1, 1); mma_kv1(acc1, xo1, 2);
        mbar_wait(mb + B_F15, 0);
        wg_fence();
        mma_kv1(acc1, xo1, 3);
        wg_commit();
        mma_kv1(acc0, xo0, 0); mma_kv1(acc0, xo0, 1);
        wg_commit();
        bar_arrive(4, 256);
        wg_wait<1>();
      }
      pinr<0, 64>(acc1);
      epi_kv(acc1, xf1, wg * 2 + (hf ^ 1), rs[1][0], rs[1][1]);
      pinu(xf1);
      if (wg) mbar_wait(mb + B_LATE, 0);
      bar_sync(5 - wg, 256);
      wg_fence();
      mma_kv1(acc0, xo0, 2); mma_kv1(acc0, xo0, 3);
      wg_commit();
      fence_async_smem();
      mma_q(acc1, xf1, xo1, false);
      wg_commit();
      bar_arrive(6 - wg, 256);
      if (wg) bar_arrive(13, 160);
      wg_wait<1>();
      pinr<0, 64>(acc0);
      if (lane == 0) mbar_arrive(mb + B_EVA);
      epi_kv(acc0, xf0, wg * 2 + hf, rs[0][0], rs[0][1]);
      fence_async_smem();
      pinu(xf0);
      const uint32_t kvb = 2 * STAGE_B + (2 + (hf ^ 1)) * UNIT - sk;
      uint32_t ka0, ka1, g0, g1;
      const uint8_t* h0, *h1;
      auto prepare = [&]() {
        const uint32_t l = lane_id();
        od1 = &P.s->obuf[(((b1 >> 4) * 4 + wg * 2 + (hf ^ 1)) * 64 + (b1 & 7)) * 128 + warp * 32 + l];
        ain = &P.s->obuf[((b1 >> 4) * 4 + wg * 2 + hf) * 64 * 128 + warp * 32 + l];
        const uint32_t zo = wid * 32 + (l & 7) * 4;
        ka0 = sm + kvb + wid * 1024 + (l & 7) * 128 + (((l >> 3) ^ (l & 7)) << 4); ka1 = sm + kvb + wid * 1024 + l * 128 + ((4 ^ l) << 4);
        g0 = sm + sk + wid * 512 + l * 16; g1 = sm + sk + zo;
        h0 = (const uint8_t*)&P.s->kvp[(b1 & 15) * 8 * 256 + wid * 32 + l]; h1 = (const uint8_t*)&P.s->zp[(b1 & 15) * 8 * 16] + zo;
        asm volatile("" : "+r"(ka0), "+r"(ka1), "+r"(g0), "+r"(g1), "+l"(h0), "+l"(h1), "+l"(od1), "+l"(ain));
        sched_fence();
      };
      if (wg) {
        float ka[36];
        auto mma_kv = [&](uint32_t tile, int i, int acc) {
          const uint32_t o = (sk >> 4) + tile * 512 + i * 128;
          wgmma_n72_ss<1, 1, 0>(ka, dsc<1024, 1>(dlo(sb, 8192) + o), dsc<1024, 1>(dlo(sb + STAGE_B, OFF_STATS - STAGE_B) + o * (1u - (1u << 16))), acc);
        };
        auto mma_q1 = [&](int j) { wgmma_n64_rs<1, 64>(acc0, xf0[j * 4], xf0[j * 4 + 1], xf0[j * 4 + 2], xf0[j * 4 + 3], dsc<1024, 1>(WD + (sk >> 4) + (j >> 2) * ST + (j & 3) * 128), 1); };
#pragma unroll
        for (int i = 0; i < 36; i++) ka[i] = 0.f;
        bar_sync(6, 256);
        wg_fence();
#pragma unroll
        for (int i = 0; i < 4; i++) {
          mma_kv(2, i, i); mma_kv(3, i, 1); mma_kv(hf ^ 1, i, 1);
          mma_q1(i);
        }
        const int kq = (b1 & 15) * 8 + (b1 >> 4);
        uint4* dst = &P.s->kvp[kq * 256 + warp * 64 + lane];
        uint32_t* dz = (uint32_t*)&P.s->zp[kq * 16] + warp * 16 + g + t * 8;
        asm volatile("" : "+l"(dst), "+l"(dz));
        bar_sync(7, 256);
#pragma unroll
        for (int i = 0; i < 4; i++) mma_kv(hf, i, 1);
        wg_commit();
#pragma unroll
        for (int j = 4; j < 8; j++) mma_q1(j);
        wg_commit();
        bar_arrive(8, 256);
        wg_wait<1>();
        pin(ka);
        uint32_t kw[8];
#pragma unroll
        for (int i = 0; i < 8; i++) {
          const int j = (i & 3) * 4 + (i >> 2) * 2;
          asm("{\n.reg .pred p;\nsetp.ne.u32 p, %5, 0;\n@p cvt.rn.bf16x2.f32 %0, %4, %3;\n@!p cvt.rn.bf16x2.f32 %0, %2, %1;\n}"
              : "=r"(kw[i]) : "f"(ka[j]), "f"(ka[j + 1]), "f"(ka[16 + j]), "f"(ka[17 + j]), "r"(warp & 2));
        }
        st_rlx4(dst, make_uint4(kw[0], kw[1], kw[2], kw[3]));
        st_rlx4(dst + 32, make_uint4(kw[4], kw[5], kw[6], kw[7]));
        if (t < 2) st_rlx(dz, __float_as_uint(t ? ka[34] : ka[32]));
        if (lane == 0) mbar_arrive(mb + B_EVB);
        asm volatile("" : "=r"(ka0), "=r"(ka1), "=r"(g0), "=r"(g1), "=l"(h0), "=l"(h1), "=l"(od1), "=l"(ain));
      } else {
        bar_arrive(7, 256);
        bar_sync(8, 256);
        wg_fence();
        mma_q(acc0, xf0, xo0, false);
        prepare();
        bar_sync(9, 256);
      }
      wg_fence();
      mma_q(acc1, xf1, xo1, true);
      wg_commit();
      if (wg) { bar_arrive(9, 256); prepare(); wg_wait<0>(); }
      else { wg_fence(); mma_q(acc0, xf0, xo0, true); wg_commit(); wg_wait<1>(); }
      pinr<64, 96>(acc1);
      uint32_t pq[16];
      epi_q(acc1, rs[1][0], rs[1][1], pq);
      bar_sync(11 + wg + zero_after(pq), 128);
      if (lane == 0) mbar_arrive(mb + B_KVB);
      if (wg) {
        wg_fence();
        mma_q(acc0, xf0, xo0, true);
        wg_commit();
      }
      {
        uint4 gv[8];
        uint32_t m[8], a[4];
        float z;
        mbar_wait(mb + B_KVP, 0);
        uint32_t zq[8];
        static_for<0, 8>([&](auto sc) { constexpr int s = decltype(sc)::value; asm volatile("ld.shared.u32 %0, [%1+%2];" : "=r"(zq[s]) : "r"(g1), "n"(UNIT + s * 256) : "memory"); });
        static_for<0, 8>([&](auto sc) { constexpr int s = decltype(sc)::value; gv[s] = lds4_o<STAGE_B + s * 4096>(g0); });
#pragma unroll 1
        for (int it = 0; it < SPIN_LIMIT; it++) {
          uint32_t mm = max4(max4(0, make_uint4(zq[0], zq[1], zq[2], zq[3])), make_uint4(zq[4], zq[5], zq[6], zq[7]));
          z = ((__uint_as_float(zq[0]) + __uint_as_float(zq[1])) + (__uint_as_float(zq[2]) + __uint_as_float(zq[3]))) +
              ((__uint_as_float(zq[4]) + __uint_as_float(zq[5])) + (__uint_as_float(zq[6]) + __uint_as_float(zq[7])));
#pragma unroll
          for (int s = 0; s < 8; s++) m[s] = max4(0, gv[s]);
#pragma unroll
          for (int s = 0; s < 8; s += 2) mm = __vimax3_u32(mm, m[s], m[s + 1]);
          a[0] = hadd2(hadd2(hadd2(gv[0].x, gv[1].x), hadd2(gv[2].x, gv[3].x)), hadd2(hadd2(gv[4].x, gv[5].x), hadd2(gv[6].x, gv[7].x)));
          a[1] = hadd2(hadd2(hadd2(gv[0].y, gv[1].y), hadd2(gv[2].y, gv[3].y)), hadd2(hadd2(gv[4].y, gv[5].y), hadd2(gv[6].y, gv[7].y)));
          a[2] = hadd2(hadd2(hadd2(gv[0].z, gv[1].z), hadd2(gv[2].z, gv[3].z)), hadd2(hadd2(gv[4].z, gv[5].z), hadd2(gv[6].z, gv[7].z)));
          a[3] = hadd2(hadd2(hadd2(gv[0].w, gv[1].w), hadd2(gv[2].w, gv[3].w)), hadd2(hadd2(gv[4].w, gv[5].w), hadd2(gv[6].w, gv[7].w)));
          pinu(a);
          if (!__any_sync(~0u, mm == SENT)) break;
#pragma unroll
          for (int s = 0; s < 8; s++) {
            zq[s] = ld_rlx(h1 + s * 256);
            if (m[s] == SENT) gv[s] = ld_rlx4(h0 + s * 4096);
          }
        }
        wg_wait<0>();
        pinr<64, 96>(acc0);
        stsm4(ka0, a[0], a[1], a[2], a[3]);
        const uint32_t zz = pack2(z, z);
        if (lane < 8) sts4(ka1, zz, zz, zz, zz);
        fence_async_smem();
        bar_sync(1, 256);
      }
      uint32_t pb[16];
      auto phi_b = [&](int j0, int j1) {
        const float rl0 = rs[0][0] * 1.44269511f, rl1 = rs[0][1] * 1.44269511f;
        const uint32_t q0 = dup2(rs[0][0]), q1 = dup2(rs[0][1]);
        uint32_t z = 0;
#pragma unroll
        for (int j = 0; j < 8; j++)
          if (j >= j0 && j < j1) {
            pb[j * 2] = phi2(acc0[64 + j * 4], acc0[65 + j * 4], rl0, q0); pb[j * 2 + 1] = phi2(acc0[66 + j * 4], acc0[67 + j * 4], rl1, q1);
            z |= pb[j * 2] | pb[j * 2 + 1];
          }
        return z & 0x80008000u;
      };
      auto make_o = [&](uint4 (&o)[4], uint32_t (&pq)[16], auto first) {
        float oa[2][20];
        wg_fence();
#pragma unroll
        for (int ks = 0; ks < 4; ks++) {
          wgmma_n40_rs<1, 0>(oa[ks >> 1], pq[ks * 4], pq[ks * 4 + 1], pq[ks * 4 + 2], pq[ks * 4 + 3], dsc<1024, 1>(dlo(sb, 8192) + (kvb >> 4) + ks * 128), ks & 1);
          if (decltype(first)::value && ks == 1) wg_commit();
        }
        wg_commit();
        if constexpr (!decltype(first)::value) {
          pinu(xf0);
#pragma unroll
          for (int q = 0; q < 32; q++) { acc[q * 2] = bf_lo(xf0[q]); acc[q * 2 + 1] = bf_hi(xf0[q]); }
          pin(acc);
          mbar_wait(mb + B_BF, 0);
        }
        if (decltype(first)::value) { wg_wait<1>(); pin(oa[0]); }
        else { wg_wait<0>(); pin(oa[0]); pin(oa[1]); }
#pragma unroll
        for (int h = 0; h < 2; h++) {
          const float (&d)[20] = oa[h];
          const float i0 = rcp(d[16] + 1e-6f), i1 = rcp(d[18] + 1e-6f);
#pragma unroll
          for (int k2 = 0; k2 < 2; k2++) {
            o[h * 2 + k2] = make_uint4(pack2(d[k2 * 8] * i0, d[k2 * 8 + 1] * i0), pack2(d[k2 * 8 + 2] * i1, d[k2 * 8 + 3] * i1),
                                       pack2(d[k2 * 8 + 4] * i0, d[k2 * 8 + 5] * i0), pack2(d[k2 * 8 + 6] * i1, d[k2 * 8 + 7] * i1));
            if (decltype(first)::value && !h && !k2) {
              st_rlx4(od1, o[0]); sched_fence();
              wg_wait<0>();
              pin(oa[1]);
              if (lane < 2) mbar_arrive_rem(eb);
            }
          }
        }
      };
      make_o(ost[1], pq, std::true_type{});
      st_rlx4(od1 + 1024 + ((ost[1][2].x | ost[1][3].w) & blockIdx.y), ost[1][1]);
      sched_fence();
      mbar_wait(mb + B_F15 + phi_b(0, R1MID), 1);
#pragma unroll
      for (int i = 0; i < 4; i++) abuf[1][i] = ld_rlx4(ain + i * 128);
      phi_b(R1MID, 8);
      st_rlx4(od1 + 2048, ost[1][2]);
      make_o(ost[0], pb, std::false_type{});
    }
   {
    IDS(b1);
    const int mb3 = rb * 4 + wg * 2 + hf;
    uint4* rp = &P.s->st2[mb3 * 64 + warp * 16 + g + t * 8];
    {
      uint4* const od0 = &P.s->obuf[(mb3 * 64 + 32 + s3 * 4) * 128 + t128];
#pragma unroll
      for (int i = 0; i < 4; i++) pin4(ost[0][i]);
      wg_fence();
#pragma unroll
      for (int k = 0; k < 4; k++) wgmma_n128_rs<1, 0>(acc, ost[0][k].x, ost[0][k].y, ost[0][k].z, ost[0][k].w, dsc<1024, 1>(dlo(sb + 4 * UNIT, 8192) + k * 128), 1);
      wg_commit();
      st_rlx4(od1 + 3072, ost[1][3]); st_rlx4(od0, ost[0][0]);
      uint32_t la = sm + t128 * 16, ev = eb + 8;
      asm volatile("" : "+r"(la), "+r"(ev));
      auto fetch = [&](uint32_t off, uint4 (&a)[4]) { const uint32_t ra = la + off; a[0] = lds4_o<0>(ra); a[1] = lds4_o<2048>(ra); a[2] = lds4_o<4096>(ra); a[3] = lds4_o<6144>(ra); };
      auto check = [&](int p, uint4 (&a)[4]) {
        if (__any_sync(~0u, max(max4(max4(0, a[0]), a[1]), max4(max4(0, a[2]), a[3])) == SENT)) {
          int pl = p; asm volatile("" : "+r"(pl));
          const uint4* q = ain + frag_of(pl);
#pragma unroll 1
          for (int it = 0;; it++) {
            uint32_t mm = 0;
#pragma unroll
            for (int i = 0; i < 4; i++) { const uint32_t m = max4(0, a[i]); mm = max(mm, m); if (m == SENT) a[i] = ld_rlx4(q + i * 128); }
            if (!__any_sync(~0u, mm == SENT)) break;
            SPINCHK(it);
          }
        }
        if (lane < 2) mbar_arrive_rem(ev);
        ev = (ev & ~0x38u) | ((ev + 8) & 0x38u);
      };
      auto mma = [&](int p, uint32_t bs, uint4 (&a)[4]) {
#pragma unroll
        for (int i = 0; i < 4; i++) pin4(a[i]);
        wg_fence();
#pragma unroll
        for (int k = 0; k < 4; k++) wgmma_n128_rs<1, 0>(acc, a[k].x, a[k].y, a[k].z, a[k].w, dsc<1024, 1>(bs + k * 128), 1);
        wg_commit();
      };
      uint32_t ta = sm + OFF_STATS + wg * 256 + 48;
      mbar_wait(mb + B_WR, 0);
      uint4 tp = lds4(ta);
      mbar_wait(mb + B_BF + 8, 0);
      check(1, abuf[1]);
      mbar_wait(mb + B_BF + 16, 0);
      fetch(ring_of(2, wg), abuf[2]);
      mma(1, dlo(sb + 11 * UNIT, 8192), abuf[1]);
      st_rlx4(od0 + 128, ost[0][1]); st_rlx4(od0 + 256, ost[0][2]);
      check(2, abuf[2]);
      mbar_wait(mb + B_BF + 24, 0);
      fetch(ring_of(3, wg), abuf[0]);
      mma(2, dlo(sb + 18 * UNIT, 8192), abuf[2]);
      st_rlx4(od0 + 384, ost[0][3]);
      wg_wait<2>();
      check(3, abuf[0]);
      mbar_wait(mb + B_BF + 32, 0);
#pragma unroll 1
      for (int p = 3; p < 15; p += 3) {
        static_for<0, 3>([&](auto jc) {
          constexpr int j = decltype(jc)::value;
          const uint4 tc = tp;
          const uint32_t bs = __shfl_sync(~0u, tc.x, 0);
          wg_wait<1>();
#pragma unroll
          for (int i = 0; i < 4; i++) pin4(abuf[(j + 1) % 3][i]);
          tp = lds4_o<16 * j + 16>(ta);
          fetch(tc.y, abuf[(j + 1) % 3]);
          mma(p + j, bs, abuf[j]);
          check(p + j + 1, abuf[(j + 1) % 3]);
          mbar_wait(tc.z, tc.w);
        });
        ta += 48;
      }
      {
        const uint32_t wa0 = sm + OFF_COLSUM + ((g & 1) ? t * 16 : 64);
        wb[0] = lds4_o<0>(wa0); wb[1] = lds4_o<128>(wa0); wb[2] = lds4_o<256>(wa0); wb[3] = lds4_o<384>(wa0);
      }
      mma(15, __shfl_sync(~0u, tp.x, 0), abuf[0]);
      wg_wait<2>();
      if (lane == 0) mbar_arrive(mb + B_E16);
      asm volatile("" : "+l"(rp));
      sched_fence();
      wg_wait<0>();
      pin(acc);
#pragma unroll
      for (int i = 0; i < 4; i++) { pin4(abuf[0][i]); pin4(abuf[1][i]); pin4(abuf[2][i]); }
    }
    {
      float q0[2] = {0.f, 0.f}, q1[2] = {0.f, 0.f}, c[2][4] = {};
#pragma unroll
      for (int j = 0; j < 16; j++) {
        hp[j * 2] = pack2(acc[j * 4], acc[j * 4 + 1]); hp[j * 2 + 1] = pack2(acc[j * 4 + 2], acc[j * 4 + 3]);
        q0[j & 1] = fmaf(acc[j * 4], acc[j * 4], fmaf(acc[j * 4 + 1], acc[j * 4 + 1], q0[j & 1]));
        q1[j & 1] = fmaf(acc[j * 4 + 2], acc[j * 4 + 2], fmaf(acc[j * 4 + 3], acc[j * 4 + 3], q1[j & 1]));
        if (j & 1) {
          const uint32_t a[4] = {hp[j * 2 - 2], hp[j * 2 - 1], hp[j * 2], hp[j * 2 + 1]};
          mma16816(c[(j >> 1) & 1], a, (j & 2) ? wb[j >> 2].z : wb[j >> 2].x, (j & 2) ? wb[j >> 2].w : wb[j >> 2].y);
        }
      }
      const bool od = t & 1;
      float q = (od ? q1[0] + q1[1] : q0[0] + q0[1]) + __shfl_xor_sync(~0u, od ? q0[0] + q0[1] : q1[0] + q1[1], 1);
      q += __shfl_xor_sync(~0u, q, 2);
      asm volatile("{\n.reg .pred p;\nsetp.lt.u32 p, %5, 2;\n@p red.relaxed.gpu.global.add.v4.f32 [%0], {%1,%2,%3,%4};\n}"
                   :: "l"(rp), "f"(od ? c[0][2] + c[1][2] : c[0][0] + c[1][0]), "f"(q), "f"(od ? c[0][3] + c[1][3] : c[0][1] + c[1][1]), "f"(1.f), "r"(t) : "memory");
    }
    const uint32_t ts = clock64();
    const uint32_t msc = sm + OFF_STATS;
    const uint32_t hst = sm + 4 * UNIT + wg * STAGE_B + warp * 4096, gslot = sm + unit_of(rank ? GT1 : GT0, wid);
    bar_sync(1, 256);
#pragma unroll
    for (int j = 0; j < 8; j++)
      stsm4(hst + (lane & 15) * 256 + (((2 * j + (lane >> 4)) ^ (lane & 7)) << 4), hp[j * 4], hp[j * 4 + 1], hp[j * 4 + 2], hp[j * 4 + 3]);
    uint32_t wa[8][4][4], wd[8][2][4];
    const uint32_t a0 = gslot + ((lane >> 4) * 8 + (lane & 7)) * 64 + ((((lane >> 3) & 1) ^ ((lane >> 1) & 3)) << 4);
    auto load_gu = [&](auto ic) { constexpr int i = decltype(ic)::value; ldsm4t_o<(i >> 2) * 1024 + ((i >> 1) & 1) * 8192>(a0 ^ ((i & 1) << 5), wa[i >> 2][i & 3]); };
    uint32_t tx;
    {
      const int row = rb * 256 + tid;
      const uint4* sp = &P.s->st2[row], *sq = &P.s->st2[row ^ 256];
      const float sw = __uint_as_float((lds1(mb + B_SW) & ~255u) | 128);
      uint4 v[2];
      uint4* d = &P.s->hsel[c3 * 128 + (g & 3) * 32 + ((rb & 6) + (lane >> 4)) * 4 + t];
      uint32_t* dk = &P.s->cand[c3 * 32 + (rb & 6) + (lane >> 4)];
      asm volatile("" : "+l"(d), "+l"(dk));
      if (fidx >= 0) mbar_wait(mb + B_FFN, 0);
      static_for<0, GU1>(load_gu);
      while ((uint32_t)clock64() - ts < SDEL2) {}
      v[0] = ld_rlx4(sp); v[1] = ld_rlx4(sq);
      static_for<GU1, GU2>(load_gu);
#pragma unroll 1
      for (int it = 0; __any_sync(~0u, min(v[0].w, v[1].w) != 0x41000000u) && it < SPIN_LIMIT; it++) {
        if (v[0].w != 0x41000000u) v[0] = ld_rlx4(sp);
        if (v[1].w != 0x41000000u) v[1] = ld_rlx4(sq);
      }
      if (lane == 0) mbar_arrive(mb + B_EVA);
      uint32_t k[2];
#pragma unroll
      for (int i = 0; i < 2; i++) {
        const float mean = __uint_as_float(v[i].x) * (1.f / D_);
        const float rstd = rsq(fmaxf(fmaf(-mean, mean, __uint_as_float(v[i].y) * (1.f / D_)), 0.f) + 1e-5f);
        const uint32_t u = __float_as_uint(rstd * fmaf(-mean, sw, __uint_as_float(v[i].z)));
        k[i] = min(((u ^ ((uint32_t)((int)u >> 31) | 0x80000000u)) & ~2047u), 0xFFFFF000u) | (2047 - (row ^ (i << 8)));
        if (i == 0 && (warp >> 1) == hf) sts2f(sm + OFF_LNP + (wg * 64 + (tid & 63)) * 8, rstd, -mean * rstd);
      }
      const uint32_t hi = max(k[0], k[1]);
      uint32_t m1 = __reduce_max_sync(~0u, hi), m2 = __reduce_max_sync(~0u, hi == m1 ? min(k[0], k[1]) : hi);
      if (lane == 0) sts2f(msc + wid * 8, __uint_as_float(m1), __uint_as_float(m2));
      bar_sync(1, 256);
      const uint32_t kk = lds1(msc + (lane & 15) * 4);
      m1 = __reduce_max_sync(~0u, kk); m2 = __reduce_max_sync(~0u, kk == m1 ? 0 : kk);
      const int c0 = 2047 - (m1 & 2047), c1 = 2047 - (m2 & 2047);
      if ((c0 >> 4) == mb3 * 4 + warp || (c1 >> 4) == mb3 * 4 + warp) {
        const int ra = (lane & 4) ? c1 : c0, rd = (lane & 16) ? c1 : c0;
        uint32_t h0, h1, h2, h3;
        ldsm4_o<0>(hst + (ra & 15) * 256 + ((((lane & 3) * 4 + (lane >> 3)) ^ (ra & 7)) << 4), h0, h1, h2, h3);
        const float2 pr = lds2f(sm + OFF_LNP + (wid * 16 + (rd & 15)) * 8);
        asm volatile("{\n.reg .pred p;\nsetp.eq.u32 p, %11, %12;\n@p st.relaxed.gpu.global.v4.u32 [%0], {%2,%3,%4,%5};\n@p st.relaxed.gpu.global.u32 [%1], %10;\n"
                     "@p st.relaxed.gpu.global.v4.u32 [%0+16384], {%6,%7,%8,%9};\n}"
                     :: "l"(d), "l"(dk), "r"(pack2(fmaf(bf_lo(h0), pr.x, pr.y), fmaf(bf_hi(h0), pr.x, pr.y))), "r"(pack2(fmaf(bf_lo(h1), pr.x, pr.y), fmaf(bf_hi(h1), pr.x, pr.y))),
                        "r"(pack2(fmaf(bf_lo(h2), pr.x, pr.y), fmaf(bf_hi(h2), pr.x, pr.y))), "r"(pack2(fmaf(bf_lo(h3), pr.x, pr.y), fmaf(bf_hi(h3), pr.x, pr.y))),
                        "r"(h0), "r"(h1), "r"(h2), "r"(h3), "r"((lane & 16) ? m2 : m1), "r"(rd >> 4), "r"(mb3 * 4 + warp) : "memory");
      }
      tx = clock64();
      if (tid == 0) { sts2f(msc + 64, __uint_as_float(m1), __uint_as_float(m2)); mbar_arrive(mb + B_OUT); }
    }
    static_for<GU2, GU3>(load_gu);
    const uint32_t dl = sm + (wid & 1) * 4096 + ((lane >> 4) * 8 + (lane & 7)) * 128 + ((((lane >> 3) & 1) ^ (lane & 7)) << 4);
    uint32_t da = dl + unit_of(DT0, wid >> 1), db = dl + unit_of(rank ? DT1 : DT0, 4 + (wid >> 1));
    uint32_t* yp = (uint32_t*)&P.s->ybuf[((wid * 8 + t * 2) * NFFN + fidx) * 2] + g;
    uint32_t k1, k2;
    uint2 key;
    uint32_t pl = sm + unit_of(rank ? GT1 : GT0, g) + (g & 1) * 64 + wid * 64 + t * 16, pa = msc + 128 + wid * 16 + ((t & 1) * 2 + (lane >> 4)) * 4 + (t >> 1) * 2;
    {
      float gu[2][4][4];
      uint4 xb[4];
      uint32_t m[4];
      const uint4* xp = &P.s->hsel[wid * 128 + lane];
      const uint2* kp = (const uint2*)&P.s->cand[wid * 32] + t;
      uint32_t ps = gslot + (wid & 1) * 64 + g * 32;
      asm volatile("" : "+l"(xp), "+l"(kp), "+l"(yp), "+r"(db), "+r"(ps), "+r"(pl), "+r"(pa));
      auto load_d = [&](auto ic) { constexpr int i = decltype(ic)::value; ldsm4t_o<(i & 1) * 2048>(da ^ ((i >> 1) << 5), wd[i >> 1][i & 1]); };
      if (fidx >= 0) mbar_wait(mb + B_FFD, 0);
      while ((uint32_t)clock64() - tx < XDELAY) {}
      key = ld_rlx2(kp);
#pragma unroll
      for (int i = 0; i < 4; i++) xb[i] = ld_rlx4(xp + i * 32);
      static_for<GU3, 32>(load_gu);
      static_for<0, 8>(load_d);
      if (fidx >= 0) mbar_wait(mb + B_KVP, 1);
#pragma unroll 1
      for (int it = 0; it < SPIN_LIMIT; it++) {
#pragma unroll
        for (int i = 0; i < 4; i++) m[i] = max4(0, xb[i]);
        if (!__any_sync(~0u, __vimax3_u32(__vimax3_u32(max(key.x, key.y), m[0], m[1]), m[2], m[3]) == SENT)) break;
        key = ld_rlx2(kp);
#pragma unroll
        for (int i = 0; i < 4; i++) if (m[i] == SENT) xb[i] = ld_rlx4(xp + i * 32);
      }
      const uint32_t hi = max(key.x, key.y);
      k1 = __reduce_max_sync(~0u, hi); k2 = __reduce_max_sync(~0u, hi == k1 ? min(key.x, key.y) : hi);
#pragma unroll
      for (int i = 0; i < 32; i++) gu[i >> 4][(i >> 2) & 3][i & 3] = 0.f;
#pragma unroll
      for (int ks = 0; ks < 8; ks++) {
#pragma unroll
        for (int i = 0; i < 4; i++) mma16816(gu[ks & 1][i], wa[ks][i], (ks & 1) ? xb[ks >> 1].z : xb[ks >> 1].x, (ks & 1) ? xb[ks >> 1].w : xb[ks >> 1].y);
        if (ks == 1) {
          const uint32_t dd = db | (__float_as_uint(gu[1][3][0]) & blockIdx.y);
          static_for<0, 8>([&](auto ic) { constexpr int i = decltype(ic)::value; ldsm4t_o<(i & 1) * 2048>(dd ^ ((i >> 1) << 5), wd[4 + (i >> 1)][i & 1]); });
          xb[3].z |= (wd[4][0][0] | wd[4][1][0] | wd[5][0][0] | wd[5][1][0] | wd[6][0][0] | wd[6][1][0] | wd[7][0][0] | wd[7][1][0]) & blockIdx.y;
        }
      }
#pragma unroll
      for (int c = 0; c < 2; c++) {
        const uint32_t kc = c ? key.y : key.x;
        float o[8];
#pragma unroll
        for (int j = 0; j < 8; j++) o[j] = gu[0][(j >> 2) + (j & 1) * 2][(j & 2) + c] + gu[1][(j >> 2) + (j & 1) * 2][(j & 2) + c];
        asm volatile("{\n.reg .pred p;\nsetp.ge.u32 p, %9, %10;\n@p st.shared.v4.f32 [%0], {%1,%2,%3,%4};\n@p st.shared.v4.f32 [%0+16], {%5,%6,%7,%8};\n}"
                     :: "r"(ps + (kc == k1 ? 0 : 256)), "f"(o[0]), "f"(o[1]), "f"(o[2]), "f"(o[3]), "f"(o[4]), "f"(o[5]), "f"(o[6]), "f"(o[7]), "r"(kc), "r"(k2) : "memory");
      }
    }
    bar_sync(1, 256);
    {
      const uint4 pv = lds4(pl);
      const bool hi = lane & 16;
      float ga = __uint_as_float(hi ? pv.z : pv.x) + __shfl_xor_sync(~0u, __uint_as_float(hi ? pv.x : pv.z), 16);
      float up = __uint_as_float(hi ? pv.w : pv.y) + __shfl_xor_sync(~0u, __uint_as_float(hi ? pv.y : pv.w), 16);
      ga += __shfl_xor_sync(~0u, ga, 8); up += __shfl_xor_sync(~0u, up, 8);
      ga += __shfl_xor_sync(~0u, ga, 4); up += __shfl_xor_sync(~0u, up, 4);
      asm volatile("st.shared.u16 [%0], %1;" :: "r"(pa), "h"((uint16_t)pack2(ga * rcp(1.f + ex2(-1.4426950408889634f * ga)) * up, 0.f)) : "memory");
      bar_sync(1, 256);
      const uint4 bv = lds4(msc + 128 + (lane & 7) * 16);
      const uint32_t bq[4] = {bv.x, bv.y, bv.z, bv.w};
      float ya[8][4];
#pragma unroll
      for (int i = 0; i < 8; i++) { ya[i][0] = 0.f; ya[i][1] = 0.f; ya[i][2] = 0.f; ya[i][3] = 0.f; }
#pragma unroll
      for (int ks = 0; ks < 2; ks++)
#pragma unroll
        for (int i = 0; i < 8; i++) mma16816(ya[i], wd[i][ks], bq[ks * 2], bq[ks * 2 + 1]);
#pragma unroll
      for (int h = 0; h < 2; h++) {
        float o[4];
#pragma unroll
        for (int j = 0; j < 4; j++) o[j] = t == 0 ? ya[h * 4][j] : t == 1 ? ya[h * 4 + 1][j] : t == 2 ? ya[h * 4 + 2][j] : ya[h * 4 + 3][j];
        asm volatile("{\n.reg .pred p;\nsetp.ge.s32 p, %3, 0;\n@p st.relaxed.gpu.global.u32 [%0], %1;\n@p st.relaxed.gpu.global.u32 [%0+%4], %2;\n}"
                     :: "l"(yp + h * (64 * NFFN * 8)), "r"(pack2(o[0], o[1])), "r"(pack2(o[2], o[3])), "r"(fidx), "n"(NFFN * 32) : "memory");
      }
    }
    if (tid == 0) { sts2f(msc + 80, __uint_as_float(k1), __uint_as_float(k2)); mbar_arrive(mb + B_SEL); }
    const uint32_t ty = clock64();
    if (wid == 0) {
      const uint32_t* yq = (const uint32_t*)&P.s->ybuf[b * NFFN * 2] + t * 8 + g;
      const uint32_t ks = (t & 1) ? k2 : k1, grp = 3 - ((ks >> 9) & 3);
      const int fs = grp * 2 + (__shfl_sync(~0u, key.y, grp) == ks);
      const uint32_t* fq = (const uint32_t*)P.s->hsel + (((b >> 4) * 4 + ((b >> 2) & 3)) * 32 + fs * 4 + (g >> 1)) * 4 + (b & 3);
      float gate = rcp(1.f + ex2(-1.4426950408889634f * __uint_as_float(ks ^ (~(uint32_t)((int)ks >> 31) | 0x80000000u))));
      __nv_bfloat16* op = P.out + (size_t)(2047 - (ks & 2047)) * D_ + b * 8 + g;
      uint32_t sel = (g & 2) ? 0x3F800000u : 0x00003F80u;
      uint32_t fn = ld_rlx(fq), fh = ld_rlx(fq + 4096), v[7][4];
      uint32_t m[7];
#pragma unroll
      for (int i = 0; i < 7; i++) { m[i] = ~blockIdx.y; asm volatile("" : "=r"(v[i][0]), "=r"(v[i][1]), "=r"(v[i][2]), "=r"(v[i][3]), "+r"(m[i])); }
      asm volatile("" : "+l"(yq), "+l"(op), "+f"(gate), "+r"(sel));
      while ((uint32_t)clock64() - ty < YDELAY) {}
      float y[2][4];
#pragma unroll 1
      for (int it = 0; it < SPIN_LIMIT; it++) {
        static_for<0, 7>([&](auto ic) { constexpr int i = decltype(ic)::value;
          asm volatile("{\n.reg .pred p;\nsetp.eq.u32 p, %5, 0xFFFFFFFF;\n@p ld.relaxed.gpu.global.u32 %0, [%4+%6];\n@p ld.relaxed.gpu.global.u32 %1, [%4+%6+128];\n"
                       "@p ld.relaxed.gpu.global.u32 %2, [%4+%6+256];\n@p ld.relaxed.gpu.global.u32 %3, [%4+%6+384];\n}"
                       : "+r"(v[i][0]), "+r"(v[i][1]), "+r"(v[i][2]), "+r"(v[i][3]) : "l"(yq), "r"(m[i]), "n"(i * 512) : "memory"); });
        uint32_t mm = max(fn, fh);
        if (mm == SENT) { fn = ld_rlx(fq); fh = ld_rlx(fq + 4096); }
#pragma unroll
        for (int i = 0; i < 8; i++) y[i >> 2][i & 3] = 0.f;
#pragma unroll
        for (int i = 0; i < 7; i++) { m[i] = __vimax3_u32(max(v[i][0], v[i][1]), v[i][2], v[i][3]); mm = max(mm, m[i]); mma16816(y[i & 1], v[i], sel, sel); }
        pin(y[0]); pin(y[1]);
        if (!__any_sync(~0u, mm == SENT)) break;
      }
      const float base = (g & 1) ? bf_hi(fh) + bf_hi(fn) : bf_lo(fh) + bf_lo(fn);
      if (t < 2) *op = __float2bfloat16(fmaf((y[0][0] + y[1][0]) + (y[0][2] + y[1][2]), gate, base));
      if (b == 0 && lane == 0) P.s->epoch = lds1(mb + B_SW) & 255;
    }
   }
  }
}

typedef CUresult (*EncodeFn)(CUtensorMap*, CUtensorMapDataType, cuuint32_t, void*, const cuuint64_t*, const cuuint64_t*, const cuuint32_t*,
                             const cuuint32_t*, CUtensorMapInterleave, CUtensorMapSwizzle, CUtensorMapL2promotion, CUtensorMapFloatOOBfill);
void make_map(EncodeFn enc, CUtensorMap* m, const void* p, int rank, std::initializer_list<cuuint64_t> dims, std::initializer_list<cuuint64_t> str,
              std::initializer_list<cuuint32_t> box, CUtensorMapSwizzle sw) {
  const cuuint32_t es[4] = {1, 1, 1, 1};
  enc(m, CU_TENSOR_MAP_DATA_TYPE_BFLOAT16, rank, const_cast<void*>(p), dims.begin(), str.begin(), box.begin(), es, CU_TENSOR_MAP_INTERLEAVE_NONE, sw,
      CU_TENSOR_MAP_L2_PROMOTION_L2_128B, CU_TENSOR_MAP_FLOAT_OOB_FILL_NONE);
}

}

extern "C" void kernel_launch(void* const* d_in, const int* in_sizes, int n_in, void* d_out, int out_size) {
  (void)in_sizes; (void)n_in; (void)out_size;
  Ptrs P;
  P.x = (const __nv_bfloat16*)d_in[0]; P.wqkv = (const __nv_bfloat16*)d_in[1]; P.wo = (const __nv_bfloat16*)d_in[2];
  P.wr = (const __nv_bfloat16*)d_in[4]; P.wg = (const __nv_bfloat16*)d_in[5]; P.wu = (const __nv_bfloat16*)d_in[6];
  P.wd = (const __nv_bfloat16*)d_in[7]; P.out = (__nv_bfloat16*)d_out;
  cudaGetSymbolAddress((void**)&P.s, g_scratch);
  void* fn = nullptr;
  cudaDriverEntryPointQueryResult q;
  cudaGetDriverEntryPoint("cuTensorMapEncodeTiled", &fn, cudaEnableDefault, &q);
  EncodeFn enc = (EncodeFn)fn;
  Maps T;
  constexpr CUtensorMapSwizzle S128 = CU_TENSOR_MAP_SWIZZLE_128B, S64 = CU_TENSOR_MAP_SWIZZLE_64B;
  make_map(enc, &T.m[M_X], P.x, 2, {D_, S_}, {D_ * 2}, {64, 128}, S128);
  make_map(enc, &T.m[M_W], P.wqkv, 3, {D_, D_, 3}, {3 * D_ * 2, D_ * 2}, {64, 64, 2}, S128);
  make_map(enc, &T.m[M_Q], P.wqkv, 2, {3 * D_, D_}, {3 * D_ * 2}, {64, 64}, S128);
  make_map(enc, &T.m[M_O], P.wo, 4, {64, 64, 16, 16}, {D_ * 2, 64 * D_ * 2, 128}, {64, 64, 1, 2}, S128);
  make_map(enc, &T.m[M_S], P.wo, 4, {64, 64, 16, 16}, {D_ * 2, 64 * D_ * 2, 128}, {64, 16, 4, 2}, S128);
  make_map(enc, &T.m[M_G], P.wg, 3, {F_, D_, 1}, {F_ * 2, F_ * 2 * D_}, {32, 128, 1}, S64);
  make_map(enc, &T.m[M_U], P.wu, 3, {F_, D_, 1}, {F_ * 2, F_ * 2 * D_}, {32, 128, 1}, S64);
  make_map(enc, &T.m[M_D], P.wd, 3, {64, F_, 16}, {D_ * 2, 128}, {64, 32, 2}, S128);
  make_map(enc, &T.m[M_L], P.wd, 2, {64, F_ * 16}, {128}, {8, 32}, CU_TENSOR_MAP_SWIZZLE_NONE);
  cudaFuncSetAttribute(fused_kernel, cudaFuncAttributeMaxDynamicSharedMemorySize, SMEM_BYTES);
  fused_kernel<<<NCTA, 384, SMEM_BYTES>>>(P, T);
}
```
